```python
import torch

def _softmax(x, axis=-1):
    return torch.softmax(x, dim=axis)
def _gelu(x):
    return torch.nn.functional.gelu(x, approximate="tanh")
def _silu(x):
    return torch.nn.functional.silu(x)
def _sigmoid(x):
    return torch.sigmoid(x)
def _layernorm(x, axis=-1, eps=1e-5):
    m = x.mean(dim=axis, keepdim=True)
    v = x.var(dim=axis, keepdim=True, unbiased=False)
    return (x - m) / torch.sqrt(v + eps)
def _scatter_add(tgt, idx, src, axis=0):
    return tgt.clone().index_add_(axis, idx, src)
def _segment_sum(src, seg, n):
    out = torch.zeros((n,) + src.shape[1:], dtype=src.dtype)
    return out.index_add_(0, seg, src)
def _pad(x, pw):
    flat = tuple(v for pair in reversed(pw) for v in pair)
    return torch.nn.functional.pad(x, flat)

kernel_name = 'parallel_sum__ssm_conv_h3__glu_gated_bilinear__prompt'

def setup_inputs():

    _w = (lambda a: (lambda t: t.to(torch.bfloat16) if t.is_floating_point() else t)(torch.as_tensor(a)))
    def _A_setup():
        B, S, D = 1, 2048, 512
        ks = 4
        return {
            "q": _w((lambda *s: torch.randn(*s, dtype=torch.bfloat16) * 0.05)(B, S, D)),
            "k": _w((lambda *s: torch.randn(*s, dtype=torch.bfloat16) * 0.2)(B, S, D)),
            "v": _w((lambda *s: torch.randn(*s, dtype=torch.bfloat16) * 0.2)(B, S, D)),
            "shift_k": _w((lambda *s: torch.randn(*s, dtype=torch.bfloat16) * 0.2)(D, ks) * 0.5),
            "ssm_k": _w((lambda *s: torch.randn(*s, dtype=torch.bfloat16) * 0.4)(D, S) * (1.0 / S ** 0.5)),
            "ssm_D": _w((lambda *s: torch.randn(*s, dtype=torch.bfloat16) * 0.2)(D)),
        }
    _A_in = _A_setup()

    def _B_setup():
        B, S, D, F = 1, 2048, 512, 1792
        return {
            "x": _w((lambda *s: torch.randn(*s, dtype=torch.bfloat16) * 0.05)(B, S, D)),
            "w_gate": _w((lambda *s: torch.randn(*s, dtype=torch.bfloat16) * 0.2)(D, F) * (D ** -0.5)),
            "w_up": _w((lambda *s: torch.randn(*s, dtype=torch.bfloat16) * 0.2)(D, F) * (D ** -0.5)),
            "w_down": _w((lambda *s: torch.randn(*s, dtype=torch.bfloat16) * 0.2)(F, D) * (F ** -0.5)),
        }
    _B_in = _B_setup()

    return {
        "A_q": _A_in["q"],
        "A_k": _A_in["k"],
        "A_v": _A_in["v"],
        "A_shift_k": _A_in["shift_k"],
        "A_ssm_k": _A_in["ssm_k"],
        "A_ssm_D": _A_in["ssm_D"],
        "B_x": _B_in["x"],
        "B_w_gate": _B_in["w_gate"],
        "B_w_up": _B_in["w_up"],
        "B_w_down": _B_in["w_down"],
    }

def reference(A_q, A_k, A_v, A_shift_k, A_ssm_k, A_ssm_D, B_x, B_w_gate, B_w_up, B_w_down):
    def _A_ref(q, k, v, shift_k, ssm_k, ssm_D):
        B, S, D = q.shape
        ks = shift_k.shape[-1]
        k_pad = _pad(k, ((0, 0), (ks - 1, 0), (0, 0)))
        k_shift = torch.zeros_like(k)
        for t in range(ks):
            k_shift = k_shift + k_pad[:, t:t + S, :] * shift_k[:, ks - 1 - t][None, None, :]
        kv = k_shift * v
        L = 2 * S
        kv_pad = _pad(kv, ((0, 0), (0, S), (0, 0)))
        kf_pad = _pad(ssm_k, ((0, 0), (0, S)))
        kv_f = (lambda x, axes=(-2,-1): torch.fft.rfft2(x.float(), dim=axes))(kv_pad[:, None, :, :], axes=(1, 2))
        kf_f = (lambda x, axes=(-2,-1): torch.fft.rfft2(x.float(), dim=axes))(kf_pad[:, None, :], axes=(1, 2))
        kf_f = (lambda x, *d: x.permute(*d))(kf_f, 1, 2, 0)
        y_f = kv_f * kf_f[None, :, :, :]
        y = (lambda x, s, axes=(-2,-1): torch.fft.irfft2(x, s=s, dim=axes).to(torch.bfloat16))(y_f, (1, L), axes=(1, 2))[:, 0, :S, :]
        y = y + kv * ssm_D[None, None, :]
        return q * y

    def _B_ref(x, w_gate, w_up, w_down):
        g = torch.einsum("bsd,df->bsf", x, w_gate)
        u = torch.einsum("bsd,df->bsf", x, w_up)
        h = g * u
        return torch.einsum("bsf,fd->bsd", h, w_down)

    x = A_q
    xn = _layernorm(x, axis=-1)
    return x + _A_ref(xn, A_k, A_v, A_shift_k, A_ssm_k, A_ssm_D) + _B_ref(xn, B_w_gate, B_w_up, B_w_down)
```

```cpp
#include <cuda_runtime.h>
#include <cuda_bf16.h>
#include <cuda.h>
#include <stdint.h>

namespace {

constexpr int SEQ = 2048, DM = 512, FF = 1792;
constexpr int NCTA = 128;
constexpr int NTHREADS = 384;
constexpr int NSTAGE = 5;
constexpr int STAGE_BYTES = 16384;

constexpr uint32_t SM_X = 0;
constexpr uint32_t SM_RING = 131072;
constexpr uint32_t SM_MISC = SM_RING + NSTAGE * STAGE_BYTES;
constexpr uint32_t SM_BARS = SM_MISC;
constexpr uint32_t SM_STATS = SM_MISC + 256;
constexpr uint32_t SM_CS = SM_STATS + 1024;
constexpr uint32_t SM_CSTMP = SM_CS + 1792;
constexpr uint32_t SM_EPOCH = SM_CSTMP + 512;
constexpr uint32_t SM_TOTAL = SM_EPOCH + 64;
constexpr int RB_Z = 25;
constexpr int RB_R1 = (128 + RB_Z) * 16;
constexpr int RB_CH = 2 * RB_R1;
constexpr int CONV_CH = RB_CH + 4096;
constexpr uint32_t SM_CONV = 0;
constexpr uint32_t SM_RED = 3 * 16384;
constexpr uint32_t SM_YT = 5 * 16384;
constexpr uint32_t SM_XE = 6 * 16384;

constexpr int B_FULL = 0, B_EMPTY = NSTAGE, B_XFULL = 2 * NSTAGE, B_CONV = B_XFULL + 8, B_YT = B_CONV + 4,
              B_STATS = B_YT + 1, B_G1DONE = B_STATS + 1, B_COUNT = B_G1DONE + 1;
static_assert(B_COUNT * 8 <= 256, "barrier space");

__device__ uint4 g_hfrag[32 * 112 * 4 * 32];
__device__ __align__(128) uint8_t g_rb[DM * RB_CH];
__device__ __align__(128) __nv_bfloat16 g_yT[DM * SEQ];
__device__ float2 g_stats[SEQ];
__device__ float g_cs[2 * FF];
__device__ unsigned g_launch[NCTA];
__device__ unsigned g_cnt_prep[32];
__device__ unsigned g_cnt_kv[32];
__device__ unsigned g_cnt_y[4 * 32];
__device__ unsigned g_flag_h[32 * 2 * 4 * 8];

struct Params {
    CUtensorMap tm_x, tm_gA, tm_gB, tm_uA, tm_uB, tm_w2, tm_yT, tm_out;
    const __nv_bfloat16 *q, *k, *v, *shift_k, *ssm_k, *ssm_D, *wg, *wu, *wd;
};

__device__ __forceinline__ void wgmma_rs_n32(float (&d)[16], uint32_t a0, uint32_t a1, uint32_t a2, uint32_t a3, uint64_t db, int sc) {
  asm volatile("{\n.reg .pred p;\nsetp.ne.b32 p, %21, 0;\n"
    "wgmma.mma_async.sync.aligned.m64n32k16.f32.bf16.bf16 {%0,%1,%2,%3,%4,%5,%6,%7,%8,%9,%10,%11,%12,%13,%14,%15}, {%16,%17,%18,%19}, %20, p, 1, 1, 0;\n}\n"
    : "+f"(d[0]),"+f"(d[1]),"+f"(d[2]),"+f"(d[3]),"+f"(d[4]),"+f"(d[5]),"+f"(d[6]),"+f"(d[7]),"+f"(d[8]),"+f"(d[9]),"+f"(d[10]),"+f"(d[11]),"+f"(d[12]),"+f"(d[13]),"+f"(d[14]),"+f"(d[15])
    : "r"(a0),"r"(a1),"r"(a2),"r"(a3),"l"(db),"r"(sc));
}
__device__ __forceinline__ void wgmma_rs_n128_tb(float (&d)[64], uint32_t a0, uint32_t a1, uint32_t a2, uint32_t a3, uint64_t db, int sc) {
  asm volatile("{\n.reg .pred p;\nsetp.ne.b32 p, %69, 0;\n"
    "wgmma.mma_async.sync.aligned.m64n128k16.f32.bf16.bf16 {%0,%1,%2,%3,%4,%5,%6,%7,%8,%9,%10,%11,%12,%13,%14,%15,%16,%17,%18,%19,%20,%21,%22,%23,%24,%25,%26,%27,%28,%29,%30,%31,%32,%33,%34,%35,%36,%37,%38,%39,%40,%41,%42,%43,%44,%45,%46,%47,%48,%49,%50,%51,%52,%53,%54,%55,%56,%57,%58,%59,%60,%61,%62,%63}, {%64,%65,%66,%67}, %68, p, 1, 1, 1;\n}\n"
    : "+f"(d[0]),"+f"(d[1]),"+f"(d[2]),"+f"(d[3]),"+f"(d[4]),"+f"(d[5]),"+f"(d[6]),"+f"(d[7]),"+f"(d[8]),"+f"(d[9]),"+f"(d[10]),"+f"(d[11]),"+f"(d[12]),"+f"(d[13]),"+f"(d[14]),"+f"(d[15]),"+f"(d[16]),"+f"(d[17]),"+f"(d[18]),"+f"(d[19]),"+f"(d[20]),"+f"(d[21]),"+f"(d[22]),"+f"(d[23]),"+f"(d[24]),"+f"(d[25]),"+f"(d[26]),"+f"(d[27]),"+f"(d[28]),"+f"(d[29]),"+f"(d[30]),"+f"(d[31]),"+f"(d[32]),"+f"(d[33]),"+f"(d[34]),"+f"(d[35]),"+f"(d[36]),"+f"(d[37]),"+f"(d[38]),"+f"(d[39]),"+f"(d[40]),"+f"(d[41]),"+f"(d[42]),"+f"(d[43]),"+f"(d[44]),"+f"(d[45]),"+f"(d[46]),"+f"(d[47]),"+f"(d[48]),"+f"(d[49]),"+f"(d[50]),"+f"(d[51]),"+f"(d[52]),"+f"(d[53]),"+f"(d[54]),"+f"(d[55]),"+f"(d[56]),"+f"(d[57]),"+f"(d[58]),"+f"(d[59]),"+f"(d[60]),"+f"(d[61]),"+f"(d[62]),"+f"(d[63])
    : "r"(a0),"r"(a1),"r"(a2),"r"(a3),"l"(db),"r"(sc));
}
__device__ __forceinline__ void wgmma_ss_n256_tb(float (&d)[128], uint64_t da, uint64_t db, int sc) {
  asm volatile("{\n.reg .pred p;\nsetp.ne.b32 p, %130, 0;\n"
    "wgmma.mma_async.sync.aligned.m64n256k16.f32.bf16.bf16 {%0,%1,%2,%3,%4,%5,%6,%7,%8,%9,%10,%11,%12,%13,%14,%15,%16,%17,%18,%19,%20,%21,%22,%23,%24,%25,%26,%27,%28,%29,%30,%31,%32,%33,%34,%35,%36,%37,%38,%39,%40,%41,%42,%43,%44,%45,%46,%47,%48,%49,%50,%51,%52,%53,%54,%55,%56,%57,%58,%59,%60,%61,%62,%63,%64,%65,%66,%67,%68,%69,%70,%71,%72,%73,%74,%75,%76,%77,%78,%79,%80,%81,%82,%83,%84,%85,%86,%87,%88,%89,%90,%91,%92,%93,%94,%95,%96,%97,%98,%99,%100,%101,%102,%103,%104,%105,%106,%107,%108,%109,%110,%111,%112,%113,%114,%115,%116,%117,%118,%119,%120,%121,%122,%123,%124,%125,%126,%127}, %128, %129, p, 1, 1, 0, 1;\n}\n"
    : "+f"(d[0]),"+f"(d[1]),"+f"(d[2]),"+f"(d[3]),"+f"(d[4]),"+f"(d[5]),"+f"(d[6]),"+f"(d[7]),"+f"(d[8]),"+f"(d[9]),"+f"(d[10]),"+f"(d[11]),"+f"(d[12]),"+f"(d[13]),"+f"(d[14]),"+f"(d[15]),"+f"(d[16]),"+f"(d[17]),"+f"(d[18]),"+f"(d[19]),"+f"(d[20]),"+f"(d[21]),"+f"(d[22]),"+f"(d[23]),"+f"(d[24]),"+f"(d[25]),"+f"(d[26]),"+f"(d[27]),"+f"(d[28]),"+f"(d[29]),"+f"(d[30]),"+f"(d[31]),"+f"(d[32]),"+f"(d[33]),"+f"(d[34]),"+f"(d[35]),"+f"(d[36]),"+f"(d[37]),"+f"(d[38]),"+f"(d[39]),"+f"(d[40]),"+f"(d[41]),"+f"(d[42]),"+f"(d[43]),"+f"(d[44]),"+f"(d[45]),"+f"(d[46]),"+f"(d[47]),"+f"(d[48]),"+f"(d[49]),"+f"(d[50]),"+f"(d[51]),"+f"(d[52]),"+f"(d[53]),"+f"(d[54]),"+f"(d[55]),"+f"(d[56]),"+f"(d[57]),"+f"(d[58]),"+f"(d[59]),"+f"(d[60]),"+f"(d[61]),"+f"(d[62]),"+f"(d[63]),"+f"(d[64]),"+f"(d[65]),"+f"(d[66]),"+f"(d[67]),"+f"(d[68]),"+f"(d[69]),"+f"(d[70]),"+f"(d[71]),"+f"(d[72]),"+f"(d[73]),"+f"(d[74]),"+f"(d[75]),"+f"(d[76]),"+f"(d[77]),"+f"(d[78]),"+f"(d[79]),"+f"(d[80]),"+f"(d[81]),"+f"(d[82]),"+f"(d[83]),"+f"(d[84]),"+f"(d[85]),"+f"(d[86]),"+f"(d[87]),"+f"(d[88]),"+f"(d[89]),"+f"(d[90]),"+f"(d[91]),"+f"(d[92]),"+f"(d[93]),"+f"(d[94]),"+f"(d[95]),"+f"(d[96]),"+f"(d[97]),"+f"(d[98]),"+f"(d[99]),"+f"(d[100]),"+f"(d[101]),"+f"(d[102]),"+f"(d[103]),"+f"(d[104]),"+f"(d[105]),"+f"(d[106]),"+f"(d[107]),"+f"(d[108]),"+f"(d[109]),"+f"(d[110]),"+f"(d[111]),"+f"(d[112]),"+f"(d[113]),"+f"(d[114]),"+f"(d[115]),"+f"(d[116]),"+f"(d[117]),"+f"(d[118]),"+f"(d[119]),"+f"(d[120]),"+f"(d[121]),"+f"(d[122]),"+f"(d[123]),"+f"(d[124]),"+f"(d[125]),"+f"(d[126]),"+f"(d[127])
    : "l"(da),"l"(db),"r"(sc));
}
__device__ __forceinline__ void wgmma_ss_n192_tb(float (&d)[96], uint64_t da, uint64_t db, int sc) {
  asm volatile("{\n.reg .pred p;\nsetp.ne.b32 p, %98, 0;\n"
    "wgmma.mma_async.sync.aligned.m64n192k16.f32.bf16.bf16 {%0,%1,%2,%3,%4,%5,%6,%7,%8,%9,%10,%11,%12,%13,%14,%15,%16,%17,%18,%19,%20,%21,%22,%23,%24,%25,%26,%27,%28,%29,%30,%31,%32,%33,%34,%35,%36,%37,%38,%39,%40,%41,%42,%43,%44,%45,%46,%47,%48,%49,%50,%51,%52,%53,%54,%55,%56,%57,%58,%59,%60,%61,%62,%63,%64,%65,%66,%67,%68,%69,%70,%71,%72,%73,%74,%75,%76,%77,%78,%79,%80,%81,%82,%83,%84,%85,%86,%87,%88,%89,%90,%91,%92,%93,%94,%95}, %96, %97, p, 1, 1, 0, 1;\n}\n"
    : "+f"(d[0]),"+f"(d[1]),"+f"(d[2]),"+f"(d[3]),"+f"(d[4]),"+f"(d[5]),"+f"(d[6]),"+f"(d[7]),"+f"(d[8]),"+f"(d[9]),"+f"(d[10]),"+f"(d[11]),"+f"(d[12]),"+f"(d[13]),"+f"(d[14]),"+f"(d[15]),"+f"(d[16]),"+f"(d[17]),"+f"(d[18]),"+f"(d[19]),"+f"(d[20]),"+f"(d[21]),"+f"(d[22]),"+f"(d[23]),"+f"(d[24]),"+f"(d[25]),"+f"(d[26]),"+f"(d[27]),"+f"(d[28]),"+f"(d[29]),"+f"(d[30]),"+f"(d[31]),"+f"(d[32]),"+f"(d[33]),"+f"(d[34]),"+f"(d[35]),"+f"(d[36]),"+f"(d[37]),"+f"(d[38]),"+f"(d[39]),"+f"(d[40]),"+f"(d[41]),"+f"(d[42]),"+f"(d[43]),"+f"(d[44]),"+f"(d[45]),"+f"(d[46]),"+f"(d[47]),"+f"(d[48]),"+f"(d[49]),"+f"(d[50]),"+f"(d[51]),"+f"(d[52]),"+f"(d[53]),"+f"(d[54]),"+f"(d[55]),"+f"(d[56]),"+f"(d[57]),"+f"(d[58]),"+f"(d[59]),"+f"(d[60]),"+f"(d[61]),"+f"(d[62]),"+f"(d[63]),"+f"(d[64]),"+f"(d[65]),"+f"(d[66]),"+f"(d[67]),"+f"(d[68]),"+f"(d[69]),"+f"(d[70]),"+f"(d[71]),"+f"(d[72]),"+f"(d[73]),"+f"(d[74]),"+f"(d[75]),"+f"(d[76]),"+f"(d[77]),"+f"(d[78]),"+f"(d[79]),"+f"(d[80]),"+f"(d[81]),"+f"(d[82]),"+f"(d[83]),"+f"(d[84]),"+f"(d[85]),"+f"(d[86]),"+f"(d[87]),"+f"(d[88]),"+f"(d[89]),"+f"(d[90]),"+f"(d[91]),"+f"(d[92]),"+f"(d[93]),"+f"(d[94]),"+f"(d[95])
    : "l"(da),"l"(db),"r"(sc));
}


__device__ __forceinline__ uint32_t smem_u32(const void* p) { return (uint32_t)__cvta_generic_to_shared(p); }
__device__ __forceinline__ void mbar_init(uint32_t bar, uint32_t cnt) { asm volatile("mbarrier.init.shared::cta.b64 [%0], %1;" :: "r"(bar), "r"(cnt)); }
__device__ __forceinline__ void mbar_expect_tx(uint32_t bar, uint32_t bytes) { asm volatile("mbarrier.arrive.expect_tx.shared::cta.b64 _, [%0], %1;" :: "r"(bar), "r"(bytes) : "memory"); }
__device__ __forceinline__ void mbar_arrive(uint32_t bar) { asm volatile("mbarrier.arrive.shared::cta.b64 _, [%0];" :: "r"(bar) : "memory"); }
__device__ __forceinline__ void mbar_arrive_cluster(uint32_t cbar, uint32_t cnt) { asm volatile("mbarrier.arrive.shared::cluster.b64 _, [%0], %1;" :: "r"(cbar), "r"(cnt) : "memory"); }
__device__ __forceinline__ uint32_t mapa(uint32_t a, uint32_t rank) { uint32_t r; asm volatile("mapa.shared::cluster.u32 %0, %1, %2;" : "=r"(r) : "r"(a), "r"(rank)); return r; }
__device__ __forceinline__ void mbar_wait(uint32_t bar, uint32_t parity) {
    uint32_t ok; uint32_t n = 0;
    do {
        asm volatile("{\n.reg .pred p;\nmbarrier.try_wait.parity.shared::cta.b64 p, [%1], %2;\nselp.u32 %0, 1, 0, p;\n}" : "=r"(ok) : "r"(bar), "r"(parity) : "memory");
    } while (!ok && ++n < (1u << 20));
}
__device__ __forceinline__ void flag_wait(const unsigned* p, unsigned target) {
    unsigned v; uint32_t n = 0;
    do {
        asm volatile("ld.acquire.gpu.global.u32 %0, [%1];" : "=r"(v) : "l"(p) : "memory");
    } while ((int)(v - target) < 0 && ++n < (1u << 17));
}
__device__ __forceinline__ void flag_add(unsigned* p) {
    asm volatile("fence.acq_rel.gpu;\nred.relaxed.gpu.global.add.u32 [%0], 1;" :: "l"(p) : "memory");
}
__device__ __forceinline__ void fence_async() { asm volatile("fence.proxy.async;" ::: "memory"); }
__device__ __forceinline__ uint64_t make_desc(uint32_t addr, uint32_t lbo, uint32_t sbo, uint32_t swz) {
    return (uint64_t)((addr & 0x3FFFF) >> 4) | ((uint64_t)((lbo & 0x3FFFF) >> 4) << 16) | ((uint64_t)((sbo & 0x3FFFF) >> 4) << 32) | ((uint64_t)swz << 62);
}
__device__ __forceinline__ void tma2d(uint32_t dst, const CUtensorMap* tm, int c0, int c1, uint32_t bar) {
    asm volatile("cp.async.bulk.tensor.2d.shared::cluster.global.mbarrier::complete_tx::bytes [%0], [%1, {%3, %4}], [%2];"
        :: "r"(dst), "l"((uint64_t)tm), "r"(bar), "r"(c0), "r"(c1) : "memory");
}
__device__ __forceinline__ void tma3d_mc(uint32_t dst, const CUtensorMap* tm, int c0, int c1, int c2, uint32_t bar) {
    asm volatile("cp.async.bulk.tensor.3d.shared::cluster.global.mbarrier::complete_tx::bytes.multicast::cluster [%0], [%1, {%3, %4, %5}], [%2], %6;"
        :: "r"(dst), "l"((uint64_t)tm), "r"(bar), "r"(c0), "r"(c1), "r"(c2), "h"((uint16_t)3) : "memory");
}
__device__ __forceinline__ void bulk_g2s(uint32_t dst, const void* src, uint32_t bytes, uint32_t bar) {
    asm volatile("cp.async.bulk.shared::cluster.global.mbarrier::complete_tx::bytes [%0], [%1], %2, [%3];"
        :: "r"(dst), "l"(src), "r"(bytes), "r"(bar) : "memory");
}
__device__ __forceinline__ void tma2d_store(const CUtensorMap* tm, int c0, int c1, uint32_t src) {
    asm volatile("cp.async.bulk.tensor.2d.global.shared::cta.bulk_group [%0, {%2, %3}], [%1];"
        :: "l"((uint64_t)tm), "r"(src), "r"(c0), "r"(c1) : "memory");
}
__device__ __forceinline__ void l2_prefetch(const void* p, uint32_t bytes) {
    asm volatile("cp.async.bulk.prefetch.L2.global [%0], %1;" :: "l"(p), "r"(bytes) : "memory");
}
__device__ __forceinline__ uint32_t lds32(uint32_t a) { uint32_t v; asm volatile("ld.shared.u32 %0, [%1];" : "=r"(v) : "r"(a)); return v; }
__device__ __forceinline__ float2 lds64f(uint32_t a) { float2 v; asm volatile("ld.shared.v2.f32 {%0,%1}, [%2];" : "=f"(v.x), "=f"(v.y) : "r"(a)); return v; }
__device__ __forceinline__ float4 lds128f(uint32_t a) { float4 v; asm volatile("ld.shared.v4.f32 {%0,%1,%2,%3}, [%4];" : "=f"(v.x), "=f"(v.y), "=f"(v.z), "=f"(v.w) : "r"(a) : "memory"); return v; }
__device__ __forceinline__ void sts32(uint32_t a, uint32_t v) { asm volatile("st.shared.u32 [%0], %1;" :: "r"(a), "r"(v) : "memory"); }
__device__ __forceinline__ void sts128f(uint32_t a, float x, float y, float z, float w) { asm volatile("st.shared.v4.f32 [%0], {%1,%2,%3,%4};" :: "r"(a), "f"(x), "f"(y), "f"(z), "f"(w) : "memory"); }
__device__ __forceinline__ uint4 ldg_cg128(const void* p) { uint4 v; asm volatile("ld.global.cg.v4.u32 {%0,%1,%2,%3}, [%4];" : "=r"(v.x), "=r"(v.y), "=r"(v.z), "=r"(v.w) : "l"(p)); return v; }
__device__ __forceinline__ uint4 ldg_nc128(const void* p) { uint4 v; asm volatile("ld.global.nc.L1::no_allocate.v4.u32 {%0,%1,%2,%3}, [%4];" : "=r"(v.x), "=r"(v.y), "=r"(v.z), "=r"(v.w) : "l"(p)); return v; }
#define WG_FENCE() asm volatile("wgmma.fence.sync.aligned;\n" ::: "memory")
#define WG_COMMIT() asm volatile("wgmma.commit_group.sync.aligned;\n" ::: "memory")
template<int N> __device__ __forceinline__ void wg_wait() { asm volatile("wgmma.wait_group.sync.aligned %0;\n" :: "n"(N) : "memory"); }
__device__ __forceinline__ void named_bar(int id, int n) { asm volatile("bar.sync %0, %1;" :: "r"(id), "r"(n) : "memory"); }

__device__ __forceinline__ float bf_lo(uint32_t u) { return __uint_as_float(u << 16); }
__device__ __forceinline__ float bf_hi(uint32_t u) { return __uint_as_float(u & 0xFFFF0000u); }
__device__ __forceinline__ uint32_t pack_bf(float lo, float hi) { uint32_t r; asm("cvt.rn.bf16x2.f32 %0, %1, %2;" : "=r"(r) : "f"(hi), "f"(lo)); return r; }
__device__ __forceinline__ float bf_round(float x) { return __bfloat162float(__float2bfloat16_rn(x)); }
__device__ __forceinline__ uint32_t bmul2(uint32_t a, uint32_t b) { uint32_t r; asm("mul.rn.bf16x2 %0, %1, %2;" : "=r"(r) : "r"(a), "r"(b)); return r; }
__device__ __forceinline__ uint32_t badd2(uint32_t a, uint32_t b) { uint32_t r; asm("add.rn.bf16x2 %0, %1, %2;" : "=r"(r) : "r"(a), "r"(b)); return r; }
__device__ __forceinline__ uint32_t bsub2(uint32_t a, uint32_t b) { uint32_t r; asm("sub.rn.bf16x2 %0, %1, %2;" : "=r"(r) : "r"(a), "r"(b)); return r; }

__device__ __forceinline__ int blk_f0(int bi, int j) {
    if (bi < 32) return 224 * ((j + (bi >> 2)) & 7) + 32 * (bi & 3);
    int b2 = bi - 32; int q3 = (b2 * 11) >> 5;
    return 224 * ((j + q3) & 7) + 128 + 32 * (b2 - 3 * q3);
}

template<int NB>
__device__ __forceinline__ void gemm1_pass(uint32_t sb, int wgi, int warp4, int lane, int& it, uint32_t e_loc, uint32_t e_rem,
                                           int rb64, int ks0, int csoff, unsigned* flag, bool passA) {
    float acc[NB * 32];
    const uint64_t descA0 = make_desc(sb + SM_X + wgi * 8192, 16, 1024, 1);
    const uint64_t descB0 = make_desc(sb + SM_RING, 2048, 512, 2);
    #pragma unroll 1
    for (int sl = 0; sl < 8; sl++) {
        if (passA) mbar_wait(sb + SM_BARS + (B_XFULL + sl) * 8, 0);
        #pragma unroll
        for (int hf = 0; hf < 2; hf++) {
            const int st = it % NSTAGE;
            mbar_wait(sb + SM_BARS + (B_FULL + st) * 8, (it / NSTAGE) & 1);
            WG_FENCE();
            #pragma unroll
            for (int kk = 0; kk < 2; kk++) {
                uint64_t da = descA0 + (uint64_t)(sl * 1024 + hf * 4 + kk * 2);
                uint64_t db = descB0 + (uint64_t)(st * 1024 + kk * 64);
                int sc = (sl | hf | kk) ? 1 : 0;
                if constexpr (NB == 4) wgmma_ss_n256_tb(acc, da, db, sc); else wgmma_ss_n192_tb(acc, da, db, sc);
            }
            WG_COMMIT();
            wg_wait<1>();
            {
                const int ps = (it + NSTAGE - 1) % NSTAGE;
                if (lane == 0 && (sl | hf)) { mbar_arrive_cluster(e_loc + ps * 8, 1); mbar_arrive_cluster(e_rem + ps * 8, 1); }
            }
            it++;
        }
    }
    wg_wait<0>();
    {
        const int ps = (it + NSTAGE - 1) % NSTAGE;
        if (lane == 0) {
            mbar_arrive_cluster(e_loc + ps * 8, 1); mbar_arrive_cluster(e_rem + ps * 8, 1);
            if (!passA) mbar_arrive(sb + SM_BARS + B_G1DONE * 8);
        }
    }
    if (passA) mbar_wait(sb + SM_BARS + B_STATS * 8, 0);
    const int g = lane >> 2, c = lane & 3;
    const int r0 = wgi * 64 + warp4 * 16 + g;
    const float2 s0 = lds64f(sb + SM_STATS + r0 * 8), s1 = lds64f(sb + SM_STATS + (r0 + 8) * 8);
    const uint32_t csg = sb + SM_CS + (csoff + 2 * c) * 4, csu = csg + 224 * 4;
    uint4* dst = g_hfrag + ((size_t)(rb64 * 112 + ks0) * 4 + warp4) * 32 + lane;
    #pragma unroll
    for (int kk = 0; kk < NB * 2; kk++) {
        uint32_t h[4];
        #pragma unroll
        for (int tt = 0; tt < 2; tt++) {
            const int t = 2 * kk + tt;
            const float2 cg = lds64f(csg + t * 32), cu = lds64f(csu + t * 32);
            const float* ag = &acc[4 * t];
            const float* au = &acc[NB * 16 + 4 * t];
            uint32_t g0 = pack_bf((ag[0] - s0.x * cg.x) * s0.y, (ag[1] - s0.x * cg.y) * s0.y);
            uint32_t u0 = pack_bf((au[0] - s0.x * cu.x) * s0.y, (au[1] - s0.x * cu.y) * s0.y);
            uint32_t g1 = pack_bf((ag[2] - s1.x * cg.x) * s1.y, (ag[3] - s1.x * cg.y) * s1.y);
            uint32_t u1 = pack_bf((au[2] - s1.x * cu.x) * s1.y, (au[3] - s1.x * cu.y) * s1.y);
            h[2 * tt] = bmul2(g0, u0);
            h[2 * tt + 1] = bmul2(g1, u1);
        }
        dst[kk * 128] = make_uint4(h[0], h[1], h[2], h[3]);
    }
    __syncwarp();
    if (lane == 0) flag_add(flag);
}

template<int P>
__device__ __forceinline__ void conv_load_a(uint32_t (&a)[2][4], uint32_t hk_lane, int m_lane) {
    #pragma unroll
    for (int q = 0; q < 2; q++) {
        const int off = (8 * q + 64 * P) * 4;
        uint32_t w0, w1, w2;
        if (P == 0 && q == 0) {
            w0 = (m_lane + 0 < 8) ? 0u : lds32(hk_lane + off);
            w1 = (m_lane + 1 < 8) ? 0u : lds32(hk_lane + off + 4);
            w2 = (m_lane + 2 < 8) ? 0u : lds32(hk_lane + off + 8);
        } else {
            w0 = lds32(hk_lane + off); w1 = lds32(hk_lane + off + 4); w2 = lds32(hk_lane + off + 8);
        }
        a[q][0] = w1;
        a[q][1] = __byte_perm(w0, w1, 0x5432);
        a[q][2] = w2;
        a[q][3] = __byte_perm(w1, w2, 0x5432);
    }
}
template<int P>
__device__ __forceinline__ void conv_steps(float (&acc)[4][16], uint32_t (&a)[4][2][4], uint64_t db, uint32_t hk_lane, int m_lane) {
    if constexpr (P < 16) {
        WG_FENCE();
        #pragma unroll
        for (int q = 0; q < 2; q++) {
            #pragma unroll
            for (int bq = P / 4; bq < 4; bq++)
                wgmma_rs_n32(acc[bq], a[P & 3][q][0], a[P & 3][q][1], a[P & 3][q][2], a[P & 3][q][3],
                             db + (uint64_t)(int64_t)(32 * bq - 8 * P - q), (P == 0 && q == 0) ? 0 : 1);
        }
        WG_COMMIT();
        if constexpr (P >= 1 && P + 3 < 16) {
            wg_wait<1>();
            conv_load_a<P + 3>(a[(P + 3) & 3], hk_lane, m_lane);
        }
        conv_steps<P + 1>(acc, a, db, hk_lane, m_lane);
    }
}

__global__ void __cluster_dims__(2, 1, 1) __launch_bounds__(NTHREADS, 1)
fused_kernel(const __grid_constant__ Params p) {
    extern __shared__ __align__(1024) uint8_t smem_raw[];
    const uint32_t sb = smem_u32(smem_raw);
    const int tid = threadIdx.x, warp = tid >> 5, lane = tid & 31;
    const int b = blockIdx.x;
    const int rank = b & 1;
    const int j = (b >> 1) & 7;
    const int i = ((b >> 4) << 1) | rank;
    const int cb = j >> 1;
    const int rbG2 = 2 * i + (j & 1);

    if (tid == 0) {
        for (int s = 0; s < NSTAGE; s++) { mbar_init(sb + SM_BARS + (B_FULL + s) * 8, 1); mbar_init(sb + SM_BARS + (B_EMPTY + s) * 8, 16); }
        for (int s = 0; s < 8; s++) mbar_init(sb + SM_BARS + (B_XFULL + s) * 8, 1);
        for (int s = 0; s < 4; s++) mbar_init(sb + SM_BARS + (B_CONV + s) * 8, 1);
        mbar_init(sb + SM_BARS + B_YT * 8, 1);
        mbar_init(sb + SM_BARS + B_STATS * 8, 1);
        mbar_init(sb + SM_BARS + B_G1DONE * 8, 8);
        asm volatile("fence.mbarrier_init.release.cluster;" ::: "memory");
        fence_async();
        for (int sl = 0; sl < 8; sl++) {
            const int kc = (sl + 2 * cb + 2) & 7;
            mbar_expect_tx(sb + SM_BARS + (B_XFULL + sl) * 8, 16384);
            tma2d(sb + SM_X + sl * 16384, &p.tm_x, 64 * kc, 128 * i, sb + SM_BARS + (B_XFULL + sl) * 8);
        }
    }
    if (tid == 32) {
        unsigned L = g_launch[b];
        g_launch[b] = L + 1;
        sts32(sb + SM_EPOCH, L + 1);
    }
    __syncthreads();
    asm volatile("barrier.cluster.arrive.release.aligned;\nbarrier.cluster.wait.acquire.aligned;\n" ::: "memory");
    const unsigned ep = lds32(sb + SM_EPOCH);

    if (warp < 8) {
        const int wgi = warp >> 2, warp4 = warp & 3;
        const uint32_t e_loc = mapa(sb + SM_BARS + B_EMPTY * 8, rank), e_rem = mapa(sb + SM_BARS + B_EMPTY * 8, rank ^ 1);
        if (wgi == 1) {
            uint4 xr[4][2];
            #pragma unroll
            for (int rr = 0; rr < 4; rr++) {
                const __nv_bfloat16* row = p.q + (size_t)(16 * b + 4 * warp4 + rr) * DM;
                xr[rr][0] = ldg_nc128(row + 8 * lane);
                xr[rr][1] = ldg_nc128(row + 256 + 8 * lane);
            }
            float csum[8];
            #pragma unroll
            for (int e = 0; e < 8; e++) csum[e] = 0.f;
            if (b < 112) {
                const __nv_bfloat16* wsrc = (b < 56 ? p.wg : p.wu) + 32 * (b < 56 ? b : b - 56) + 8 * (lane & 3) + (size_t)(128 * warp4 + (lane >> 2)) * FF;
                #pragma unroll
                for (int hh = 0; hh < 2; hh++) {
                    uint4 wv[8];
                    #pragma unroll
                    for (int t = 0; t < 8; t++) wv[t] = ldg_nc128(wsrc + (size_t)(hh * 64 + t * 8) * FF);
                    #pragma unroll
                    for (int t = 0; t < 8; t++) {
                        csum[0] += bf_lo(wv[t].x); csum[1] += bf_hi(wv[t].x); csum[2] += bf_lo(wv[t].y); csum[3] += bf_hi(wv[t].y);
                        csum[4] += bf_lo(wv[t].z); csum[5] += bf_hi(wv[t].z); csum[6] += bf_lo(wv[t].w); csum[7] += bf_hi(wv[t].w);
                    }
                }
            }
            #pragma unroll
            for (int rr = 0; rr < 4; rr++) {
                float v[16];
                const uint32_t* u = (const uint32_t*)&xr[rr][0];
                #pragma unroll
                for (int e = 0; e < 8; e++) { v[2 * e] = bf_lo(u[e]); v[2 * e + 1] = bf_hi(u[e]); }
                float s = 0.f;
                #pragma unroll
                for (int e = 0; e < 16; e++) s += v[e];
                #pragma unroll
                for (int o = 16; o > 0; o >>= 1) s += __shfl_xor_sync(0xffffffffu, s, o);
                const float mean = s * (1.0f / DM);
                float ss = 0.f;
                #pragma unroll
                for (int e = 0; e < 16; e++) { float d = v[e] - mean; ss += d * d; }
                #pragma unroll
                for (int o = 16; o > 0; o >>= 1) ss += __shfl_xor_sync(0xffffffffu, ss, o);
                if (lane == 0) {
                    const float var_b = bf_round(ss * (1.0f / DM));
                    const float sd = bf_round(sqrtf(bf_round(var_b + 1e-5f)));
                    g_stats[16 * b + 4 * warp4 + rr] = make_float2(bf_round(mean), 1.0f / sd);
                }
            }
            #pragma unroll
            for (int e = 0; e < 8; e++) {
                csum[e] += __shfl_xor_sync(0xffffffffu, csum[e], 4);
                csum[e] += __shfl_xor_sync(0xffffffffu, csum[e], 8);
                csum[e] += __shfl_xor_sync(0xffffffffu, csum[e], 16);
            }
            if (lane < 4) {
                sts128f(sb + SM_CSTMP + (warp4 * 32 + lane * 8) * 4, csum[0], csum[1], csum[2], csum[3]);
                sts128f(sb + SM_CSTMP + (warp4 * 32 + lane * 8 + 4) * 4, csum[4], csum[5], csum[6], csum[7]);
            }
            named_bar(2, 128);
            if (warp4 == 0) {
                if (b < 112) {
                    float t = 0.f;
                    #pragma unroll
                    for (int ww = 0; ww < 4; ww++) t += __uint_as_float(lds32(sb + SM_CSTMP + (ww * 32 + lane) * 4));
                    g_cs[32 * b + lane] = t;
                }
                __syncwarp();
                if (lane == 0) flag_add(&g_cnt_prep[0]);
            }
        }
        int it = 0;
        const int rb64 = 2 * i + wgi;
        gemm1_pass<4>(sb, wgi, warp4, lane, it, e_loc, e_rem, rb64, 14 * j, 0, &g_flag_h[((rb64 * 2 + 0) * 4 + warp4) * 8], true);
        gemm1_pass<3>(sb, wgi, warp4, lane, it, e_loc, e_rem, rb64, 14 * j + 8, 128, &g_flag_h[((rb64 * 2 + 1) * 4 + warp4) * 8], false);

        const int g = lane >> 2, c = lane & 3;
        if (wgi == 0) {
            float acc[64];
            uint4 af[4][4];
            const uint4* hsrc = g_hfrag + ((size_t)rbG2 * 112 * 4 + warp4) * 32 + lane;
            const uint64_t descB0 = make_desc(sb + SM_RING, 4096, 1024, 1);
            if (lane == 0) flag_wait(&g_flag_h[((rbG2 * 2 + 0) * 4 + warp4) * 8], ep * 8);
            __syncwarp();
            auto load_group = [&](uint4 (&dstf)[4], int u) {
                #pragma unroll
                for (int hb = 0; hb < 2; hb++) {
                    const int ks = blk_f0(2 * u + hb, j) >> 4;
                    dstf[2 * hb] = ldg_cg128(hsrc + ks * 128);
                    dstf[2 * hb + 1] = ldg_cg128(hsrc + ks * 128 + 128);
                }
            };
            load_group(af[0], 0); load_group(af[1], 1); load_group(af[2], 2);
            auto g2_step = [&](int u, uint4 (&cur)[4], uint4 (&nxt)[4], bool do_load) {
                const int st = it % NSTAGE;
                mbar_wait(sb + SM_BARS + (B_FULL + st) * 8, (it / NSTAGE) & 1);
                WG_FENCE();
                #pragma unroll
                for (int kk = 0; kk < 4; kk++) {
                    uint64_t db = descB0 + (uint64_t)(st * 1024 + (kk >> 1) * 512 + (kk & 1) * 128);
                    wgmma_rs_n128_tb(acc, cur[kk].x, cur[kk].y, cur[kk].z, cur[kk].w, db, (u | kk) ? 1 : 0);
                }
                WG_COMMIT();
                wg_wait<1>();
                const int ps = (it + NSTAGE - 1) % NSTAGE;
                if (lane == 0 && u > 0 && u - 1 + NSTAGE < 28) { mbar_arrive_cluster(e_loc + ps * 8, 2); mbar_arrive_cluster(e_rem + ps * 8, 2); }
                if (u + 3 == 16) {
                    if (lane == 0) flag_wait(&g_flag_h[((rbG2 * 2 + 1) * 4 + warp4) * 8], ep * 8);
                    __syncwarp();
                }
                if (do_load) load_group(nxt, u + 3);
                it++;
            };
            #pragma unroll 1
            for (int u0 = 0; u0 < 24; u0 += 4) {
                g2_step(u0, af[0], af[3], true);
                g2_step(u0 + 1, af[1], af[0], true);
                g2_step(u0 + 2, af[2], af[1], true);
                g2_step(u0 + 3, af[3], af[2], true);
            }
            g2_step(24, af[0], af[3], true);
            g2_step(25, af[1], af[0], false);
            g2_step(26, af[2], af[1], false);
            g2_step(27, af[3], af[2], false);
            wg_wait<0>();
            mbar_wait(sb + SM_BARS + B_YT * 8, 0);
            const int r0 = (j & 1) * 64 + warp4 * 16 + g;
            const float2 s0 = lds64f(sb + SM_STATS + r0 * 8), s1 = lds64f(sb + SM_STATS + (r0 + 8) * 8);
            const uint32_t m0 = pack_bf(s0.x, s0.x), m1 = pack_bf(s1.x, s1.x);
            const uint32_t xrow0 = sb + SM_XE + r0 * 128 + c * 4, xrow1 = xrow0 + 8 * 128;
            const int mi = lane >> 3, lr = lane & 7;
            const uint32_t yaddr = sb + SM_YT + ((mi >> 1) * 8 + lr) * 128 + (((2 * warp4 + (mi & 1)) ^ lr) << 4);
            #pragma unroll
            for (int t2 = 0; t2 < 8; t2++) {
                uint32_t y[4];
                asm volatile("ldmatrix.sync.aligned.m8n8.x4.trans.shared.b16 {%0,%1,%2,%3}, [%4];"
                    : "=r"(y[0]), "=r"(y[1]), "=r"(y[2]), "=r"(y[3]) : "r"(yaddr + t2 * 2048) : "memory");
                #pragma unroll
                for (int tt = 0; tt < 2; tt++) {
                    const int t = 2 * t2 + tt;
                    const uint32_t off = (t >> 3) * 16384 + (((t & 7) ^ g) << 4);
                    const uint32_t x0 = lds32(xrow0 + off), x1 = lds32(xrow1 + off);
                    const uint32_t d0 = bsub2(x0, m0), d1 = bsub2(x1, m1);
                    const uint32_t n0 = pack_bf(bf_lo(d0) * s0.y, bf_hi(d0) * s0.y), n1 = pack_bf(bf_lo(d1) * s1.y, bf_hi(d1) * s1.y);
                    const uint32_t o0 = badd2(badd2(x0, bmul2(n0, y[2 * tt])), pack_bf(acc[4 * t], acc[4 * t + 1]));
                    const uint32_t o1 = badd2(badd2(x1, bmul2(n1, y[2 * tt + 1])), pack_bf(acc[4 * t + 2], acc[4 * t + 3]));
                    sts32(xrow0 + off, o0); sts32(xrow1 + off, o1);
                }
            }
            asm volatile("fence.proxy.async.shared::cta;" ::: "memory");
            named_bar(1, 128);
            if (tid == 0) {
                tma2d_store(&p.tm_out, 128 * cb, 64 * rbG2, sb + SM_XE + (j & 1) * 8192);
                tma2d_store(&p.tm_out, 128 * cb + 64, 64 * rbG2, sb + SM_XE + 16384 + (j & 1) * 8192);
                asm volatile("cp.async.bulk.commit_group;" ::: "memory");
                asm volatile("cp.async.bulk.wait_group.read 0;" ::: "memory");
            }
        } else {
            const int m_lane = g + 2 * c + 16 * warp4;
            const int cp = (c + warp4) & 3, ish = (c + warp4) >> 2;
            const uint32_t rdst = sb + SM_RED + warp4 * 8192 + ish * 512 + (g * 4 + cp) * 16;
            const uint32_t rsrc = sb + SM_RED + warp4 * 2048 + lane * 16;
            #pragma unroll 1
            for (int ch = 0; ch < 4; ch++) {
                const int gch = 4 * b + ch;
                const float dcoef = __bfloat162float(p.ssm_D[gch]);
                const uint32_t d2 = pack_bf(dcoef, dcoef);
                const uint32_t cbase = sb + SM_CONV + ch * CONV_CH;
                const uint64_t db = make_desc(cbase + RB_Z * 16, RB_R1, 128, 0);
                const uint32_t hk_lane = cbase + RB_CH + (m_lane - 8) * 4;
                float acc[4][16];
                uint32_t a[4][2][4];
                mbar_wait(sb + SM_BARS + (B_CONV + ch) * 8, 0);
                conv_load_a<0>(a[0], hk_lane, m_lane);
                conv_load_a<1>(a[1], hk_lane, m_lane);
                conv_load_a<2>(a[2], hk_lane, m_lane);
                conv_load_a<3>(a[3], hk_lane, m_lane);
                conv_steps<0>(acc, a, db, hk_lane, m_lane);
                wg_wait<0>();
                if (ch == 0) mbar_wait(sb + SM_BARS + B_G1DONE * 8, 0);
                else named_bar(2, 128);
                #pragma unroll
                for (int ii = 0; ii < 16; ii++) {
                    if (ii < 15 || ish == 0)
                        sts128f(rdst + ii * 512, acc[ii >> 2][4 * (ii & 3)], acc[ii >> 2][4 * (ii & 3) + 1], acc[ii >> 2][4 * (ii & 3) + 2], acc[ii >> 2][4 * (ii & 3) + 3]);
                }
                named_bar(2, 128);
                const uint32_t kvaddr = cbase + ((7 - g) & 1) * RB_R1 + (RB_Z + 32 * warp4 + 2 * c) * 16 + ((7 - g) >> 1) * 4;
                uint32_t* ydst = (uint32_t*)(g_yT + (size_t)gch * SEQ + 512 * warp4 + 32 * c + 2 * g);
                #pragma unroll
                for (int ii = 0; ii < 4; ii++) {
                    float4 s = lds128f(rsrc + ii * 512);
                    #pragma unroll
                    for (int ww = 1; ww < 4; ww++) {
                        float4 t = lds128f(rsrc + ww * 8192 + ii * 512);
                        if (ii == 0 && warp4 == 0 && c < ww) t = make_float4(0.f, 0.f, 0.f, 0.f);
                        s.x += t.x; s.y += t.y; s.z += t.z; s.w += t.w;
                    }
                    uint32_t k0 = lds32(kvaddr + ii * 128), k1 = lds32(kvaddr + ii * 128 + 16);
                    k0 = __byte_perm(k0, k0, 0x1032); k1 = __byte_perm(k1, k1, 0x1032);
                    ydst[ii * 64] = badd2(pack_bf(s.z, s.x), bmul2(k0, d2));
                    ydst[ii * 64 + 8] = badd2(pack_bf(s.w, s.y), bmul2(k1, d2));
                }
            }
            asm volatile("fence.proxy.async.global;" ::: "memory");
            __syncwarp();
            if (lane == 0) flag_add(&g_cnt_y[(b >> 5) * 32]);
        }
    } else if (warp == 8) {
        if (lane == 0) {
            int it = 0, st = 0; uint32_t ph = 1;
            #pragma unroll 1
            for (int pass = 0; pass < 2; pass++) {
                const int nb = pass ? 3 : 4;
                const CUtensorMap* tm = pass ? (rank ? &p.tm_uB : &p.tm_gB) : (rank ? &p.tm_uA : &p.tm_gA);
                const int cblk = 7 * j + (pass ? 4 : 0);
                #pragma unroll 1
                for (int s2 = 0; s2 < 16; s2++) {
                    mbar_wait(sb + SM_BARS + (B_EMPTY + st) * 8, ph);
                    const int k0 = ((s2 + 4 * cb + 4) & 15) * 32;
                    mbar_expect_tx(sb + SM_BARS + (B_FULL + st) * 8, nb * 4096);
                    tma3d_mc(sb + SM_RING + st * STAGE_BYTES + rank * nb * 2048, tm, 0, k0, cblk, sb + SM_BARS + (B_FULL + st) * 8);
                    if (it == 21 + NSTAGE) {
                        flag_wait(&g_cnt_kv[0], ep * 256);
                        fence_async();
                        for (int ch = 0; ch < 4; ch++) {
                            const uint32_t bar = sb + SM_BARS + (B_CONV + ch) * 8;
                            mbar_expect_tx(bar, CONV_CH);
                            bulk_g2s(sb + SM_CONV + ch * CONV_CH, g_rb + (size_t)(4 * b + ch) * RB_CH, RB_CH, bar);
                            bulk_g2s(sb + SM_CONV + ch * CONV_CH + RB_CH, p.ssm_k + (size_t)(4 * b + ch) * SEQ, 4096, bar);
                        }
                    }
                    it++;
                    if (++st == NSTAGE) { st = 0; ph ^= 1; }
                }
            }
            #pragma unroll 1
            for (int u = 0; u < 28; u++) {
                mbar_wait(sb + SM_BARS + (B_EMPTY + st) * 8, ph);
                mbar_expect_tx(sb + SM_BARS + (B_FULL + st) * 8, 16384);
                tma3d_mc(sb + SM_RING + st * STAGE_BYTES + rank * 8192, &p.tm_w2, 0, blk_f0(2 * u + rank, j), 2 * cb, sb + SM_BARS + (B_FULL + st) * 8);
                if (++st == NSTAGE) { st = 0; ph ^= 1; }
            }
            mbar_wait(sb + SM_BARS + B_G1DONE * 8, 0);
            flag_wait(&g_cnt_y[cb * 32], ep * 128);
            fence_async();
            mbar_expect_tx(sb + SM_BARS + B_YT * 8, 16384);
            tma2d(sb + SM_YT, &p.tm_yT, 64 * rbG2, 128 * cb, sb + SM_BARS + B_YT * 8);
        }
    } else if (warp < 11) {
        const int tt = tid - 288;
        uint32_t sk[4][4];
        {
            const uint4* sp = (const uint4*)(p.shift_k + 32 * tt);
            #pragma unroll
            for (int pr = 0; pr < 4; pr++) {
                uint4 w = ldg_nc128(sp + pr);
                sk[0][pr] = __byte_perm(w.x, w.z, 0x5410); sk[1][pr] = __byte_perm(w.x, w.z, 0x7632);
                sk[2][pr] = __byte_perm(w.y, w.w, 0x5410); sk[3][pr] = __byte_perm(w.y, w.w, 0x7632);
            }
        }
        const __nv_bfloat16* kp = p.k + (size_t)(16 * b) * DM + 8 * tt;
        const __nv_bfloat16* vp = p.v + (size_t)(16 * b) * DM + 8 * tt;
        uint4 kr[19];
        uint32_t kv[16][4];
        #pragma unroll
        for (int r = 0; r < 3; r++) kr[r] = (b > 0) ? ldg_nc128(kp + (r - 3) * DM) : make_uint4(0, 0, 0, 0);
        #pragma unroll
        for (int hh = 0; hh < 2; hh++) {
            uint4 vr[8];
            #pragma unroll
            for (int r = 0; r < 8; r++) { kr[3 + hh * 8 + r] = ldg_nc128(kp + (hh * 8 + r) * DM); vr[r] = ldg_nc128(vp + (hh * 8 + r) * DM); }
            #pragma unroll
            for (int r = 0; r < 8; r++) {
                const int s = hh * 8 + r;
                #pragma unroll
                for (int pr = 0; pr < 4; pr++) {
                    uint32_t a = bmul2(((const uint32_t*)&kr[s])[pr], sk[3][pr]);
                    a = badd2(a, bmul2(((const uint32_t*)&kr[s + 1])[pr], sk[2][pr]));
                    a = badd2(a, bmul2(((const uint32_t*)&kr[s + 2])[pr], sk[1][pr]));
                    a = badd2(a, bmul2(((const uint32_t*)&kr[s + 3])[pr], sk[0][pr]));
                    kv[s][pr] = bmul2(a, ((const uint32_t*)&vr[r])[pr]);
                }
            }
        }
        #pragma unroll
        for (int pr = 0; pr < 4; pr++) {
            #pragma unroll
            for (int hl = 0; hl < 2; hl++) {
                const uint32_t sel = hl ? 0x7632 : 0x5410;
                uint8_t* dst = g_rb + (size_t)(8 * tt + 2 * pr + hl) * RB_CH + (RB_Z + b) * 16;
                *(uint4*)dst = make_uint4(__byte_perm(kv[15][pr], kv[14][pr], sel), __byte_perm(kv[11][pr], kv[10][pr], sel),
                                          __byte_perm(kv[7][pr], kv[6][pr], sel), __byte_perm(kv[3][pr], kv[2][pr], sel));
                *(uint4*)(dst + RB_R1) = make_uint4(__byte_perm(kv[13][pr], kv[12][pr], sel), __byte_perm(kv[9][pr], kv[8][pr], sel),
                                                    __byte_perm(kv[5][pr], kv[4][pr], sel), __byte_perm(kv[1][pr], kv[0][pr], sel));
                if (b < RB_Z) {
                    uint8_t* z = g_rb + (size_t)(8 * tt + 2 * pr + hl) * RB_CH + b * 16;
                    *(uint4*)z = make_uint4(0, 0, 0, 0);
                    *(uint4*)(z + RB_R1) = make_uint4(0, 0, 0, 0);
                }
            }
        }
        asm volatile("fence.proxy.async.global;" ::: "memory");
        __syncwarp();
        if (lane == 0) flag_add(&g_cnt_kv[0]);
    } else {
        if (lane == 0) flag_wait(&g_cnt_prep[0], ep * 128);
        __syncwarp();
        #pragma unroll
        for (int t = 0; t < 2; t++) {
            uint4 v = ldg_cg128((const uint4*)(g_stats + 128 * i) + t * 32 + lane);
            asm volatile("st.shared.v4.u32 [%0], {%1,%2,%3,%4};" :: "r"(sb + SM_STATS + (t * 32 + lane) * 16), "r"(v.x), "r"(v.y), "r"(v.z), "r"(v.w) : "memory");
        }
        #pragma unroll
        for (int t = 0; t < 4; t++) {
            const int idx = t * 32 + lane;
            if (idx < 112) {
                const int m = idx >= 56;
                uint4 v = ldg_cg128((const uint4*)(g_cs + m * FF + 224 * j) + (idx - 56 * m));
                asm volatile("st.shared.v4.u32 [%0], {%1,%2,%3,%4};" :: "r"(sb + SM_CS + idx * 16), "r"(v.x), "r"(v.y), "r"(v.z), "r"(v.w) : "memory");
            }
        }
        __syncwarp();
        if (lane == 0) {
            mbar_arrive(sb + SM_BARS + B_STATS * 8);
            l2_prefetch(p.wd + (size_t)b * (FF * DM / NCTA), FF * DM / NCTA * 2);
            l2_prefetch(p.ssm_k + (size_t)(4 * b) * SEQ, 4 * SEQ * 2);
        }
    }
}

typedef CUresult (*EncodeFn)(CUtensorMap*, CUtensorMapDataType, cuuint32_t, void*, const cuuint64_t*, const cuuint64_t*,
                             const cuuint32_t*, const cuuint32_t*, CUtensorMapInterleave, CUtensorMapSwizzle,
                             CUtensorMapL2promotion, CUtensorMapFloatOOBfill);

void encode(EncodeFn fn, CUtensorMap* tm, const void* base, int rank, const cuuint64_t* dims, const cuuint64_t* strides,
            const cuuint32_t* box, CUtensorMapSwizzle swz) {
    cuuint32_t es[5] = {1, 1, 1, 1, 1};
    fn(tm, CU_TENSOR_MAP_DATA_TYPE_BFLOAT16, rank, (void*)base, dims, strides, box, es, CU_TENSOR_MAP_INTERLEAVE_NONE, swz,
       CU_TENSOR_MAP_L2_PROMOTION_L2_128B, CU_TENSOR_MAP_FLOAT_OOB_FILL_NONE);
}

}

extern "C" void kernel_launch(void* const* d_in, const int* in_sizes, int n_in, void* d_out, int out_size) {
    (void)in_sizes; (void)n_in; (void)out_size;
    static EncodeFn enc = nullptr;
    static void* yT_ptr = nullptr;
    if (!enc) {
        void* fn = nullptr; cudaDriverEntryPointQueryResult qr;
        cudaGetDriverEntryPoint("cuTensorMapEncodeTiled", &fn, cudaEnableDefault, &qr);
        enc = (EncodeFn)fn;
        cudaGetSymbolAddress(&yT_ptr, g_yT);
        cudaFuncSetAttribute(fused_kernel, cudaFuncAttributeMaxDynamicSharedMemorySize, SM_TOTAL);
    }
    Params p;
    p.q = (const __nv_bfloat16*)d_in[0]; p.k = (const __nv_bfloat16*)d_in[1]; p.v = (const __nv_bfloat16*)d_in[2];
    p.shift_k = (const __nv_bfloat16*)d_in[3]; p.ssm_k = (const __nv_bfloat16*)d_in[4]; p.ssm_D = (const __nv_bfloat16*)d_in[5];
    p.wg = (const __nv_bfloat16*)d_in[7]; p.wu = (const __nv_bfloat16*)d_in[8]; p.wd = (const __nv_bfloat16*)d_in[9];
    {
        cuuint64_t dims[2] = {DM, SEQ}; cuuint64_t str[1] = {DM * 2};
        cuuint32_t box[2] = {64, 128};
        encode(enc, &p.tm_x, p.q, 2, dims, str, box, CU_TENSOR_MAP_SWIZZLE_128B);
        cuuint32_t box2[2] = {64, 64};
        encode(enc, &p.tm_out, d_out, 2, dims, str, box2, CU_TENSOR_MAP_SWIZZLE_128B);
    }
    {
        cuuint64_t dims[3] = {32, DM, FF / 32}; cuuint64_t str[2] = {FF * 2, 64};
        cuuint32_t boxA[3] = {32, 32, 4}, boxB[3] = {32, 32, 3};
        encode(enc, &p.tm_gA, p.wg, 3, dims, str, boxA, CU_TENSOR_MAP_SWIZZLE_64B);
        encode(enc, &p.tm_gB, p.wg, 3, dims, str, boxB, CU_TENSOR_MAP_SWIZZLE_64B);
        encode(enc, &p.tm_uA, p.wu, 3, dims, str, boxA, CU_TENSOR_MAP_SWIZZLE_64B);
        encode(enc, &p.tm_uB, p.wu, 3, dims, str, boxB, CU_TENSOR_MAP_SWIZZLE_64B);
    }
    {
        cuuint64_t dims[3] = {64, FF, DM / 64}; cuuint64_t str[2] = {DM * 2, 128};
        cuuint32_t box[3] = {64, 32, 2};
        encode(enc, &p.tm_w2, p.wd, 3, dims, str, box, CU_TENSOR_MAP_SWIZZLE_128B);
    }
    {
        cuuint64_t dims[2] = {SEQ, DM}; cuuint64_t str[1] = {SEQ * 2};
        cuuint32_t box[2] = {64, 128};
        encode(enc, &p.tm_yT, yT_ptr, 2, dims, str, box, CU_TENSOR_MAP_SWIZZLE_128B);
    }
    fused_kernel<<<NCTA, NTHREADS, SM_TOTAL>>>(p);
}
```

```cpp
#include <cuda_runtime.h>
#include <cuda_bf16.h>
#include <cuda.h>
#include <stdint.h>

namespace {

constexpr int SEQ = 2048, DM = 512, FF = 1792;
constexpr int NCTA = 128;
constexpr int NTHREADS = 384;
constexpr int NSTAGE = 3;
constexpr int STAGE_BYTES = 32768;

constexpr uint32_t SM_X = 0;
constexpr uint32_t SM_RING = 131072;
constexpr uint32_t SM_MISC = SM_RING + NSTAGE * STAGE_BYTES;
constexpr uint32_t SM_BARS = SM_MISC;
constexpr uint32_t SM_EPOCH = SM_MISC + 248;
constexpr uint32_t SM_STATS = SM_MISC + 256;
constexpr uint32_t SM_CS = SM_STATS + 1024;
constexpr uint32_t SM_CSTMP = SM_CS;
constexpr uint32_t SM_TOTAL = SM_CS + 1792;
static_assert(SM_TOTAL <= 232448, "smem");
constexpr int RB_Z = 25;
constexpr int RB_R1 = (128 + RB_Z) * 16;
constexpr int RB_CH = 2 * RB_R1;
constexpr int CONV_CH = RB_CH + 4096;
constexpr uint32_t SM_CONV = 0;
constexpr uint32_t SM_RED = 3 * 16384;
constexpr uint32_t SM_YT = 5 * 16384;
constexpr uint32_t SM_XE = 6 * 16384;

constexpr int B_FULL = 0, B_EMPTY = NSTAGE, B_XFULL = 2 * NSTAGE, B_CONV = B_XFULL + 8, B_YT = B_CONV + 4,
              B_STATS = B_YT + 1, B_G1DONE = B_STATS + 1, B_PREPD = B_G1DONE + 1, B_HD = B_PREPD + 1, B_HRDY = B_HD + 4,
              B_COUNT = B_HRDY + 2;
static_assert(B_COUNT * 8 <= 248, "barrier space");

__device__ uint4 g_hfrag[32 * 112 * 4 * 32];
__device__ __align__(128) uint8_t g_rb[DM * RB_CH];
__device__ __align__(128) __nv_bfloat16 g_yT[DM * SEQ];
__device__ float2 g_stats[SEQ];
__device__ float g_cs[2 * FF];
__device__ unsigned g_launch[NCTA];
__device__ unsigned g_cnt_prep[32];
__device__ unsigned g_cnt_kv[32];
__device__ unsigned g_cnt_y[4 * 32];
__device__ unsigned g_flag_h[32 * 2 * 8];

#define PROF(idx)
#define PROF2(a, idx)
#define PROFW(idx, w)

struct Params {
    CUtensorMap tm_x, tm_gA, tm_gB, tm_uA, tm_uB, tm_w2, tm_yT, tm_out;
    const __nv_bfloat16 *q, *k, *v, *shift_k, *ssm_k, *ssm_D, *wg, *wu, *wd;
};

__device__ __forceinline__ void wgmma_rs_n32(float (&d)[16], uint32_t a0, uint32_t a1, uint32_t a2, uint32_t a3, uint64_t db, int sc) {
  asm volatile("{\n.reg .pred p;\nsetp.ne.b32 p, %21, 0;\n"
    "wgmma.mma_async.sync.aligned.m64n32k16.f32.bf16.bf16 {%0,%1,%2,%3,%4,%5,%6,%7,%8,%9,%10,%11,%12,%13,%14,%15}, {%16,%17,%18,%19}, %20, p, 1, 1, 0;\n}\n"
    : "+f"(d[0]),"+f"(d[1]),"+f"(d[2]),"+f"(d[3]),"+f"(d[4]),"+f"(d[5]),"+f"(d[6]),"+f"(d[7]),"+f"(d[8]),"+f"(d[9]),"+f"(d[10]),"+f"(d[11]),"+f"(d[12]),"+f"(d[13]),"+f"(d[14]),"+f"(d[15])
    : "r"(a0),"r"(a1),"r"(a2),"r"(a3),"l"(db),"r"(sc));
}
__device__ __forceinline__ void wgmma_rs_n128_tb(float (&d)[64], uint32_t a0, uint32_t a1, uint32_t a2, uint32_t a3, uint64_t db, int sc) {
  asm volatile("{\n.reg .pred p;\nsetp.ne.b32 p, %69, 0;\n"
    "wgmma.mma_async.sync.aligned.m64n128k16.f32.bf16.bf16 {%0,%1,%2,%3,%4,%5,%6,%7,%8,%9,%10,%11,%12,%13,%14,%15,%16,%17,%18,%19,%20,%21,%22,%23,%24,%25,%26,%27,%28,%29,%30,%31,%32,%33,%34,%35,%36,%37,%38,%39,%40,%41,%42,%43,%44,%45,%46,%47,%48,%49,%50,%51,%52,%53,%54,%55,%56,%57,%58,%59,%60,%61,%62,%63}, {%64,%65,%66,%67}, %68, p, 1, 1, 1;\n}\n"
    : "+f"(d[0]),"+f"(d[1]),"+f"(d[2]),"+f"(d[3]),"+f"(d[4]),"+f"(d[5]),"+f"(d[6]),"+f"(d[7]),"+f"(d[8]),"+f"(d[9]),"+f"(d[10]),"+f"(d[11]),"+f"(d[12]),"+f"(d[13]),"+f"(d[14]),"+f"(d[15]),"+f"(d[16]),"+f"(d[17]),"+f"(d[18]),"+f"(d[19]),"+f"(d[20]),"+f"(d[21]),"+f"(d[22]),"+f"(d[23]),"+f"(d[24]),"+f"(d[25]),"+f"(d[26]),"+f"(d[27]),"+f"(d[28]),"+f"(d[29]),"+f"(d[30]),"+f"(d[31]),"+f"(d[32]),"+f"(d[33]),"+f"(d[34]),"+f"(d[35]),"+f"(d[36]),"+f"(d[37]),"+f"(d[38]),"+f"(d[39]),"+f"(d[40]),"+f"(d[41]),"+f"(d[42]),"+f"(d[43]),"+f"(d[44]),"+f"(d[45]),"+f"(d[46]),"+f"(d[47]),"+f"(d[48]),"+f"(d[49]),"+f"(d[50]),"+f"(d[51]),"+f"(d[52]),"+f"(d[53]),"+f"(d[54]),"+f"(d[55]),"+f"(d[56]),"+f"(d[57]),"+f"(d[58]),"+f"(d[59]),"+f"(d[60]),"+f"(d[61]),"+f"(d[62]),"+f"(d[63])
    : "r"(a0),"r"(a1),"r"(a2),"r"(a3),"l"(db),"r"(sc));
}
__device__ __forceinline__ void wgmma_ss_n256_tb(float (&d)[128], uint64_t da, uint64_t db, int sc) {
  asm volatile("{\n.reg .pred p;\nsetp.ne.b32 p, %130, 0;\n"
    "wgmma.mma_async.sync.aligned.m64n256k16.f32.bf16.bf16 {%0,%1,%2,%3,%4,%5,%6,%7,%8,%9,%10,%11,%12,%13,%14,%15,%16,%17,%18,%19,%20,%21,%22,%23,%24,%25,%26,%27,%28,%29,%30,%31,%32,%33,%34,%35,%36,%37,%38,%39,%40,%41,%42,%43,%44,%45,%46,%47,%48,%49,%50,%51,%52,%53,%54,%55,%56,%57,%58,%59,%60,%61,%62,%63,%64,%65,%66,%67,%68,%69,%70,%71,%72,%73,%74,%75,%76,%77,%78,%79,%80,%81,%82,%83,%84,%85,%86,%87,%88,%89,%90,%91,%92,%93,%94,%95,%96,%97,%98,%99,%100,%101,%102,%103,%104,%105,%106,%107,%108,%109,%110,%111,%112,%113,%114,%115,%116,%117,%118,%119,%120,%121,%122,%123,%124,%125,%126,%127}, %128, %129, p, 1, 1, 0, 1;\n}\n"
    : "+f"(d[0]),"+f"(d[1]),"+f"(d[2]),"+f"(d[3]),"+f"(d[4]),"+f"(d[5]),"+f"(d[6]),"+f"(d[7]),"+f"(d[8]),"+f"(d[9]),"+f"(d[10]),"+f"(d[11]),"+f"(d[12]),"+f"(d[13]),"+f"(d[14]),"+f"(d[15]),"+f"(d[16]),"+f"(d[17]),"+f"(d[18]),"+f"(d[19]),"+f"(d[20]),"+f"(d[21]),"+f"(d[22]),"+f"(d[23]),"+f"(d[24]),"+f"(d[25]),"+f"(d[26]),"+f"(d[27]),"+f"(d[28]),"+f"(d[29]),"+f"(d[30]),"+f"(d[31]),"+f"(d[32]),"+f"(d[33]),"+f"(d[34]),"+f"(d[35]),"+f"(d[36]),"+f"(d[37]),"+f"(d[38]),"+f"(d[39]),"+f"(d[40]),"+f"(d[41]),"+f"(d[42]),"+f"(d[43]),"+f"(d[44]),"+f"(d[45]),"+f"(d[46]),"+f"(d[47]),"+f"(d[48]),"+f"(d[49]),"+f"(d[50]),"+f"(d[51]),"+f"(d[52]),"+f"(d[53]),"+f"(d[54]),"+f"(d[55]),"+f"(d[56]),"+f"(d[57]),"+f"(d[58]),"+f"(d[59]),"+f"(d[60]),"+f"(d[61]),"+f"(d[62]),"+f"(d[63]),"+f"(d[64]),"+f"(d[65]),"+f"(d[66]),"+f"(d[67]),"+f"(d[68]),"+f"(d[69]),"+f"(d[70]),"+f"(d[71]),"+f"(d[72]),"+f"(d[73]),"+f"(d[74]),"+f"(d[75]),"+f"(d[76]),"+f"(d[77]),"+f"(d[78]),"+f"(d[79]),"+f"(d[80]),"+f"(d[81]),"+f"(d[82]),"+f"(d[83]),"+f"(d[84]),"+f"(d[85]),"+f"(d[86]),"+f"(d[87]),"+f"(d[88]),"+f"(d[89]),"+f"(d[90]),"+f"(d[91]),"+f"(d[92]),"+f"(d[93]),"+f"(d[94]),"+f"(d[95]),"+f"(d[96]),"+f"(d[97]),"+f"(d[98]),"+f"(d[99]),"+f"(d[100]),"+f"(d[101]),"+f"(d[102]),"+f"(d[103]),"+f"(d[104]),"+f"(d[105]),"+f"(d[106]),"+f"(d[107]),"+f"(d[108]),"+f"(d[109]),"+f"(d[110]),"+f"(d[111]),"+f"(d[112]),"+f"(d[113]),"+f"(d[114]),"+f"(d[115]),"+f"(d[116]),"+f"(d[117]),"+f"(d[118]),"+f"(d[119]),"+f"(d[120]),"+f"(d[121]),"+f"(d[122]),"+f"(d[123]),"+f"(d[124]),"+f"(d[125]),"+f"(d[126]),"+f"(d[127])
    : "l"(da),"l"(db),"r"(sc));
}
__device__ __forceinline__ void wgmma_ss_n192_tb(float (&d)[96], uint64_t da, uint64_t db, int sc) {
  asm volatile("{\n.reg .pred p;\nsetp.ne.b32 p, %98, 0;\n"
    "wgmma.mma_async.sync.aligned.m64n192k16.f32.bf16.bf16 {%0,%1,%2,%3,%4,%5,%6,%7,%8,%9,%10,%11,%12,%13,%14,%15,%16,%17,%18,%19,%20,%21,%22,%23,%24,%25,%26,%27,%28,%29,%30,%31,%32,%33,%34,%35,%36,%37,%38,%39,%40,%41,%42,%43,%44,%45,%46,%47,%48,%49,%50,%51,%52,%53,%54,%55,%56,%57,%58,%59,%60,%61,%62,%63,%64,%65,%66,%67,%68,%69,%70,%71,%72,%73,%74,%75,%76,%77,%78,%79,%80,%81,%82,%83,%84,%85,%86,%87,%88,%89,%90,%91,%92,%93,%94,%95}, %96, %97, p, 1, 1, 0, 1;\n}\n"
    : "+f"(d[0]),"+f"(d[1]),"+f"(d[2]),"+f"(d[3]),"+f"(d[4]),"+f"(d[5]),"+f"(d[6]),"+f"(d[7]),"+f"(d[8]),"+f"(d[9]),"+f"(d[10]),"+f"(d[11]),"+f"(d[12]),"+f"(d[13]),"+f"(d[14]),"+f"(d[15]),"+f"(d[16]),"+f"(d[17]),"+f"(d[18]),"+f"(d[19]),"+f"(d[20]),"+f"(d[21]),"+f"(d[22]),"+f"(d[23]),"+f"(d[24]),"+f"(d[25]),"+f"(d[26]),"+f"(d[27]),"+f"(d[28]),"+f"(d[29]),"+f"(d[30]),"+f"(d[31]),"+f"(d[32]),"+f"(d[33]),"+f"(d[34]),"+f"(d[35]),"+f"(d[36]),"+f"(d[37]),"+f"(d[38]),"+f"(d[39]),"+f"(d[40]),"+f"(d[41]),"+f"(d[42]),"+f"(d[43]),"+f"(d[44]),"+f"(d[45]),"+f"(d[46]),"+f"(d[47]),"+f"(d[48]),"+f"(d[49]),"+f"(d[50]),"+f"(d[51]),"+f"(d[52]),"+f"(d[53]),"+f"(d[54]),"+f"(d[55]),"+f"(d[56]),"+f"(d[57]),"+f"(d[58]),"+f"(d[59]),"+f"(d[60]),"+f"(d[61]),"+f"(d[62]),"+f"(d[63]),"+f"(d[64]),"+f"(d[65]),"+f"(d[66]),"+f"(d[67]),"+f"(d[68]),"+f"(d[69]),"+f"(d[70]),"+f"(d[71]),"+f"(d[72]),"+f"(d[73]),"+f"(d[74]),"+f"(d[75]),"+f"(d[76]),"+f"(d[77]),"+f"(d[78]),"+f"(d[79]),"+f"(d[80]),"+f"(d[81]),"+f"(d[82]),"+f"(d[83]),"+f"(d[84]),"+f"(d[85]),"+f"(d[86]),"+f"(d[87]),"+f"(d[88]),"+f"(d[89]),"+f"(d[90]),"+f"(d[91]),"+f"(d[92]),"+f"(d[93]),"+f"(d[94]),"+f"(d[95])
    : "l"(da),"l"(db),"r"(sc));
}

__device__ __forceinline__ uint32_t smem_u32(const void* p) { return (uint32_t)__cvta_generic_to_shared(p); }
__device__ __forceinline__ void mbar_init(uint32_t bar, uint32_t cnt) { asm volatile("mbarrier.init.shared::cta.b64 [%0], %1;" :: "r"(bar), "r"(cnt)); }
__device__ __forceinline__ void mbar_expect_tx(uint32_t bar, uint32_t bytes) { asm volatile("mbarrier.arrive.expect_tx.shared::cta.b64 _, [%0], %1;" :: "r"(bar), "r"(bytes) : "memory"); }
__device__ __forceinline__ void mbar_arrive(uint32_t bar) { asm volatile("mbarrier.arrive.shared::cta.b64 _, [%0];" :: "r"(bar) : "memory"); }
__device__ __forceinline__ void mbar_arrive_cluster(uint32_t cbar, uint32_t cnt) { asm volatile("mbarrier.arrive.shared::cluster.b64 _, [%0], %1;" :: "r"(cbar), "r"(cnt) : "memory"); }
__device__ __forceinline__ uint32_t mapa(uint32_t a, uint32_t rank) { uint32_t r; asm volatile("mapa.shared::cluster.u32 %0, %1, %2;" : "=r"(r) : "r"(a), "r"(rank)); return r; }
__device__ __forceinline__ void mbar_wait(uint32_t bar, uint32_t parity) {
    uint32_t ok; uint32_t n = 0;
    do {
        asm volatile("{\n.reg .pred p;\nmbarrier.try_wait.parity.shared::cta.b64 p, [%1], %2;\nselp.u32 %0, 1, 0, p;\n}" : "=r"(ok) : "r"(bar), "r"(parity) : "memory");
    } while (!ok && ++n < (1u << 17));
}
__device__ __forceinline__ void flag_wait(const unsigned* p, unsigned target) {
    unsigned v; uint32_t n = 0;
    do {
        asm volatile("ld.acquire.gpu.global.u32 %0, [%1];" : "=r"(v) : "l"(p) : "memory");
    } while ((int)(v - target) < 0 && ++n < (1u << 17));
}
__device__ __forceinline__ void flag_add(unsigned* p) {
    asm volatile("fence.acq_rel.gpu;\nred.relaxed.gpu.global.add.u32 [%0], 1;" :: "l"(p) : "memory");
}
__device__ __forceinline__ uint64_t make_desc(uint32_t addr, uint32_t lbo, uint32_t sbo, uint32_t swz) {
    return (uint64_t)((addr & 0x3FFFF) >> 4) | ((uint64_t)((lbo & 0x3FFFF) >> 4) << 16) | ((uint64_t)((sbo & 0x3FFFF) >> 4) << 32) | ((uint64_t)swz << 62);
}
__device__ __forceinline__ uint64_t desc_add(uint64_t d, uint32_t off16) {
    return (d & 0xFFFFFFFF00000000ull) | (uint64_t)((uint32_t)d + off16);
}
__device__ __forceinline__ void tma2d(uint32_t dst, const CUtensorMap* tm, int c0, int c1, uint32_t bar) {
    asm volatile("cp.async.bulk.tensor.2d.shared::cluster.global.mbarrier::complete_tx::bytes [%0], [%1, {%3, %4}], [%2];"
        :: "r"(dst), "l"((uint64_t)tm), "r"(bar), "r"(c0), "r"(c1) : "memory");
}
__device__ __forceinline__ void tma3d_mc(uint32_t dst, const CUtensorMap* tm, int c0, int c1, int c2, uint32_t bar) {
    asm volatile("cp.async.bulk.tensor.3d.shared::cluster.global.mbarrier::complete_tx::bytes.multicast::cluster [%0], [%1, {%3, %4, %5}], [%2], %6;"
        :: "r"(dst), "l"((uint64_t)tm), "r"(bar), "r"(c0), "r"(c1), "r"(c2), "h"((uint16_t)3) : "memory");
}
__device__ __forceinline__ void bulk_g2s(uint32_t dst, const void* src, uint32_t bytes, uint32_t bar) {
    asm volatile("cp.async.bulk.shared::cluster.global.mbarrier::complete_tx::bytes [%0], [%1], %2, [%3];"
        :: "r"(dst), "l"(src), "r"(bytes), "r"(bar) : "memory");
}
__device__ __forceinline__ void tma2d_store(const CUtensorMap* tm, int c0, int c1, uint32_t src) {
    asm volatile("cp.async.bulk.tensor.2d.global.shared::cta.bulk_group [%0, {%2, %3}], [%1];"
        :: "l"((uint64_t)tm), "r"(src), "r"(c0), "r"(c1) : "memory");
}
__device__ __forceinline__ void l2_prefetch(const void* p, uint32_t bytes) {
    asm volatile("cp.async.bulk.prefetch.L2.global [%0], %1;" :: "l"(p), "r"(bytes) : "memory");
}
__device__ __forceinline__ void tmap_prefetch(const CUtensorMap* tm) { asm volatile("prefetch.tensormap [%0];" :: "l"((uint64_t)tm) : "memory"); }
__device__ __forceinline__ uint32_t lds32(uint32_t a) { uint32_t v; asm volatile("ld.shared.u32 %0, [%1];" : "=r"(v) : "r"(a)); return v; }
__device__ __forceinline__ float2 lds64f(uint32_t a) { float2 v; asm volatile("ld.shared.v2.f32 {%0,%1}, [%2];" : "=f"(v.x), "=f"(v.y) : "r"(a)); return v; }
__device__ __forceinline__ float4 lds128f(uint32_t a) { float4 v; asm volatile("ld.shared.v4.f32 {%0,%1,%2,%3}, [%4];" : "=f"(v.x), "=f"(v.y), "=f"(v.z), "=f"(v.w) : "r"(a) : "memory"); return v; }
__device__ __forceinline__ void sts32(uint32_t a, uint32_t v) { asm volatile("st.shared.u32 [%0], %1;" :: "r"(a), "r"(v) : "memory"); }
__device__ __forceinline__ void sts128f(uint32_t a, float x, float y, float z, float w) { asm volatile("st.shared.v4.f32 [%0], {%1,%2,%3,%4};" :: "r"(a), "f"(x), "f"(y), "f"(z), "f"(w) : "memory"); }
__device__ __forceinline__ uint4 ldg_cg128(const void* p) { uint4 v; asm volatile("ld.global.cg.v4.u32 {%0,%1,%2,%3}, [%4];" : "=r"(v.x), "=r"(v.y), "=r"(v.z), "=r"(v.w) : "l"(p)); return v; }
__device__ __forceinline__ uint4 ldg_nc128(const void* p) { uint4 v; asm volatile("ld.global.nc.L1::no_allocate.v4.u32 {%0,%1,%2,%3}, [%4];" : "=r"(v.x), "=r"(v.y), "=r"(v.z), "=r"(v.w) : "l"(p)); return v; }
__device__ __forceinline__ uint2 ldg_nc64(const void* p) { uint2 v; asm volatile("ld.global.nc.L1::no_allocate.v2.u32 {%0,%1}, [%2];" : "=r"(v.x), "=r"(v.y) : "l"(p)); return v; }
#define WG_FENCE() asm volatile("wgmma.fence.sync.aligned;\n" ::: "memory")
#define WG_COMMIT() asm volatile("wgmma.commit_group.sync.aligned;\n" ::: "memory")
template<int N> __device__ __forceinline__ void wg_wait() { asm volatile("wgmma.wait_group.sync.aligned %0;\n" :: "n"(N) : "memory"); }
__device__ __forceinline__ void named_bar(int id, int n) { asm volatile("bar.sync %0, %1;" :: "r"(id), "r"(n) : "memory"); }

__device__ __forceinline__ float bf_lo(uint32_t u) { return __uint_as_float(u << 16); }
__device__ __forceinline__ float bf_hi(uint32_t u) { return __uint_as_float(u & 0xFFFF0000u); }
__device__ __forceinline__ uint32_t pack_bf(float lo, float hi) { uint32_t r; asm("cvt.rn.bf16x2.f32 %0, %1, %2;" : "=r"(r) : "f"(hi), "f"(lo)); return r; }
__device__ __forceinline__ float bf_round(float x) { return __bfloat162float(__float2bfloat16_rn(x)); }
__device__ __forceinline__ uint32_t bmul2(uint32_t a, uint32_t b) { uint32_t r; asm("mul.rn.bf16x2 %0, %1, %2;" : "=r"(r) : "r"(a), "r"(b)); return r; }
__device__ __forceinline__ uint32_t badd2(uint32_t a, uint32_t b) { uint32_t r; asm("add.rn.bf16x2 %0, %1, %2;" : "=r"(r) : "r"(a), "r"(b)); return r; }
__device__ __forceinline__ uint32_t bsub2(uint32_t a, uint32_t b) { uint32_t r; asm("sub.rn.bf16x2 %0, %1, %2;" : "=r"(r) : "r"(a), "r"(b)); return r; }

__device__ __forceinline__ int blk_f0(int bi, int j) {
    if (bi < 32) return 224 * ((j + (bi >> 2)) & 7) + 32 * (bi & 3);
    int b2 = bi - 32; int q3 = (b2 * 11) >> 5;
    return 224 * ((j + q3) & 7) + 128 + 32 * (b2 - 3 * q3);
}

struct Ring { int st; uint32_t ph; };
__device__ __forceinline__ void ring_next(Ring& r) { if (++r.st == NSTAGE) { r.st = 0; r.ph ^= 1; } }

template<int NB>
__device__ __forceinline__ void gemm1_pass(uint32_t sb, int wgi, int warp4, int lane, Ring& rg, uint32_t e_cl,
                                           int rb64, int ks0, int csoff) {
    constexpr bool passA = (NB == 4);
    float acc[NB * 32];
    const uint64_t descA0 = make_desc(sb + SM_X + wgi * 8192, 16, 1024, 1);
    const uint64_t descB0 = make_desc(sb + SM_RING, 4096, 512, 2);
    int prev = 0;
    #pragma unroll 1
    for (int sl = 0; sl < 8; sl++) {
        if (passA) mbar_wait(sb + SM_BARS + (B_XFULL + sl) * 8, 0);
        if (warp4 == 0 && wgi == 0) PROF2(2, sl + (passA ? 0 : 8));
        mbar_wait(sb + SM_BARS + (B_FULL + rg.st) * 8, rg.ph);
        if (sl == 0 && warp4 == 0) PROF(2 + wgi * 8 + (passA ? 0 : 3));
        if (warp4 == 0 && wgi == 0) PROF2(1, sl + (passA ? 0 : 8));
        const uint64_t da = desc_add(descA0, sl * 1024), db = desc_add(descB0, rg.st * 2048);
        WG_FENCE();
        #pragma unroll
        for (int kk = 0; kk < 4; kk++) {
            int sc = (sl | kk) ? 1 : 0;
            if constexpr (NB == 4) wgmma_ss_n256_tb(acc, da + kk * 2, db + kk * 64, sc); else wgmma_ss_n192_tb(acc, da + kk * 2, db + kk * 64, sc);
        }
        WG_COMMIT();
        wg_wait<1>();
        if (warp4 == 0 && wgi == 0) PROF2(3, sl + (passA ? 0 : 8));
        if (lane < 2 && sl) mbar_arrive_cluster(e_cl + prev * 8, 1);
        prev = rg.st;
        ring_next(rg);
    }
    wg_wait<0>();
    if (lane < 2) mbar_arrive_cluster(e_cl + prev * 8, 1);
    if (!passA && lane == 0) mbar_arrive(sb + SM_BARS + B_G1DONE * 8);
    if (warp4 == 0) PROF(3 + wgi * 8 + (passA ? 0 : 3));
    if (passA) mbar_wait(sb + SM_BARS + B_STATS * 8, 0);
    const int g = lane >> 2, c = lane & 3;
    const int r0 = wgi * 64 + warp4 * 16 + g;
    const float2 s0 = lds64f(sb + SM_STATS + r0 * 8), s1 = lds64f(sb + SM_STATS + (r0 + 8) * 8);
    const uint32_t csg = sb + SM_CS + (csoff + 2 * c) * 4, csu = csg + 224 * 4;
    uint4* dst = g_hfrag + ((size_t)(rb64 * 112 + ks0) * 4 + warp4) * 32 + lane;
    #pragma unroll
    for (int kk = 0; kk < NB * 2; kk++) {
        uint32_t h[4];
        #pragma unroll
        for (int tt = 0; tt < 2; tt++) {
            const int t = 2 * kk + tt;
            const float2 cg = lds64f(csg + t * 32), cu = lds64f(csu + t * 32);
            const float* ag = &acc[4 * t];
            const float* au = &acc[NB * 16 + 4 * t];
            uint32_t g0 = pack_bf((ag[0] - s0.x * cg.x) * s0.y, (ag[1] - s0.x * cg.y) * s0.y);
            uint32_t u0 = pack_bf((au[0] - s0.x * cu.x) * s0.y, (au[1] - s0.x * cu.y) * s0.y);
            uint32_t g1 = pack_bf((ag[2] - s1.x * cg.x) * s1.y, (ag[3] - s1.x * cg.y) * s1.y);
            uint32_t u1 = pack_bf((au[2] - s1.x * cu.x) * s1.y, (au[3] - s1.x * cu.y) * s1.y);
            h[2 * tt] = bmul2(g0, u0);
            h[2 * tt + 1] = bmul2(g1, u1);
        }
        dst[kk * 128] = make_uint4(h[0], h[1], h[2], h[3]);
    }
    __syncwarp();
    if (lane == 0) mbar_arrive(sb + SM_BARS + (B_HD + wgi * 2 + (passA ? 0 : 1)) * 8);
    if (warp4 == 0) PROF(4 + wgi * 8 + (passA ? 0 : 3));
}

template<int P0, int NP>
__device__ __forceinline__ void conv_load_a(uint32_t (&a)[NP][2][4], uint32_t hk_lane, int m_lane) {
    #pragma unroll
    for (int pp = 0; pp < NP; pp++) {
        #pragma unroll
        for (int q = 0; q < 2; q++) {
            const int off = (8 * q + 64 * (P0 + pp)) * 4;
            uint32_t w0, w1, w2;
            if (P0 + pp == 0 && q == 0) {
                w0 = (m_lane + 0 < 8) ? 0u : lds32(hk_lane + off);
                w1 = (m_lane + 1 < 8) ? 0u : lds32(hk_lane + off + 4);
                w2 = (m_lane + 2 < 8) ? 0u : lds32(hk_lane + off + 8);
            } else {
                w0 = lds32(hk_lane + off); w1 = lds32(hk_lane + off + 4); w2 = lds32(hk_lane + off + 8);
            }
            a[pp][q][0] = w1;
            a[pp][q][1] = __byte_perm(w0, w1, 0x5432);
            a[pp][q][2] = w2;
            a[pp][q][3] = __byte_perm(w1, w2, 0x5432);
        }
    }
}
template<int P0, int NP>
__device__ __forceinline__ void conv_mma(float (&acc)[4][16], uint32_t (&a)[NP][2][4], uint64_t db) {
    WG_FENCE();
    #pragma unroll
    for (int pp = 0; pp < NP; pp++) {
        #pragma unroll
        for (int q = 0; q < 2; q++) {
            const int P = P0 + pp;
            #pragma unroll
            for (int bq = P / 4; bq < 4; bq++)
                wgmma_rs_n32(acc[bq], a[pp][q][0], a[pp][q][1], a[pp][q][2], a[pp][q][3],
                             db + (uint64_t)(int64_t)(32 * bq - 8 * P - q), (P == 0 && q == 0) ? 0 : 1);
        }
    }
    WG_COMMIT();
}

__global__ void __cluster_dims__(2, 1, 1) __launch_bounds__(NTHREADS, 1)
fused_kernel(const __grid_constant__ Params p) {
    extern __shared__ __align__(1024) uint8_t smem_raw[];
    const uint32_t sb = smem_u32(smem_raw);
    const int tid = threadIdx.x, warp = tid >> 5, lane = tid & 31;
    const int b = blockIdx.x;
    const int rank = b & 1;
    const int j = (b >> 1) & 7;
    const int i = ((b >> 4) << 1) | rank;
    const int cb = j >> 1;
    const int rbG2 = 2 * i + (j & 1);

    if (tid == 256) {
        tmap_prefetch(&p.tm_x);
        tmap_prefetch(rank ? &p.tm_uA : &p.tm_gA);
        for (int s = 0; s < NSTAGE; s++) { mbar_init(sb + SM_BARS + (B_FULL + s) * 8, 1); mbar_init(sb + SM_BARS + (B_EMPTY + s) * 8, 16); }
        for (int s = 0; s < 8; s++) mbar_init(sb + SM_BARS + (B_XFULL + s) * 8, 1);
        for (int s = 0; s < 4; s++) mbar_init(sb + SM_BARS + (B_CONV + s) * 8, 1);
        mbar_init(sb + SM_BARS + B_YT * 8, 1);
        mbar_init(sb + SM_BARS + B_STATS * 8, 1);
        mbar_init(sb + SM_BARS + B_G1DONE * 8, 8);
        mbar_init(sb + SM_BARS + B_PREPD * 8, 1);
        for (int s = 0; s < 4; s++) mbar_init(sb + SM_BARS + (B_HD + s) * 8, 4);
        for (int s = 0; s < 2; s++) mbar_init(sb + SM_BARS + (B_HRDY + s) * 8, 1);
        asm volatile("fence.mbarrier_init.release.cluster;" ::: "memory");
        asm volatile("fence.proxy.async.shared::cta;" ::: "memory");
        for (int sl = 0; sl < 2; sl++) {
            const int kc = (sl + 2 * cb + 2) & 7;
            mbar_expect_tx(sb + SM_BARS + (B_XFULL + sl) * 8, 16384);
            tma2d(sb + SM_X + sl * 16384, &p.tm_x, 64 * kc, 128 * i, sb + SM_BARS + (B_XFULL + sl) * 8);
        }
    }
    __syncwarp();
    asm volatile("barrier.cluster.arrive.relaxed.aligned;\nbarrier.cluster.wait.aligned;\n" ::: "memory");
    PROFW(1, 0);

    if (warp < 8) {
        asm volatile("setmaxnreg.inc.sync.aligned.u32 208;");
        const int wgi = warp >> 2, warp4 = warp & 3;
        const uint32_t e_cl = mapa(sb + SM_BARS + B_EMPTY * 8, lane & 1);
        if (wgi == 1) {
            uint4 xr[4][2];
            #pragma unroll
            for (int rr = 0; rr < 4; rr++) {
                const __nv_bfloat16* row = p.q + (size_t)(16 * b + 4 * warp4 + rr) * DM;
                xr[rr][0] = ldg_nc128(row + 8 * lane);
                xr[rr][1] = ldg_nc128(row + 256 + 8 * lane);
            }
            float csum[8];
            #pragma unroll
            for (int e = 0; e < 8; e++) csum[e] = 0.f;
            if (b < 112) {
                const __nv_bfloat16* wsrc = (b < 56 ? p.wg : p.wu) + 32 * (b < 56 ? b : b - 56) + 8 * (lane & 3) + (size_t)(128 * warp4 + (lane >> 2)) * FF;
                uint4 wv[16];
                #pragma unroll
                for (int t = 0; t < 16; t++) wv[t] = ldg_nc128(wsrc + (size_t)(t * 8) * FF);
                #pragma unroll
                for (int t = 0; t < 16; t++) {
                    csum[0] += bf_lo(wv[t].x); csum[1] += bf_hi(wv[t].x); csum[2] += bf_lo(wv[t].y); csum[3] += bf_hi(wv[t].y);
                    csum[4] += bf_lo(wv[t].z); csum[5] += bf_hi(wv[t].z); csum[6] += bf_lo(wv[t].w); csum[7] += bf_hi(wv[t].w);
                }
            }
            float rs[4], rq[4];
            #pragma unroll
            for (int rr = 0; rr < 4; rr++) {
                const uint32_t* u = (const uint32_t*)&xr[rr][0];
                float s = 0.f;
                #pragma unroll
                for (int e = 0; e < 8; e++) s += bf_lo(u[e]) + bf_hi(u[e]);
                rs[rr] = s;
            }
            #pragma unroll
            for (int o = 16; o > 0; o >>= 1) {
                #pragma unroll
                for (int rr = 0; rr < 4; rr++) rs[rr] += __shfl_xor_sync(0xffffffffu, rs[rr], o);
            }
            #pragma unroll
            for (int rr = 0; rr < 4; rr++) {
                const uint32_t* u = (const uint32_t*)&xr[rr][0];
                const float mean = rs[rr] * (1.0f / DM);
                float ss = 0.f;
                #pragma unroll
                for (int e = 0; e < 8; e++) { float d0 = bf_lo(u[e]) - mean, d1 = bf_hi(u[e]) - mean; ss += d0 * d0; ss += d1 * d1; }
                rq[rr] = ss;
            }
            #pragma unroll
            for (int o = 16; o > 0; o >>= 1) {
                #pragma unroll
                for (int rr = 0; rr < 4; rr++) rq[rr] += __shfl_xor_sync(0xffffffffu, rq[rr], o);
            }
            if (lane < 4) {
                const float s = lane == 0 ? rs[0] : lane == 1 ? rs[1] : lane == 2 ? rs[2] : rs[3];
                const float ss = lane == 0 ? rq[0] : lane == 1 ? rq[1] : lane == 2 ? rq[2] : rq[3];
                const float var_b = bf_round(ss * (1.0f / DM));
                const float sd = bf_round(sqrtf(bf_round(var_b + 1e-5f)));
                g_stats[16 * b + 4 * warp4 + lane] = make_float2(bf_round(s * (1.0f / DM)), 1.0f / sd);
            }
            #pragma unroll
            for (int e = 0; e < 8; e++) {
                csum[e] += __shfl_xor_sync(0xffffffffu, csum[e], 4);
                csum[e] += __shfl_xor_sync(0xffffffffu, csum[e], 8);
                csum[e] += __shfl_xor_sync(0xffffffffu, csum[e], 16);
            }
            if (lane < 4) {
                sts128f(sb + SM_CSTMP + (warp4 * 32 + lane * 8) * 4, csum[0], csum[1], csum[2], csum[3]);
                sts128f(sb + SM_CSTMP + (warp4 * 32 + lane * 8 + 4) * 4, csum[4], csum[5], csum[6], csum[7]);
            }
            named_bar(2, 128);
            if (warp4 == 0) {
                if (b < 112) {
                    float t = 0.f;
                    #pragma unroll
                    for (int ww = 0; ww < 4; ww++) t += __uint_as_float(lds32(sb + SM_CSTMP + (ww * 32 + lane) * 4));
                    g_cs[32 * b + lane] = t;
                }
                __syncwarp();
                if (lane == 0) mbar_arrive(sb + SM_BARS + B_PREPD * 8);
            }
            PROFW(18, 4);
        }
        Ring rg = {0, 0};
        const int rb64 = 2 * i + wgi;
        gemm1_pass<4>(sb, wgi, warp4, lane, rg, e_cl, rb64, 14 * j, 0);
        gemm1_pass<3>(sb, wgi, warp4, lane, rg, e_cl, rb64, 14 * j + 8, 128);

        const int g = lane >> 2, c = lane & 3;
        if (wgi == 0) {
            float acc[64];
            uint4 af[3][8];
            const uint4* hsrc = g_hfrag + ((size_t)rbG2 * 112 * 4 + warp4) * 32 + lane;
            const uint64_t descB0 = make_desc(sb + SM_RING, 4096, 1024, 1);
            int prev = 0;
            auto load_group = [&](uint4 (&dstf)[8], int u) {
                #pragma unroll
                for (int hb = 0; hb < 4; hb++) {
                    const int ks = blk_f0(4 * u + hb, j) >> 4;
                    dstf[2 * hb] = ldg_cg128(hsrc + ks * 128);
                    dstf[2 * hb + 1] = ldg_cg128(hsrc + ks * 128 + 128);
                }
            };
            auto g2_step = [&](int u, uint4 (&cur)[8], uint4 (&nxt)[8], bool do_load) {
                if (warp4 == 0) PROF2(2, 16 + u);
                mbar_wait(sb + SM_BARS + (B_FULL + rg.st) * 8, rg.ph);
                if (warp4 == 0) PROF2(1, 16 + u);
                const uint64_t db = desc_add(descB0, rg.st * 2048);
                WG_FENCE();
                #pragma unroll
                for (int kk = 0; kk < 8; kk++)
                    wgmma_rs_n128_tb(acc, cur[kk].x, cur[kk].y, cur[kk].z, cur[kk].w, db + ((kk >> 1) * 512 + (kk & 1) * 128), (u | kk) ? 1 : 0);
                WG_COMMIT();
                wg_wait<1>();
                if (warp4 == 0) PROF2(3, 16 + u);
                if (lane < 2 && u > 0 && u - 1 + NSTAGE < 14) mbar_arrive_cluster(e_cl + prev * 8, 2);
                prev = rg.st;
                ring_next(rg);
                if (u + 2 == 8) mbar_wait(sb + SM_BARS + (B_HRDY + 1) * 8, 0);
                if (do_load) load_group(nxt, u + 2);
            };
            mbar_wait(sb + SM_BARS + B_HRDY * 8, 0);
            PROFW(20, 0);
            load_group(af[0], 0); load_group(af[1], 1);
            #pragma unroll 1
            for (int u0 = 0; u0 < 12; u0 += 3) {
                g2_step(u0, af[0], af[2], true);
                g2_step(u0 + 1, af[1], af[0], true);
                g2_step(u0 + 2, af[2], af[1], true);
                PROFW(21 + (u0 / 3), 0);
            }
            g2_step(12, af[0], af[2], false);
            g2_step(13, af[1], af[0], false);
            wg_wait<0>();
            PROFW(27, 0);
            mbar_wait(sb + SM_BARS + B_YT * 8, 0);
            PROFW(28, 0);
            const int r0 = (j & 1) * 64 + warp4 * 16 + g;
            const float2 s0 = lds64f(sb + SM_STATS + r0 * 8), s1 = lds64f(sb + SM_STATS + (r0 + 8) * 8);
            const uint32_t m0 = pack_bf(s0.x, s0.x), m1 = pack_bf(s1.x, s1.x);
            const uint32_t xrow0 = sb + SM_XE + r0 * 128 + c * 4, xrow1 = xrow0 + 8 * 128;
            const int mi = lane >> 3, lr = lane & 7;
            const uint32_t yaddr = sb + SM_YT + ((mi >> 1) * 8 + lr) * 128 + (((2 * warp4 + (mi & 1)) ^ lr) << 4);
            #pragma unroll
            for (int t2 = 0; t2 < 8; t2++) {
                uint32_t y[4];
                asm volatile("ldmatrix.sync.aligned.m8n8.x4.trans.shared.b16 {%0,%1,%2,%3}, [%4];"
                    : "=r"(y[0]), "=r"(y[1]), "=r"(y[2]), "=r"(y[3]) : "r"(yaddr + t2 * 2048) : "memory");
                #pragma unroll
                for (int tt = 0; tt < 2; tt++) {
                    const int t = 2 * t2 + tt;
                    const uint32_t off = (t >> 3) * 16384 + (((t & 7) ^ g) << 4);
                    const uint32_t x0 = lds32(xrow0 + off), x1 = lds32(xrow1 + off);
                    const uint32_t d0 = bsub2(x0, m0), d1 = bsub2(x1, m1);
                    const uint32_t n0 = pack_bf(bf_lo(d0) * s0.y, bf_hi(d0) * s0.y), n1 = pack_bf(bf_lo(d1) * s1.y, bf_hi(d1) * s1.y);
                    const uint32_t o0 = badd2(badd2(x0, bmul2(n0, y[2 * tt])), pack_bf(acc[4 * t], acc[4 * t + 1]));
                    const uint32_t o1 = badd2(badd2(x1, bmul2(n1, y[2 * tt + 1])), pack_bf(acc[4 * t + 2], acc[4 * t + 3]));
                    sts32(xrow0 + off, o0); sts32(xrow1 + off, o1);
                }
            }
            asm volatile("fence.proxy.async.shared::cta;" ::: "memory");
            named_bar(1, 128);
            if (tid == 0) {
                tma2d_store(&p.tm_out, 128 * cb, 64 * rbG2, sb + SM_XE + (j & 1) * 8192);
                tma2d_store(&p.tm_out, 128 * cb + 64, 64 * rbG2, sb + SM_XE + 16384 + (j & 1) * 8192);
                asm volatile("cp.async.bulk.commit_group;" ::: "memory");
                asm volatile("cp.async.bulk.wait_group.read 0;" ::: "memory");
                PROFW(29, 0);
            }
        } else {
            const int m_lane = g + 2 * c + 16 * warp4;
            const int cp = (c + warp4) & 3, ish = (c + warp4) >> 2;
            const uint32_t rdst = sb + SM_RED + warp4 * 8192 + ish * 512 + (g * 4 + cp) * 16;
            const uint32_t rsrc = sb + SM_RED + warp4 * 2048 + lane * 16;
            const uint2 dd = ldg_nc64(p.ssm_D + 4 * b);
            uint32_t a0[4][2][4], a1[4][2][4];
            mbar_wait(sb + SM_BARS + B_CONV * 8, 0);
            conv_load_a<0, 4>(a0, sb + SM_CONV + RB_CH + (m_lane - 8) * 4, m_lane);
            #pragma unroll 1
            for (int ch = 0; ch < 4; ch++) {
                const int gch = 4 * b + ch;
                const uint32_t dw = (ch & 2) ? dd.y : dd.x;
                const uint32_t d2 = __byte_perm(dw, dw, (ch & 1) ? 0x3232 : 0x1010);
                const uint32_t cbase = sb + SM_CONV + ch * CONV_CH;
                const uint64_t db = make_desc(cbase + RB_Z * 16, RB_R1, 128, 0);
                const uint32_t hk_lane = cbase + RB_CH + (m_lane - 8) * 4;
                float acc[4][16];
                PROFW(32 + ch * 3, 4);
                conv_mma<0, 4>(acc, a0, db);
                conv_load_a<4, 4>(a1, hk_lane, m_lane);
                conv_mma<4, 4>(acc, a1, db);
                wg_wait<1>();
                conv_load_a<8, 4>(a0, hk_lane, m_lane);
                conv_mma<8, 4>(acc, a0, db);
                wg_wait<1>();
                conv_load_a<12, 4>(a1, hk_lane, m_lane);
                conv_mma<12, 4>(acc, a1, db);
                const int nch = ch < 3 ? ch + 1 : 3;
                mbar_wait(sb + SM_BARS + (B_CONV + nch) * 8, 0);
                wg_wait<1>();
                conv_load_a<0, 4>(a0, sb + SM_CONV + nch * CONV_CH + RB_CH + (m_lane - 8) * 4, m_lane);
                wg_wait<0>();
                PROFW(33 + ch * 3, 4);
                if (ch == 0) mbar_wait(sb + SM_BARS + B_G1DONE * 8, 0);
                else named_bar(2, 128);
                #pragma unroll
                for (int ii = 0; ii < 16; ii++) {
                    if (ii < 15 || ish == 0)
                        sts128f(rdst + ii * 512, acc[ii >> 2][4 * (ii & 3)], acc[ii >> 2][4 * (ii & 3) + 1], acc[ii >> 2][4 * (ii & 3) + 2], acc[ii >> 2][4 * (ii & 3) + 3]);
                }
                named_bar(2, 128);
                const uint32_t kvaddr = cbase + ((7 - g) & 1) * RB_R1 + (RB_Z + 32 * warp4 + 2 * c) * 16 + ((7 - g) >> 1) * 4;
                uint32_t* ydst = (uint32_t*)(g_yT + (size_t)gch * SEQ + 512 * warp4 + 32 * c + 2 * g);
                #pragma unroll
                for (int ii = 0; ii < 4; ii++) {
                    float4 s = lds128f(rsrc + ii * 512);
                    #pragma unroll
                    for (int ww = 1; ww < 4; ww++) {
                        float4 t = lds128f(rsrc + ww * 8192 + ii * 512);
                        if (ii == 0 && warp4 == 0 && c < ww) t = make_float4(0.f, 0.f, 0.f, 0.f);
                        s.x += t.x; s.y += t.y; s.z += t.z; s.w += t.w;
                    }
                    uint32_t k0 = lds32(kvaddr + ii * 128), k1 = lds32(kvaddr + ii * 128 + 16);
                    k0 = __byte_perm(k0, k0, 0x1032); k1 = __byte_perm(k1, k1, 0x1032);
                    ydst[ii * 64] = badd2(pack_bf(s.z, s.x), bmul2(k0, d2));
                    ydst[ii * 64 + 8] = badd2(pack_bf(s.w, s.y), bmul2(k1, d2));
                }
            }
            PROFW(44, 4);
            asm volatile("fence.proxy.async.global;" ::: "memory");
            __syncwarp();
            if (lane == 0) flag_add(&g_cnt_y[(b >> 5) * 32]);
            PROFW(45, 4);
        }
    } else {
        asm volatile("setmaxnreg.dec.sync.aligned.u32 88;");
        if (warp == 8) {
            if (lane == 0) {
                int st = 0; uint32_t ph = 1;
                #pragma unroll 1
                for (int it = 0; it < 16; it++) {
                    const int pass = it >> 3, sl = it & 7;
                    const int nb = pass ? 3 : 4;
                    const CUtensorMap* tm = pass ? (rank ? &p.tm_uB : &p.tm_gB) : (rank ? &p.tm_uA : &p.tm_gA);
                    mbar_wait(sb + SM_BARS + (B_EMPTY + st) * 8, ph);
                    PROF2(0, it);
                    mbar_expect_tx(sb + SM_BARS + (B_FULL + st) * 8, nb * 8192);
                    tma3d_mc(sb + SM_RING + st * STAGE_BYTES + rank * nb * 4096, tm, 0, ((sl + 2 * cb + 2) & 7) * 64, 7 * j + 4 * pass, sb + SM_BARS + (B_FULL + st) * 8);
                    if (it < 3) {
                        for (int s2 = 2 + 2 * it; s2 < 4 + 2 * it; s2++) {
                            mbar_expect_tx(sb + SM_BARS + (B_XFULL + s2) * 8, 16384);
                            tma2d(sb + SM_X + s2 * 16384, &p.tm_x, 64 * ((s2 + 2 * cb + 2) & 7), 128 * i, sb + SM_BARS + (B_XFULL + s2) * 8);
                        }
                    }
                    if (it == 10 + NSTAGE) {
                        PROF(53);
                        const unsigned ep = lds32(sb + SM_EPOCH);
                        flag_wait(&g_cnt_kv[0], ep * 256);
                        asm volatile("fence.proxy.async.global;" ::: "memory");
                        PROF(54);
                        for (int ch = 0; ch < 4; ch++) {
                            const uint32_t bar = sb + SM_BARS + (B_CONV + ch) * 8;
                            mbar_expect_tx(bar, CONV_CH);
                            bulk_g2s(sb + SM_CONV + ch * CONV_CH, g_rb + (size_t)(4 * b + ch) * RB_CH, RB_CH, bar);
                            bulk_g2s(sb + SM_CONV + ch * CONV_CH + RB_CH, p.ssm_k + (size_t)(4 * b + ch) * SEQ, 4096, bar);
                        }
                    }
                    if (++st == NSTAGE) { st = 0; ph ^= 1; }
                }
                #pragma unroll 1
                for (int u = 0; u < 14; u++) {
                    mbar_wait(sb + SM_BARS + (B_EMPTY + st) * 8, ph);
                    PROF2(0, 16 + u);
                    mbar_expect_tx(sb + SM_BARS + (B_FULL + st) * 8, 32768);
                    tma3d_mc(sb + SM_RING + st * STAGE_BYTES + rank * 8192, &p.tm_w2, 0, blk_f0(4 * u + rank, j), 2 * cb, sb + SM_BARS + (B_FULL + st) * 8);
                    tma3d_mc(sb + SM_RING + st * STAGE_BYTES + 16384 + rank * 8192, &p.tm_w2, 0, blk_f0(4 * u + 2 + rank, j), 2 * cb, sb + SM_BARS + (B_FULL + st) * 8);
                    if (++st == NSTAGE) { st = 0; ph ^= 1; }
                }
                PROF(48);
                const unsigned ep = lds32(sb + SM_EPOCH);
                mbar_wait(sb + SM_BARS + B_G1DONE * 8, 0);
                flag_wait(&g_cnt_y[cb * 32], ep * 128);
                PROF(49);
                asm volatile("fence.proxy.async.global;" ::: "memory");
                mbar_expect_tx(sb + SM_BARS + B_YT * 8, 16384);
                tma2d(sb + SM_YT, &p.tm_yT, 64 * rbG2, 128 * cb, sb + SM_BARS + B_YT * 8);
            }
        } else if (warp < 11) {
            mbar_wait(sb + SM_BARS + (B_XFULL + 7) * 8, 0);
            #pragma unroll 1
            for (int rnd = 0; rnd < 2; rnd++) {
                const int tt = (tid - 288) + 64 * rnd;
                uint32_t sk[4][2];
                {
                    const uint4* sp = (const uint4*)(p.shift_k + 16 * tt);
                    #pragma unroll
                    for (int pr = 0; pr < 2; pr++) {
                        uint4 w = ldg_nc128(sp + pr);
                        sk[0][pr] = __byte_perm(w.x, w.z, 0x5410); sk[1][pr] = __byte_perm(w.x, w.z, 0x7632);
                        sk[2][pr] = __byte_perm(w.y, w.w, 0x5410); sk[3][pr] = __byte_perm(w.y, w.w, 0x7632);
                    }
                }
                const __nv_bfloat16* kp = p.k + (size_t)(16 * b) * DM + 4 * tt;
                const __nv_bfloat16* vp = p.v + (size_t)(16 * b) * DM + 4 * tt;
                uint2 kr[19];
                uint2 kv[16];
                #pragma unroll
                for (int r = 0; r < 3; r++) kr[r] = (b > 0) ? ldg_nc64(kp + (r - 3) * DM) : make_uint2(0, 0);
                #pragma unroll
                for (int hh = 0; hh < 2; hh++) {
                    #pragma unroll
                    for (int r = 0; r < 8; r++) { kr[3 + hh * 8 + r] = ldg_nc64(kp + (hh * 8 + r) * DM); kv[hh * 8 + r] = ldg_nc64(vp + (hh * 8 + r) * DM); }
                    #pragma unroll
                    for (int r = 0; r < 8; r++) {
                        const int s = hh * 8 + r;
                        uint32_t a = bmul2(kr[s].x, sk[3][0]);
                        a = badd2(a, bmul2(kr[s + 1].x, sk[2][0]));
                        a = badd2(a, bmul2(kr[s + 2].x, sk[1][0]));
                        a = badd2(a, bmul2(kr[s + 3].x, sk[0][0]));
                        kv[s].x = bmul2(a, kv[s].x);
                        a = bmul2(kr[s].y, sk[3][1]);
                        a = badd2(a, bmul2(kr[s + 1].y, sk[2][1]));
                        a = badd2(a, bmul2(kr[s + 2].y, sk[1][1]));
                        a = badd2(a, bmul2(kr[s + 3].y, sk[0][1]));
                        kv[s].y = bmul2(a, kv[s].y);
                    }
                }
                #pragma unroll
                for (int cc = 0; cc < 4; cc++) {
                    const uint32_t sel = (cc & 1) ? 0x7632 : 0x5410;
                    #define KVW(r) ((cc & 2) ? kv[r].y : kv[r].x)
                    uint8_t* dst = g_rb + (size_t)(4 * tt + cc) * RB_CH + (RB_Z + b) * 16;
                    *(uint4*)dst = make_uint4(__byte_perm(KVW(15), KVW(14), sel), __byte_perm(KVW(11), KVW(10), sel),
                                              __byte_perm(KVW(7), KVW(6), sel), __byte_perm(KVW(3), KVW(2), sel));
                    *(uint4*)(dst + RB_R1) = make_uint4(__byte_perm(KVW(13), KVW(12), sel), __byte_perm(KVW(9), KVW(8), sel),
                                                        __byte_perm(KVW(5), KVW(4), sel), __byte_perm(KVW(1), KVW(0), sel));
                    #undef KVW
                    if (b < RB_Z) {
                        uint8_t* z = g_rb + (size_t)(4 * tt + cc) * RB_CH + b * 16;
                        *(uint4*)z = make_uint4(0, 0, 0, 0);
                        *(uint4*)(z + RB_R1) = make_uint4(0, 0, 0, 0);
                    }
                }
            }
            asm volatile("fence.proxy.async.global;" ::: "memory");
            __syncwarp();
            if (lane == 0) {
                flag_add(&g_cnt_kv[0]);
                PROFW(50, 9);
                const int wgi = warp - 9;
                mbar_wait(sb + SM_BARS + (B_HD + wgi * 2) * 8, 0);
                flag_add(&g_flag_h[((2 * i + wgi) * 2 + 0) * 8]);
                mbar_wait(sb + SM_BARS + (B_HD + wgi * 2 + 1) * 8, 0);
                flag_add(&g_flag_h[((2 * i + wgi) * 2 + 1) * 8]);
            }
        } else {
            unsigned ep = 0;
            if (lane == 0) {
                ep = g_launch[b] + 1;
                g_launch[b] = ep;
                sts32(sb + SM_EPOCH, ep);
                mbar_wait(sb + SM_BARS + B_PREPD * 8, 0);
                flag_add(&g_cnt_prep[0]);
                flag_wait(&g_cnt_prep[0], ep * 128);
            }
            PROF(51);
            __syncwarp();
            #pragma unroll
            for (int t = 0; t < 2; t++) {
                uint4 v = ldg_cg128((const uint4*)(g_stats + 128 * i) + t * 32 + lane);
                asm volatile("st.shared.v4.u32 [%0], {%1,%2,%3,%4};" :: "r"(sb + SM_STATS + (t * 32 + lane) * 16), "r"(v.x), "r"(v.y), "r"(v.z), "r"(v.w) : "memory");
            }
            #pragma unroll
            for (int t = 0; t < 4; t++) {
                const int idx = t * 32 + lane;
                if (idx < 112) {
                    const int m = idx >= 56;
                    uint4 v = ldg_cg128((const uint4*)(g_cs + m * FF + 224 * j) + (idx - 56 * m));
                    asm volatile("st.shared.v4.u32 [%0], {%1,%2,%3,%4};" :: "r"(sb + SM_CS + idx * 16), "r"(v.x), "r"(v.y), "r"(v.z), "r"(v.w) : "memory");
                }
            }
            __syncwarp();
            if (lane == 0) {
                mbar_arrive(sb + SM_BARS + B_STATS * 8);
                PROF(52);
                l2_prefetch(p.wd + (size_t)b * (FF * DM / NCTA), FF * DM / NCTA * 2);
                l2_prefetch(p.ssm_k + (size_t)(4 * b) * SEQ, 4 * SEQ * 2);
                tmap_prefetch(rank ? &p.tm_uB : &p.tm_gB);
                tmap_prefetch(&p.tm_w2); tmap_prefetch(&p.tm_yT); tmap_prefetch(&p.tm_out);
                mbar_wait(sb + SM_BARS + (B_HD + 0) * 8, 0);
                flag_wait(&g_flag_h[(rbG2 * 2 + 0) * 8], ep * 8);
                mbar_arrive(sb + SM_BARS + B_HRDY * 8);
                mbar_wait(sb + SM_BARS + B_G1DONE * 8, 0);
                flag_wait(&g_flag_h[(rbG2 * 2 + 1) * 8], ep * 8);
                mbar_arrive(sb + SM_BARS + (B_HRDY + 1) * 8);
            }
        }
    }
}

typedef CUresult (*EncodeFn)(CUtensorMap*, CUtensorMapDataType, cuuint32_t, void*, const cuuint64_t*, const cuuint64_t*,
                             const cuuint32_t*, const cuuint32_t*, CUtensorMapInterleave, CUtensorMapSwizzle,
                             CUtensorMapL2promotion, CUtensorMapFloatOOBfill);

void encode(EncodeFn fn, CUtensorMap* tm, const void* base, int rank, const cuuint64_t* dims, const cuuint64_t* strides,
            const cuuint32_t* box, CUtensorMapSwizzle swz) {
    cuuint32_t es[5] = {1, 1, 1, 1, 1};
    fn(tm, CU_TENSOR_MAP_DATA_TYPE_BFLOAT16, rank, (void*)base, dims, strides, box, es, CU_TENSOR_MAP_INTERLEAVE_NONE, swz,
       CU_TENSOR_MAP_L2_PROMOTION_L2_128B, CU_TENSOR_MAP_FLOAT_OOB_FILL_NONE);
}

}

extern "C" void kernel_launch(void* const* d_in, const int* in_sizes, int n_in, void* d_out, int out_size) {
    (void)in_sizes; (void)n_in; (void)out_size;
    static EncodeFn enc = nullptr;
    static void* yT_ptr = nullptr;
    if (!enc) {
        void* fn = nullptr; cudaDriverEntryPointQueryResult qr;
        cudaGetDriverEntryPoint("cuTensorMapEncodeTiled", &fn, cudaEnableDefault, &qr);
        enc = (EncodeFn)fn;
        cudaGetSymbolAddress(&yT_ptr, g_yT);
        cudaFuncSetAttribute(fused_kernel, cudaFuncAttributeMaxDynamicSharedMemorySize, SM_TOTAL);
    }
    Params p;
    p.q = (const __nv_bfloat16*)d_in[0]; p.k = (const __nv_bfloat16*)d_in[1]; p.v = (const __nv_bfloat16*)d_in[2];
    p.shift_k = (const __nv_bfloat16*)d_in[3]; p.ssm_k = (const __nv_bfloat16*)d_in[4]; p.ssm_D = (const __nv_bfloat16*)d_in[5];
    p.wg = (const __nv_bfloat16*)d_in[7]; p.wu = (const __nv_bfloat16*)d_in[8]; p.wd = (const __nv_bfloat16*)d_in[9];
    {
        cuuint64_t dims[2] = {DM, SEQ}; cuuint64_t str[1] = {DM * 2};
        cuuint32_t box[2] = {64, 128};
        encode(enc, &p.tm_x, p.q, 2, dims, str, box, CU_TENSOR_MAP_SWIZZLE_128B);
        cuuint32_t box2[2] = {64, 64};
        encode(enc, &p.tm_out, d_out, 2, dims, str, box2, CU_TENSOR_MAP_SWIZZLE_128B);
    }
    {
        cuuint64_t dims[3] = {32, DM, FF / 32}; cuuint64_t str[2] = {FF * 2, 64};
        cuuint32_t boxA[3] = {32, 64, 4}, boxB[3] = {32, 64, 3};
        encode(enc, &p.tm_gA, p.wg, 3, dims, str, boxA, CU_TENSOR_MAP_SWIZZLE_64B);
        encode(enc, &p.tm_gB, p.wg, 3, dims, str, boxB, CU_TENSOR_MAP_SWIZZLE_64B);
        encode(enc, &p.tm_uA, p.wu, 3, dims, str, boxA, CU_TENSOR_MAP_SWIZZLE_64B);
        encode(enc, &p.tm_uB, p.wu, 3, dims, str, boxB, CU_TENSOR_MAP_SWIZZLE_64B);
    }
    {
        cuuint64_t dims[3] = {64, FF, DM / 64}; cuuint64_t str[2] = {DM * 2, 128};
        cuuint32_t box[3] = {64, 32, 2};
        encode(enc, &p.tm_w2, p.wd, 3, dims, str, box, CU_TENSOR_MAP_SWIZZLE_128B);
    }
    {
        cuuint64_t dims[2] = {SEQ, DM}; cuuint64_t str[1] = {SEQ * 2};
        cuuint32_t box[2] = {64, 128};
        encode(enc, &p.tm_yT, yT_ptr, 2, dims, str, box, CU_TENSOR_MAP_SWIZZLE_128B);
    }
    fused_kernel<<<NCTA, NTHREADS, SM_TOTAL>>>(p);
}
```

```cpp
#include <cuda_runtime.h>
#include <cuda_bf16.h>
#include <cuda.h>
#include <stdint.h>

namespace {

constexpr int SEQ = 2048, DM = 512, FF = 1792;
constexpr int NCTA = 128;
constexpr int NTHREADS = 384;
constexpr int NSTAGE = 3;
constexpr int STAGE_BYTES = 32768;

constexpr uint32_t SM_X = 0;
constexpr uint32_t SM_RING = 131072;
constexpr uint32_t SM_MISC = SM_RING + NSTAGE * STAGE_BYTES;
constexpr uint32_t SM_BARS = SM_MISC;
constexpr uint32_t SM_EPOCH = SM_MISC + 248;
constexpr uint32_t SM_STATS = SM_MISC + 256;
constexpr uint32_t SM_CS = SM_STATS + 1024;
constexpr uint32_t SM_CSTMP = SM_CS;
constexpr uint32_t SM_TOTAL = SM_CS + 1792;
static_assert(SM_TOTAL <= 232448, "smem");
constexpr int RB_Z = 25;
constexpr int RB_R1 = (128 + RB_Z) * 16;
constexpr int RB_CH = 2 * RB_R1;
constexpr int CONV_CH = RB_CH + 4096;
constexpr uint32_t SM_CONV = 0;
constexpr uint32_t SM_RED = 3 * 16384;
constexpr uint32_t SM_YT = 5 * 16384;
constexpr uint32_t SM_XE = 6 * 16384;

constexpr int B_FULL = 0, B_EMPTY = NSTAGE, B_XFULL = 2 * NSTAGE, B_CONV = B_XFULL + 8, B_YT = B_CONV + 4,
              B_STATS = B_YT + 1, B_G1DONE = B_STATS + 1, B_PREPD = B_G1DONE + 1, B_HD = B_PREPD + 1, B_HRDY = B_HD + 4,
              B_XFREE = B_HRDY + 2, B_COUNT = B_XFREE + 1;
static_assert(B_COUNT * 8 <= 248, "barrier space");

__device__ uint4 g_hfrag[32 * 112 * 4 * 32];
__device__ __align__(128) uint8_t g_rb[DM * RB_CH];
__device__ __align__(128) __nv_bfloat16 g_yT[DM * SEQ];
__device__ float2 g_stats[SEQ];
__device__ float g_cs[2 * 2 * FF];
__device__ unsigned g_launch[NCTA];
__device__ unsigned g_cnt_prep[32];
__device__ unsigned g_cnt_kv[32];
__device__ unsigned g_cnt_y[4 * 32];
__device__ unsigned g_flag_h[32 * 2 * 8];

#define PROF(idx)
#define PROF2(a, idx)
#define PROFW(idx, w)

struct Params {
    CUtensorMap tm_x, tm_gA, tm_gB, tm_uA, tm_uB, tm_w2, tm_yT, tm_out;
    const __nv_bfloat16 *q, *k, *v, *shift_k, *ssm_k, *ssm_D, *wg, *wu, *wd;
};

__device__ __forceinline__ void wgmma_rs_n32(float (&d)[16], uint32_t a0, uint32_t a1, uint32_t a2, uint32_t a3, uint64_t db, int sc) {
  asm volatile("{\n.reg .pred p;\nsetp.ne.b32 p, %21, 0;\n"
    "wgmma.mma_async.sync.aligned.m64n32k16.f32.bf16.bf16 {%0,%1,%2,%3,%4,%5,%6,%7,%8,%9,%10,%11,%12,%13,%14,%15}, {%16,%17,%18,%19}, %20, p, 1, 1, 0;\n}\n"
    : "+f"(d[0]),"+f"(d[1]),"+f"(d[2]),"+f"(d[3]),"+f"(d[4]),"+f"(d[5]),"+f"(d[6]),"+f"(d[7]),"+f"(d[8]),"+f"(d[9]),"+f"(d[10]),"+f"(d[11]),"+f"(d[12]),"+f"(d[13]),"+f"(d[14]),"+f"(d[15])
    : "r"(a0),"r"(a1),"r"(a2),"r"(a3),"l"(db),"r"(sc));
}
__device__ __forceinline__ void wgmma_rs_n128_tb(float (&d)[64], uint32_t a0, uint32_t a1, uint32_t a2, uint32_t a3, uint64_t db, int sc) {
  asm volatile("{\n.reg .pred p;\nsetp.ne.b32 p, %69, 0;\n"
    "wgmma.mma_async.sync.aligned.m64n128k16.f32.bf16.bf16 {%0,%1,%2,%3,%4,%5,%6,%7,%8,%9,%10,%11,%12,%13,%14,%15,%16,%17,%18,%19,%20,%21,%22,%23,%24,%25,%26,%27,%28,%29,%30,%31,%32,%33,%34,%35,%36,%37,%38,%39,%40,%41,%42,%43,%44,%45,%46,%47,%48,%49,%50,%51,%52,%53,%54,%55,%56,%57,%58,%59,%60,%61,%62,%63}, {%64,%65,%66,%67}, %68, p, 1, 1, 1;\n}\n"
    : "+f"(d[0]),"+f"(d[1]),"+f"(d[2]),"+f"(d[3]),"+f"(d[4]),"+f"(d[5]),"+f"(d[6]),"+f"(d[7]),"+f"(d[8]),"+f"(d[9]),"+f"(d[10]),"+f"(d[11]),"+f"(d[12]),"+f"(d[13]),"+f"(d[14]),"+f"(d[15]),"+f"(d[16]),"+f"(d[17]),"+f"(d[18]),"+f"(d[19]),"+f"(d[20]),"+f"(d[21]),"+f"(d[22]),"+f"(d[23]),"+f"(d[24]),"+f"(d[25]),"+f"(d[26]),"+f"(d[27]),"+f"(d[28]),"+f"(d[29]),"+f"(d[30]),"+f"(d[31]),"+f"(d[32]),"+f"(d[33]),"+f"(d[34]),"+f"(d[35]),"+f"(d[36]),"+f"(d[37]),"+f"(d[38]),"+f"(d[39]),"+f"(d[40]),"+f"(d[41]),"+f"(d[42]),"+f"(d[43]),"+f"(d[44]),"+f"(d[45]),"+f"(d[46]),"+f"(d[47]),"+f"(d[48]),"+f"(d[49]),"+f"(d[50]),"+f"(d[51]),"+f"(d[52]),"+f"(d[53]),"+f"(d[54]),"+f"(d[55]),"+f"(d[56]),"+f"(d[57]),"+f"(d[58]),"+f"(d[59]),"+f"(d[60]),"+f"(d[61]),"+f"(d[62]),"+f"(d[63])
    : "r"(a0),"r"(a1),"r"(a2),"r"(a3),"l"(db),"r"(sc));
}
__device__ __forceinline__ void wgmma_ss_n256_tb(float (&d)[128], uint64_t da, uint64_t db, int sc) {
  asm volatile("{\n.reg .pred p;\nsetp.ne.b32 p, %130, 0;\n"
    "wgmma.mma_async.sync.aligned.m64n256k16.f32.bf16.bf16 {%0,%1,%2,%3,%4,%5,%6,%7,%8,%9,%10,%11,%12,%13,%14,%15,%16,%17,%18,%19,%20,%21,%22,%23,%24,%25,%26,%27,%28,%29,%30,%31,%32,%33,%34,%35,%36,%37,%38,%39,%40,%41,%42,%43,%44,%45,%46,%47,%48,%49,%50,%51,%52,%53,%54,%55,%56,%57,%58,%59,%60,%61,%62,%63,%64,%65,%66,%67,%68,%69,%70,%71,%72,%73,%74,%75,%76,%77,%78,%79,%80,%81,%82,%83,%84,%85,%86,%87,%88,%89,%90,%91,%92,%93,%94,%95,%96,%97,%98,%99,%100,%101,%102,%103,%104,%105,%106,%107,%108,%109,%110,%111,%112,%113,%114,%115,%116,%117,%118,%119,%120,%121,%122,%123,%124,%125,%126,%127}, %128, %129, p, 1, 1, 0, 1;\n}\n"
    : "+f"(d[0]),"+f"(d[1]),"+f"(d[2]),"+f"(d[3]),"+f"(d[4]),"+f"(d[5]),"+f"(d[6]),"+f"(d[7]),"+f"(d[8]),"+f"(d[9]),"+f"(d[10]),"+f"(d[11]),"+f"(d[12]),"+f"(d[13]),"+f"(d[14]),"+f"(d[15]),"+f"(d[16]),"+f"(d[17]),"+f"(d[18]),"+f"(d[19]),"+f"(d[20]),"+f"(d[21]),"+f"(d[22]),"+f"(d[23]),"+f"(d[24]),"+f"(d[25]),"+f"(d[26]),"+f"(d[27]),"+f"(d[28]),"+f"(d[29]),"+f"(d[30]),"+f"(d[31]),"+f"(d[32]),"+f"(d[33]),"+f"(d[34]),"+f"(d[35]),"+f"(d[36]),"+f"(d[37]),"+f"(d[38]),"+f"(d[39]),"+f"(d[40]),"+f"(d[41]),"+f"(d[42]),"+f"(d[43]),"+f"(d[44]),"+f"(d[45]),"+f"(d[46]),"+f"(d[47]),"+f"(d[48]),"+f"(d[49]),"+f"(d[50]),"+f"(d[51]),"+f"(d[52]),"+f"(d[53]),"+f"(d[54]),"+f"(d[55]),"+f"(d[56]),"+f"(d[57]),"+f"(d[58]),"+f"(d[59]),"+f"(d[60]),"+f"(d[61]),"+f"(d[62]),"+f"(d[63]),"+f"(d[64]),"+f"(d[65]),"+f"(d[66]),"+f"(d[67]),"+f"(d[68]),"+f"(d[69]),"+f"(d[70]),"+f"(d[71]),"+f"(d[72]),"+f"(d[73]),"+f"(d[74]),"+f"(d[75]),"+f"(d[76]),"+f"(d[77]),"+f"(d[78]),"+f"(d[79]),"+f"(d[80]),"+f"(d[81]),"+f"(d[82]),"+f"(d[83]),"+f"(d[84]),"+f"(d[85]),"+f"(d[86]),"+f"(d[87]),"+f"(d[88]),"+f"(d[89]),"+f"(d[90]),"+f"(d[91]),"+f"(d[92]),"+f"(d[93]),"+f"(d[94]),"+f"(d[95]),"+f"(d[96]),"+f"(d[97]),"+f"(d[98]),"+f"(d[99]),"+f"(d[100]),"+f"(d[101]),"+f"(d[102]),"+f"(d[103]),"+f"(d[104]),"+f"(d[105]),"+f"(d[106]),"+f"(d[107]),"+f"(d[108]),"+f"(d[109]),"+f"(d[110]),"+f"(d[111]),"+f"(d[112]),"+f"(d[113]),"+f"(d[114]),"+f"(d[115]),"+f"(d[116]),"+f"(d[117]),"+f"(d[118]),"+f"(d[119]),"+f"(d[120]),"+f"(d[121]),"+f"(d[122]),"+f"(d[123]),"+f"(d[124]),"+f"(d[125]),"+f"(d[126]),"+f"(d[127])
    : "l"(da),"l"(db),"r"(sc));
}
__device__ __forceinline__ void wgmma_ss_n192_tb(float (&d)[96], uint64_t da, uint64_t db, int sc) {
  asm volatile("{\n.reg .pred p;\nsetp.ne.b32 p, %98, 0;\n"
    "wgmma.mma_async.sync.aligned.m64n192k16.f32.bf16.bf16 {%0,%1,%2,%3,%4,%5,%6,%7,%8,%9,%10,%11,%12,%13,%14,%15,%16,%17,%18,%19,%20,%21,%22,%23,%24,%25,%26,%27,%28,%29,%30,%31,%32,%33,%34,%35,%36,%37,%38,%39,%40,%41,%42,%43,%44,%45,%46,%47,%48,%49,%50,%51,%52,%53,%54,%55,%56,%57,%58,%59,%60,%61,%62,%63,%64,%65,%66,%67,%68,%69,%70,%71,%72,%73,%74,%75,%76,%77,%78,%79,%80,%81,%82,%83,%84,%85,%86,%87,%88,%89,%90,%91,%92,%93,%94,%95}, %96, %97, p, 1, 1, 0, 1;\n}\n"
    : "+f"(d[0]),"+f"(d[1]),"+f"(d[2]),"+f"(d[3]),"+f"(d[4]),"+f"(d[5]),"+f"(d[6]),"+f"(d[7]),"+f"(d[8]),"+f"(d[9]),"+f"(d[10]),"+f"(d[11]),"+f"(d[12]),"+f"(d[13]),"+f"(d[14]),"+f"(d[15]),"+f"(d[16]),"+f"(d[17]),"+f"(d[18]),"+f"(d[19]),"+f"(d[20]),"+f"(d[21]),"+f"(d[22]),"+f"(d[23]),"+f"(d[24]),"+f"(d[25]),"+f"(d[26]),"+f"(d[27]),"+f"(d[28]),"+f"(d[29]),"+f"(d[30]),"+f"(d[31]),"+f"(d[32]),"+f"(d[33]),"+f"(d[34]),"+f"(d[35]),"+f"(d[36]),"+f"(d[37]),"+f"(d[38]),"+f"(d[39]),"+f"(d[40]),"+f"(d[41]),"+f"(d[42]),"+f"(d[43]),"+f"(d[44]),"+f"(d[45]),"+f"(d[46]),"+f"(d[47]),"+f"(d[48]),"+f"(d[49]),"+f"(d[50]),"+f"(d[51]),"+f"(d[52]),"+f"(d[53]),"+f"(d[54]),"+f"(d[55]),"+f"(d[56]),"+f"(d[57]),"+f"(d[58]),"+f"(d[59]),"+f"(d[60]),"+f"(d[61]),"+f"(d[62]),"+f"(d[63]),"+f"(d[64]),"+f"(d[65]),"+f"(d[66]),"+f"(d[67]),"+f"(d[68]),"+f"(d[69]),"+f"(d[70]),"+f"(d[71]),"+f"(d[72]),"+f"(d[73]),"+f"(d[74]),"+f"(d[75]),"+f"(d[76]),"+f"(d[77]),"+f"(d[78]),"+f"(d[79]),"+f"(d[80]),"+f"(d[81]),"+f"(d[82]),"+f"(d[83]),"+f"(d[84]),"+f"(d[85]),"+f"(d[86]),"+f"(d[87]),"+f"(d[88]),"+f"(d[89]),"+f"(d[90]),"+f"(d[91]),"+f"(d[92]),"+f"(d[93]),"+f"(d[94]),"+f"(d[95])
    : "l"(da),"l"(db),"r"(sc));
}

__device__ __forceinline__ uint32_t smem_u32(const void* p) { return (uint32_t)__cvta_generic_to_shared(p); }
__device__ __forceinline__ void mbar_init(uint32_t bar, uint32_t cnt) { asm volatile("mbarrier.init.shared::cta.b64 [%0], %1;" :: "r"(bar), "r"(cnt)); }
__device__ __forceinline__ void mbar_expect_tx(uint32_t bar, uint32_t bytes) { asm volatile("mbarrier.arrive.expect_tx.shared::cta.b64 _, [%0], %1;" :: "r"(bar), "r"(bytes) : "memory"); }
__device__ __forceinline__ void mbar_arrive(uint32_t bar) { asm volatile("mbarrier.arrive.shared::cta.b64 _, [%0];" :: "r"(bar) : "memory"); }
__device__ __forceinline__ void mbar_arrive_cluster(uint32_t cbar, uint32_t cnt) { asm volatile("mbarrier.arrive.shared::cluster.b64 _, [%0], %1;" :: "r"(cbar), "r"(cnt) : "memory"); }
__device__ __forceinline__ uint32_t mapa(uint32_t a, uint32_t rank) { uint32_t r; asm volatile("mapa.shared::cluster.u32 %0, %1, %2;" : "=r"(r) : "r"(a), "r"(rank)); return r; }
__device__ __forceinline__ void mbar_wait(uint32_t bar, uint32_t parity) {
    uint32_t ok; uint32_t n = 0;
    do {
        asm volatile("{\n.reg .pred p;\nmbarrier.try_wait.parity.shared::cta.b64 p, [%1], %2;\nselp.u32 %0, 1, 0, p;\n}" : "=r"(ok) : "r"(bar), "r"(parity) : "memory");
    } while (!ok && ++n < (1u << 17));
}
__device__ __forceinline__ void flag_wait(const unsigned* p, unsigned target) {
    unsigned v; uint32_t n = 0;
    while (true) {
        asm volatile("ld.acquire.gpu.global.u32 %0, [%1];" : "=r"(v) : "l"(p) : "memory");
        if ((int)(v - target) >= 0 || ++n >= (1u << 17)) break;
        __nanosleep(200);
    }
}
__device__ __forceinline__ void flag_add(unsigned* p) {
    asm volatile("fence.acq_rel.gpu;\nred.relaxed.gpu.global.add.u32 [%0], 1;" :: "l"(p) : "memory");
}
__device__ __forceinline__ uint64_t make_desc(uint32_t addr, uint32_t lbo, uint32_t sbo, uint32_t swz) {
    return (uint64_t)((addr & 0x3FFFF) >> 4) | ((uint64_t)((lbo & 0x3FFFF) >> 4) << 16) | ((uint64_t)((sbo & 0x3FFFF) >> 4) << 32) | ((uint64_t)swz << 62);
}
__device__ __forceinline__ uint64_t desc_add(uint64_t d, uint32_t off16) {
    return (d & 0xFFFFFFFF00000000ull) | (uint64_t)((uint32_t)d + off16);
}
__device__ __forceinline__ void tma2d(uint32_t dst, const CUtensorMap* tm, int c0, int c1, uint32_t bar) {
    asm volatile("cp.async.bulk.tensor.2d.shared::cluster.global.mbarrier::complete_tx::bytes [%0], [%1, {%3, %4}], [%2];"
        :: "r"(dst), "l"((uint64_t)tm), "r"(bar), "r"(c0), "r"(c1) : "memory");
}
__device__ __forceinline__ void tma3d_mc(uint32_t dst, const CUtensorMap* tm, int c0, int c1, int c2, uint32_t bar) {
    asm volatile("cp.async.bulk.tensor.3d.shared::cluster.global.mbarrier::complete_tx::bytes.multicast::cluster [%0], [%1, {%3, %4, %5}], [%2], %6;"
        :: "r"(dst), "l"((uint64_t)tm), "r"(bar), "r"(c0), "r"(c1), "r"(c2), "h"((uint16_t)3) : "memory");
}
__device__ __forceinline__ void bulk_g2s(uint32_t dst, const void* src, uint32_t bytes, uint32_t bar) {
    asm volatile("cp.async.bulk.shared::cluster.global.mbarrier::complete_tx::bytes [%0], [%1], %2, [%3];"
        :: "r"(dst), "l"(src), "r"(bytes), "r"(bar) : "memory");
}
__device__ __forceinline__ void tma2d_store(const CUtensorMap* tm, int c0, int c1, uint32_t src) {
    asm volatile("cp.async.bulk.tensor.2d.global.shared::cta.bulk_group [%0, {%2, %3}], [%1];"
        :: "l"((uint64_t)tm), "r"(src), "r"(c0), "r"(c1) : "memory");
}
__device__ __forceinline__ void l2_prefetch(const void* p, uint32_t bytes) {
    asm volatile("cp.async.bulk.prefetch.L2.global [%0], %1;" :: "l"(p), "r"(bytes) : "memory");
}
__device__ __forceinline__ void tmap_prefetch(const CUtensorMap* tm) { asm volatile("prefetch.tensormap [%0];" :: "l"((uint64_t)tm) : "memory"); }
__device__ __forceinline__ uint32_t lds32(uint32_t a) { uint32_t v; asm volatile("ld.shared.u32 %0, [%1];" : "=r"(v) : "r"(a)); return v; }
__device__ __forceinline__ float2 lds64f(uint32_t a) { float2 v; asm volatile("ld.shared.v2.f32 {%0,%1}, [%2];" : "=f"(v.x), "=f"(v.y) : "r"(a)); return v; }
__device__ __forceinline__ float4 lds128f(uint32_t a) { float4 v; asm volatile("ld.shared.v4.f32 {%0,%1,%2,%3}, [%4];" : "=f"(v.x), "=f"(v.y), "=f"(v.z), "=f"(v.w) : "r"(a) : "memory"); return v; }
__device__ __forceinline__ void sts32(uint32_t a, uint32_t v) { asm volatile("st.shared.u32 [%0], %1;" :: "r"(a), "r"(v) : "memory"); }
__device__ __forceinline__ void sts128f(uint32_t a, float x, float y, float z, float w) { asm volatile("st.shared.v4.f32 [%0], {%1,%2,%3,%4};" :: "r"(a), "f"(x), "f"(y), "f"(z), "f"(w) : "memory"); }
__device__ __forceinline__ uint4 ldg_cg128(const void* p) { uint4 v; asm volatile("ld.global.cg.v4.u32 {%0,%1,%2,%3}, [%4];" : "=r"(v.x), "=r"(v.y), "=r"(v.z), "=r"(v.w) : "l"(p)); return v; }
__device__ __forceinline__ uint4 ldg_nc128(const void* p) { uint4 v; asm volatile("ld.global.nc.L1::no_allocate.v4.u32 {%0,%1,%2,%3}, [%4];" : "=r"(v.x), "=r"(v.y), "=r"(v.z), "=r"(v.w) : "l"(p)); return v; }
__device__ __forceinline__ uint2 ldg_nc64(const void* p) { uint2 v; asm volatile("ld.global.nc.L1::no_allocate.v2.u32 {%0,%1}, [%2];" : "=r"(v.x), "=r"(v.y) : "l"(p)); return v; }
#define WG_FENCE() asm volatile("wgmma.fence.sync.aligned;\n" ::: "memory")
#define WG_COMMIT() asm volatile("wgmma.commit_group.sync.aligned;\n" ::: "memory")
template<int N> __device__ __forceinline__ void wg_wait() { asm volatile("wgmma.wait_group.sync.aligned %0;\n" :: "n"(N) : "memory"); }
__device__ __forceinline__ void named_bar(int id, int n) { asm volatile("bar.sync %0, %1;" :: "r"(id), "r"(n) : "memory"); }

__device__ __forceinline__ float bf_lo(uint32_t u) { return __uint_as_float(u << 16); }
__device__ __forceinline__ float bf_hi(uint32_t u) { return __uint_as_float(u & 0xFFFF0000u); }
__device__ __forceinline__ uint32_t pack_bf(float lo, float hi) { uint32_t r; asm("cvt.rn.bf16x2.f32 %0, %1, %2;" : "=r"(r) : "f"(hi), "f"(lo)); return r; }
__device__ __forceinline__ float bf_round(float x) { return __bfloat162float(__float2bfloat16_rn(x)); }
__device__ __forceinline__ uint32_t bmul2(uint32_t a, uint32_t b) { uint32_t r; asm("mul.rn.bf16x2 %0, %1, %2;" : "=r"(r) : "r"(a), "r"(b)); return r; }
__device__ __forceinline__ uint32_t badd2(uint32_t a, uint32_t b) { uint32_t r; asm("add.rn.bf16x2 %0, %1, %2;" : "=r"(r) : "r"(a), "r"(b)); return r; }
__device__ __forceinline__ uint32_t bsub2(uint32_t a, uint32_t b) { uint32_t r; asm("sub.rn.bf16x2 %0, %1, %2;" : "=r"(r) : "r"(a), "r"(b)); return r; }

__device__ __forceinline__ int blk_f0(int bi, int j) {
    if (bi < 32) return 224 * ((j + (bi >> 2)) & 7) + 32 * (bi & 3);
    int b2 = bi - 32; int q3 = (b2 * 11) >> 5;
    return 224 * ((j + q3) & 7) + 128 + 32 * (b2 - 3 * q3);
}

struct Ring { int st; uint32_t ph; };
__device__ __forceinline__ void ring_next(Ring& r) { if (++r.st == NSTAGE) { r.st = 0; r.ph ^= 1; } }

template<int NB>
__device__ __forceinline__ void gemm1_pass(uint32_t sb, int wgi, int warp4, int lane, Ring& rg, uint32_t e_cl,
                                           int rb64, int ks0, int csoff) {
    constexpr bool passA = (NB == 4);
    float acc[NB * 32];
    const uint64_t descA0 = make_desc(sb + SM_X + wgi * 8192, 16, 1024, 1);
    const uint64_t descB0 = make_desc(sb + SM_RING, 4096, 512, 2);
    int prev = 0;
    #pragma unroll 1
    for (int sl = 0; sl < 8; sl++) {
        if (passA) mbar_wait(sb + SM_BARS + (B_XFULL + sl) * 8, 0);
        if (warp4 == 0 && wgi == 0) PROF2(2, sl + (passA ? 0 : 8));
        mbar_wait(sb + SM_BARS + (B_FULL + rg.st) * 8, rg.ph);
        if (sl == 0 && warp4 == 0) PROF(2 + wgi * 8 + (passA ? 0 : 3));
        if (warp4 == 0 && wgi == 0) PROF2(1, sl + (passA ? 0 : 8));
        const uint64_t da = desc_add(descA0, sl * 1024), db = desc_add(descB0, rg.st * 2048);
        WG_FENCE();
        #pragma unroll
        for (int kk = 0; kk < 4; kk++) {
            int sc = (sl | kk) ? 1 : 0;
            if constexpr (NB == 4) wgmma_ss_n256_tb(acc, da + kk * 2, db + kk * 64, sc); else wgmma_ss_n192_tb(acc, da + kk * 2, db + kk * 64, sc);
        }
        WG_COMMIT();
        wg_wait<1>();
        if (warp4 == 0 && wgi == 0) PROF2(3, sl + (passA ? 0 : 8));
        if (lane < 2 && sl) mbar_arrive_cluster(e_cl + prev * 8, 1);
        if (!passA && sl == 3 && lane == 0) mbar_arrive(sb + SM_BARS + B_XFREE * 8);
        prev = rg.st;
        ring_next(rg);
    }
    wg_wait<0>();
    if (lane < 2) mbar_arrive_cluster(e_cl + prev * 8, 1);
    if (!passA && lane == 0) mbar_arrive(sb + SM_BARS + B_G1DONE * 8);
    if (warp4 == 0) PROF(3 + wgi * 8 + (passA ? 0 : 3));
    if (passA) mbar_wait(sb + SM_BARS + B_STATS * 8, 0);
    const int g = lane >> 2, c = lane & 3;
    const int r0 = wgi * 64 + warp4 * 16 + g;
    const float2 s0 = lds64f(sb + SM_STATS + r0 * 8), s1 = lds64f(sb + SM_STATS + (r0 + 8) * 8);
    const uint32_t csg = sb + SM_CS + (csoff + 2 * c) * 4, csu = csg + 224 * 4;
    uint4* dst = g_hfrag + ((size_t)(rb64 * 112 + ks0) * 4 + warp4) * 32 + lane;
    #pragma unroll
    for (int kk = 0; kk < NB * 2; kk++) {
        uint32_t h[4];
        #pragma unroll
        for (int tt = 0; tt < 2; tt++) {
            const int t = 2 * kk + tt;
            const float2 cg = lds64f(csg + t * 32), cu = lds64f(csu + t * 32);
            const float* ag = &acc[4 * t];
            const float* au = &acc[NB * 16 + 4 * t];
            uint32_t g0 = pack_bf((ag[0] - s0.x * cg.x) * s0.y, (ag[1] - s0.x * cg.y) * s0.y);
            uint32_t u0 = pack_bf((au[0] - s0.x * cu.x) * s0.y, (au[1] - s0.x * cu.y) * s0.y);
            uint32_t g1 = pack_bf((ag[2] - s1.x * cg.x) * s1.y, (ag[3] - s1.x * cg.y) * s1.y);
            uint32_t u1 = pack_bf((au[2] - s1.x * cu.x) * s1.y, (au[3] - s1.x * cu.y) * s1.y);
            h[2 * tt] = bmul2(g0, u0);
            h[2 * tt + 1] = bmul2(g1, u1);
        }
        dst[kk * 128] = make_uint4(h[0], h[1], h[2], h[3]);
    }
    __syncwarp();
    if (lane == 0) mbar_arrive(sb + SM_BARS + (B_HD + wgi * 2 + (passA ? 0 : 1)) * 8);
    if (warp4 == 0) PROF(4 + wgi * 8 + (passA ? 0 : 3));
}

template<int P0, int NP>
__device__ __forceinline__ void conv_load_a(uint32_t (&a)[NP][2][4], uint32_t hk_lane, int m_lane) {
    #pragma unroll
    for (int pp = 0; pp < NP; pp++) {
        #pragma unroll
        for (int q = 0; q < 2; q++) {
            const int off = (8 * q + 64 * (P0 + pp)) * 4;
            uint32_t w0, w1, w2;
            if (P0 + pp == 0 && q == 0) {
                w0 = (m_lane + 0 < 8) ? 0u : lds32(hk_lane + off);
                w1 = (m_lane + 1 < 8) ? 0u : lds32(hk_lane + off + 4);
                w2 = (m_lane + 2 < 8) ? 0u : lds32(hk_lane + off + 8);
            } else {
                w0 = lds32(hk_lane + off); w1 = lds32(hk_lane + off + 4); w2 = lds32(hk_lane + off + 8);
            }
            a[pp][q][0] = w1;
            a[pp][q][1] = __byte_perm(w0, w1, 0x5432);
            a[pp][q][2] = w2;
            a[pp][q][3] = __byte_perm(w1, w2, 0x5432);
        }
    }
}
template<int P0, int NP>
__device__ __forceinline__ void conv_mma(float (&acc)[4][16], uint32_t (&a)[NP][2][4], uint64_t db) {
    WG_FENCE();
    #pragma unroll
    for (int pp = 0; pp < NP; pp++) {
        #pragma unroll
        for (int q = 0; q < 2; q++) {
            const int P = P0 + pp;
            #pragma unroll
            for (int bq = P / 4; bq < 4; bq++)
                wgmma_rs_n32(acc[bq], a[pp][q][0], a[pp][q][1], a[pp][q][2], a[pp][q][3],
                             db + (uint64_t)(int64_t)(32 * bq - 8 * P - q), (P == 0 && q == 0) ? 0 : 1);
        }
    }
    WG_COMMIT();
}

__global__ void __cluster_dims__(2, 1, 1) __launch_bounds__(NTHREADS, 1)
fused_kernel(const __grid_constant__ Params p) {
    extern __shared__ __align__(1024) uint8_t smem_raw[];
    const uint32_t sb = smem_u32(smem_raw);
    const int tid = threadIdx.x, warp = tid >> 5, lane = tid & 31;
    const int b = blockIdx.x;
    const int rank = b & 1;
    const int j = (b >> 1) & 7;
    const int i = ((b >> 4) << 1) | rank;
    const int cb = j >> 1;
    const int rbG2 = 2 * i + (j & 1);

    if (tid == 256) {
        tmap_prefetch(&p.tm_x);
        tmap_prefetch(rank ? &p.tm_uA : &p.tm_gA);
        for (int s = 0; s < NSTAGE; s++) { mbar_init(sb + SM_BARS + (B_FULL + s) * 8, 1); mbar_init(sb + SM_BARS + (B_EMPTY + s) * 8, 16); }
        for (int s = 0; s < 8; s++) mbar_init(sb + SM_BARS + (B_XFULL + s) * 8, 1);
        for (int s = 0; s < 4; s++) mbar_init(sb + SM_BARS + (B_CONV + s) * 8, 1);
        mbar_init(sb + SM_BARS + B_YT * 8, 1);
        mbar_init(sb + SM_BARS + B_STATS * 8, 1);
        mbar_init(sb + SM_BARS + B_G1DONE * 8, 8);
        mbar_init(sb + SM_BARS + B_PREPD * 8, 4);
        mbar_init(sb + SM_BARS + B_XFREE * 8, 8);
        for (int s = 0; s < 4; s++) mbar_init(sb + SM_BARS + (B_HD + s) * 8, 4);
        for (int s = 0; s < 2; s++) mbar_init(sb + SM_BARS + (B_HRDY + s) * 8, 1);
        asm volatile("fence.mbarrier_init.release.cluster;" ::: "memory");
        asm volatile("fence.proxy.async.shared::cta;" ::: "memory");
        for (int sl = 0; sl < 2; sl++) {
            const int kc = (sl + 2 * cb + 2) & 7;
            mbar_expect_tx(sb + SM_BARS + (B_XFULL + sl) * 8, 16384);
            tma2d(sb + SM_X + sl * 16384, &p.tm_x, 64 * kc, 128 * i, sb + SM_BARS + (B_XFULL + sl) * 8);
        }
    }
    __syncwarp();
    asm volatile("barrier.cluster.arrive.relaxed.aligned;\nbarrier.cluster.wait.aligned;\n" ::: "memory");
    PROFW(1, 0);

    if (warp < 8) {
        asm volatile("setmaxnreg.inc.sync.aligned.u32 200;");
        const int wgi = warp >> 2, warp4 = warp & 3;
        const uint32_t e_cl = mapa(sb + SM_BARS + B_EMPTY * 8, lane & 1);
        if (wgi == 1) {
            uint4 xr[4][2];
            #pragma unroll
            for (int rr = 0; rr < 4; rr++) {
                const __nv_bfloat16* row = p.q + (size_t)(16 * b + 4 * warp4 + rr) * DM;
                xr[rr][0] = ldg_nc128(row + 8 * lane);
                xr[rr][1] = ldg_nc128(row + 256 + 8 * lane);
            }
            float rs[4], rq[4];
            #pragma unroll
            for (int rr = 0; rr < 4; rr++) {
                const uint32_t* u = (const uint32_t*)&xr[rr][0];
                float s = 0.f;
                #pragma unroll
                for (int e = 0; e < 8; e++) s += bf_lo(u[e]) + bf_hi(u[e]);
                rs[rr] = s;
            }
            #pragma unroll
            for (int o = 16; o > 0; o >>= 1) {
                #pragma unroll
                for (int rr = 0; rr < 4; rr++) rs[rr] += __shfl_xor_sync(0xffffffffu, rs[rr], o);
            }
            #pragma unroll
            for (int rr = 0; rr < 4; rr++) {
                const uint32_t* u = (const uint32_t*)&xr[rr][0];
                const float mean = rs[rr] * (1.0f / DM);
                float ss = 0.f;
                #pragma unroll
                for (int e = 0; e < 8; e++) { float d0 = bf_lo(u[e]) - mean, d1 = bf_hi(u[e]) - mean; ss += d0 * d0; ss += d1 * d1; }
                rq[rr] = ss;
            }
            #pragma unroll
            for (int o = 16; o > 0; o >>= 1) {
                #pragma unroll
                for (int rr = 0; rr < 4; rr++) rq[rr] += __shfl_xor_sync(0xffffffffu, rq[rr], o);
            }
            if (lane < 4) {
                const float s = lane == 0 ? rs[0] : lane == 1 ? rs[1] : lane == 2 ? rs[2] : rs[3];
                const float ss = lane == 0 ? rq[0] : lane == 1 ? rq[1] : lane == 2 ? rq[2] : rq[3];
                const float var_b = bf_round(ss * (1.0f / DM));
                const float sd = bf_round(sqrtf(bf_round(var_b + 1e-5f)));
                g_stats[16 * b + 4 * warp4 + lane] = make_float2(bf_round(s * (1.0f / DM)), 1.0f / sd);
            }
            __syncwarp();
            if (lane == 0) mbar_arrive(sb + SM_BARS + B_PREPD * 8);
            PROFW(18, 4);
        }
        Ring rg = {0, 0};
        const int rb64 = 2 * i + wgi;
        gemm1_pass<4>(sb, wgi, warp4, lane, rg, e_cl, rb64, 14 * j, 0);
        gemm1_pass<3>(sb, wgi, warp4, lane, rg, e_cl, rb64, 14 * j + 8, 128);

        const int g = lane >> 2, c = lane & 3;
        if (wgi == 0) {
            float acc[64];
            uint4 af[3][8];
            const uint4* hsrc = g_hfrag + ((size_t)rbG2 * 112 * 4 + warp4) * 32 + lane;
            const uint64_t descB0 = make_desc(sb + SM_RING, 4096, 1024, 1);
            int prev = 0;
            auto load_group = [&](uint4 (&dstf)[8], int u) {
                #pragma unroll
                for (int hb = 0; hb < 4; hb++) {
                    const int ks = blk_f0(4 * u + hb, j) >> 4;
                    dstf[2 * hb] = ldg_cg128(hsrc + ks * 128);
                    dstf[2 * hb + 1] = ldg_cg128(hsrc + ks * 128 + 128);
                }
            };
            auto g2_step = [&](int u, uint4 (&cur)[8], uint4 (&nxt)[8], bool do_load) {
                if (warp4 == 0) PROF2(2, 16 + u);
                mbar_wait(sb + SM_BARS + (B_FULL + rg.st) * 8, rg.ph);
                if (warp4 == 0) PROF2(1, 16 + u);
                const uint64_t db = desc_add(descB0, rg.st * 2048);
                WG_FENCE();
                #pragma unroll
                for (int kk = 0; kk < 8; kk++)
                    wgmma_rs_n128_tb(acc, cur[kk].x, cur[kk].y, cur[kk].z, cur[kk].w, db + ((kk >> 1) * 512 + (kk & 1) * 128), (u | kk) ? 1 : 0);
                WG_COMMIT();
                wg_wait<1>();
                if (warp4 == 0) PROF2(3, 16 + u);
                if (lane < 2 && u > 0 && u - 1 + NSTAGE < 14) mbar_arrive_cluster(e_cl + prev * 8, 2);
                prev = rg.st;
                ring_next(rg);
                if (u + 2 == 8) mbar_wait(sb + SM_BARS + (B_HRDY + 1) * 8, 0);
                if (do_load) load_group(nxt, u + 2);
            };
            mbar_wait(sb + SM_BARS + B_HRDY * 8, 0);
            PROFW(20, 0);
            load_group(af[0], 0); load_group(af[1], 1);
            #pragma unroll 1
            for (int u0 = 0; u0 < 12; u0 += 3) {
                g2_step(u0, af[0], af[2], true);
                g2_step(u0 + 1, af[1], af[0], true);
                g2_step(u0 + 2, af[2], af[1], true);
                PROFW(21 + (u0 / 3), 0);
            }
            g2_step(12, af[0], af[2], false);
            g2_step(13, af[1], af[0], false);
            wg_wait<0>();
            PROFW(27, 0);
            mbar_wait(sb + SM_BARS + B_YT * 8, 0);
            PROFW(28, 0);
            const int r0 = (j & 1) * 64 + warp4 * 16 + g;
            const float2 s0 = lds64f(sb + SM_STATS + r0 * 8), s1 = lds64f(sb + SM_STATS + (r0 + 8) * 8);
            const uint32_t m0 = pack_bf(s0.x, s0.x), m1 = pack_bf(s1.x, s1.x);
            const uint32_t xrow0 = sb + SM_XE + r0 * 128 + c * 4, xrow1 = xrow0 + 8 * 128;
            const int mi = lane >> 3, lr = lane & 7;
            const uint32_t yaddr = sb + SM_YT + ((mi >> 1) * 8 + lr) * 128 + (((2 * warp4 + (mi & 1)) ^ lr) << 4);
            #pragma unroll
            for (int t2 = 0; t2 < 8; t2++) {
                uint32_t y[4];
                asm volatile("ldmatrix.sync.aligned.m8n8.x4.trans.shared.b16 {%0,%1,%2,%3}, [%4];"
                    : "=r"(y[0]), "=r"(y[1]), "=r"(y[2]), "=r"(y[3]) : "r"(yaddr + t2 * 2048) : "memory");
                #pragma unroll
                for (int tt = 0; tt < 2; tt++) {
                    const int t = 2 * t2 + tt;
                    const uint32_t off = (t >> 3) * 16384 + (((t & 7) ^ g) << 4);
                    const uint32_t x0 = lds32(xrow0 + off), x1 = lds32(xrow1 + off);
                    const uint32_t d0 = bsub2(x0, m0), d1 = bsub2(x1, m1);
                    const uint32_t n0 = pack_bf(bf_lo(d0) * s0.y, bf_hi(d0) * s0.y), n1 = pack_bf(bf_lo(d1) * s1.y, bf_hi(d1) * s1.y);
                    const uint32_t o0 = badd2(badd2(x0, bmul2(n0, y[2 * tt])), pack_bf(acc[4 * t], acc[4 * t + 1]));
                    const uint32_t o1 = badd2(badd2(x1, bmul2(n1, y[2 * tt + 1])), pack_bf(acc[4 * t + 2], acc[4 * t + 3]));
                    sts32(xrow0 + off, o0); sts32(xrow1 + off, o1);
                }
            }
            asm volatile("fence.proxy.async.shared::cta;" ::: "memory");
            named_bar(1, 128);
            if (tid == 0) {
                tma2d_store(&p.tm_out, 128 * cb, 64 * rbG2, sb + SM_XE + (j & 1) * 8192);
                tma2d_store(&p.tm_out, 128 * cb + 64, 64 * rbG2, sb + SM_XE + 16384 + (j & 1) * 8192);
                asm volatile("cp.async.bulk.commit_group;" ::: "memory");
                asm volatile("cp.async.bulk.wait_group.read 0;" ::: "memory");
                PROFW(29, 0);
            }
        } else {
            const int m_lane = g + 2 * c + 16 * warp4;
            const int cp = (c + warp4) & 3, ish = (c + warp4) >> 2;
            const uint32_t rdst = sb + SM_RED + warp4 * 8192 + ish * 512 + (g * 4 + cp) * 16;
            const uint32_t rsrc = sb + SM_RED + warp4 * 2048 + lane * 16;
            const uint2 dd = ldg_nc64(p.ssm_D + 4 * b);
            uint32_t a0[4][2][4], a1[4][2][4];
            mbar_wait(sb + SM_BARS + B_CONV * 8, 0);
            conv_load_a<0, 4>(a0, sb + SM_CONV + RB_CH + (m_lane - 8) * 4, m_lane);
            #pragma unroll 1
            for (int ch = 0; ch < 4; ch++) {
                const int gch = 4 * b + ch;
                const uint32_t dw = (ch & 2) ? dd.y : dd.x;
                const uint32_t d2 = __byte_perm(dw, dw, (ch & 1) ? 0x3232 : 0x1010);
                const uint32_t cbase = sb + SM_CONV + ch * CONV_CH;
                const uint64_t db = make_desc(cbase + RB_Z * 16, RB_R1, 128, 0);
                const uint32_t hk_lane = cbase + RB_CH + (m_lane - 8) * 4;
                float acc[4][16];
                PROFW(32 + ch * 3, 4);
                conv_mma<0, 4>(acc, a0, db);
                conv_load_a<4, 4>(a1, hk_lane, m_lane);
                conv_mma<4, 4>(acc, a1, db);
                wg_wait<1>();
                conv_load_a<8, 4>(a0, hk_lane, m_lane);
                conv_mma<8, 4>(acc, a0, db);
                wg_wait<1>();
                conv_load_a<12, 4>(a1, hk_lane, m_lane);
                conv_mma<12, 4>(acc, a1, db);
                const int nch = ch < 3 ? ch + 1 : 3;
                mbar_wait(sb + SM_BARS + (B_CONV + nch) * 8, 0);
                wg_wait<1>();
                conv_load_a<0, 4>(a0, sb + SM_CONV + nch * CONV_CH + RB_CH + (m_lane - 8) * 4, m_lane);
                wg_wait<0>();
                PROFW(33 + ch * 3, 4);
                if (ch == 0) mbar_wait(sb + SM_BARS + B_G1DONE * 8, 0);
                else named_bar(2, 128);
                #pragma unroll
                for (int ii = 0; ii < 16; ii++) {
                    if (ii < 15 || ish == 0)
                        sts128f(rdst + ii * 512, acc[ii >> 2][4 * (ii & 3)], acc[ii >> 2][4 * (ii & 3) + 1], acc[ii >> 2][4 * (ii & 3) + 2], acc[ii >> 2][4 * (ii & 3) + 3]);
                }
                named_bar(2, 128);
                const uint32_t kvaddr = cbase + ((7 - g) & 1) * RB_R1 + (RB_Z + 32 * warp4 + 2 * c) * 16 + ((7 - g) >> 1) * 4;
                uint32_t* ydst = (uint32_t*)(g_yT + (size_t)gch * SEQ + 512 * warp4 + 32 * c + 2 * g);
                #pragma unroll
                for (int ii = 0; ii < 4; ii++) {
                    float4 s = lds128f(rsrc + ii * 512);
                    #pragma unroll
                    for (int ww = 1; ww < 4; ww++) {
                        float4 t = lds128f(rsrc + ww * 8192 + ii * 512);
                        if (ii == 0 && warp4 == 0 && c < ww) t = make_float4(0.f, 0.f, 0.f, 0.f);
                        s.x += t.x; s.y += t.y; s.z += t.z; s.w += t.w;
                    }
                    uint32_t k0 = lds32(kvaddr + ii * 128), k1 = lds32(kvaddr + ii * 128 + 16);
                    k0 = __byte_perm(k0, k0, 0x1032); k1 = __byte_perm(k1, k1, 0x1032);
                    ydst[ii * 64] = badd2(pack_bf(s.z, s.x), bmul2(k0, d2));
                    ydst[ii * 64 + 8] = badd2(pack_bf(s.w, s.y), bmul2(k1, d2));
                }
            }
            PROFW(44, 4);
            asm volatile("fence.proxy.async.global;" ::: "memory");
            __syncwarp();
            if (lane == 0) flag_add(&g_cnt_y[(b >> 5) * 32]);
            PROFW(45, 4);
        }
    } else {
        asm volatile("setmaxnreg.dec.sync.aligned.u32 104;");
        if (warp == 8) {
            if (lane == 0) {
                int st = 0; uint32_t ph = 1;
                #pragma unroll 1
                for (int it = 0; it < 16; it++) {
                    const int pass = it >> 3, sl = it & 7;
                    const int nb = pass ? 3 : 4;
                    const CUtensorMap* tm = pass ? (rank ? &p.tm_uB : &p.tm_gB) : (rank ? &p.tm_uA : &p.tm_gA);
                    mbar_wait(sb + SM_BARS + (B_EMPTY + st) * 8, ph);
                    PROF2(0, it);
                    mbar_expect_tx(sb + SM_BARS + (B_FULL + st) * 8, nb * 8192);
                    tma3d_mc(sb + SM_RING + st * STAGE_BYTES + rank * nb * 4096, tm, 0, ((sl + 2 * cb + 2) & 7) * 64, 7 * j + 4 * pass, sb + SM_BARS + (B_FULL + st) * 8);
                    if (it < 3) {
                        for (int s2 = 2 + 2 * it; s2 < 4 + 2 * it; s2++) {
                            mbar_expect_tx(sb + SM_BARS + (B_XFULL + s2) * 8, 16384);
                            tma2d(sb + SM_X + s2 * 16384, &p.tm_x, 64 * ((s2 + 2 * cb + 2) & 7), 128 * i, sb + SM_BARS + (B_XFULL + s2) * 8);
                        }
                    }
                    if (++st == NSTAGE) { st = 0; ph ^= 1; }
                }
                #pragma unroll 1
                for (int u = 0; u < 14; u++) {
                    mbar_wait(sb + SM_BARS + (B_EMPTY + st) * 8, ph);
                    PROF2(0, 16 + u);
                    mbar_expect_tx(sb + SM_BARS + (B_FULL + st) * 8, 32768);
                    tma3d_mc(sb + SM_RING + st * STAGE_BYTES + rank * 8192, &p.tm_w2, 0, blk_f0(4 * u + rank, j), 2 * cb, sb + SM_BARS + (B_FULL + st) * 8);
                    tma3d_mc(sb + SM_RING + st * STAGE_BYTES + 16384 + rank * 8192, &p.tm_w2, 0, blk_f0(4 * u + 2 + rank, j), 2 * cb, sb + SM_BARS + (B_FULL + st) * 8);
                    if (++st == NSTAGE) { st = 0; ph ^= 1; }
                }
                PROF(48);
                const unsigned ep = lds32(sb + SM_EPOCH);
                mbar_wait(sb + SM_BARS + B_G1DONE * 8, 0);
                flag_wait(&g_cnt_y[cb * 32], ep * 128);
                PROF(49);
                asm volatile("fence.proxy.async.global;" ::: "memory");
                mbar_expect_tx(sb + SM_BARS + B_YT * 8, 16384);
                tma2d(sb + SM_YT, &p.tm_yT, 64 * rbG2, 128 * cb, sb + SM_BARS + B_YT * 8);
            }
        } else {
          unsigned ep = 0;
          if (tid == 352) { ep = g_launch[b] + 1; g_launch[b] = ep; sts32(sb + SM_EPOCH, ep); }
          {
            float csum[8];
            #pragma unroll
            for (int e = 0; e < 8; e++) csum[e] = 0.f;
            const int cgp = (b >> 1) % 28, rh = (b >> 1) / 28;
            if (b < 112) {
                const __nv_bfloat16* wsrc = ((b & 1) ? p.wu : p.wg) + 64 * cgp + 8 * (lane & 7) + (size_t)(256 * rh + 4 * (warp - 9) + (lane >> 3)) * FF;
                uint4 wv[22];
                #pragma unroll
                for (int t = 0; t < 21; t++) wv[t] = ldg_nc128(wsrc + (size_t)(t * 12) * FF);
                wv[21] = (warp == 9) ? ldg_nc128(wsrc + (size_t)(21 * 12) * FF) : make_uint4(0, 0, 0, 0);
                #pragma unroll
                for (int t = 0; t < 22; t++) {
                    csum[0] += bf_lo(wv[t].x); csum[1] += bf_hi(wv[t].x); csum[2] += bf_lo(wv[t].y); csum[3] += bf_hi(wv[t].y);
                    csum[4] += bf_lo(wv[t].z); csum[5] += bf_hi(wv[t].z); csum[6] += bf_lo(wv[t].w); csum[7] += bf_hi(wv[t].w);
                }
            }
            #pragma unroll
            for (int e = 0; e < 8; e++) {
                csum[e] += __shfl_xor_sync(0xffffffffu, csum[e], 8);
                csum[e] += __shfl_xor_sync(0xffffffffu, csum[e], 16);
            }
            if (lane < 8) {
                sts128f(sb + SM_CSTMP + ((warp - 9) * 64 + lane * 8) * 4, csum[0], csum[1], csum[2], csum[3]);
                sts128f(sb + SM_CSTMP + ((warp - 9) * 64 + lane * 8 + 4) * 4, csum[4], csum[5], csum[6], csum[7]);
            }
            named_bar(3, 96);
            if (warp == 11 && b < 112) {
                const float2 t0 = lds64f(sb + SM_CSTMP + lane * 8), t1 = lds64f(sb + SM_CSTMP + 256 + lane * 8), t2 = lds64f(sb + SM_CSTMP + 512 + lane * 8);
                *(float2*)(g_cs + (rh * 2 + (b & 1)) * FF + 64 * cgp + 2 * lane) = make_float2(t0.x + t1.x + t2.x, t0.y + t1.y + t2.y);
            }
            PROFW(55, 11);
          }
          if (warp < 11) {
            #pragma unroll 1
            for (int rnd = 0; rnd < 2; rnd++) {
                const int tt = (tid - 288) + 64 * rnd;
                uint32_t sk[4][2];
                uint4 skw[2];
                skw[0] = ldg_nc128(p.shift_k + 16 * tt); skw[1] = ldg_nc128(p.shift_k + 16 * tt + 8);
                const __nv_bfloat16* kp = p.k + (size_t)(16 * b) * DM + 4 * tt;
                const __nv_bfloat16* vp = p.v + (size_t)(16 * b) * DM + 4 * tt;
                uint2 kr[19];
                uint2 kv[16];
                #pragma unroll
                for (int r = 0; r < 3; r++) kr[r] = (b > 0) ? ldg_nc64(kp + (r - 3) * DM) : make_uint2(0, 0);
                #pragma unroll
                for (int r = 0; r < 16; r++) { kr[3 + r] = ldg_nc64(kp + r * DM); kv[r] = ldg_nc64(vp + r * DM); }
                {
                    const uint4 w0 = skw[0], w1 = skw[1];
                    sk[0][0] = __byte_perm(w0.x, w0.z, 0x5410); sk[1][0] = __byte_perm(w0.x, w0.z, 0x7632);
                    sk[2][0] = __byte_perm(w0.y, w0.w, 0x5410); sk[3][0] = __byte_perm(w0.y, w0.w, 0x7632);
                    sk[0][1] = __byte_perm(w1.x, w1.z, 0x5410); sk[1][1] = __byte_perm(w1.x, w1.z, 0x7632);
                    sk[2][1] = __byte_perm(w1.y, w1.w, 0x5410); sk[3][1] = __byte_perm(w1.y, w1.w, 0x7632);
                }
                #pragma unroll
                for (int s = 0; s < 16; s++) {
                    uint32_t a = bmul2(kr[s].x, sk[3][0]);
                    a = badd2(a, bmul2(kr[s + 1].x, sk[2][0]));
                    a = badd2(a, bmul2(kr[s + 2].x, sk[1][0]));
                    a = badd2(a, bmul2(kr[s + 3].x, sk[0][0]));
                    kv[s].x = bmul2(a, kv[s].x);
                    a = bmul2(kr[s].y, sk[3][1]);
                    a = badd2(a, bmul2(kr[s + 1].y, sk[2][1]));
                    a = badd2(a, bmul2(kr[s + 2].y, sk[1][1]));
                    a = badd2(a, bmul2(kr[s + 3].y, sk[0][1]));
                    kv[s].y = bmul2(a, kv[s].y);
                }
                #pragma unroll
                for (int cc = 0; cc < 4; cc++) {
                    const uint32_t sel = (cc & 1) ? 0x7632 : 0x5410;
                    #define KVW(r) ((cc & 2) ? kv[r].y : kv[r].x)
                    uint8_t* dst = g_rb + (size_t)(4 * tt + cc) * RB_CH + (RB_Z + b) * 16;
                    *(uint4*)dst = make_uint4(__byte_perm(KVW(15), KVW(14), sel), __byte_perm(KVW(11), KVW(10), sel),
                                              __byte_perm(KVW(7), KVW(6), sel), __byte_perm(KVW(3), KVW(2), sel));
                    *(uint4*)(dst + RB_R1) = make_uint4(__byte_perm(KVW(13), KVW(12), sel), __byte_perm(KVW(9), KVW(8), sel),
                                                        __byte_perm(KVW(5), KVW(4), sel), __byte_perm(KVW(1), KVW(0), sel));
                    #undef KVW
                    if (b < RB_Z) {
                        uint8_t* z = g_rb + (size_t)(4 * tt + cc) * RB_CH + b * 16;
                        *(uint4*)z = make_uint4(0, 0, 0, 0);
                        *(uint4*)(z + RB_R1) = make_uint4(0, 0, 0, 0);
                    }
                }
            }
            asm volatile("fence.proxy.async.global;" ::: "memory");
            __syncwarp();
            if (lane == 0) {
                flag_add(&g_cnt_kv[0]);
                PROFW(50, 9);
                const int wgi = warp - 9;
                mbar_wait(sb + SM_BARS + (B_HD + wgi * 2) * 8, 0);
                flag_add(&g_flag_h[((2 * i + wgi) * 2 + 0) * 8]);
                if (wgi == 0) {
                    const unsigned ep = lds32(sb + SM_EPOCH);
                    flag_wait(&g_cnt_kv[0], ep * 256);
                    asm volatile("fence.proxy.async.global;" ::: "memory");
                    PROF(53);
                    mbar_wait(sb + SM_BARS + B_XFREE * 8, 0);
                    PROF(54);
                    for (int ch = 0; ch < 4; ch++) {
                        const uint32_t bar = sb + SM_BARS + (B_CONV + ch) * 8;
                        mbar_expect_tx(bar, CONV_CH);
                        bulk_g2s(sb + SM_CONV + ch * CONV_CH, g_rb + (size_t)(4 * b + ch) * RB_CH, RB_CH, bar);
                        bulk_g2s(sb + SM_CONV + ch * CONV_CH + RB_CH, p.ssm_k + (size_t)(4 * b + ch) * SEQ, 4096, bar);
                    }
                }
                mbar_wait(sb + SM_BARS + (B_HD + wgi * 2 + 1) * 8, 0);
                flag_add(&g_flag_h[((2 * i + wgi) * 2 + 1) * 8]);
            }
        } else {
            __syncwarp();
            if (lane == 0) {
                mbar_wait(sb + SM_BARS + B_PREPD * 8, 0);
                flag_add(&g_cnt_prep[0]);
                flag_wait(&g_cnt_prep[0], ep * 128);
            }
            PROF(51);
            __syncwarp();
            {
                uint4 sv[2], c0[4], c1[4];
                #pragma unroll
                for (int t = 0; t < 2; t++) sv[t] = ldg_cg128((const uint4*)(g_stats + 128 * i) + t * 32 + lane);
                #pragma unroll
                for (int t = 0; t < 4; t++) {
                    const int idx = min(t * 32 + lane, 111);
                    const int m = idx >= 56;
                    const uint4* src = (const uint4*)(g_cs + m * FF + 224 * j) + (idx - 56 * m);
                    c0[t] = ldg_cg128(src); c1[t] = ldg_cg128(src + 2 * FF / 4);
                }
                #pragma unroll
                for (int t = 0; t < 2; t++)
                    asm volatile("st.shared.v4.u32 [%0], {%1,%2,%3,%4};" :: "r"(sb + SM_STATS + (t * 32 + lane) * 16), "r"(sv[t].x), "r"(sv[t].y), "r"(sv[t].z), "r"(sv[t].w) : "memory");
                #pragma unroll
                for (int t = 0; t < 4; t++) {
                    const int idx = min(t * 32 + lane, 111);
                    sts128f(sb + SM_CS + idx * 16, __uint_as_float(c0[t].x) + __uint_as_float(c1[t].x), __uint_as_float(c0[t].y) + __uint_as_float(c1[t].y),
                            __uint_as_float(c0[t].z) + __uint_as_float(c1[t].z), __uint_as_float(c0[t].w) + __uint_as_float(c1[t].w));
                }
            }
            __syncwarp();
            if (lane == 0) {
                mbar_arrive(sb + SM_BARS + B_STATS * 8);
                PROF(52);
                l2_prefetch(p.wd + (size_t)b * (FF * DM / NCTA), FF * DM / NCTA * 2);
                l2_prefetch(p.ssm_k + (size_t)(4 * b) * SEQ, 4 * SEQ * 2);
                tmap_prefetch(rank ? &p.tm_uB : &p.tm_gB);
                tmap_prefetch(&p.tm_w2); tmap_prefetch(&p.tm_yT); tmap_prefetch(&p.tm_out);
                mbar_wait(sb + SM_BARS + (B_HD + 0) * 8, 0);
                flag_wait(&g_flag_h[(rbG2 * 2 + 0) * 8], ep * 8);
                mbar_arrive(sb + SM_BARS + B_HRDY * 8);
                mbar_wait(sb + SM_BARS + B_G1DONE * 8, 0);
                flag_wait(&g_flag_h[(rbG2 * 2 + 1) * 8], ep * 8);
                mbar_arrive(sb + SM_BARS + (B_HRDY + 1) * 8);
            }
          }
        }
    }
}

typedef CUresult (*EncodeFn)(CUtensorMap*, CUtensorMapDataType, cuuint32_t, void*, const cuuint64_t*, const cuuint64_t*,
                             const cuuint32_t*, const cuuint32_t*, CUtensorMapInterleave, CUtensorMapSwizzle,
                             CUtensorMapL2promotion, CUtensorMapFloatOOBfill);

void encode(EncodeFn fn, CUtensorMap* tm, const void* base, int rank, const cuuint64_t* dims, const cuuint64_t* strides,
            const cuuint32_t* box, CUtensorMapSwizzle swz) {
    cuuint32_t es[5] = {1, 1, 1, 1, 1};
    fn(tm, CU_TENSOR_MAP_DATA_TYPE_BFLOAT16, rank, (void*)base, dims, strides, box, es, CU_TENSOR_MAP_INTERLEAVE_NONE, swz,
       CU_TENSOR_MAP_L2_PROMOTION_L2_128B, CU_TENSOR_MAP_FLOAT_OOB_FILL_NONE);
}

}

extern "C" void kernel_launch(void* const* d_in, const int* in_sizes, int n_in, void* d_out, int out_size) {
    (void)in_sizes; (void)n_in; (void)out_size;
    static EncodeFn enc = nullptr;
    static void* yT_ptr = nullptr;
    if (!enc) {
        void* fn = nullptr; cudaDriverEntryPointQueryResult qr;
        cudaGetDriverEntryPoint("cuTensorMapEncodeTiled", &fn, cudaEnableDefault, &qr);
        enc = (EncodeFn)fn;
        cudaGetSymbolAddress(&yT_ptr, g_yT);
        cudaFuncSetAttribute(fused_kernel, cudaFuncAttributeMaxDynamicSharedMemorySize, SM_TOTAL);
    }
    Params p;
    p.q = (const __nv_bfloat16*)d_in[0]; p.k = (const __nv_bfloat16*)d_in[1]; p.v = (const __nv_bfloat16*)d_in[2];
    p.shift_k = (const __nv_bfloat16*)d_in[3]; p.ssm_k = (const __nv_bfloat16*)d_in[4]; p.ssm_D = (const __nv_bfloat16*)d_in[5];
    p.wg = (const __nv_bfloat16*)d_in[7]; p.wu = (const __nv_bfloat16*)d_in[8]; p.wd = (const __nv_bfloat16*)d_in[9];
    {
        cuuint64_t dims[2] = {DM, SEQ}; cuuint64_t str[1] = {DM * 2};
        cuuint32_t box[2] = {64, 128};
        encode(enc, &p.tm_x, p.q, 2, dims, str, box, CU_TENSOR_MAP_SWIZZLE_128B);
        cuuint32_t box2[2] = {64, 64};
        encode(enc, &p.tm_out, d_out, 2, dims, str, box2, CU_TENSOR_MAP_SWIZZLE_128B);
    }
    {
        cuuint64_t dims[3] = {32, DM, FF / 32}; cuuint64_t str[2] = {FF * 2, 64};
        cuuint32_t boxA[3] = {32, 64, 4}, boxB[3] = {32, 64, 3};
        encode(enc, &p.tm_gA, p.wg, 3, dims, str, boxA, CU_TENSOR_MAP_SWIZZLE_64B);
        encode(enc, &p.tm_gB, p.wg, 3, dims, str, boxB, CU_TENSOR_MAP_SWIZZLE_64B);
        encode(enc, &p.tm_uA, p.wu, 3, dims, str, boxA, CU_TENSOR_MAP_SWIZZLE_64B);
        encode(enc, &p.tm_uB, p.wu, 3, dims, str, boxB, CU_TENSOR_MAP_SWIZZLE_64B);
    }
    {
        cuuint64_t dims[3] = {64, FF, DM / 64}; cuuint64_t str[2] = {DM * 2, 128};
        cuuint32_t box[3] = {64, 32, 2};
        encode(enc, &p.tm_w2, p.wd, 3, dims, str, box, CU_TENSOR_MAP_SWIZZLE_128B);
    }
    {
        cuuint64_t dims[2] = {SEQ, DM}; cuuint64_t str[1] = {SEQ * 2};
        cuuint32_t box[2] = {64, 128};
        encode(enc, &p.tm_yT, yT_ptr, 2, dims, str, box, CU_TENSOR_MAP_SWIZZLE_128B);
    }
    fused_kernel<<<NCTA, NTHREADS, SM_TOTAL>>>(p);
}
```

```cpp
#include <cuda_runtime.h>
#include <cuda_bf16.h>
#include <cuda.h>
#include <stdint.h>

namespace {

constexpr int SEQ = 2048, DM = 512, FF = 1792;
constexpr int NCTA = 128;
constexpr int NTHREADS = 384;
constexpr int STAGE_BYTES = 32768;

constexpr uint32_t SM_X = 0;
constexpr uint32_t SM_RING = 131072;
constexpr uint32_t SM_MISC = SM_RING + 3 * STAGE_BYTES;
constexpr uint32_t SM_BARS = SM_MISC;
constexpr uint32_t SM_EPOCH = SM_MISC + 248;
constexpr uint32_t SM_STATS = SM_MISC + 256;
constexpr uint32_t SM_TOTAL = SM_STATS + 512;
static_assert(SM_TOTAL <= 232448, "smem");
__host__ __device__ constexpr uint32_t stage_off(int s) { return s < 3 ? SM_RING + s * STAGE_BYTES : (uint32_t)(s - 2) * STAGE_BYTES; }
constexpr uint32_t SM_CVX = 0;
constexpr uint32_t SM_CVH = 16384;
constexpr uint32_t SM_YT = 0;
constexpr uint32_t SM_XE = 6 * 16384;

constexpr int B_FULL = 0, B_EMPTY = 5, B_XFULL = 10, B_CONV = 11, B_YT = 15, B_XR = 16, B_G1DONE = 17, B_HD = 18, B_HRDY = 22,
              B_XFREE = 24, B_CVDONE = 25, B_COUNT = 26;
static_assert(B_COUNT * 8 <= 248, "barrier space");

__device__ uint4 g_hfrag[32 * 112 * 4 * 32];
__device__ __align__(128) __nv_bfloat16 g_kvT[DM * SEQ];
__device__ __align__(128) __nv_bfloat16 g_yT[DM * SEQ];
__device__ unsigned g_launch[NCTA];
__device__ unsigned g_cnt_kv[32];
__device__ unsigned g_cnt_y[4 * 32];
__device__ unsigned g_flag_h[32 * 2 * 8];

#define PROF(idx)
#define PROF2(a, idx)
#define PROFW(idx, w)

struct Params {
    CUtensorMap tm_x, tm_gA, tm_gB, tm_uA, tm_uB, tm_w2, tm_yT, tm_out, tm_xe;
    const __nv_bfloat16 *q, *k, *v, *shift_k, *ssm_k, *ssm_D, *wg, *wu, *wd;
};

__device__ __forceinline__ void wgmma_rs_n32(float (&d)[16], uint32_t a0, uint32_t a1, uint32_t a2, uint32_t a3, uint64_t db, int sc) {
  asm volatile("{\n.reg .pred p;\nsetp.ne.b32 p, %21, 0;\n"
    "wgmma.mma_async.sync.aligned.m64n32k16.f32.bf16.bf16 {%0,%1,%2,%3,%4,%5,%6,%7,%8,%9,%10,%11,%12,%13,%14,%15}, {%16,%17,%18,%19}, %20, p, 1, 1, 0;\n}\n"
    : "+f"(d[0]),"+f"(d[1]),"+f"(d[2]),"+f"(d[3]),"+f"(d[4]),"+f"(d[5]),"+f"(d[6]),"+f"(d[7]),"+f"(d[8]),"+f"(d[9]),"+f"(d[10]),"+f"(d[11]),"+f"(d[12]),"+f"(d[13]),"+f"(d[14]),"+f"(d[15])
    : "r"(a0),"r"(a1),"r"(a2),"r"(a3),"l"(db),"r"(sc));
}
__device__ __forceinline__ void wgmma_rs_n128_tb(float (&d)[64], uint32_t a0, uint32_t a1, uint32_t a2, uint32_t a3, uint64_t db, int sc) {
  asm volatile("{\n.reg .pred p;\nsetp.ne.b32 p, %69, 0;\n"
    "wgmma.mma_async.sync.aligned.m64n128k16.f32.bf16.bf16 {%0,%1,%2,%3,%4,%5,%6,%7,%8,%9,%10,%11,%12,%13,%14,%15,%16,%17,%18,%19,%20,%21,%22,%23,%24,%25,%26,%27,%28,%29,%30,%31,%32,%33,%34,%35,%36,%37,%38,%39,%40,%41,%42,%43,%44,%45,%46,%47,%48,%49,%50,%51,%52,%53,%54,%55,%56,%57,%58,%59,%60,%61,%62,%63}, {%64,%65,%66,%67}, %68, p, 1, 1, 1;\n}\n"
    : "+f"(d[0]),"+f"(d[1]),"+f"(d[2]),"+f"(d[3]),"+f"(d[4]),"+f"(d[5]),"+f"(d[6]),"+f"(d[7]),"+f"(d[8]),"+f"(d[9]),"+f"(d[10]),"+f"(d[11]),"+f"(d[12]),"+f"(d[13]),"+f"(d[14]),"+f"(d[15]),"+f"(d[16]),"+f"(d[17]),"+f"(d[18]),"+f"(d[19]),"+f"(d[20]),"+f"(d[21]),"+f"(d[22]),"+f"(d[23]),"+f"(d[24]),"+f"(d[25]),"+f"(d[26]),"+f"(d[27]),"+f"(d[28]),"+f"(d[29]),"+f"(d[30]),"+f"(d[31]),"+f"(d[32]),"+f"(d[33]),"+f"(d[34]),"+f"(d[35]),"+f"(d[36]),"+f"(d[37]),"+f"(d[38]),"+f"(d[39]),"+f"(d[40]),"+f"(d[41]),"+f"(d[42]),"+f"(d[43]),"+f"(d[44]),"+f"(d[45]),"+f"(d[46]),"+f"(d[47]),"+f"(d[48]),"+f"(d[49]),"+f"(d[50]),"+f"(d[51]),"+f"(d[52]),"+f"(d[53]),"+f"(d[54]),"+f"(d[55]),"+f"(d[56]),"+f"(d[57]),"+f"(d[58]),"+f"(d[59]),"+f"(d[60]),"+f"(d[61]),"+f"(d[62]),"+f"(d[63])
    : "r"(a0),"r"(a1),"r"(a2),"r"(a3),"l"(db),"r"(sc));
}
__device__ __forceinline__ void wgmma_ss_n256_tb(float (&d)[128], uint64_t da, uint64_t db, int sc) {
  asm volatile("{\n.reg .pred p;\nsetp.ne.b32 p, %130, 0;\n"
    "wgmma.mma_async.sync.aligned.m64n256k16.f32.bf16.bf16 {%0,%1,%2,%3,%4,%5,%6,%7,%8,%9,%10,%11,%12,%13,%14,%15,%16,%17,%18,%19,%20,%21,%22,%23,%24,%25,%26,%27,%28,%29,%30,%31,%32,%33,%34,%35,%36,%37,%38,%39,%40,%41,%42,%43,%44,%45,%46,%47,%48,%49,%50,%51,%52,%53,%54,%55,%56,%57,%58,%59,%60,%61,%62,%63,%64,%65,%66,%67,%68,%69,%70,%71,%72,%73,%74,%75,%76,%77,%78,%79,%80,%81,%82,%83,%84,%85,%86,%87,%88,%89,%90,%91,%92,%93,%94,%95,%96,%97,%98,%99,%100,%101,%102,%103,%104,%105,%106,%107,%108,%109,%110,%111,%112,%113,%114,%115,%116,%117,%118,%119,%120,%121,%122,%123,%124,%125,%126,%127}, %128, %129, p, 1, 1, 0, 1;\n}\n"
    : "+f"(d[0]),"+f"(d[1]),"+f"(d[2]),"+f"(d[3]),"+f"(d[4]),"+f"(d[5]),"+f"(d[6]),"+f"(d[7]),"+f"(d[8]),"+f"(d[9]),"+f"(d[10]),"+f"(d[11]),"+f"(d[12]),"+f"(d[13]),"+f"(d[14]),"+f"(d[15]),"+f"(d[16]),"+f"(d[17]),"+f"(d[18]),"+f"(d[19]),"+f"(d[20]),"+f"(d[21]),"+f"(d[22]),"+f"(d[23]),"+f"(d[24]),"+f"(d[25]),"+f"(d[26]),"+f"(d[27]),"+f"(d[28]),"+f"(d[29]),"+f"(d[30]),"+f"(d[31]),"+f"(d[32]),"+f"(d[33]),"+f"(d[34]),"+f"(d[35]),"+f"(d[36]),"+f"(d[37]),"+f"(d[38]),"+f"(d[39]),"+f"(d[40]),"+f"(d[41]),"+f"(d[42]),"+f"(d[43]),"+f"(d[44]),"+f"(d[45]),"+f"(d[46]),"+f"(d[47]),"+f"(d[48]),"+f"(d[49]),"+f"(d[50]),"+f"(d[51]),"+f"(d[52]),"+f"(d[53]),"+f"(d[54]),"+f"(d[55]),"+f"(d[56]),"+f"(d[57]),"+f"(d[58]),"+f"(d[59]),"+f"(d[60]),"+f"(d[61]),"+f"(d[62]),"+f"(d[63]),"+f"(d[64]),"+f"(d[65]),"+f"(d[66]),"+f"(d[67]),"+f"(d[68]),"+f"(d[69]),"+f"(d[70]),"+f"(d[71]),"+f"(d[72]),"+f"(d[73]),"+f"(d[74]),"+f"(d[75]),"+f"(d[76]),"+f"(d[77]),"+f"(d[78]),"+f"(d[79]),"+f"(d[80]),"+f"(d[81]),"+f"(d[82]),"+f"(d[83]),"+f"(d[84]),"+f"(d[85]),"+f"(d[86]),"+f"(d[87]),"+f"(d[88]),"+f"(d[89]),"+f"(d[90]),"+f"(d[91]),"+f"(d[92]),"+f"(d[93]),"+f"(d[94]),"+f"(d[95]),"+f"(d[96]),"+f"(d[97]),"+f"(d[98]),"+f"(d[99]),"+f"(d[100]),"+f"(d[101]),"+f"(d[102]),"+f"(d[103]),"+f"(d[104]),"+f"(d[105]),"+f"(d[106]),"+f"(d[107]),"+f"(d[108]),"+f"(d[109]),"+f"(d[110]),"+f"(d[111]),"+f"(d[112]),"+f"(d[113]),"+f"(d[114]),"+f"(d[115]),"+f"(d[116]),"+f"(d[117]),"+f"(d[118]),"+f"(d[119]),"+f"(d[120]),"+f"(d[121]),"+f"(d[122]),"+f"(d[123]),"+f"(d[124]),"+f"(d[125]),"+f"(d[126]),"+f"(d[127])
    : "l"(da),"l"(db),"r"(sc));
}
__device__ __forceinline__ void wgmma_ss_n192_tb(float (&d)[96], uint64_t da, uint64_t db, int sc) {
  asm volatile("{\n.reg .pred p;\nsetp.ne.b32 p, %98, 0;\n"
    "wgmma.mma_async.sync.aligned.m64n192k16.f32.bf16.bf16 {%0,%1,%2,%3,%4,%5,%6,%7,%8,%9,%10,%11,%12,%13,%14,%15,%16,%17,%18,%19,%20,%21,%22,%23,%24,%25,%26,%27,%28,%29,%30,%31,%32,%33,%34,%35,%36,%37,%38,%39,%40,%41,%42,%43,%44,%45,%46,%47,%48,%49,%50,%51,%52,%53,%54,%55,%56,%57,%58,%59,%60,%61,%62,%63,%64,%65,%66,%67,%68,%69,%70,%71,%72,%73,%74,%75,%76,%77,%78,%79,%80,%81,%82,%83,%84,%85,%86,%87,%88,%89,%90,%91,%92,%93,%94,%95}, %96, %97, p, 1, 1, 0, 1;\n}\n"
    : "+f"(d[0]),"+f"(d[1]),"+f"(d[2]),"+f"(d[3]),"+f"(d[4]),"+f"(d[5]),"+f"(d[6]),"+f"(d[7]),"+f"(d[8]),"+f"(d[9]),"+f"(d[10]),"+f"(d[11]),"+f"(d[12]),"+f"(d[13]),"+f"(d[14]),"+f"(d[15]),"+f"(d[16]),"+f"(d[17]),"+f"(d[18]),"+f"(d[19]),"+f"(d[20]),"+f"(d[21]),"+f"(d[22]),"+f"(d[23]),"+f"(d[24]),"+f"(d[25]),"+f"(d[26]),"+f"(d[27]),"+f"(d[28]),"+f"(d[29]),"+f"(d[30]),"+f"(d[31]),"+f"(d[32]),"+f"(d[33]),"+f"(d[34]),"+f"(d[35]),"+f"(d[36]),"+f"(d[37]),"+f"(d[38]),"+f"(d[39]),"+f"(d[40]),"+f"(d[41]),"+f"(d[42]),"+f"(d[43]),"+f"(d[44]),"+f"(d[45]),"+f"(d[46]),"+f"(d[47]),"+f"(d[48]),"+f"(d[49]),"+f"(d[50]),"+f"(d[51]),"+f"(d[52]),"+f"(d[53]),"+f"(d[54]),"+f"(d[55]),"+f"(d[56]),"+f"(d[57]),"+f"(d[58]),"+f"(d[59]),"+f"(d[60]),"+f"(d[61]),"+f"(d[62]),"+f"(d[63]),"+f"(d[64]),"+f"(d[65]),"+f"(d[66]),"+f"(d[67]),"+f"(d[68]),"+f"(d[69]),"+f"(d[70]),"+f"(d[71]),"+f"(d[72]),"+f"(d[73]),"+f"(d[74]),"+f"(d[75]),"+f"(d[76]),"+f"(d[77]),"+f"(d[78]),"+f"(d[79]),"+f"(d[80]),"+f"(d[81]),"+f"(d[82]),"+f"(d[83]),"+f"(d[84]),"+f"(d[85]),"+f"(d[86]),"+f"(d[87]),"+f"(d[88]),"+f"(d[89]),"+f"(d[90]),"+f"(d[91]),"+f"(d[92]),"+f"(d[93]),"+f"(d[94]),"+f"(d[95])
    : "l"(da),"l"(db),"r"(sc));
}

__device__ __forceinline__ uint32_t smem_u32(const void* p) { return (uint32_t)__cvta_generic_to_shared(p); }
__device__ __forceinline__ void mbar_init(uint32_t bar, uint32_t cnt) { asm volatile("mbarrier.init.shared::cta.b64 [%0], %1;" :: "r"(bar), "r"(cnt)); }
__device__ __forceinline__ void mbar_expect_tx(uint32_t bar, uint32_t bytes) { asm volatile("mbarrier.arrive.expect_tx.shared::cta.b64 _, [%0], %1;" :: "r"(bar), "r"(bytes) : "memory"); }
__device__ __forceinline__ void mbar_arrive(uint32_t bar) { asm volatile("mbarrier.arrive.shared::cta.b64 _, [%0];" :: "r"(bar) : "memory"); }
__device__ __forceinline__ void mbar_arrive_cluster(uint32_t cbar, uint32_t cnt) { asm volatile("mbarrier.arrive.shared::cluster.b64 _, [%0], %1;" :: "r"(cbar), "r"(cnt) : "memory"); }
__device__ __forceinline__ uint32_t mapa(uint32_t a, uint32_t rank) { uint32_t r; asm volatile("mapa.shared::cluster.u32 %0, %1, %2;" : "=r"(r) : "r"(a), "r"(rank)); return r; }
__device__ __forceinline__ void mbar_wait(uint32_t bar, uint32_t parity) {
    uint32_t ok; uint32_t n = 0;
    do {
        asm volatile("{\n.reg .pred p;\nmbarrier.try_wait.parity.shared::cta.b64 p, [%1], %2;\nselp.u32 %0, 1, 0, p;\n}" : "=r"(ok) : "r"(bar), "r"(parity) : "memory");
    } while (!ok && ++n < (1u << 17));
}
__device__ __forceinline__ void flag_wait(const unsigned* p, unsigned target) {
    unsigned v; uint32_t n = 0;
    while (true) {
        asm volatile("ld.acquire.gpu.global.u32 %0, [%1];" : "=r"(v) : "l"(p) : "memory");
        if ((int)(v - target) >= 0 || ++n >= (1u << 17)) break;
        __nanosleep(100);
    }
}
__device__ __forceinline__ void flag_add(unsigned* p) {
    asm volatile("fence.acq_rel.gpu;\nred.relaxed.gpu.global.add.u32 [%0], 1;" :: "l"(p) : "memory");
}
__device__ __forceinline__ uint64_t make_desc(uint32_t addr, uint32_t lbo, uint32_t sbo, uint32_t swz) {
    return (uint64_t)((addr & 0x3FFFF) >> 4) | ((uint64_t)((lbo & 0x3FFFF) >> 4) << 16) | ((uint64_t)((sbo & 0x3FFFF) >> 4) << 32) | ((uint64_t)swz << 62);
}
__device__ __forceinline__ uint64_t desc_add(uint64_t d, uint32_t off16) {
    return (d & 0xFFFFFFFF00000000ull) | (uint64_t)((uint32_t)d + off16);
}
__device__ __forceinline__ void tma2d(uint32_t dst, const CUtensorMap* tm, int c0, int c1, uint32_t bar) {
    asm volatile("cp.async.bulk.tensor.2d.shared::cluster.global.mbarrier::complete_tx::bytes [%0], [%1, {%3, %4}], [%2];"
        :: "r"(dst), "l"((uint64_t)tm), "r"(bar), "r"(c0), "r"(c1) : "memory");
}
__device__ __forceinline__ void tma3d_mc(uint32_t dst, const CUtensorMap* tm, int c0, int c1, int c2, uint32_t bar) {
    asm volatile("cp.async.bulk.tensor.3d.shared::cluster.global.mbarrier::complete_tx::bytes.multicast::cluster [%0], [%1, {%3, %4, %5}], [%2], %6;"
        :: "r"(dst), "l"((uint64_t)tm), "r"(bar), "r"(c0), "r"(c1), "r"(c2), "h"((uint16_t)3) : "memory");
}
__device__ __forceinline__ void bulk_g2s(uint32_t dst, const void* src, uint32_t bytes, uint32_t bar) {
    asm volatile("cp.async.bulk.shared::cluster.global.mbarrier::complete_tx::bytes [%0], [%1], %2, [%3];"
        :: "r"(dst), "l"(src), "r"(bytes), "r"(bar) : "memory");
}
__device__ __forceinline__ void bulk_s2g(void* dst, uint32_t src, uint32_t bytes) {
    asm volatile("cp.async.bulk.global.shared::cta.bulk_group [%0], [%1], %2;" :: "l"(dst), "r"(src), "r"(bytes) : "memory");
}
__device__ __forceinline__ void tma2d_store(const CUtensorMap* tm, int c0, int c1, uint32_t src) {
    asm volatile("cp.async.bulk.tensor.2d.global.shared::cta.bulk_group [%0, {%2, %3}], [%1];"
        :: "l"((uint64_t)tm), "r"(src), "r"(c0), "r"(c1) : "memory");
}
__device__ __forceinline__ void l2_prefetch(const void* p, uint32_t bytes) {
    asm volatile("cp.async.bulk.prefetch.L2.global [%0], %1;" :: "l"(p), "r"(bytes) : "memory");
}
__device__ __forceinline__ void tmap_prefetch(const CUtensorMap* tm) { asm volatile("prefetch.tensormap [%0];" :: "l"((uint64_t)tm) : "memory"); }
__device__ __forceinline__ uint32_t lds32(uint32_t a) { uint32_t v; asm volatile("ld.shared.u32 %0, [%1];" : "=r"(v) : "r"(a)); return v; }
__device__ __forceinline__ uint2 lds64(uint32_t a) { uint2 v; asm volatile("ld.shared.v2.u32 {%0,%1}, [%2];" : "=r"(v.x), "=r"(v.y) : "r"(a)); return v; }
__device__ __forceinline__ uint4 lds128(uint32_t a) { uint4 v; asm volatile("ld.shared.v4.u32 {%0,%1,%2,%3}, [%4];" : "=r"(v.x), "=r"(v.y), "=r"(v.z), "=r"(v.w) : "r"(a)); return v; }
__device__ __forceinline__ void sts32(uint32_t a, uint32_t v) { asm volatile("st.shared.u32 [%0], %1;" :: "r"(a), "r"(v) : "memory"); }
__device__ __forceinline__ void sts128(uint32_t a, uint4 v) { asm volatile("st.shared.v4.u32 [%0], {%1,%2,%3,%4};" :: "r"(a), "r"(v.x), "r"(v.y), "r"(v.z), "r"(v.w) : "memory"); }
__device__ __forceinline__ uint4 ldg_cg128(const void* p) { uint4 v; asm volatile("ld.global.cg.v4.u32 {%0,%1,%2,%3}, [%4];" : "=r"(v.x), "=r"(v.y), "=r"(v.z), "=r"(v.w) : "l"(p)); return v; }
__device__ __forceinline__ uint4 ldg_nc128(const void* p) { uint4 v; asm volatile("ld.global.nc.L1::no_allocate.v4.u32 {%0,%1,%2,%3}, [%4];" : "=r"(v.x), "=r"(v.y), "=r"(v.z), "=r"(v.w) : "l"(p)); return v; }
__device__ __forceinline__ uint2 ldg_nc64(const void* p) { uint2 v; asm volatile("ld.global.nc.L1::no_allocate.v2.u32 {%0,%1}, [%2];" : "=r"(v.x), "=r"(v.y) : "l"(p)); return v; }
#define WG_FENCE() asm volatile("wgmma.fence.sync.aligned;\n" ::: "memory")
#define WG_COMMIT() asm volatile("wgmma.commit_group.sync.aligned;\n" ::: "memory")
template<int N> __device__ __forceinline__ void wg_wait() { asm volatile("wgmma.wait_group.sync.aligned %0;\n" :: "n"(N) : "memory"); }
__device__ __forceinline__ void named_bar(int id, int n) { asm volatile("bar.sync %0, %1;" :: "r"(id), "r"(n) : "memory"); }

__device__ __forceinline__ float bf_lo(uint32_t u) { return __uint_as_float(u << 16); }
__device__ __forceinline__ float bf_hi(uint32_t u) { return __uint_as_float(u & 0xFFFF0000u); }
__device__ __forceinline__ uint32_t pack_bf(float lo, float hi) { uint32_t r; asm("cvt.rn.bf16x2.f32 %0, %1, %2;" : "=r"(r) : "f"(hi), "f"(lo)); return r; }
__device__ __forceinline__ float bf_round(float x) { return __bfloat162float(__float2bfloat16_rn(x)); }
__device__ __forceinline__ uint32_t bmul2(uint32_t a, uint32_t b) { uint32_t r; asm("mul.rn.bf16x2 %0, %1, %2;" : "=r"(r) : "r"(a), "r"(b)); return r; }
__device__ __forceinline__ uint32_t badd2(uint32_t a, uint32_t b) { uint32_t r; asm("add.rn.bf16x2 %0, %1, %2;" : "=r"(r) : "r"(a), "r"(b)); return r; }
__device__ __forceinline__ uint32_t bsub2(uint32_t a, uint32_t b) { uint32_t r; asm("sub.rn.bf16x2 %0, %1, %2;" : "=r"(r) : "r"(a), "r"(b)); return r; }
__device__ __forceinline__ void mma16816(float (&d)[4], uint32_t a0, uint32_t a1, uint32_t a2, uint32_t a3, uint2 b) {
    asm volatile("mma.sync.aligned.m16n8k16.row.col.f32.bf16.bf16.f32 {%0,%1,%2,%3}, {%4,%5,%6,%7}, {%8,%9}, {%0,%1,%2,%3};\n"
        : "+f"(d[0]), "+f"(d[1]), "+f"(d[2]), "+f"(d[3]) : "r"(a0), "r"(a1), "r"(a2), "r"(a3), "r"(b.x), "r"(b.y));
}

__device__ __forceinline__ int blk_f0(int bi, int j) {
    if (bi < 32) return 224 * ((j + (bi >> 2)) & 7) + 32 * (bi & 3);
    int b2 = bi - 32; int q3 = (b2 * 11) >> 5;
    return 224 * ((j + q3) & 7) + 128 + 32 * (b2 - 3 * q3);
}
__device__ __forceinline__ int next_st2(int s) { return (0x14023 >> (4 * s)) & 7; }
__device__ __forceinline__ uint32_t stage_off_rt(int s) { return s < 3 ? SM_RING + s * STAGE_BYTES : (uint32_t)(s - 2) * STAGE_BYTES; }

template<int NB>
__device__ __forceinline__ void gemm1_pass(uint32_t sb, int wgi, int warp4, int lane, int& st, uint32_t& fph, uint32_t e_cl,
                                           int rb64, int ks0) {
    constexpr bool passA = (NB == 4);
    float acc[NB * 32];
    const uint64_t descA0 = make_desc(sb + SM_X + wgi * 8192, 16, 1024, 1);
    const uint64_t descB0 = make_desc(sb + SM_RING, 4096, 512, 2);
    int prev = 0;
    #pragma unroll 1
    for (int sl = 0; sl < 8; sl++) {
        if (warp4 == 0 && wgi == 0) PROF2(2, sl + (passA ? 0 : 8));
        mbar_wait(sb + SM_BARS + (B_FULL + st) * 8, (fph >> st) & 1);
        fph ^= 1u << st;
        if (sl == 0 && warp4 == 0) PROF(2 + wgi * 8 + (passA ? 0 : 3));
        if (warp4 == 0 && wgi == 0) PROF2(1, sl + (passA ? 0 : 8));
        const uint64_t da = desc_add(descA0, sl * 1024), db = desc_add(descB0, st * 2048);
        WG_FENCE();
        #pragma unroll
        for (int kk = 0; kk < 4; kk++) {
            int sc = (sl | kk) ? 1 : 0;
            if constexpr (NB == 4) wgmma_ss_n256_tb(acc, da + kk * 2, db + kk * 64, sc); else wgmma_ss_n192_tb(acc, da + kk * 2, db + kk * 64, sc);
        }
        WG_COMMIT();
        wg_wait<1>();
        if (warp4 == 0 && wgi == 0) PROF2(3, sl + (passA ? 0 : 8));
        if (lane < 2 && sl) mbar_arrive_cluster(e_cl + prev * 8, 1);
        if (!passA) {
            if (sl == 2 && lane == 0) mbar_arrive(sb + SM_BARS + B_XFREE * 8);
            if ((sl == 4 || sl == 6) && lane < 2) mbar_arrive_cluster(e_cl + (1 + (sl >> 1)) * 8, 1);
        }
        prev = st;
        st = (st == 2) ? 0 : st + 1;
    }
    wg_wait<0>();
    if (lane < 2) mbar_arrive_cluster(e_cl + prev * 8, 1);
    if (!passA && lane == 0) mbar_arrive(sb + SM_BARS + B_G1DONE * 8);
    if (warp4 == 0) PROF(3 + wgi * 8 + (passA ? 0 : 3));
    const int g = lane >> 2;
    const int r0 = wgi * 64 + warp4 * 16 + g;
    const float s0 = __uint_as_float(lds32(sb + SM_STATS + r0 * 4)), s1 = __uint_as_float(lds32(sb + SM_STATS + (r0 + 8) * 4));
    uint4* dst = g_hfrag + ((size_t)(rb64 * 112 + ks0) * 4 + warp4) * 32 + lane;
    #pragma unroll
    for (int kk = 0; kk < NB * 2; kk++) {
        uint32_t h[4];
        #pragma unroll
        for (int tt = 0; tt < 2; tt++) {
            const int t = 2 * kk + tt;
            const float* ag = &acc[4 * t];
            const float* au = &acc[NB * 16 + 4 * t];
            h[2 * tt] = bmul2(pack_bf(ag[0] * s0, ag[1] * s0), pack_bf(au[0] * s0, au[1] * s0));
            h[2 * tt + 1] = bmul2(pack_bf(ag[2] * s1, ag[3] * s1), pack_bf(au[2] * s1, au[3] * s1));
        }
        dst[kk * 128] = make_uint4(h[0], h[1], h[2], h[3]);
    }
    __syncwarp();
    if (lane == 0) mbar_arrive(sb + SM_BARS + (B_HD + wgi * 2 + (passA ? 0 : 1)) * 8);
    if (warp4 == 0) PROF(4 + wgi * 8 + (passA ? 0 : 3));
}

__global__ void __cluster_dims__(2, 1, 1) __launch_bounds__(NTHREADS, 1)
fused_kernel(const __grid_constant__ Params p) {
    extern __shared__ __align__(1024) uint8_t smem_raw[];
    const uint32_t sb = smem_u32(smem_raw);
    const int tid = threadIdx.x, warp = tid >> 5, lane = tid & 31;
    const int b = blockIdx.x;
    const int rank = b & 1;
    const int j = (b >> 1) & 7;
    const int i = ((b >> 4) << 1) | rank;
    const int cb = j >> 1;
    const int rbG2 = 2 * i + (j & 1);

    if (tid == 256) {
        mbar_init(sb + SM_BARS + B_XFULL * 8, 1);
        asm volatile("fence.proxy.async.shared::cta;" ::: "memory");
        mbar_expect_tx(sb + SM_BARS + B_XFULL * 8, 131072);
        for (int sl = 0; sl < 8; sl++)
            tma2d(sb + SM_X + sl * 16384, &p.tm_x, 64 * ((sl + 2 * cb + 2) & 7), 128 * i, sb + SM_BARS + B_XFULL * 8);
    }
    if (tid == 288) {
        tmap_prefetch(rank ? &p.tm_uA : &p.tm_gA);
        for (int s = 0; s < 5; s++) { mbar_init(sb + SM_BARS + (B_FULL + s) * 8, 1); mbar_init(sb + SM_BARS + (B_EMPTY + s) * 8, 16); }
        for (int s = 0; s < 4; s++) mbar_init(sb + SM_BARS + (B_CONV + s) * 8, 1);
        mbar_init(sb + SM_BARS + B_YT * 8, 1);
        mbar_init(sb + SM_BARS + B_XR * 8, 1);
        mbar_init(sb + SM_BARS + B_G1DONE * 8, 8);
        mbar_init(sb + SM_BARS + B_XFREE * 8, 8);
        mbar_init(sb + SM_BARS + B_CVDONE * 8, 4);
        for (int s = 0; s < 4; s++) mbar_init(sb + SM_BARS + (B_HD + s) * 8, 4);
        for (int s = 0; s < 2; s++) mbar_init(sb + SM_BARS + (B_HRDY + s) * 8, 1);
        asm volatile("fence.mbarrier_init.release.cluster;" ::: "memory");
        asm volatile("fence.proxy.async.shared::cta;" ::: "memory");
    }
    __syncwarp();
    asm volatile("barrier.cluster.arrive.relaxed.aligned;\nbarrier.cluster.wait.aligned;\n" ::: "memory");
    PROFW(1, 0);

    if (warp < 8) {
        asm volatile("setmaxnreg.inc.sync.aligned.u32 200;");
        const int wgi = warp >> 2, warp4 = warp & 3;
        const int g = lane >> 2, c = lane & 3;
        const uint32_t e_cl = mapa(sb + SM_BARS + B_EMPTY * 8, lane & 1);
        {
            const uint32_t xa = sb + SM_X + (lane >> 3) * 16384 + warp * 16 * 128;
            uint4 xr[16][2];
            float v[32];
            mbar_wait(sb + SM_BARS + B_XFULL * 8, 0);
            PROFW(16, 0);
            #pragma unroll
            for (int r = 0; r < 16; r++) {
                const uint32_t a = xa + r * 128 + (((lane & 7) ^ (r & 7)) << 4);
                xr[r][0] = lds128(a); xr[r][1] = lds128(a + 65536);
            }
            #pragma unroll
            for (int r = 0; r < 16; r++) {
                const uint32_t* u = (const uint32_t*)&xr[r][0];
                float s = 0.f, q = 0.f;
                #pragma unroll
                for (int e = 0; e < 8; e++) { const float lo = bf_lo(u[e]), hi = bf_hi(u[e]); s += lo; q = fmaf(lo, lo, q); s += hi; q = fmaf(hi, hi, q); }
                v[r] = s; v[16 + r] = q;
            }
            #pragma unroll
            for (int hs = 16; hs >= 1; hs >>= 1) {
                const bool up = lane & hs;
                #pragma unroll
                for (int e = 0; e < hs; e++) {
                    const float keep = up ? v[e + hs] : v[e];
                    const float send = up ? v[e] : v[e + hs];
                    v[e] = keep + __shfl_xor_sync(0xffffffffu, send, hs);
                }
            }
            const float other = __shfl_xor_sync(0xffffffffu, v[0], 16);
            const float mean = (lane < 16 ? v[0] : other) * (1.0f / DM);
            const float msq = (lane < 16 ? other : v[0]) * (1.0f / DM);
            const float var_b = bf_round(fmaxf(msq - mean * mean, 0.f));
            const float sd = bf_round(sqrtf(bf_round(var_b + 1e-5f)));
            if (lane < 16) sts32(sb + SM_STATS + (warp * 16 + lane) * 4, __float_as_uint(1.0f / sd));
            const uint32_t mb = pack_bf(mean, mean);
            #pragma unroll
            for (int r = 0; r < 16; r++) {
                const uint32_t m = __shfl_sync(0xffffffffu, mb, r);
                const uint32_t a = xa + r * 128 + (((lane & 7) ^ (r & 7)) << 4);
                #pragma unroll
                for (int hh = 0; hh < 2; hh++) {
                    uint4 t = xr[r][hh];
                    t.x = bsub2(t.x, m); t.y = bsub2(t.y, m); t.z = bsub2(t.z, m); t.w = bsub2(t.w, m);
                    sts128(a + hh * 65536, t);
                }
            }
            asm volatile("fence.proxy.async.shared::cta;" ::: "memory");
            named_bar(1 + wgi, 128);
            PROFW(17, 0);
        }
        int st = 0; uint32_t fph = 0;
        const int rb64 = 2 * i + wgi;
        gemm1_pass<4>(sb, wgi, warp4, lane, st, fph, e_cl, rb64, 14 * j);
        gemm1_pass<3>(sb, wgi, warp4, lane, st, fph, e_cl, rb64, 14 * j + 8);

        if (wgi == 0) {
            float acc[64];
            uint4 af[3][8];
            const uint4* hsrc = g_hfrag + ((size_t)rbG2 * 112 * 4 + warp4) * 32 + lane;
            const uint64_t descB0 = make_desc(sb, 4096, 1024, 1);
            int prev = 0;
            st = 3;
            auto load_group = [&](uint4 (&dstf)[8], int u) {
                #pragma unroll
                for (int hb = 0; hb < 4; hb++) {
                    const int ks = blk_f0(4 * u + hb, j) >> 4;
                    dstf[2 * hb] = ldg_cg128(hsrc + ks * 128);
                    dstf[2 * hb + 1] = ldg_cg128(hsrc + ks * 128 + 128);
                }
            };
            auto g2_step = [&](int u, uint4 (&cur)[8], uint4 (&nxt)[8], bool do_load) {
                if (warp4 == 0) PROF2(2, 16 + u);
                mbar_wait(sb + SM_BARS + (B_FULL + st) * 8, (fph >> st) & 1);
                fph ^= 1u << st;
                if (warp4 == 0) PROF2(1, 16 + u);
                const uint64_t db = desc_add(descB0, stage_off_rt(st) >> 4);
                WG_FENCE();
                #pragma unroll
                for (int kk = 0; kk < 8; kk++)
                    wgmma_rs_n128_tb(acc, cur[kk].x, cur[kk].y, cur[kk].z, cur[kk].w, db + ((kk >> 1) * 512 + (kk & 1) * 128), (u | kk) ? 1 : 0);
                WG_COMMIT();
                wg_wait<1>();
                if (warp4 == 0) PROF2(3, 16 + u);
                if (lane < 2 && u > 0 && u - 1 + 5 < 14) mbar_arrive_cluster(e_cl + prev * 8, 2);
                prev = st;
                st = next_st2(st);
                if (u + 2 == 8) mbar_wait(sb + SM_BARS + (B_HRDY + 1) * 8, 0);
                if (do_load) load_group(nxt, u + 2);
            };
            mbar_wait(sb + SM_BARS + B_HRDY * 8, 0);
            PROFW(20, 0);
            load_group(af[0], 0); load_group(af[1], 1);
            #pragma unroll 1
            for (int u0 = 0; u0 < 12; u0 += 3) {
                g2_step(u0, af[0], af[2], true);
                g2_step(u0 + 1, af[1], af[0], true);
                g2_step(u0 + 2, af[2], af[1], true);
                PROFW(21 + (u0 / 3), 0);
            }
            g2_step(12, af[0], af[2], false);
            g2_step(13, af[1], af[0], false);
            wg_wait<0>();
            PROFW(27, 0);
            mbar_wait(sb + SM_BARS + B_XR * 8, 0);
            mbar_wait(sb + SM_BARS + B_YT * 8, 0);
            PROFW(28, 0);
            const int r0 = (j & 1) * 64 + warp4 * 16 + g;
            const float s0 = __uint_as_float(lds32(sb + SM_STATS + r0 * 4)), s1 = __uint_as_float(lds32(sb + SM_STATS + (r0 + 8) * 4));
            const uint32_t drow0 = sb + SM_XE + r0 * 128 + c * 4;
            const uint32_t xrow0 = sb + SM_XE + (r0 ^ 64) * 128 + c * 4;
            const int mi = lane >> 3, lr = lane & 7;
            const uint32_t yaddr = sb + SM_YT + ((mi >> 1) * 8 + lr) * 128 + (((2 * warp4 + (mi & 1)) ^ lr) << 4);
            #pragma unroll
            for (int t2 = 0; t2 < 8; t2++) {
                uint32_t y[4];
                asm volatile("ldmatrix.sync.aligned.m8n8.x4.trans.shared.b16 {%0,%1,%2,%3}, [%4];"
                    : "=r"(y[0]), "=r"(y[1]), "=r"(y[2]), "=r"(y[3]) : "r"(yaddr + t2 * 2048) : "memory");
                #pragma unroll
                for (int tt = 0; tt < 2; tt++) {
                    const int t = 2 * t2 + tt;
                    const uint32_t off = (t >> 3) * 16384 + (((t & 7) ^ g) << 4);
                    const uint32_t x0 = lds32(xrow0 + off), x1 = lds32(xrow0 + 1024 + off);
                    const uint32_t d0 = lds32(drow0 + off), d1 = lds32(drow0 + 1024 + off);
                    const uint32_t n0 = pack_bf(bf_lo(d0) * s0, bf_hi(d0) * s0), n1 = pack_bf(bf_lo(d1) * s1, bf_hi(d1) * s1);
                    const uint32_t o0 = badd2(badd2(x0, bmul2(n0, y[2 * tt])), pack_bf(acc[4 * t], acc[4 * t + 1]));
                    const uint32_t o1 = badd2(badd2(x1, bmul2(n1, y[2 * tt + 1])), pack_bf(acc[4 * t + 2], acc[4 * t + 3]));
                    sts32(xrow0 + off, o0); sts32(xrow0 + 1024 + off, o1);
                }
            }
            asm volatile("fence.proxy.async.shared::cta;" ::: "memory");
            named_bar(1, 128);
            if (tid == 0) {
                tma2d_store(&p.tm_out, 128 * cb, 64 * rbG2, sb + SM_XE + ((j & 1) ^ 1) * 8192);
                tma2d_store(&p.tm_out, 128 * cb + 64, 64 * rbG2, sb + SM_XE + 16384 + ((j & 1) ^ 1) * 8192);
                asm volatile("cp.async.bulk.commit_group;" ::: "memory");
                asm volatile("cp.async.bulk.wait_group.read 0;" ::: "memory");
                PROFW(29, 0);
            }
        } else {
            const int gch = 4 * b + warp4;
            const uint32_t xb = sb + SM_CVX + warp4 * 4096;
            const uint32_t hb = sb + SM_CVH + warp4 * 4096;
            const uint32_t dw = ((const unsigned short*)p.ssm_D)[gch];
            const uint32_t d2 = dw | (dw << 16);
            mbar_wait(sb + SM_BARS + (B_CONV + warp4) * 8, 0);
            PROFW(32, 4);
            float acc[16][4];
            #pragma unroll
            for (int jj = 0; jj < 16; jj++) { acc[jj][0] = 0.f; acc[jj][1] = 0.f; acc[jj][2] = 0.f; acc[jj][3] = 0.f; }
            uint2 bf[16];
            uint32_t xl = xb + g * 32 + c * 8;
            uint32_t hl = hb + (g + 2 * c - 8) * 4;
            #pragma unroll
            for (int d = 0; d < 16; d++) bf[d] = lds64(xl + d * 256);
            uint32_t w0 = 0, w1 = 0, w2 = 0;
            if (g + 2 * c >= 8) w0 = lds32(hl);
            if (g + 2 * c >= 7) w1 = lds32(hl + 4);
            if (g + 2 * c >= 6) w2 = lds32(hl + 8);
            #pragma unroll 1
            for (int m0 = 0; m0 < 8; m0++) {
                xl -= 32;
                #pragma unroll
                for (int ii = 0; ii < 16; ii++) {
                    const uint32_t a0 = w1, a1 = __byte_perm(w0, w1, 0x5432), a2 = w2, a3 = __byte_perm(w1, w2, 0x5432);
                    const uint32_t nx = (ii < 15) ? hl + (ii + 1) * 256 : hl + 32;
                    w0 = lds32(nx); w1 = lds32(nx + 4); w2 = lds32(nx + 8);
                    #pragma unroll
                    for (int jj = 15; jj >= ii; jj--) mma16816(acc[jj], a0, a1, a2, a3, bf[jj - ii]);
                    if (ii < 15) bf[15 - ii] = lds64(xl + (15 - ii) * 256);
                    else { bf[0] = make_uint2(0, 0); if (g > m0) bf[0] = lds64(xl); }
                }
                hl += 32;
            }
            PROFW(33, 4);
            const uint32_t kvl = xb + c * 64 + (7 - g) * 4;
            const uint32_t yl = hb + c * 64 + g * 4;
            __syncwarp();
            #pragma unroll
            for (int jj = 0; jj < 16; jj++) {
                uint32_t k0 = lds32(kvl + jj * 256), k1 = lds32(kvl + jj * 256 + 32);
                k0 = __byte_perm(k0, k0, 0x1032); k1 = __byte_perm(k1, k1, 0x1032);
                sts32(yl + jj * 256, badd2(pack_bf(acc[jj][2], acc[jj][0]), bmul2(k0, d2)));
                sts32(yl + jj * 256 + 32, badd2(pack_bf(acc[jj][3], acc[jj][1]), bmul2(k1, d2)));
            }
            asm volatile("fence.proxy.async.shared::cta;" ::: "memory");
            __syncwarp();
            PROFW(44, 4);
            if (lane == 0) {
                bulk_s2g(g_yT + (size_t)gch * SEQ, hb, 4096);
                asm volatile("cp.async.bulk.commit_group;" ::: "memory");
                asm volatile("cp.async.bulk.wait_group 0;" ::: "memory");
                mbar_arrive(sb + SM_BARS + B_CVDONE * 8);
                asm volatile("fence.proxy.async.global;" ::: "memory");
                flag_add(&g_cnt_y[(b >> 5) * 32]);
            }
            PROFW(45, 4);
        }
    } else {
        asm volatile("setmaxnreg.dec.sync.aligned.u32 104;");
        if (warp == 8) {
            if (lane == 0) {
                int st = 0; uint32_t eph = 7;
                #pragma unroll 1
                for (int it = 0; it < 16; it++) {
                    const int pass = it >> 3, sl = it & 7;
                    const int nb = pass ? 3 : 4;
                    const CUtensorMap* tm = pass ? (rank ? &p.tm_uB : &p.tm_gB) : (rank ? &p.tm_uA : &p.tm_gA);
                    mbar_wait(sb + SM_BARS + (B_EMPTY + st) * 8, (eph >> st) & 1);
                    eph ^= 1u << st;
                    PROF2(0, it);
                    mbar_expect_tx(sb + SM_BARS + (B_FULL + st) * 8, nb * 8192);
                    tma3d_mc(sb + SM_RING + st * STAGE_BYTES + rank * nb * 4096, tm, 0, ((sl + 2 * cb + 2) & 7) * 64, 7 * j + 4 * pass, sb + SM_BARS + (B_FULL + st) * 8);
                    st = (st == 2) ? 0 : st + 1;
                }
                st = 3;
                #pragma unroll 1
                for (int u = 0; u < 14; u++) {
                    mbar_wait(sb + SM_BARS + (B_EMPTY + st) * 8, (eph >> st) & 1);
                    eph ^= 1u << st;
                    PROF2(0, 16 + u);
                    const uint32_t so = sb + stage_off_rt(st) + rank * 8192;
                    mbar_expect_tx(sb + SM_BARS + (B_FULL + st) * 8, 32768);
                    tma3d_mc(so, &p.tm_w2, 0, blk_f0(4 * u + rank, j), 2 * cb, sb + SM_BARS + (B_FULL + st) * 8);
                    tma3d_mc(so + 16384, &p.tm_w2, 0, blk_f0(4 * u + 2 + rank, j), 2 * cb, sb + SM_BARS + (B_FULL + st) * 8);
                    st = next_st2(st);
                }
                PROF(48);
                const unsigned ep = lds32(sb + SM_EPOCH);
                mbar_wait(sb + SM_BARS + B_CVDONE * 8, 0);
                flag_wait(&g_cnt_y[cb * 32], ep * 128);
                PROF(49);
                asm volatile("fence.proxy.async.global;" ::: "memory");
                mbar_expect_tx(sb + SM_BARS + B_YT * 8, 16384);
                tma2d(sb + SM_YT, &p.tm_yT, 64 * rbG2, 128 * cb, sb + SM_BARS + B_YT * 8);
            }
        } else if (warp < 11) {
            mbar_wait(sb + SM_BARS + B_XFULL * 8, 0);
            #pragma unroll 1
            for (int rnd = 0; rnd < 2; rnd++) {
                const int tt = (tid - 288) + 64 * rnd;
                uint32_t sk[4][2];
                uint4 skw[2];
                skw[0] = ldg_nc128(p.shift_k + 16 * tt); skw[1] = ldg_nc128(p.shift_k + 16 * tt + 8);
                const __nv_bfloat16* kp = p.k + (size_t)(16 * b) * DM + 4 * tt;
                const __nv_bfloat16* vp = p.v + (size_t)(16 * b) * DM + 4 * tt;
                uint2 kr[19];
                uint2 kv[16];
                #pragma unroll
                for (int r = 0; r < 3; r++) kr[r] = (b > 0) ? ldg_nc64(kp + (r - 3) * DM) : make_uint2(0, 0);
                #pragma unroll
                for (int r = 0; r < 16; r++) { kr[3 + r] = ldg_nc64(kp + r * DM); kv[r] = ldg_nc64(vp + r * DM); }
                {
                    const uint4 w0 = skw[0], w1 = skw[1];
                    sk[0][0] = __byte_perm(w0.x, w0.z, 0x5410); sk[1][0] = __byte_perm(w0.x, w0.z, 0x7632);
                    sk[2][0] = __byte_perm(w0.y, w0.w, 0x5410); sk[3][0] = __byte_perm(w0.y, w0.w, 0x7632);
                    sk[0][1] = __byte_perm(w1.x, w1.z, 0x5410); sk[1][1] = __byte_perm(w1.x, w1.z, 0x7632);
                    sk[2][1] = __byte_perm(w1.y, w1.w, 0x5410); sk[3][1] = __byte_perm(w1.y, w1.w, 0x7632);
                }
                #pragma unroll
                for (int s = 0; s < 16; s++) {
                    uint32_t a = bmul2(kr[s].x, sk[3][0]);
                    a = badd2(a, bmul2(kr[s + 1].x, sk[2][0]));
                    a = badd2(a, bmul2(kr[s + 2].x, sk[1][0]));
                    a = badd2(a, bmul2(kr[s + 3].x, sk[0][0]));
                    kv[s].x = bmul2(a, kv[s].x);
                    a = bmul2(kr[s].y, sk[3][1]);
                    a = badd2(a, bmul2(kr[s + 1].y, sk[2][1]));
                    a = badd2(a, bmul2(kr[s + 2].y, sk[1][1]));
                    a = badd2(a, bmul2(kr[s + 3].y, sk[0][1]));
                    kv[s].y = bmul2(a, kv[s].y);
                }
                PROFW(57 + 2 * rnd, 9);
                #pragma unroll
                for (int cc = 0; cc < 4; cc++) {
                    const uint32_t sel = (cc & 1) ? 0x7632 : 0x5410;
                    #define KVW(r) ((cc & 2) ? kv[r].y : kv[r].x)
                    uint4* dst = (uint4*)(g_kvT + (size_t)(4 * tt + cc) * SEQ + 16 * b);
                    dst[0] = make_uint4(__byte_perm(KVW(15), KVW(14), sel), __byte_perm(KVW(13), KVW(12), sel),
                                        __byte_perm(KVW(11), KVW(10), sel), __byte_perm(KVW(9), KVW(8), sel));
                    dst[1] = make_uint4(__byte_perm(KVW(7), KVW(6), sel), __byte_perm(KVW(5), KVW(4), sel),
                                        __byte_perm(KVW(3), KVW(2), sel), __byte_perm(KVW(1), KVW(0), sel));
                    #undef KVW
                }
                PROFW(58 + 2 * rnd, 9);
            }
            asm volatile("fence.proxy.async.global;" ::: "memory");
            __syncwarp();
            if (lane == 0) {
                flag_add(&g_cnt_kv[0]);
                PROFW(50, 9);
                const int wgi = warp - 9;
                mbar_wait(sb + SM_BARS + (B_HD + wgi * 2) * 8, 0);
                flag_add(&g_flag_h[((2 * i + wgi) * 2 + 0) * 8]);
                mbar_wait(sb + SM_BARS + (B_HD + wgi * 2 + 1) * 8, 0);
                flag_add(&g_flag_h[((2 * i + wgi) * 2 + 1) * 8]);
            }
        } else {
            if (lane == 0) {
                const unsigned ep = g_launch[b] + 1;
                g_launch[b] = ep;
                sts32(sb + SM_EPOCH, ep);
                tmap_prefetch(rank ? &p.tm_uB : &p.tm_gB);
                tmap_prefetch(&p.tm_w2); tmap_prefetch(&p.tm_yT); tmap_prefetch(&p.tm_out); tmap_prefetch(&p.tm_xe);
                mbar_wait(sb + SM_BARS + (B_FULL + 2) * 8, 0);
                l2_prefetch(p.ssm_k + (size_t)(4 * b) * SEQ, 4 * SEQ * 2);
                l2_prefetch(p.wd + (size_t)b * (FF * DM / NCTA), FF * DM / NCTA * 2);
                mbar_wait(sb + SM_BARS + (B_HD + 0) * 8, 0);
                flag_wait(&g_cnt_kv[0], ep * 256);
                asm volatile("fence.proxy.async.global;" ::: "memory");
                PROF(53);
                mbar_wait(sb + SM_BARS + B_XFREE * 8, 0);
                PROF(54);
                for (int ch = 0; ch < 4; ch++) {
                    const uint32_t bar = sb + SM_BARS + (B_CONV + ch) * 8;
                    mbar_expect_tx(bar, 8192);
                    bulk_g2s(sb + SM_CVX + ch * 4096, g_kvT + (size_t)(4 * b + ch) * SEQ, 4096, bar);
                    bulk_g2s(sb + SM_CVH + ch * 4096, p.ssm_k + (size_t)(4 * b + ch) * SEQ, 4096, bar);
                }
                flag_wait(&g_flag_h[(rbG2 * 2 + 0) * 8], ep * 8);
                mbar_arrive(sb + SM_BARS + B_HRDY * 8);
                mbar_wait(sb + SM_BARS + B_G1DONE * 8, 0);
                mbar_expect_tx(sb + SM_BARS + B_XR * 8, 16384);
                tma2d(sb + SM_XE + ((j & 1) ^ 1) * 8192, &p.tm_xe, 128 * cb, 64 * rbG2, sb + SM_BARS + B_XR * 8);
                tma2d(sb + SM_XE + 16384 + ((j & 1) ^ 1) * 8192, &p.tm_xe, 128 * cb + 64, 64 * rbG2, sb + SM_BARS + B_XR * 8);
                flag_wait(&g_flag_h[(rbG2 * 2 + 1) * 8], ep * 8);
                mbar_arrive(sb + SM_BARS + (B_HRDY + 1) * 8);
            }
        }
    }
}

typedef CUresult (*EncodeFn)(CUtensorMap*, CUtensorMapDataType, cuuint32_t, void*, const cuuint64_t*, const cuuint64_t*,
                             const cuuint32_t*, const cuuint32_t*, CUtensorMapInterleave, CUtensorMapSwizzle,
                             CUtensorMapL2promotion, CUtensorMapFloatOOBfill);

void encode(EncodeFn fn, CUtensorMap* tm, const void* base, int rank, const cuuint64_t* dims, const cuuint64_t* strides,
            const cuuint32_t* box, CUtensorMapSwizzle swz) {
    cuuint32_t es[5] = {1, 1, 1, 1, 1};
    fn(tm, CU_TENSOR_MAP_DATA_TYPE_BFLOAT16, rank, (void*)base, dims, strides, box, es, CU_TENSOR_MAP_INTERLEAVE_NONE, swz,
       CU_TENSOR_MAP_L2_PROMOTION_L2_128B, CU_TENSOR_MAP_FLOAT_OOB_FILL_NONE);
}

}

extern "C" void kernel_launch(void* const* d_in, const int* in_sizes, int n_in, void* d_out, int out_size) {
    (void)in_sizes; (void)n_in; (void)out_size;
    static EncodeFn enc = nullptr;
    static void* yT_ptr = nullptr;
    if (!enc) {
        void* fn = nullptr; cudaDriverEntryPointQueryResult qr;
        cudaGetDriverEntryPoint("cuTensorMapEncodeTiled", &fn, cudaEnableDefault, &qr);
        enc = (EncodeFn)fn;
        cudaGetSymbolAddress(&yT_ptr, g_yT);
        cudaFuncSetAttribute(fused_kernel, cudaFuncAttributeMaxDynamicSharedMemorySize, SM_TOTAL);
    }
    Params p;
    p.q = (const __nv_bfloat16*)d_in[0]; p.k = (const __nv_bfloat16*)d_in[1]; p.v = (const __nv_bfloat16*)d_in[2];
    p.shift_k = (const __nv_bfloat16*)d_in[3]; p.ssm_k = (const __nv_bfloat16*)d_in[4]; p.ssm_D = (const __nv_bfloat16*)d_in[5];
    p.wg = (const __nv_bfloat16*)d_in[7]; p.wu = (const __nv_bfloat16*)d_in[8]; p.wd = (const __nv_bfloat16*)d_in[9];
    {
        cuuint64_t dims[2] = {DM, SEQ}; cuuint64_t str[1] = {DM * 2};
        cuuint32_t box[2] = {64, 128};
        encode(enc, &p.tm_x, p.q, 2, dims, str, box, CU_TENSOR_MAP_SWIZZLE_128B);
        cuuint32_t box2[2] = {64, 64};
        encode(enc, &p.tm_out, d_out, 2, dims, str, box2, CU_TENSOR_MAP_SWIZZLE_128B);
        encode(enc, &p.tm_xe, p.q, 2, dims, str, box2, CU_TENSOR_MAP_SWIZZLE_128B);
    }
    {
        cuuint64_t dims[3] = {32, DM, FF / 32}; cuuint64_t str[2] = {FF * 2, 64};
        cuuint32_t boxA[3] = {32, 64, 4}, boxB[3] = {32, 64, 3};
        encode(enc, &p.tm_gA, p.wg, 3, dims, str, boxA, CU_TENSOR_MAP_SWIZZLE_64B);
        encode(enc, &p.tm_gB, p.wg, 3, dims, str, boxB, CU_TENSOR_MAP_SWIZZLE_64B);
        encode(enc, &p.tm_uA, p.wu, 3, dims, str, boxA, CU_TENSOR_MAP_SWIZZLE_64B);
        encode(enc, &p.tm_uB, p.wu, 3, dims, str, boxB, CU_TENSOR_MAP_SWIZZLE_64B);
    }
    {
        cuuint64_t dims[3] = {64, FF, DM / 64}; cuuint64_t str[2] = {DM * 2, 128};
        cuuint32_t box[3] = {64, 32, 2};
        encode(enc, &p.tm_w2, p.wd, 3, dims, str, box, CU_TENSOR_MAP_SWIZZLE_128B);
    }
    {
        cuuint64_t dims[2] = {SEQ, DM}; cuuint64_t str[1] = {SEQ * 2};
        cuuint32_t box[2] = {64, 128};
        encode(enc, &p.tm_yT, yT_ptr, 2, dims, str, box, CU_TENSOR_MAP_SWIZZLE_128B);
    }
    fused_kernel<<<NCTA, NTHREADS, SM_TOTAL>>>(p);
}
```

```cpp
#include <cuda_runtime.h>
#include <cuda_bf16.h>
#include <cuda.h>
#include <stdint.h>

namespace {

constexpr int SEQ = 2048, DM = 512, FF = 1792;
constexpr int NCTA = 128;
constexpr int NTHREADS = 384;
constexpr int STAGE_BYTES = 32768;
#define CVGO_M0 6

constexpr uint32_t SM_X = 0;
constexpr uint32_t SM_RING = 131072;
constexpr uint32_t SM_MISC = SM_RING + 3 * STAGE_BYTES;
constexpr uint32_t SM_BARS = SM_MISC;
constexpr uint32_t SM_EPOCH = SM_MISC + 248;
constexpr uint32_t SM_STATS = SM_MISC + 256;
constexpr uint32_t SM_TOTAL = SM_STATS + 512;
static_assert(SM_TOTAL <= 232448, "smem");
__host__ __device__ constexpr uint32_t stage_off(int s) { return s < 3 ? SM_RING + s * STAGE_BYTES : (uint32_t)(s - 2) * STAGE_BYTES; }
constexpr uint32_t SM_CVX = 0;
constexpr uint32_t SM_CVH = 16384;
constexpr uint32_t SM_YT = 0;
constexpr uint32_t SM_XE = 6 * 16384;

constexpr int B_FULL = 0, B_EMPTY = 5, B_XFULL = 10, B_CONV = 11, B_YT = 15, B_XR = 16, B_G1DONE = 17, B_HD = 18, B_HRDY = 22,
              B_XFREE = 24, B_CVDONE = 25, B_CVGO = 26, B_YST = 27, B_COUNT = 28;
static_assert(B_COUNT * 8 <= 248, "barrier space");

__device__ uint4 g_hfrag[32 * 112 * 4 * 32];
__device__ __align__(128) __nv_bfloat16 g_kvT[DM * SEQ];
__device__ __align__(128) __nv_bfloat16 g_yT[DM * SEQ];
__device__ unsigned g_launch[NCTA];
__device__ unsigned g_cnt_kv[32];
__device__ unsigned g_cnt_y[4 * 32];
__device__ unsigned g_flag_h[32 * 2 * 8];

#define PROF(idx)
#define PROF2(a, idx)
#define PROFW(idx, w)

struct Params {
    CUtensorMap tm_x, tm_gA, tm_gB, tm_uA, tm_uB, tm_w2, tm_yT, tm_out, tm_xe;
    const __nv_bfloat16 *q, *k, *v, *shift_k, *ssm_k, *ssm_D, *wg, *wu, *wd;
};

__device__ __forceinline__ void wgmma_rs_n32(float (&d)[16], uint32_t a0, uint32_t a1, uint32_t a2, uint32_t a3, uint64_t db, int sc) {
  asm volatile("{\n.reg .pred p;\nsetp.ne.b32 p, %21, 0;\n"
    "wgmma.mma_async.sync.aligned.m64n32k16.f32.bf16.bf16 {%0,%1,%2,%3,%4,%5,%6,%7,%8,%9,%10,%11,%12,%13,%14,%15}, {%16,%17,%18,%19}, %20, p, 1, 1, 0;\n}\n"
    : "+f"(d[0]),"+f"(d[1]),"+f"(d[2]),"+f"(d[3]),"+f"(d[4]),"+f"(d[5]),"+f"(d[6]),"+f"(d[7]),"+f"(d[8]),"+f"(d[9]),"+f"(d[10]),"+f"(d[11]),"+f"(d[12]),"+f"(d[13]),"+f"(d[14]),"+f"(d[15])
    : "r"(a0),"r"(a1),"r"(a2),"r"(a3),"l"(db),"r"(sc));
}
__device__ __forceinline__ void wgmma_rs_n128_tb(float (&d)[64], uint32_t a0, uint32_t a1, uint32_t a2, uint32_t a3, uint64_t db, int sc) {
  asm volatile("{\n.reg .pred p;\nsetp.ne.b32 p, %69, 0;\n"
    "wgmma.mma_async.sync.aligned.m64n128k16.f32.bf16.bf16 {%0,%1,%2,%3,%4,%5,%6,%7,%8,%9,%10,%11,%12,%13,%14,%15,%16,%17,%18,%19,%20,%21,%22,%23,%24,%25,%26,%27,%28,%29,%30,%31,%32,%33,%34,%35,%36,%37,%38,%39,%40,%41,%42,%43,%44,%45,%46,%47,%48,%49,%50,%51,%52,%53,%54,%55,%56,%57,%58,%59,%60,%61,%62,%63}, {%64,%65,%66,%67}, %68, p, 1, 1, 1;\n}\n"
    : "+f"(d[0]),"+f"(d[1]),"+f"(d[2]),"+f"(d[3]),"+f"(d[4]),"+f"(d[5]),"+f"(d[6]),"+f"(d[7]),"+f"(d[8]),"+f"(d[9]),"+f"(d[10]),"+f"(d[11]),"+f"(d[12]),"+f"(d[13]),"+f"(d[14]),"+f"(d[15]),"+f"(d[16]),"+f"(d[17]),"+f"(d[18]),"+f"(d[19]),"+f"(d[20]),"+f"(d[21]),"+f"(d[22]),"+f"(d[23]),"+f"(d[24]),"+f"(d[25]),"+f"(d[26]),"+f"(d[27]),"+f"(d[28]),"+f"(d[29]),"+f"(d[30]),"+f"(d[31]),"+f"(d[32]),"+f"(d[33]),"+f"(d[34]),"+f"(d[35]),"+f"(d[36]),"+f"(d[37]),"+f"(d[38]),"+f"(d[39]),"+f"(d[40]),"+f"(d[41]),"+f"(d[42]),"+f"(d[43]),"+f"(d[44]),"+f"(d[45]),"+f"(d[46]),"+f"(d[47]),"+f"(d[48]),"+f"(d[49]),"+f"(d[50]),"+f"(d[51]),"+f"(d[52]),"+f"(d[53]),"+f"(d[54]),"+f"(d[55]),"+f"(d[56]),"+f"(d[57]),"+f"(d[58]),"+f"(d[59]),"+f"(d[60]),"+f"(d[61]),"+f"(d[62]),"+f"(d[63])
    : "r"(a0),"r"(a1),"r"(a2),"r"(a3),"l"(db),"r"(sc));
}
__device__ __forceinline__ void wgmma_ss_n256_tb(float (&d)[128], uint64_t da, uint64_t db, int sc) {
  asm volatile("{\n.reg .pred p;\nsetp.ne.b32 p, %130, 0;\n"
    "wgmma.mma_async.sync.aligned.m64n256k16.f32.bf16.bf16 {%0,%1,%2,%3,%4,%5,%6,%7,%8,%9,%10,%11,%12,%13,%14,%15,%16,%17,%18,%19,%20,%21,%22,%23,%24,%25,%26,%27,%28,%29,%30,%31,%32,%33,%34,%35,%36,%37,%38,%39,%40,%41,%42,%43,%44,%45,%46,%47,%48,%49,%50,%51,%52,%53,%54,%55,%56,%57,%58,%59,%60,%61,%62,%63,%64,%65,%66,%67,%68,%69,%70,%71,%72,%73,%74,%75,%76,%77,%78,%79,%80,%81,%82,%83,%84,%85,%86,%87,%88,%89,%90,%91,%92,%93,%94,%95,%96,%97,%98,%99,%100,%101,%102,%103,%104,%105,%106,%107,%108,%109,%110,%111,%112,%113,%114,%115,%116,%117,%118,%119,%120,%121,%122,%123,%124,%125,%126,%127}, %128, %129, p, 1, 1, 0, 1;\n}\n"
    : "+f"(d[0]),"+f"(d[1]),"+f"(d[2]),"+f"(d[3]),"+f"(d[4]),"+f"(d[5]),"+f"(d[6]),"+f"(d[7]),"+f"(d[8]),"+f"(d[9]),"+f"(d[10]),"+f"(d[11]),"+f"(d[12]),"+f"(d[13]),"+f"(d[14]),"+f"(d[15]),"+f"(d[16]),"+f"(d[17]),"+f"(d[18]),"+f"(d[19]),"+f"(d[20]),"+f"(d[21]),"+f"(d[22]),"+f"(d[23]),"+f"(d[24]),"+f"(d[25]),"+f"(d[26]),"+f"(d[27]),"+f"(d[28]),"+f"(d[29]),"+f"(d[30]),"+f"(d[31]),"+f"(d[32]),"+f"(d[33]),"+f"(d[34]),"+f"(d[35]),"+f"(d[36]),"+f"(d[37]),"+f"(d[38]),"+f"(d[39]),"+f"(d[40]),"+f"(d[41]),"+f"(d[42]),"+f"(d[43]),"+f"(d[44]),"+f"(d[45]),"+f"(d[46]),"+f"(d[47]),"+f"(d[48]),"+f"(d[49]),"+f"(d[50]),"+f"(d[51]),"+f"(d[52]),"+f"(d[53]),"+f"(d[54]),"+f"(d[55]),"+f"(d[56]),"+f"(d[57]),"+f"(d[58]),"+f"(d[59]),"+f"(d[60]),"+f"(d[61]),"+f"(d[62]),"+f"(d[63]),"+f"(d[64]),"+f"(d[65]),"+f"(d[66]),"+f"(d[67]),"+f"(d[68]),"+f"(d[69]),"+f"(d[70]),"+f"(d[71]),"+f"(d[72]),"+f"(d[73]),"+f"(d[74]),"+f"(d[75]),"+f"(d[76]),"+f"(d[77]),"+f"(d[78]),"+f"(d[79]),"+f"(d[80]),"+f"(d[81]),"+f"(d[82]),"+f"(d[83]),"+f"(d[84]),"+f"(d[85]),"+f"(d[86]),"+f"(d[87]),"+f"(d[88]),"+f"(d[89]),"+f"(d[90]),"+f"(d[91]),"+f"(d[92]),"+f"(d[93]),"+f"(d[94]),"+f"(d[95]),"+f"(d[96]),"+f"(d[97]),"+f"(d[98]),"+f"(d[99]),"+f"(d[100]),"+f"(d[101]),"+f"(d[102]),"+f"(d[103]),"+f"(d[104]),"+f"(d[105]),"+f"(d[106]),"+f"(d[107]),"+f"(d[108]),"+f"(d[109]),"+f"(d[110]),"+f"(d[111]),"+f"(d[112]),"+f"(d[113]),"+f"(d[114]),"+f"(d[115]),"+f"(d[116]),"+f"(d[117]),"+f"(d[118]),"+f"(d[119]),"+f"(d[120]),"+f"(d[121]),"+f"(d[122]),"+f"(d[123]),"+f"(d[124]),"+f"(d[125]),"+f"(d[126]),"+f"(d[127])
    : "l"(da),"l"(db),"r"(sc));
}
__device__ __forceinline__ void wgmma_ss_n192_tb(float (&d)[96], uint64_t da, uint64_t db, int sc) {
  asm volatile("{\n.reg .pred p;\nsetp.ne.b32 p, %98, 0;\n"
    "wgmma.mma_async.sync.aligned.m64n192k16.f32.bf16.bf16 {%0,%1,%2,%3,%4,%5,%6,%7,%8,%9,%10,%11,%12,%13,%14,%15,%16,%17,%18,%19,%20,%21,%22,%23,%24,%25,%26,%27,%28,%29,%30,%31,%32,%33,%34,%35,%36,%37,%38,%39,%40,%41,%42,%43,%44,%45,%46,%47,%48,%49,%50,%51,%52,%53,%54,%55,%56,%57,%58,%59,%60,%61,%62,%63,%64,%65,%66,%67,%68,%69,%70,%71,%72,%73,%74,%75,%76,%77,%78,%79,%80,%81,%82,%83,%84,%85,%86,%87,%88,%89,%90,%91,%92,%93,%94,%95}, %96, %97, p, 1, 1, 0, 1;\n}\n"
    : "+f"(d[0]),"+f"(d[1]),"+f"(d[2]),"+f"(d[3]),"+f"(d[4]),"+f"(d[5]),"+f"(d[6]),"+f"(d[7]),"+f"(d[8]),"+f"(d[9]),"+f"(d[10]),"+f"(d[11]),"+f"(d[12]),"+f"(d[13]),"+f"(d[14]),"+f"(d[15]),"+f"(d[16]),"+f"(d[17]),"+f"(d[18]),"+f"(d[19]),"+f"(d[20]),"+f"(d[21]),"+f"(d[22]),"+f"(d[23]),"+f"(d[24]),"+f"(d[25]),"+f"(d[26]),"+f"(d[27]),"+f"(d[28]),"+f"(d[29]),"+f"(d[30]),"+f"(d[31]),"+f"(d[32]),"+f"(d[33]),"+f"(d[34]),"+f"(d[35]),"+f"(d[36]),"+f"(d[37]),"+f"(d[38]),"+f"(d[39]),"+f"(d[40]),"+f"(d[41]),"+f"(d[42]),"+f"(d[43]),"+f"(d[44]),"+f"(d[45]),"+f"(d[46]),"+f"(d[47]),"+f"(d[48]),"+f"(d[49]),"+f"(d[50]),"+f"(d[51]),"+f"(d[52]),"+f"(d[53]),"+f"(d[54]),"+f"(d[55]),"+f"(d[56]),"+f"(d[57]),"+f"(d[58]),"+f"(d[59]),"+f"(d[60]),"+f"(d[61]),"+f"(d[62]),"+f"(d[63]),"+f"(d[64]),"+f"(d[65]),"+f"(d[66]),"+f"(d[67]),"+f"(d[68]),"+f"(d[69]),"+f"(d[70]),"+f"(d[71]),"+f"(d[72]),"+f"(d[73]),"+f"(d[74]),"+f"(d[75]),"+f"(d[76]),"+f"(d[77]),"+f"(d[78]),"+f"(d[79]),"+f"(d[80]),"+f"(d[81]),"+f"(d[82]),"+f"(d[83]),"+f"(d[84]),"+f"(d[85]),"+f"(d[86]),"+f"(d[87]),"+f"(d[88]),"+f"(d[89]),"+f"(d[90]),"+f"(d[91]),"+f"(d[92]),"+f"(d[93]),"+f"(d[94]),"+f"(d[95])
    : "l"(da),"l"(db),"r"(sc));
}

__device__ __forceinline__ uint32_t smem_u32(const void* p) { return (uint32_t)__cvta_generic_to_shared(p); }
__device__ __forceinline__ void mbar_init(uint32_t bar, uint32_t cnt) { asm volatile("mbarrier.init.shared::cta.b64 [%0], %1;" :: "r"(bar), "r"(cnt)); }
__device__ __forceinline__ void mbar_expect_tx(uint32_t bar, uint32_t bytes) { asm volatile("mbarrier.arrive.expect_tx.shared::cta.b64 _, [%0], %1;" :: "r"(bar), "r"(bytes) : "memory"); }
__device__ __forceinline__ void mbar_arrive(uint32_t bar) { asm volatile("mbarrier.arrive.shared::cta.b64 _, [%0];" :: "r"(bar) : "memory"); }
__device__ __forceinline__ void mbar_arrive_cluster(uint32_t cbar, uint32_t cnt) { asm volatile("mbarrier.arrive.shared::cluster.b64 _, [%0], %1;" :: "r"(cbar), "r"(cnt) : "memory"); }
__device__ __forceinline__ uint32_t mapa(uint32_t a, uint32_t rank) { uint32_t r; asm volatile("mapa.shared::cluster.u32 %0, %1, %2;" : "=r"(r) : "r"(a), "r"(rank)); return r; }
__device__ __forceinline__ void mbar_wait(uint32_t bar, uint32_t parity) {
    uint32_t ok; uint32_t n = 0;
    do {
        asm volatile("{\n.reg .pred p;\nmbarrier.try_wait.parity.shared::cta.b64 p, [%1], %2;\nselp.u32 %0, 1, 0, p;\n}" : "=r"(ok) : "r"(bar), "r"(parity) : "memory");
    } while (!ok && ++n < (1u << 17));
}
__device__ __forceinline__ void flag_wait(const unsigned* p, unsigned target) {
    unsigned v; uint32_t n = 0;
    while (true) {
        asm volatile("ld.acquire.gpu.global.u32 %0, [%1];" : "=r"(v) : "l"(p) : "memory");
        if ((int)(v - target) >= 0 || ++n >= (1u << 17)) break;
        __nanosleep(100);
    }
}
__device__ __forceinline__ void flag_add(unsigned* p) {
    asm volatile("fence.acq_rel.gpu;\nred.relaxed.gpu.global.add.u32 [%0], 1;" :: "l"(p) : "memory");
}
__device__ __forceinline__ uint64_t make_desc(uint32_t addr, uint32_t lbo, uint32_t sbo, uint32_t swz) {
    return (uint64_t)((addr & 0x3FFFF) >> 4) | ((uint64_t)((lbo & 0x3FFFF) >> 4) << 16) | ((uint64_t)((sbo & 0x3FFFF) >> 4) << 32) | ((uint64_t)swz << 62);
}
__device__ __forceinline__ uint64_t desc_add(uint64_t d, uint32_t off16) {
    return (d & 0xFFFFFFFF00000000ull) | (uint64_t)((uint32_t)d + off16);
}
__device__ __forceinline__ void tma2d(uint32_t dst, const CUtensorMap* tm, int c0, int c1, uint32_t bar) {
    asm volatile("cp.async.bulk.tensor.2d.shared::cluster.global.mbarrier::complete_tx::bytes [%0], [%1, {%3, %4}], [%2];"
        :: "r"(dst), "l"((uint64_t)tm), "r"(bar), "r"(c0), "r"(c1) : "memory");
}
__device__ __forceinline__ void tma3d_mc(uint32_t dst, const CUtensorMap* tm, int c0, int c1, int c2, uint32_t bar) {
    asm volatile("cp.async.bulk.tensor.3d.shared::cluster.global.mbarrier::complete_tx::bytes.multicast::cluster [%0], [%1, {%3, %4, %5}], [%2], %6;"
        :: "r"(dst), "l"((uint64_t)tm), "r"(bar), "r"(c0), "r"(c1), "r"(c2), "h"((uint16_t)3) : "memory");
}
__device__ __forceinline__ void bulk_g2s(uint32_t dst, const void* src, uint32_t bytes, uint32_t bar) {
    asm volatile("cp.async.bulk.shared::cluster.global.mbarrier::complete_tx::bytes [%0], [%1], %2, [%3];"
        :: "r"(dst), "l"(src), "r"(bytes), "r"(bar) : "memory");
}
__device__ __forceinline__ void bulk_s2g(void* dst, uint32_t src, uint32_t bytes) {
    asm volatile("cp.async.bulk.global.shared::cta.bulk_group [%0], [%1], %2;" :: "l"(dst), "r"(src), "r"(bytes) : "memory");
}
__device__ __forceinline__ void tma2d_store(const CUtensorMap* tm, int c0, int c1, uint32_t src) {
    asm volatile("cp.async.bulk.tensor.2d.global.shared::cta.bulk_group [%0, {%2, %3}], [%1];"
        :: "l"((uint64_t)tm), "r"(src), "r"(c0), "r"(c1) : "memory");
}
__device__ __forceinline__ void l2_prefetch(const void* p, uint32_t bytes) {
    asm volatile("cp.async.bulk.prefetch.L2.global [%0], %1;" :: "l"(p), "r"(bytes) : "memory");
}
__device__ __forceinline__ void tmap_prefetch(const CUtensorMap* tm) { asm volatile("prefetch.tensormap [%0];" :: "l"((uint64_t)tm) : "memory"); }
__device__ __forceinline__ uint32_t lds32(uint32_t a) { uint32_t v; asm volatile("ld.shared.u32 %0, [%1];" : "=r"(v) : "r"(a)); return v; }
__device__ __forceinline__ uint2 lds64(uint32_t a) { uint2 v; asm volatile("ld.shared.v2.u32 {%0,%1}, [%2];" : "=r"(v.x), "=r"(v.y) : "r"(a)); return v; }
__device__ __forceinline__ uint4 lds128(uint32_t a) { uint4 v; asm volatile("ld.shared.v4.u32 {%0,%1,%2,%3}, [%4];" : "=r"(v.x), "=r"(v.y), "=r"(v.z), "=r"(v.w) : "r"(a)); return v; }
__device__ __forceinline__ void sts32(uint32_t a, uint32_t v) { asm volatile("st.shared.u32 [%0], %1;" :: "r"(a), "r"(v) : "memory"); }
__device__ __forceinline__ void sts128(uint32_t a, uint4 v) { asm volatile("st.shared.v4.u32 [%0], {%1,%2,%3,%4};" :: "r"(a), "r"(v.x), "r"(v.y), "r"(v.z), "r"(v.w) : "memory"); }
__device__ __forceinline__ uint4 ldg_cg128(const void* p) { uint4 v; asm volatile("ld.global.cg.v4.u32 {%0,%1,%2,%3}, [%4];" : "=r"(v.x), "=r"(v.y), "=r"(v.z), "=r"(v.w) : "l"(p)); return v; }
__device__ __forceinline__ uint4 ldg_nc128(const void* p) { uint4 v; asm volatile("ld.global.nc.L1::no_allocate.v4.u32 {%0,%1,%2,%3}, [%4];" : "=r"(v.x), "=r"(v.y), "=r"(v.z), "=r"(v.w) : "l"(p)); return v; }
__device__ __forceinline__ uint2 ldg_nc64(const void* p) { uint2 v; asm volatile("ld.global.nc.L1::no_allocate.v2.u32 {%0,%1}, [%2];" : "=r"(v.x), "=r"(v.y) : "l"(p)); return v; }
#define WG_FENCE() asm volatile("wgmma.fence.sync.aligned;\n" ::: "memory")
#define WG_COMMIT() asm volatile("wgmma.commit_group.sync.aligned;\n" ::: "memory")
template<int N> __device__ __forceinline__ void wg_wait() { asm volatile("wgmma.wait_group.sync.aligned %0;\n" :: "n"(N) : "memory"); }
__device__ __forceinline__ void named_bar(int id, int n) { asm volatile("bar.sync %0, %1;" :: "r"(id), "r"(n) : "memory"); }

__device__ __forceinline__ float bf_lo(uint32_t u) { return __uint_as_float(u << 16); }
__device__ __forceinline__ float bf_hi(uint32_t u) { return __uint_as_float(u & 0xFFFF0000u); }
__device__ __forceinline__ uint32_t pack_bf(float lo, float hi) { uint32_t r; asm("cvt.rn.bf16x2.f32 %0, %1, %2;" : "=r"(r) : "f"(hi), "f"(lo)); return r; }
__device__ __forceinline__ float bf_round(float x) { return __bfloat162float(__float2bfloat16_rn(x)); }
__device__ __forceinline__ uint32_t bmul2(uint32_t a, uint32_t b) { uint32_t r; asm("mul.rn.bf16x2 %0, %1, %2;" : "=r"(r) : "r"(a), "r"(b)); return r; }
__device__ __forceinline__ uint32_t badd2(uint32_t a, uint32_t b) { uint32_t r; asm("add.rn.bf16x2 %0, %1, %2;" : "=r"(r) : "r"(a), "r"(b)); return r; }
__device__ __forceinline__ uint32_t bsub2(uint32_t a, uint32_t b) { uint32_t r; asm("sub.rn.bf16x2 %0, %1, %2;" : "=r"(r) : "r"(a), "r"(b)); return r; }
__device__ __forceinline__ void mma16816(float (&d)[4], uint32_t a0, uint32_t a1, uint32_t a2, uint32_t a3, uint2 b) {
    asm volatile("mma.sync.aligned.m16n8k16.row.col.f32.bf16.bf16.f32 {%0,%1,%2,%3}, {%4,%5,%6,%7}, {%8,%9}, {%0,%1,%2,%3};\n"
        : "+f"(d[0]), "+f"(d[1]), "+f"(d[2]), "+f"(d[3]) : "r"(a0), "r"(a1), "r"(a2), "r"(a3), "r"(b.x), "r"(b.y));
}

__device__ __forceinline__ int blk_f0(int bi, int j) {
    if (bi < 32) return 224 * ((j + (bi >> 2)) & 7) + 32 * (bi & 3);
    int b2 = bi - 32; int q3 = (b2 * 11) >> 5;
    return 224 * ((j + q3) & 7) + 128 + 32 * (b2 - 3 * q3);
}
__device__ __forceinline__ int next_st2(int s) { return (0x14023 >> (4 * s)) & 7; }
__device__ __forceinline__ uint32_t stage_off_rt(int s) { return s < 3 ? SM_RING + s * STAGE_BYTES : (uint32_t)(s - 2) * STAGE_BYTES; }

template<int NB>
__device__ __forceinline__ void gemm1_pass(uint32_t sb, int wgi, int warp4, int lane, int& st, uint32_t& fph, uint32_t e_cl,
                                           int rb64, int ks0) {
    constexpr bool passA = (NB == 4);
    float acc[NB * 32];
    const uint64_t descA0 = make_desc(sb + SM_X + wgi * 8192, 16, 1024, 1);
    const uint64_t descB0 = make_desc(sb + SM_RING, 4096, 512, 2);
    int prev = 0;
    #pragma unroll 1
    for (int sl = 0; sl < 8; sl++) {
        if (warp4 == 0 && wgi == 0) PROF2(2, sl + (passA ? 0 : 8));
        mbar_wait(sb + SM_BARS + (B_FULL + st) * 8, (fph >> st) & 1);
        fph ^= 1u << st;
        if (sl == 0 && warp4 == 0) PROF(2 + wgi * 8 + (passA ? 0 : 3));
        if (warp4 == 0 && wgi == 0) PROF2(1, sl + (passA ? 0 : 8));
        const uint64_t da = desc_add(descA0, sl * 1024), db = desc_add(descB0, st * 2048);
        WG_FENCE();
        #pragma unroll
        for (int kk = 0; kk < 4; kk++) {
            int sc = (sl | kk) ? 1 : 0;
            if constexpr (NB == 4) wgmma_ss_n256_tb(acc, da + kk * 2, db + kk * 64, sc); else wgmma_ss_n192_tb(acc, da + kk * 2, db + kk * 64, sc);
        }
        WG_COMMIT();
        wg_wait<1>();
        if (warp4 == 0 && wgi == 0) PROF2(3, sl + (passA ? 0 : 8));
        if (lane < 2 && sl) mbar_arrive_cluster(e_cl + prev * 8, 1);
        if (!passA) {
            if (sl == 2 && lane == 0) mbar_arrive(sb + SM_BARS + B_XFREE * 8);
            if ((sl == 4 || sl == 6) && lane < 2) mbar_arrive_cluster(e_cl + (1 + (sl >> 1)) * 8, 1);
        }
        prev = st;
        st = (st == 2) ? 0 : st + 1;
    }
    wg_wait<0>();
    if (lane < 2) mbar_arrive_cluster(e_cl + prev * 8, 1);
    if (!passA && lane == 0) mbar_arrive(sb + SM_BARS + B_G1DONE * 8);
    if (warp4 == 0) PROF(3 + wgi * 8 + (passA ? 0 : 3));
    const int g = lane >> 2;
    const int r0 = wgi * 64 + warp4 * 16 + g;
    const float s0 = __uint_as_float(lds32(sb + SM_STATS + r0 * 4)), s1 = __uint_as_float(lds32(sb + SM_STATS + (r0 + 8) * 4));
    uint4* dst = g_hfrag + ((size_t)(rb64 * 112 + ks0) * 4 + warp4) * 32 + lane;
    #pragma unroll
    for (int kk = 0; kk < NB * 2; kk++) {
        uint32_t h[4];
        #pragma unroll
        for (int tt = 0; tt < 2; tt++) {
            const int t = 2 * kk + tt;
            const float* ag = &acc[4 * t];
            const float* au = &acc[NB * 16 + 4 * t];
            h[2 * tt] = bmul2(pack_bf(ag[0] * s0, ag[1] * s0), pack_bf(au[0] * s0, au[1] * s0));
            h[2 * tt + 1] = bmul2(pack_bf(ag[2] * s1, ag[3] * s1), pack_bf(au[2] * s1, au[3] * s1));
        }
        dst[kk * 128] = make_uint4(h[0], h[1], h[2], h[3]);
    }
    __syncwarp();
    if (lane == 0) mbar_arrive(sb + SM_BARS + (B_HD + wgi * 2 + (passA ? 0 : 1)) * 8);
    if (warp4 == 0) PROF(4 + wgi * 8 + (passA ? 0 : 3));
}

__global__ void __cluster_dims__(2, 1, 1) __launch_bounds__(NTHREADS, 1)
fused_kernel(const __grid_constant__ Params p) {
    extern __shared__ __align__(1024) uint8_t smem_raw[];
    const uint32_t sb = smem_u32(smem_raw);
    const int tid = threadIdx.x, warp = tid >> 5, lane = tid & 31;
    const int b = blockIdx.x;
    const int rank = b & 1;
    const int j = (b >> 1) & 7;
    const int i = ((b >> 4) << 1) | rank;
    const int cb = j >> 1;
    const int rbG2 = 2 * i + (j & 1);

    if (tid == 256) {
        mbar_init(sb + SM_BARS + B_XFULL * 8, 1);
        asm volatile("fence.proxy.async.shared::cta;" ::: "memory");
        mbar_expect_tx(sb + SM_BARS + B_XFULL * 8, 131072);
        for (int sl = 0; sl < 8; sl++)
            tma2d(sb + SM_X + sl * 16384, &p.tm_x, 64 * ((sl + 2 * cb + 2) & 7), 128 * i, sb + SM_BARS + B_XFULL * 8);
    }
    if (tid == 288) {
        tmap_prefetch(rank ? &p.tm_uA : &p.tm_gA);
        for (int s = 0; s < 5; s++) { mbar_init(sb + SM_BARS + (B_FULL + s) * 8, 1); mbar_init(sb + SM_BARS + (B_EMPTY + s) * 8, 16); }
        for (int s = 0; s < 4; s++) mbar_init(sb + SM_BARS + (B_CONV + s) * 8, 1);
        mbar_init(sb + SM_BARS + B_YT * 8, 1);
        mbar_init(sb + SM_BARS + B_XR * 8, 1);
        mbar_init(sb + SM_BARS + B_G1DONE * 8, 8);
        mbar_init(sb + SM_BARS + B_XFREE * 8, 8);
        mbar_init(sb + SM_BARS + B_CVDONE * 8, 1);
        mbar_init(sb + SM_BARS + B_CVGO * 8, 4);
        mbar_init(sb + SM_BARS + B_YST * 8, 4);
        for (int s = 0; s < 4; s++) mbar_init(sb + SM_BARS + (B_HD + s) * 8, 4);
        for (int s = 0; s < 2; s++) mbar_init(sb + SM_BARS + (B_HRDY + s) * 8, 1);
        asm volatile("fence.mbarrier_init.release.cluster;" ::: "memory");
        asm volatile("fence.proxy.async.shared::cta;" ::: "memory");
    }
    __syncwarp();
    asm volatile("barrier.cluster.arrive.relaxed.aligned;\nbarrier.cluster.wait.aligned;\n" ::: "memory");
    PROFW(1, 0);

    if (warp < 8) {
        asm volatile("setmaxnreg.inc.sync.aligned.u32 200;");
        const int wgi = warp >> 2, warp4 = warp & 3;
        const int g = lane >> 2, c = lane & 3;
        const uint32_t e_cl = mapa(sb + SM_BARS + B_EMPTY * 8, lane & 1);
        {
            const uint32_t xa = sb + SM_X + (lane >> 3) * 16384 + warp * 16 * 128;
            uint4 xr[16][2];
            float v[32];
            mbar_wait(sb + SM_BARS + B_XFULL * 8, 0);
            PROFW(16, 0);
            #pragma unroll
            for (int r = 0; r < 16; r++) {
                const uint32_t a = xa + r * 128 + (((lane & 7) ^ (r & 7)) << 4);
                xr[r][0] = lds128(a); xr[r][1] = lds128(a + 65536);
            }
            #pragma unroll
            for (int r = 0; r < 16; r++) {
                const uint32_t* u = (const uint32_t*)&xr[r][0];
                float s = 0.f, q = 0.f;
                #pragma unroll
                for (int e = 0; e < 8; e++) { const float lo = bf_lo(u[e]), hi = bf_hi(u[e]); s += lo; q = fmaf(lo, lo, q); s += hi; q = fmaf(hi, hi, q); }
                v[r] = s; v[16 + r] = q;
            }
            #pragma unroll
            for (int hs = 16; hs >= 1; hs >>= 1) {
                const int up = lane & hs;
                #pragma unroll
                for (int e = 0; e < hs; e++) {
                    float keep, send;
                    asm("{\n.reg .pred p;\nsetp.ne.b32 p, %4, 0;\nselp.f32 %0, %3, %2, p;\nselp.f32 %1, %2, %3, p;\n}"
                        : "=f"(keep), "=f"(send) : "f"(v[e]), "f"(v[e + hs]), "r"(up));
                    v[e] = keep + __shfl_xor_sync(0xffffffffu, send, hs);
                }
            }
            const float other = __shfl_xor_sync(0xffffffffu, v[0], 16);
            const float mean = (lane < 16 ? v[0] : other) * (1.0f / DM);
            const float msq = (lane < 16 ? other : v[0]) * (1.0f / DM);
            const float var_b = bf_round(fmaxf(msq - mean * mean, 0.f));
            const float sd = bf_round(sqrtf(bf_round(var_b + 1e-5f)));
            if (lane < 16) sts32(sb + SM_STATS + (warp * 16 + lane) * 4, __float_as_uint(1.0f / sd));
            const uint32_t mb = pack_bf(mean, mean);
            #pragma unroll
            for (int r = 0; r < 16; r++) {
                const uint32_t m = __shfl_sync(0xffffffffu, mb, r);
                const uint32_t a = xa + r * 128 + (((lane & 7) ^ (r & 7)) << 4);
                #pragma unroll
                for (int hh = 0; hh < 2; hh++) {
                    uint4 t = xr[r][hh];
                    t.x = bsub2(t.x, m); t.y = bsub2(t.y, m); t.z = bsub2(t.z, m); t.w = bsub2(t.w, m);
                    sts128(a + hh * 65536, t);
                }
            }
            asm volatile("fence.proxy.async.shared::cta;" ::: "memory");
            named_bar(1 + wgi, 128);
            PROFW(17, 0);
        }
        int st = 0; uint32_t fph = 0;
        const int rb64 = 2 * i + wgi;
        gemm1_pass<4>(sb, wgi, warp4, lane, st, fph, e_cl, rb64, 14 * j);
        gemm1_pass<3>(sb, wgi, warp4, lane, st, fph, e_cl, rb64, 14 * j + 8);

        if (wgi == 1) {
            const int gch = 4 * b + warp4;
            const uint32_t xb = sb + SM_CVX + warp4 * 4096;
            const uint32_t hb = sb + SM_CVH + warp4 * 4096;
            const uint32_t dw = ((const unsigned short*)p.ssm_D)[gch];
            const uint32_t d2 = dw | (dw << 16);
            mbar_wait(sb + SM_BARS + (B_CONV + warp4) * 8, 0);
            PROFW(32, 4);
            float acc[16][4];
            #pragma unroll
            for (int jj = 0; jj < 16; jj++) { acc[jj][0] = 0.f; acc[jj][1] = 0.f; acc[jj][2] = 0.f; acc[jj][3] = 0.f; }
            uint2 bf[16];
            uint32_t xl = xb + g * 32 + c * 8;
            uint32_t hl = hb + (g + 2 * c - 8) * 4;
            #pragma unroll
            for (int d = 0; d < 16; d++) bf[d] = lds64(xl + d * 256);
            uint32_t w0 = 0, w1 = 0, w2 = 0;
            if (g + 2 * c >= 8) w0 = lds32(hl);
            if (g + 2 * c >= 7) w1 = lds32(hl + 4);
            if (g + 2 * c >= 6) w2 = lds32(hl + 8);
            #pragma unroll 1
            for (int m0 = 0; m0 < 8; m0++) {
                xl -= 32;
                #pragma unroll
                for (int ii = 0; ii < 16; ii++) {
                    const uint32_t a0 = w1, a1 = __byte_perm(w0, w1, 0x5432), a2 = w2, a3 = __byte_perm(w1, w2, 0x5432);
                    const uint32_t nx = (ii < 15) ? hl + (ii + 1) * 256 : hl + 32;
                    w0 = lds32(nx); w1 = lds32(nx + 4); w2 = lds32(nx + 8);
                    #pragma unroll
                    for (int jj = 15; jj >= ii; jj--) mma16816(acc[jj], a0, a1, a2, a3, bf[jj - ii]);
                    if (ii < 15) bf[15 - ii] = lds64(xl + (15 - ii) * 256);
                    else { bf[0] = make_uint2(0, 0); if (g > m0) bf[0] = lds64(xl); }
                }
                hl += 32;
                if (m0 == CVGO_M0 && lane == 0) mbar_arrive(sb + SM_BARS + B_CVGO * 8);
            }
            PROFW(33, 4);
            const uint32_t kvl = xb + c * 64 + (7 - g) * 4;
            const uint32_t yl = hb + c * 64 + g * 4;
            __syncwarp();
            #pragma unroll
            for (int jj = 0; jj < 16; jj++) {
                uint32_t k0 = lds32(kvl + jj * 256), k1 = lds32(kvl + jj * 256 + 32);
                k0 = __byte_perm(k0, k0, 0x1032); k1 = __byte_perm(k1, k1, 0x1032);
                sts32(yl + jj * 256, badd2(pack_bf(acc[jj][2], acc[jj][0]), bmul2(k0, d2)));
                sts32(yl + jj * 256 + 32, badd2(pack_bf(acc[jj][3], acc[jj][1]), bmul2(k1, d2)));
            }
            asm volatile("fence.proxy.async.shared::cta;" ::: "memory");
            __syncwarp();
            PROFW(44, 4);
            if (lane == 0) mbar_arrive(sb + SM_BARS + B_YST * 8);
            PROFW(45, 4);
        }
        {
            float acc[64];
            uint4 af[3][8];
            const uint4* hsrc = g_hfrag + ((size_t)rbG2 * 112 * 4 + warp4) * 32 + lane;
            const uint64_t descB0 = make_desc(sb, 4096, 1024, 1);
            int prev = 0;
            st = 3 + wgi;
            auto load_group = [&](uint4 (&dstf)[8], int u) {
                #pragma unroll
                for (int hb = 0; hb < 4; hb++) {
                    const int ks = blk_f0(4 * u + hb, j) >> 4;
                    dstf[2 * hb] = ldg_cg128(hsrc + ks * 128);
                    dstf[2 * hb + 1] = ldg_cg128(hsrc + ks * 128 + 128);
                }
            };
            auto g2_step = [&](int o, uint4 (&cur)[8], uint4 (&nxt)[8], bool do_load) {
                const int u = 2 * o + wgi;
                if (warp == 0) PROF2(2, 16 + u);
                mbar_wait(sb + SM_BARS + (B_FULL + st) * 8, ((6u >> st) ^ (uint32_t)((u * 13) >> 6)) & 1);
                if (warp == 0) PROF2(1, 16 + u);
                const uint64_t db = desc_add(descB0, stage_off_rt(st) >> 4);
                WG_FENCE();
                #pragma unroll
                for (int kk = 0; kk < 8; kk++)
                    wgmma_rs_n128_tb(acc, cur[kk].x, cur[kk].y, cur[kk].z, cur[kk].w, db + ((kk >> 1) * 512 + (kk & 1) * 128), (o | kk) ? 1 : 0);
                WG_COMMIT();
                wg_wait<1>();
                if (warp == 0) PROF2(3, 16 + u);
                if (lane < 2 && o > 0 && u - 2 + 5 < 14) mbar_arrive_cluster(e_cl + prev * 8, 2);
                prev = st;
                st = next_st2(next_st2(st));
                if (o == 2) mbar_wait(sb + SM_BARS + (B_HRDY + 1) * 8, 0);
                if (do_load) load_group(nxt, u + 4);
            };
            mbar_wait(sb + SM_BARS + B_HRDY * 8, 0);
            load_group(af[0], wgi); load_group(af[1], 2 + wgi);
            if (wgi == 0) mbar_wait(sb + SM_BARS + B_CVGO * 8, 0);
            PROFW(20, 0);
            g2_step(0, af[0], af[2], true);
            g2_step(1, af[1], af[0], true);
            g2_step(2, af[2], af[1], true);
            PROFW(22, 0);
            g2_step(3, af[0], af[2], true);
            g2_step(4, af[1], af[0], true);
            g2_step(5, af[2], af[1], false);
            PROFW(24, 0);
            g2_step(6, af[0], af[2], false);
            wg_wait<0>();
            PROFW(27, 0);
            named_bar(3, 256);
            {
                const uint32_t ex = sb + SM_RING + (tid & 127) * 16;
                #pragma unroll
                for (int q = 0; q < 8; q++) {
                    const float e0 = wgi ? acc[4 * q] : acc[32 + 4 * q], e1 = wgi ? acc[4 * q + 1] : acc[33 + 4 * q];
                    const float e2 = wgi ? acc[4 * q + 2] : acc[34 + 4 * q], e3 = wgi ? acc[4 * q + 3] : acc[35 + 4 * q];
                    sts128(ex + wgi * 16384 + q * 2048, make_uint4(__float_as_uint(e0), __float_as_uint(e1), __float_as_uint(e2), __float_as_uint(e3)));
                }
                named_bar(3, 256);
                #pragma unroll
                for (int q = 0; q < 8; q++) {
                    const uint4 t = lds128(ex + (wgi ^ 1) * 16384 + q * 2048);
                    acc[4 * q] = (wgi ? acc[32 + 4 * q] : acc[4 * q]) + __uint_as_float(t.x);
                    acc[4 * q + 1] = (wgi ? acc[33 + 4 * q] : acc[4 * q + 1]) + __uint_as_float(t.y);
                    acc[4 * q + 2] = (wgi ? acc[34 + 4 * q] : acc[4 * q + 2]) + __uint_as_float(t.z);
                    acc[4 * q + 3] = (wgi ? acc[35 + 4 * q] : acc[4 * q + 3]) + __uint_as_float(t.w);
                }
            }
            mbar_wait(sb + SM_BARS + B_XR * 8, 0);
            mbar_wait(sb + SM_BARS + B_YT * 8, 0);
            PROFW(28, 0);
            const int r0 = (j & 1) * 64 + warp4 * 16 + g;
            const float s0 = __uint_as_float(lds32(sb + SM_STATS + r0 * 4)), s1 = __uint_as_float(lds32(sb + SM_STATS + (r0 + 8) * 4));
            const uint32_t drow0 = sb + SM_XE + wgi * 16384 + r0 * 128 + c * 4;
            const uint32_t xrow0 = sb + SM_XE + wgi * 16384 + (r0 ^ 64) * 128 + c * 4;
            const int mi = lane >> 3, lr = lane & 7;
            const uint32_t yaddr = sb + SM_YT + wgi * 8192 + ((mi >> 1) * 8 + lr) * 128 + (((2 * warp4 + (mi & 1)) ^ lr) << 4);
            uint32_t y[4][4], xv[8][2], dv[8][2];
            #pragma unroll
            for (int t2 = 0; t2 < 4; t2++)
                asm volatile("ldmatrix.sync.aligned.m8n8.x4.trans.shared.b16 {%0,%1,%2,%3}, [%4];"
                    : "=r"(y[t2][0]), "=r"(y[t2][1]), "=r"(y[t2][2]), "=r"(y[t2][3]) : "r"(yaddr + t2 * 2048) : "memory");
            #pragma unroll
            for (int t = 0; t < 8; t++) {
                const uint32_t off = (t ^ g) << 4;
                xv[t][0] = lds32(xrow0 + off); xv[t][1] = lds32(xrow0 + 1024 + off);
                dv[t][0] = lds32(drow0 + off); dv[t][1] = lds32(drow0 + 1024 + off);
            }
            #pragma unroll
            for (int t = 0; t < 8; t++) {
                const uint32_t off = (t ^ g) << 4;
                const uint32_t n0 = pack_bf(bf_lo(dv[t][0]) * s0, bf_hi(dv[t][0]) * s0), n1 = pack_bf(bf_lo(dv[t][1]) * s1, bf_hi(dv[t][1]) * s1);
                const uint32_t o0 = badd2(badd2(xv[t][0], bmul2(n0, y[t >> 1][2 * (t & 1)])), pack_bf(acc[4 * t], acc[4 * t + 1]));
                const uint32_t o1 = badd2(badd2(xv[t][1], bmul2(n1, y[t >> 1][2 * (t & 1) + 1])), pack_bf(acc[4 * t + 2], acc[4 * t + 3]));
                sts32(xrow0 + off, o0); sts32(xrow0 + 1024 + off, o1);
            }
            asm volatile("fence.proxy.async.shared::cta;" ::: "memory");
            named_bar(1 + wgi, 128);
            if ((tid & 127) == 0) {
                tma2d_store(&p.tm_out, 128 * cb + 64 * wgi, 64 * rbG2, sb + SM_XE + wgi * 16384 + ((j & 1) ^ 1) * 8192);
                asm volatile("cp.async.bulk.commit_group;" ::: "memory");
                asm volatile("cp.async.bulk.wait_group.read 0;" ::: "memory");
                PROFW(29, 0);
            }
        }
    } else {
        asm volatile("setmaxnreg.dec.sync.aligned.u32 104;");
        if (warp == 8) {
            if (lane == 0) {
                int st = 0; uint32_t eph = 7;
                #pragma unroll 1
                for (int it = 0; it < 16; it++) {
                    const int pass = it >> 3, sl = it & 7;
                    const int nb = pass ? 3 : 4;
                    const CUtensorMap* tm = pass ? (rank ? &p.tm_uB : &p.tm_gB) : (rank ? &p.tm_uA : &p.tm_gA);
                    mbar_wait(sb + SM_BARS + (B_EMPTY + st) * 8, (eph >> st) & 1);
                    eph ^= 1u << st;
                    PROF2(0, it);
                    mbar_expect_tx(sb + SM_BARS + (B_FULL + st) * 8, nb * 8192);
                    tma3d_mc(sb + SM_RING + st * STAGE_BYTES + rank * nb * 4096, tm, 0, ((sl + 2 * cb + 2) & 7) * 64, 7 * j + 4 * pass, sb + SM_BARS + (B_FULL + st) * 8);
                    st = (st == 2) ? 0 : st + 1;
                }
                st = 3;
                #pragma unroll 1
                for (int u = 0; u < 14; u++) {
                    mbar_wait(sb + SM_BARS + (B_EMPTY + st) * 8, (eph >> st) & 1);
                    eph ^= 1u << st;
                    PROF2(0, 16 + u);
                    const uint32_t so = sb + stage_off_rt(st) + rank * 8192;
                    mbar_expect_tx(sb + SM_BARS + (B_FULL + st) * 8, 32768);
                    tma3d_mc(so, &p.tm_w2, 0, blk_f0(4 * u + rank, j), 2 * cb, sb + SM_BARS + (B_FULL + st) * 8);
                    tma3d_mc(so + 16384, &p.tm_w2, 0, blk_f0(4 * u + 2 + rank, j), 2 * cb, sb + SM_BARS + (B_FULL + st) * 8);
                    st = next_st2(st);
                }
                PROF(48);
                const unsigned ep = lds32(sb + SM_EPOCH);
                mbar_wait(sb + SM_BARS + B_CVDONE * 8, 0);
                flag_wait(&g_cnt_y[cb * 32], ep * 32);
                PROF(49);
                asm volatile("fence.proxy.async.global;" ::: "memory");
                mbar_expect_tx(sb + SM_BARS + B_YT * 8, 16384);
                tma2d(sb + SM_YT, &p.tm_yT, 64 * rbG2, 128 * cb, sb + SM_BARS + B_YT * 8);
            }
        } else if (warp < 11) {
            mbar_wait(sb + SM_BARS + B_XFULL * 8, 0);
            #pragma unroll 1
            for (int rnd = 0; rnd < 2; rnd++) {
                const int tt = (tid - 288) + 64 * rnd;
                uint32_t sk[4][2];
                uint4 skw[2];
                skw[0] = ldg_nc128(p.shift_k + 16 * tt); skw[1] = ldg_nc128(p.shift_k + 16 * tt + 8);
                const __nv_bfloat16* kp = p.k + (size_t)(16 * b) * DM + 4 * tt;
                const __nv_bfloat16* vp = p.v + (size_t)(16 * b) * DM + 4 * tt;
                uint2 kr[19];
                uint2 kv[16];
                #pragma unroll
                for (int r = 0; r < 3; r++) kr[r] = (b > 0) ? ldg_nc64(kp + (r - 3) * DM) : make_uint2(0, 0);
                #pragma unroll
                for (int r = 0; r < 16; r++) { kr[3 + r] = ldg_nc64(kp + r * DM); kv[r] = ldg_nc64(vp + r * DM); }
                {
                    const uint4 w0 = skw[0], w1 = skw[1];
                    sk[0][0] = __byte_perm(w0.x, w0.z, 0x5410); sk[1][0] = __byte_perm(w0.x, w0.z, 0x7632);
                    sk[2][0] = __byte_perm(w0.y, w0.w, 0x5410); sk[3][0] = __byte_perm(w0.y, w0.w, 0x7632);
                    sk[0][1] = __byte_perm(w1.x, w1.z, 0x5410); sk[1][1] = __byte_perm(w1.x, w1.z, 0x7632);
                    sk[2][1] = __byte_perm(w1.y, w1.w, 0x5410); sk[3][1] = __byte_perm(w1.y, w1.w, 0x7632);
                }
                #pragma unroll
                for (int s = 0; s < 16; s++) {
                    uint32_t a = bmul2(kr[s].x, sk[3][0]);
                    a = badd2(a, bmul2(kr[s + 1].x, sk[2][0]));
                    a = badd2(a, bmul2(kr[s + 2].x, sk[1][0]));
                    a = badd2(a, bmul2(kr[s + 3].x, sk[0][0]));
                    kv[s].x = bmul2(a, kv[s].x);
                    a = bmul2(kr[s].y, sk[3][1]);
                    a = badd2(a, bmul2(kr[s + 1].y, sk[2][1]));
                    a = badd2(a, bmul2(kr[s + 2].y, sk[1][1]));
                    a = badd2(a, bmul2(kr[s + 3].y, sk[0][1]));
                    kv[s].y = bmul2(a, kv[s].y);
                }
                PROFW(57 + 2 * rnd, 9);
                #pragma unroll
                for (int cc = 0; cc < 4; cc++) {
                    const uint32_t sel = (cc & 1) ? 0x7632 : 0x5410;
                    #define KVW(r) ((cc & 2) ? kv[r].y : kv[r].x)
                    uint4* dst = (uint4*)(g_kvT + (size_t)(4 * tt + cc) * SEQ + 16 * b);
                    dst[0] = make_uint4(__byte_perm(KVW(15), KVW(14), sel), __byte_perm(KVW(13), KVW(12), sel),
                                        __byte_perm(KVW(11), KVW(10), sel), __byte_perm(KVW(9), KVW(8), sel));
                    dst[1] = make_uint4(__byte_perm(KVW(7), KVW(6), sel), __byte_perm(KVW(5), KVW(4), sel),
                                        __byte_perm(KVW(3), KVW(2), sel), __byte_perm(KVW(1), KVW(0), sel));
                    #undef KVW
                }
                PROFW(58 + 2 * rnd, 9);
            }
            asm volatile("fence.proxy.async.global;" ::: "memory");
            __syncwarp();
            if (lane == 0) {
                flag_add(&g_cnt_kv[0]);
                PROFW(50, 9);
                const int wgi = warp - 9;
                mbar_wait(sb + SM_BARS + (B_HD + wgi * 2) * 8, 0);
                flag_add(&g_flag_h[((2 * i + wgi) * 2 + 0) * 8]);
                mbar_wait(sb + SM_BARS + (B_HD + wgi * 2 + 1) * 8, 0);
                flag_add(&g_flag_h[((2 * i + wgi) * 2 + 1) * 8]);
                if (wgi == 1) {
                    mbar_wait(sb + SM_BARS + B_YST * 8, 0);
                    bulk_s2g(g_yT + (size_t)(4 * b) * SEQ, sb + SM_CVH, 16384);
                    asm volatile("cp.async.bulk.commit_group;" ::: "memory");
                    asm volatile("cp.async.bulk.wait_group 0;" ::: "memory");
                    mbar_arrive(sb + SM_BARS + B_CVDONE * 8);
                    asm volatile("fence.proxy.async.global;" ::: "memory");
                    flag_add(&g_cnt_y[(b >> 5) * 32]);
                    PROF(46);
                }
            }
        } else {
            if (lane == 0) {
                const unsigned ep = g_launch[b] + 1;
                g_launch[b] = ep;
                sts32(sb + SM_EPOCH, ep);
                tmap_prefetch(rank ? &p.tm_uB : &p.tm_gB);
                tmap_prefetch(&p.tm_w2); tmap_prefetch(&p.tm_yT); tmap_prefetch(&p.tm_out); tmap_prefetch(&p.tm_xe);
                mbar_wait(sb + SM_BARS + (B_FULL + 2) * 8, 0);
                l2_prefetch(p.ssm_k + (size_t)(4 * b) * SEQ, 4 * SEQ * 2);
                l2_prefetch(p.wd + (size_t)b * (FF * DM / NCTA), FF * DM / NCTA * 2);
                mbar_wait(sb + SM_BARS + (B_HD + 0) * 8, 0);
                flag_wait(&g_cnt_kv[0], ep * 256);
                asm volatile("fence.proxy.async.global;" ::: "memory");
                PROF(53);
                mbar_wait(sb + SM_BARS + B_XFREE * 8, 0);
                PROF(54);
                for (int ch = 0; ch < 4; ch++) {
                    const uint32_t bar = sb + SM_BARS + (B_CONV + ch) * 8;
                    mbar_expect_tx(bar, 8192);
                    bulk_g2s(sb + SM_CVX + ch * 4096, g_kvT + (size_t)(4 * b + ch) * SEQ, 4096, bar);
                    bulk_g2s(sb + SM_CVH + ch * 4096, p.ssm_k + (size_t)(4 * b + ch) * SEQ, 4096, bar);
                }
                flag_wait(&g_flag_h[(rbG2 * 2 + 0) * 8], ep * 8);
                mbar_arrive(sb + SM_BARS + B_HRDY * 8);
                mbar_wait(sb + SM_BARS + B_G1DONE * 8, 0);
                mbar_expect_tx(sb + SM_BARS + B_XR * 8, 16384);
                tma2d(sb + SM_XE + ((j & 1) ^ 1) * 8192, &p.tm_xe, 128 * cb, 64 * rbG2, sb + SM_BARS + B_XR * 8);
                tma2d(sb + SM_XE + 16384 + ((j & 1) ^ 1) * 8192, &p.tm_xe, 128 * cb + 64, 64 * rbG2, sb + SM_BARS + B_XR * 8);
                flag_wait(&g_flag_h[(rbG2 * 2 + 1) * 8], ep * 8);
                mbar_arrive(sb + SM_BARS + (B_HRDY + 1) * 8);
            }
        }
    }
}

typedef CUresult (*EncodeFn)(CUtensorMap*, CUtensorMapDataType, cuuint32_t, void*, const cuuint64_t*, const cuuint64_t*,
                             const cuuint32_t*, const cuuint32_t*, CUtensorMapInterleave, CUtensorMapSwizzle,
                             CUtensorMapL2promotion, CUtensorMapFloatOOBfill);

void encode(EncodeFn fn, CUtensorMap* tm, const void* base, int rank, const cuuint64_t* dims, const cuuint64_t* strides,
            const cuuint32_t* box, CUtensorMapSwizzle swz) {
    cuuint32_t es[5] = {1, 1, 1, 1, 1};
    fn(tm, CU_TENSOR_MAP_DATA_TYPE_BFLOAT16, rank, (void*)base, dims, strides, box, es, CU_TENSOR_MAP_INTERLEAVE_NONE, swz,
       CU_TENSOR_MAP_L2_PROMOTION_L2_128B, CU_TENSOR_MAP_FLOAT_OOB_FILL_NONE);
}

}

extern "C" void kernel_launch(void* const* d_in, const int* in_sizes, int n_in, void* d_out, int out_size) {
    (void)in_sizes; (void)n_in; (void)out_size;
    static EncodeFn enc = nullptr;
    static void* yT_ptr = nullptr;
    if (!enc) {
        void* fn = nullptr; cudaDriverEntryPointQueryResult qr;
        cudaGetDriverEntryPoint("cuTensorMapEncodeTiled", &fn, cudaEnableDefault, &qr);
        enc = (EncodeFn)fn;
        cudaGetSymbolAddress(&yT_ptr, g_yT);
        cudaFuncSetAttribute(fused_kernel, cudaFuncAttributeMaxDynamicSharedMemorySize, SM_TOTAL);
    }
    Params p;
    p.q = (const __nv_bfloat16*)d_in[0]; p.k = (const __nv_bfloat16*)d_in[1]; p.v = (const __nv_bfloat16*)d_in[2];
    p.shift_k = (const __nv_bfloat16*)d_in[3]; p.ssm_k = (const __nv_bfloat16*)d_in[4]; p.ssm_D = (const __nv_bfloat16*)d_in[5];
    p.wg = (const __nv_bfloat16*)d_in[7]; p.wu = (const __nv_bfloat16*)d_in[8]; p.wd = (const __nv_bfloat16*)d_in[9];
    {
        cuuint64_t dims[2] = {DM, SEQ}; cuuint64_t str[1] = {DM * 2};
        cuuint32_t box[2] = {64, 128};
        encode(enc, &p.tm_x, p.q, 2, dims, str, box, CU_TENSOR_MAP_SWIZZLE_128B);
        cuuint32_t box2[2] = {64, 64};
        encode(enc, &p.tm_out, d_out, 2, dims, str, box2, CU_TENSOR_MAP_SWIZZLE_128B);
        encode(enc, &p.tm_xe, p.q, 2, dims, str, box2, CU_TENSOR_MAP_SWIZZLE_128B);
    }
    {
        cuuint64_t dims[3] = {32, DM, FF / 32}; cuuint64_t str[2] = {FF * 2, 64};
        cuuint32_t boxA[3] = {32, 64, 4}, boxB[3] = {32, 64, 3};
        encode(enc, &p.tm_gA, p.wg, 3, dims, str, boxA, CU_TENSOR_MAP_SWIZZLE_64B);
        encode(enc, &p.tm_gB, p.wg, 3, dims, str, boxB, CU_TENSOR_MAP_SWIZZLE_64B);
        encode(enc, &p.tm_uA, p.wu, 3, dims, str, boxA, CU_TENSOR_MAP_SWIZZLE_64B);
        encode(enc, &p.tm_uB, p.wu, 3, dims, str, boxB, CU_TENSOR_MAP_SWIZZLE_64B);
    }
    {
        cuuint64_t dims[3] = {64, FF, DM / 64}; cuuint64_t str[2] = {DM * 2, 128};
        cuuint32_t box[3] = {64, 32, 2};
        encode(enc, &p.tm_w2, p.wd, 3, dims, str, box, CU_TENSOR_MAP_SWIZZLE_128B);
    }
    {
        cuuint64_t dims[2] = {SEQ, DM}; cuuint64_t str[1] = {SEQ * 2};
        cuuint32_t box[2] = {64, 128};
        encode(enc, &p.tm_yT, yT_ptr, 2, dims, str, box, CU_TENSOR_MAP_SWIZZLE_128B);
    }
    fused_kernel<<<NCTA, NTHREADS, SM_TOTAL>>>(p);
}
```

```cpp
#include <cuda_runtime.h>
#include <cuda_bf16.h>
#include <cuda.h>
#include <stdint.h>

namespace {

constexpr int SEQ = 2048, DM = 512, FF = 1792;
constexpr int NCTA = 128;
constexpr int NTHREADS = 384;
constexpr int STAGE_BYTES = 32768;
#define PACE0 1

constexpr uint32_t SM_X = 0;
constexpr uint32_t SM_RING = 131072;
constexpr uint32_t SM_MISC = SM_RING + 3 * STAGE_BYTES;
constexpr uint32_t SM_BARS = SM_MISC;
constexpr uint32_t SM_EPOCH = SM_MISC + 248;
constexpr uint32_t SM_CVCNT = SM_MISC + 252;
constexpr uint32_t SM_STATS = SM_MISC + 256;
constexpr uint32_t SM_TOTAL = SM_STATS + 512;
static_assert(SM_TOTAL <= 232448, "smem");
__host__ __device__ constexpr uint32_t stage_off(int s) { return s < 3 ? SM_RING + s * STAGE_BYTES : (uint32_t)(s - 2) * STAGE_BYTES; }
constexpr uint32_t SM_CVX = 0;
constexpr uint32_t SM_CVH = 16384;
constexpr uint32_t SM_YT = 0;
constexpr uint32_t SM_XE = 6 * 16384;

constexpr int B_FULL = 0, B_EMPTY = 5, B_XFULL = 10, B_CONV = 11, B_YT = 15, B_XR = 16, B_G1DONE = 17, B_HD = 18, B_HRDY = 22,
              B_XFREE = 24, B_CVDONE = 25, B_CVGO = 26, B_YST = 27, B_COUNT = 28;
static_assert(B_COUNT * 8 <= 248, "barrier space");

__device__ uint4 g_hfrag[32 * 112 * 4 * 32];
__device__ __align__(128) __nv_bfloat16 g_kvT[DM * SEQ];
__device__ __align__(128) __nv_bfloat16 g_yT[DM * SEQ];
__device__ unsigned g_launch[NCTA];
__device__ unsigned g_cnt_kv[32];
__device__ unsigned g_cnt_y[4 * 32];
__device__ unsigned g_flag_h[32 * 2 * 8];

#define PROF(idx)
#define PROF2(a, idx)
#define PROFW(idx, w)

struct Params {
    CUtensorMap tm_x, tm_gA, tm_gB, tm_uA, tm_uB, tm_w2, tm_yT, tm_out, tm_xe;
    const __nv_bfloat16 *q, *k, *v, *shift_k, *ssm_k, *ssm_D, *wg, *wu, *wd;
};

__device__ __forceinline__ void wgmma_rs_n32(float (&d)[16], uint32_t a0, uint32_t a1, uint32_t a2, uint32_t a3, uint64_t db, int sc) {
  asm volatile("{\n.reg .pred p;\nsetp.ne.b32 p, %21, 0;\n"
    "wgmma.mma_async.sync.aligned.m64n32k16.f32.bf16.bf16 {%0,%1,%2,%3,%4,%5,%6,%7,%8,%9,%10,%11,%12,%13,%14,%15}, {%16,%17,%18,%19}, %20, p, 1, 1, 0;\n}\n"
    : "+f"(d[0]),"+f"(d[1]),"+f"(d[2]),"+f"(d[3]),"+f"(d[4]),"+f"(d[5]),"+f"(d[6]),"+f"(d[7]),"+f"(d[8]),"+f"(d[9]),"+f"(d[10]),"+f"(d[11]),"+f"(d[12]),"+f"(d[13]),"+f"(d[14]),"+f"(d[15])
    : "r"(a0),"r"(a1),"r"(a2),"r"(a3),"l"(db),"r"(sc));
}
__device__ __forceinline__ void wgmma_rs_n128_tb(float (&d)[64], uint32_t a0, uint32_t a1, uint32_t a2, uint32_t a3, uint64_t db, int sc) {
  asm volatile("{\n.reg .pred p;\nsetp.ne.b32 p, %69, 0;\n"
    "wgmma.mma_async.sync.aligned.m64n128k16.f32.bf16.bf16 {%0,%1,%2,%3,%4,%5,%6,%7,%8,%9,%10,%11,%12,%13,%14,%15,%16,%17,%18,%19,%20,%21,%22,%23,%24,%25,%26,%27,%28,%29,%30,%31,%32,%33,%34,%35,%36,%37,%38,%39,%40,%41,%42,%43,%44,%45,%46,%47,%48,%49,%50,%51,%52,%53,%54,%55,%56,%57,%58,%59,%60,%61,%62,%63}, {%64,%65,%66,%67}, %68, p, 1, 1, 1;\n}\n"
    : "+f"(d[0]),"+f"(d[1]),"+f"(d[2]),"+f"(d[3]),"+f"(d[4]),"+f"(d[5]),"+f"(d[6]),"+f"(d[7]),"+f"(d[8]),"+f"(d[9]),"+f"(d[10]),"+f"(d[11]),"+f"(d[12]),"+f"(d[13]),"+f"(d[14]),"+f"(d[15]),"+f"(d[16]),"+f"(d[17]),"+f"(d[18]),"+f"(d[19]),"+f"(d[20]),"+f"(d[21]),"+f"(d[22]),"+f"(d[23]),"+f"(d[24]),"+f"(d[25]),"+f"(d[26]),"+f"(d[27]),"+f"(d[28]),"+f"(d[29]),"+f"(d[30]),"+f"(d[31]),"+f"(d[32]),"+f"(d[33]),"+f"(d[34]),"+f"(d[35]),"+f"(d[36]),"+f"(d[37]),"+f"(d[38]),"+f"(d[39]),"+f"(d[40]),"+f"(d[41]),"+f"(d[42]),"+f"(d[43]),"+f"(d[44]),"+f"(d[45]),"+f"(d[46]),"+f"(d[47]),"+f"(d[48]),"+f"(d[49]),"+f"(d[50]),"+f"(d[51]),"+f"(d[52]),"+f"(d[53]),"+f"(d[54]),"+f"(d[55]),"+f"(d[56]),"+f"(d[57]),"+f"(d[58]),"+f"(d[59]),"+f"(d[60]),"+f"(d[61]),"+f"(d[62]),"+f"(d[63])
    : "r"(a0),"r"(a1),"r"(a2),"r"(a3),"l"(db),"r"(sc));
}
__device__ __forceinline__ void wgmma_ss_n256_tb(float (&d)[128], uint64_t da, uint64_t db, int sc) {
  asm volatile("{\n.reg .pred p;\nsetp.ne.b32 p, %130, 0;\n"
    "wgmma.mma_async.sync.aligned.m64n256k16.f32.bf16.bf16 {%0,%1,%2,%3,%4,%5,%6,%7,%8,%9,%10,%11,%12,%13,%14,%15,%16,%17,%18,%19,%20,%21,%22,%23,%24,%25,%26,%27,%28,%29,%30,%31,%32,%33,%34,%35,%36,%37,%38,%39,%40,%41,%42,%43,%44,%45,%46,%47,%48,%49,%50,%51,%52,%53,%54,%55,%56,%57,%58,%59,%60,%61,%62,%63,%64,%65,%66,%67,%68,%69,%70,%71,%72,%73,%74,%75,%76,%77,%78,%79,%80,%81,%82,%83,%84,%85,%86,%87,%88,%89,%90,%91,%92,%93,%94,%95,%96,%97,%98,%99,%100,%101,%102,%103,%104,%105,%106,%107,%108,%109,%110,%111,%112,%113,%114,%115,%116,%117,%118,%119,%120,%121,%122,%123,%124,%125,%126,%127}, %128, %129, p, 1, 1, 0, 1;\n}\n"
    : "+f"(d[0]),"+f"(d[1]),"+f"(d[2]),"+f"(d[3]),"+f"(d[4]),"+f"(d[5]),"+f"(d[6]),"+f"(d[7]),"+f"(d[8]),"+f"(d[9]),"+f"(d[10]),"+f"(d[11]),"+f"(d[12]),"+f"(d[13]),"+f"(d[14]),"+f"(d[15]),"+f"(d[16]),"+f"(d[17]),"+f"(d[18]),"+f"(d[19]),"+f"(d[20]),"+f"(d[21]),"+f"(d[22]),"+f"(d[23]),"+f"(d[24]),"+f"(d[25]),"+f"(d[26]),"+f"(d[27]),"+f"(d[28]),"+f"(d[29]),"+f"(d[30]),"+f"(d[31]),"+f"(d[32]),"+f"(d[33]),"+f"(d[34]),"+f"(d[35]),"+f"(d[36]),"+f"(d[37]),"+f"(d[38]),"+f"(d[39]),"+f"(d[40]),"+f"(d[41]),"+f"(d[42]),"+f"(d[43]),"+f"(d[44]),"+f"(d[45]),"+f"(d[46]),"+f"(d[47]),"+f"(d[48]),"+f"(d[49]),"+f"(d[50]),"+f"(d[51]),"+f"(d[52]),"+f"(d[53]),"+f"(d[54]),"+f"(d[55]),"+f"(d[56]),"+f"(d[57]),"+f"(d[58]),"+f"(d[59]),"+f"(d[60]),"+f"(d[61]),"+f"(d[62]),"+f"(d[63]),"+f"(d[64]),"+f"(d[65]),"+f"(d[66]),"+f"(d[67]),"+f"(d[68]),"+f"(d[69]),"+f"(d[70]),"+f"(d[71]),"+f"(d[72]),"+f"(d[73]),"+f"(d[74]),"+f"(d[75]),"+f"(d[76]),"+f"(d[77]),"+f"(d[78]),"+f"(d[79]),"+f"(d[80]),"+f"(d[81]),"+f"(d[82]),"+f"(d[83]),"+f"(d[84]),"+f"(d[85]),"+f"(d[86]),"+f"(d[87]),"+f"(d[88]),"+f"(d[89]),"+f"(d[90]),"+f"(d[91]),"+f"(d[92]),"+f"(d[93]),"+f"(d[94]),"+f"(d[95]),"+f"(d[96]),"+f"(d[97]),"+f"(d[98]),"+f"(d[99]),"+f"(d[100]),"+f"(d[101]),"+f"(d[102]),"+f"(d[103]),"+f"(d[104]),"+f"(d[105]),"+f"(d[106]),"+f"(d[107]),"+f"(d[108]),"+f"(d[109]),"+f"(d[110]),"+f"(d[111]),"+f"(d[112]),"+f"(d[113]),"+f"(d[114]),"+f"(d[115]),"+f"(d[116]),"+f"(d[117]),"+f"(d[118]),"+f"(d[119]),"+f"(d[120]),"+f"(d[121]),"+f"(d[122]),"+f"(d[123]),"+f"(d[124]),"+f"(d[125]),"+f"(d[126]),"+f"(d[127])
    : "l"(da),"l"(db),"r"(sc));
}
__device__ __forceinline__ void wgmma_ss_n192_tb(float (&d)[96], uint64_t da, uint64_t db, int sc) {
  asm volatile("{\n.reg .pred p;\nsetp.ne.b32 p, %98, 0;\n"
    "wgmma.mma_async.sync.aligned.m64n192k16.f32.bf16.bf16 {%0,%1,%2,%3,%4,%5,%6,%7,%8,%9,%10,%11,%12,%13,%14,%15,%16,%17,%18,%19,%20,%21,%22,%23,%24,%25,%26,%27,%28,%29,%30,%31,%32,%33,%34,%35,%36,%37,%38,%39,%40,%41,%42,%43,%44,%45,%46,%47,%48,%49,%50,%51,%52,%53,%54,%55,%56,%57,%58,%59,%60,%61,%62,%63,%64,%65,%66,%67,%68,%69,%70,%71,%72,%73,%74,%75,%76,%77,%78,%79,%80,%81,%82,%83,%84,%85,%86,%87,%88,%89,%90,%91,%92,%93,%94,%95}, %96, %97, p, 1, 1, 0, 1;\n}\n"
    : "+f"(d[0]),"+f"(d[1]),"+f"(d[2]),"+f"(d[3]),"+f"(d[4]),"+f"(d[5]),"+f"(d[6]),"+f"(d[7]),"+f"(d[8]),"+f"(d[9]),"+f"(d[10]),"+f"(d[11]),"+f"(d[12]),"+f"(d[13]),"+f"(d[14]),"+f"(d[15]),"+f"(d[16]),"+f"(d[17]),"+f"(d[18]),"+f"(d[19]),"+f"(d[20]),"+f"(d[21]),"+f"(d[22]),"+f"(d[23]),"+f"(d[24]),"+f"(d[25]),"+f"(d[26]),"+f"(d[27]),"+f"(d[28]),"+f"(d[29]),"+f"(d[30]),"+f"(d[31]),"+f"(d[32]),"+f"(d[33]),"+f"(d[34]),"+f"(d[35]),"+f"(d[36]),"+f"(d[37]),"+f"(d[38]),"+f"(d[39]),"+f"(d[40]),"+f"(d[41]),"+f"(d[42]),"+f"(d[43]),"+f"(d[44]),"+f"(d[45]),"+f"(d[46]),"+f"(d[47]),"+f"(d[48]),"+f"(d[49]),"+f"(d[50]),"+f"(d[51]),"+f"(d[52]),"+f"(d[53]),"+f"(d[54]),"+f"(d[55]),"+f"(d[56]),"+f"(d[57]),"+f"(d[58]),"+f"(d[59]),"+f"(d[60]),"+f"(d[61]),"+f"(d[62]),"+f"(d[63]),"+f"(d[64]),"+f"(d[65]),"+f"(d[66]),"+f"(d[67]),"+f"(d[68]),"+f"(d[69]),"+f"(d[70]),"+f"(d[71]),"+f"(d[72]),"+f"(d[73]),"+f"(d[74]),"+f"(d[75]),"+f"(d[76]),"+f"(d[77]),"+f"(d[78]),"+f"(d[79]),"+f"(d[80]),"+f"(d[81]),"+f"(d[82]),"+f"(d[83]),"+f"(d[84]),"+f"(d[85]),"+f"(d[86]),"+f"(d[87]),"+f"(d[88]),"+f"(d[89]),"+f"(d[90]),"+f"(d[91]),"+f"(d[92]),"+f"(d[93]),"+f"(d[94]),"+f"(d[95])
    : "l"(da),"l"(db),"r"(sc));
}

__device__ __forceinline__ uint32_t smem_u32(const void* p) { return (uint32_t)__cvta_generic_to_shared(p); }
__device__ __forceinline__ void mbar_init(uint32_t bar, uint32_t cnt) { asm volatile("mbarrier.init.shared::cta.b64 [%0], %1;" :: "r"(bar), "r"(cnt)); }
__device__ __forceinline__ void mbar_expect_tx(uint32_t bar, uint32_t bytes) { asm volatile("mbarrier.arrive.expect_tx.shared::cta.b64 _, [%0], %1;" :: "r"(bar), "r"(bytes) : "memory"); }
__device__ __forceinline__ void mbar_arrive(uint32_t bar) { asm volatile("mbarrier.arrive.shared::cta.b64 _, [%0];" :: "r"(bar) : "memory"); }
__device__ __forceinline__ void mbar_arrive_cluster(uint32_t cbar, uint32_t cnt) { asm volatile("mbarrier.arrive.shared::cluster.b64 _, [%0], %1;" :: "r"(cbar), "r"(cnt) : "memory"); }
__device__ __forceinline__ uint32_t mapa(uint32_t a, uint32_t rank) { uint32_t r; asm volatile("mapa.shared::cluster.u32 %0, %1, %2;" : "=r"(r) : "r"(a), "r"(rank)); return r; }
__device__ __forceinline__ void mbar_wait(uint32_t bar, uint32_t parity) {
    uint32_t ok; uint32_t n = 0;
    do {
        asm volatile("{\n.reg .pred p;\nmbarrier.try_wait.parity.shared::cta.b64 p, [%1], %2;\nselp.u32 %0, 1, 0, p;\n}" : "=r"(ok) : "r"(bar), "r"(parity) : "memory");
    } while (!ok && ++n < (1u << 17));
}
__device__ __forceinline__ void pace_wait(uint32_t a, uint32_t target) {
    uint32_t v, n = 0;
    do {
        asm volatile("ld.volatile.shared.u32 %0, [%1];" : "=r"(v) : "r"(a) : "memory");
        if (v < target) __nanosleep(40);
    } while (v < target && ++n < (1u << 14));
}
__device__ __forceinline__ void flag_wait(const unsigned* p, unsigned target) {
    unsigned v; uint32_t n = 0;
    while (true) {
        asm volatile("ld.acquire.gpu.global.u32 %0, [%1];" : "=r"(v) : "l"(p) : "memory");
        if ((int)(v - target) >= 0 || ++n >= (1u << 17)) break;
        __nanosleep(100);
    }
}
__device__ __forceinline__ void flag_add(unsigned* p) {
    asm volatile("fence.acq_rel.gpu;\nred.relaxed.gpu.global.add.u32 [%0], 1;" :: "l"(p) : "memory");
}
__device__ __forceinline__ uint64_t make_desc(uint32_t addr, uint32_t lbo, uint32_t sbo, uint32_t swz) {
    return (uint64_t)((addr & 0x3FFFF) >> 4) | ((uint64_t)((lbo & 0x3FFFF) >> 4) << 16) | ((uint64_t)((sbo & 0x3FFFF) >> 4) << 32) | ((uint64_t)swz << 62);
}
__device__ __forceinline__ uint64_t desc_add(uint64_t d, uint32_t off16) {
    return (d & 0xFFFFFFFF00000000ull) | (uint64_t)((uint32_t)d + off16);
}
__device__ __forceinline__ void tma2d(uint32_t dst, const CUtensorMap* tm, int c0, int c1, uint32_t bar) {
    asm volatile("cp.async.bulk.tensor.2d.shared::cluster.global.mbarrier::complete_tx::bytes [%0], [%1, {%3, %4}], [%2];"
        :: "r"(dst), "l"((uint64_t)tm), "r"(bar), "r"(c0), "r"(c1) : "memory");
}
__device__ __forceinline__ void tma3d_mc(uint32_t dst, const CUtensorMap* tm, int c0, int c1, int c2, uint32_t bar) {
    asm volatile("cp.async.bulk.tensor.3d.shared::cluster.global.mbarrier::complete_tx::bytes.multicast::cluster [%0], [%1, {%3, %4, %5}], [%2], %6;"
        :: "r"(dst), "l"((uint64_t)tm), "r"(bar), "r"(c0), "r"(c1), "r"(c2), "h"((uint16_t)3) : "memory");
}
__device__ __forceinline__ void bulk_g2s(uint32_t dst, const void* src, uint32_t bytes, uint32_t bar) {
    asm volatile("cp.async.bulk.shared::cluster.global.mbarrier::complete_tx::bytes [%0], [%1], %2, [%3];"
        :: "r"(dst), "l"(src), "r"(bytes), "r"(bar) : "memory");
}
__device__ __forceinline__ void bulk_s2g(void* dst, uint32_t src, uint32_t bytes) {
    asm volatile("cp.async.bulk.global.shared::cta.bulk_group [%0], [%1], %2;" :: "l"(dst), "r"(src), "r"(bytes) : "memory");
}
__device__ __forceinline__ void tma2d_store(const CUtensorMap* tm, int c0, int c1, uint32_t src) {
    asm volatile("cp.async.bulk.tensor.2d.global.shared::cta.bulk_group [%0, {%2, %3}], [%1];"
        :: "l"((uint64_t)tm), "r"(src), "r"(c0), "r"(c1) : "memory");
}
__device__ __forceinline__ void l2_prefetch(const void* p, uint32_t bytes) {
    asm volatile("cp.async.bulk.prefetch.L2.global [%0], %1;" :: "l"(p), "r"(bytes) : "memory");
}
__device__ __forceinline__ void tmap_prefetch(const CUtensorMap* tm) { asm volatile("prefetch.tensormap [%0];" :: "l"((uint64_t)tm) : "memory"); }
__device__ __forceinline__ uint32_t lds32(uint32_t a) { uint32_t v; asm volatile("ld.shared.u32 %0, [%1];" : "=r"(v) : "r"(a)); return v; }
__device__ __forceinline__ uint2 lds64(uint32_t a) { uint2 v; asm volatile("ld.shared.v2.u32 {%0,%1}, [%2];" : "=r"(v.x), "=r"(v.y) : "r"(a)); return v; }
__device__ __forceinline__ uint4 lds128(uint32_t a) { uint4 v; asm volatile("ld.shared.v4.u32 {%0,%1,%2,%3}, [%4];" : "=r"(v.x), "=r"(v.y), "=r"(v.z), "=r"(v.w) : "r"(a)); return v; }
__device__ __forceinline__ void sts32(uint32_t a, uint32_t v) { asm volatile("st.shared.u32 [%0], %1;" :: "r"(a), "r"(v) : "memory"); }
__device__ __forceinline__ void sts128(uint32_t a, uint4 v) { asm volatile("st.shared.v4.u32 [%0], {%1,%2,%3,%4};" :: "r"(a), "r"(v.x), "r"(v.y), "r"(v.z), "r"(v.w) : "memory"); }
__device__ __forceinline__ uint4 ldg_cg128(const void* p) { uint4 v; asm volatile("ld.global.cg.v4.u32 {%0,%1,%2,%3}, [%4];" : "=r"(v.x), "=r"(v.y), "=r"(v.z), "=r"(v.w) : "l"(p)); return v; }
__device__ __forceinline__ uint4 ldg_nc128(const void* p) { uint4 v; asm volatile("ld.global.nc.L1::no_allocate.v4.u32 {%0,%1,%2,%3}, [%4];" : "=r"(v.x), "=r"(v.y), "=r"(v.z), "=r"(v.w) : "l"(p)); return v; }
__device__ __forceinline__ uint2 ldg_nc64(const void* p) { uint2 v; asm volatile("ld.global.nc.L1::no_allocate.v2.u32 {%0,%1}, [%2];" : "=r"(v.x), "=r"(v.y) : "l"(p)); return v; }
#define WG_FENCE() asm volatile("wgmma.fence.sync.aligned;\n" ::: "memory")
#define WG_COMMIT() asm volatile("wgmma.commit_group.sync.aligned;\n" ::: "memory")
template<int N> __device__ __forceinline__ void wg_wait() { asm volatile("wgmma.wait_group.sync.aligned %0;\n" :: "n"(N) : "memory"); }
__device__ __forceinline__ void named_bar(int id, int n) { asm volatile("bar.sync %0, %1;" :: "r"(id), "r"(n) : "memory"); }

__device__ __forceinline__ float bf_lo(uint32_t u) { return __uint_as_float(u << 16); }
__device__ __forceinline__ float bf_hi(uint32_t u) { return __uint_as_float(u & 0xFFFF0000u); }
__device__ __forceinline__ uint32_t pack_bf(float lo, float hi) { uint32_t r; asm("cvt.rn.bf16x2.f32 %0, %1, %2;" : "=r"(r) : "f"(hi), "f"(lo)); return r; }
__device__ __forceinline__ float bf_round(float x) { return __bfloat162float(__float2bfloat16_rn(x)); }
__device__ __forceinline__ uint32_t bmul2(uint32_t a, uint32_t b) { uint32_t r; asm("mul.rn.bf16x2 %0, %1, %2;" : "=r"(r) : "r"(a), "r"(b)); return r; }
__device__ __forceinline__ uint32_t badd2(uint32_t a, uint32_t b) { uint32_t r; asm("add.rn.bf16x2 %0, %1, %2;" : "=r"(r) : "r"(a), "r"(b)); return r; }
__device__ __forceinline__ uint32_t bsub2(uint32_t a, uint32_t b) { uint32_t r; asm("sub.rn.bf16x2 %0, %1, %2;" : "=r"(r) : "r"(a), "r"(b)); return r; }
__device__ __forceinline__ void mma16816(float (&d)[4], uint32_t a0, uint32_t a1, uint32_t a2, uint32_t a3, uint2 b) {
    asm volatile("mma.sync.aligned.m16n8k16.row.col.f32.bf16.bf16.f32 {%0,%1,%2,%3}, {%4,%5,%6,%7}, {%8,%9}, {%0,%1,%2,%3};\n"
        : "+f"(d[0]), "+f"(d[1]), "+f"(d[2]), "+f"(d[3]) : "r"(a0), "r"(a1), "r"(a2), "r"(a3), "r"(b.x), "r"(b.y));
}

template<int HS> __device__ __forceinline__ void xreduce(float (&v)[32], int lane) {
    const int up = lane & HS;
    #pragma unroll
    for (int e = 0; e < HS; e++) {
        float keep, send;
        asm("{\n.reg .pred p;\nsetp.ne.b32 p, %4, 0;\nselp.f32 %0, %3, %2, p;\nselp.f32 %1, %2, %3, p;\n}"
            : "=f"(keep), "=f"(send) : "f"(v[e]), "f"(v[e + HS]), "r"(up));
        v[e] = keep + __shfl_xor_sync(0xffffffffu, send, HS);
    }
}

__device__ __forceinline__ int blk_f0(int bi, int j) {
    if (bi < 32) return 224 * ((j + (bi >> 2)) & 7) + 32 * (bi & 3);
    int b2 = bi - 32; int q3 = (b2 * 11) >> 5;
    return 224 * ((j + q3) & 7) + 128 + 32 * (b2 - 3 * q3);
}
__device__ __forceinline__ int next_st2(int s) { return (0x14023 >> (4 * s)) & 7; }
__device__ __forceinline__ uint32_t stage_off_rt(int s) { return s < 3 ? SM_RING + s * STAGE_BYTES : (uint32_t)(s - 2) * STAGE_BYTES; }

template<int NB>
__device__ __forceinline__ void gemm1_pass(uint32_t sb, int wgi, int warp4, int lane, int& st, uint32_t& fph, uint32_t e_cl,
                                           int rb64, int ks0) {
    constexpr bool passA = (NB == 4);
    float acc[NB * 32];
    const uint64_t descA0 = make_desc(sb + SM_X + wgi * 8192, 16, 1024, 1);
    const uint64_t descB0 = make_desc(sb + SM_RING, 4096, 512, 2);
    int prev = 0;
    #pragma unroll 1
    for (int sl = 0; sl < 8; sl++) {
        if (warp4 == 0 && wgi == 0) PROF2(2, sl + (passA ? 0 : 8));
        mbar_wait(sb + SM_BARS + (B_FULL + st) * 8, (fph >> st) & 1);
        fph ^= 1u << st;
        if (sl == 0 && warp4 == 0) PROF(2 + wgi * 8 + (passA ? 0 : 3));
        if (warp4 == 0 && wgi == 0) PROF2(1, sl + (passA ? 0 : 8));
        const uint64_t da = desc_add(descA0, sl * 1024), db = desc_add(descB0, st * 2048);
        WG_FENCE();
        #pragma unroll
        for (int kk = 0; kk < 4; kk++) {
            int sc = (sl | kk) ? 1 : 0;
            if constexpr (NB == 4) wgmma_ss_n256_tb(acc, da + kk * 2, db + kk * 64, sc); else wgmma_ss_n192_tb(acc, da + kk * 2, db + kk * 64, sc);
        }
        WG_COMMIT();
        wg_wait<1>();
        if (warp4 == 0 && wgi == 0) PROF2(3, sl + (passA ? 0 : 8));
        if (lane < 2 && sl) mbar_arrive_cluster(e_cl + prev * 8, 1);
        if (!passA) {
            if (sl == 2 && lane == 0) mbar_arrive(sb + SM_BARS + B_XFREE * 8);
            if ((sl == 4 || sl == 6) && lane < 2) mbar_arrive_cluster(e_cl + (1 + (sl >> 1)) * 8, 1);
        }
        prev = st;
        st = (st == 2) ? 0 : st + 1;
    }
    wg_wait<0>();
    if (lane < 2) mbar_arrive_cluster(e_cl + prev * 8, 1);
    if (!passA && lane == 0) mbar_arrive(sb + SM_BARS + B_G1DONE * 8);
    if (warp4 == 0) PROF(3 + wgi * 8 + (passA ? 0 : 3));
    const int g = lane >> 2;
    const int r0 = wgi * 64 + warp4 * 16 + g;
    const float s0 = __uint_as_float(lds32(sb + SM_STATS + r0 * 4)), s1 = __uint_as_float(lds32(sb + SM_STATS + (r0 + 8) * 4));
    uint4* dst = g_hfrag + ((size_t)(rb64 * 112 + ks0) * 4 + warp4) * 32 + lane;
    #pragma unroll
    for (int kk = 0; kk < NB * 2; kk++) {
        uint32_t h[4];
        #pragma unroll
        for (int tt = 0; tt < 2; tt++) {
            const int t = 2 * kk + tt;
            const float* ag = &acc[4 * t];
            const float* au = &acc[NB * 16 + 4 * t];
            h[2 * tt] = bmul2(pack_bf(ag[0] * s0, ag[1] * s0), pack_bf(au[0] * s0, au[1] * s0));
            h[2 * tt + 1] = bmul2(pack_bf(ag[2] * s1, ag[3] * s1), pack_bf(au[2] * s1, au[3] * s1));
        }
        dst[kk * 128] = make_uint4(h[0], h[1], h[2], h[3]);
    }
    __syncwarp();
    if (lane == 0) mbar_arrive(sb + SM_BARS + (B_HD + wgi * 2 + (passA ? 0 : 1)) * 8);
    if (warp4 == 0) PROF(4 + wgi * 8 + (passA ? 0 : 3));
}

__global__ void __cluster_dims__(2, 1, 1) __launch_bounds__(NTHREADS, 1)
fused_kernel(const __grid_constant__ Params p) {
    extern __shared__ __align__(1024) uint8_t smem_raw[];
    const uint32_t sb = smem_u32(smem_raw);
    const int tid = threadIdx.x, warp = tid >> 5, lane = tid & 31;
    const int b = blockIdx.x;
    const int rank = b & 1;
    const int j = (b >> 1) & 7;
    const int i = ((b >> 4) << 1) | rank;
    const int cb = j >> 1;
    const int rbG2 = 2 * i + (j & 1);

    if (tid == 256) {
        mbar_init(sb + SM_BARS + B_XFULL * 8, 1);
        asm volatile("fence.proxy.async.shared::cta;" ::: "memory");
        mbar_expect_tx(sb + SM_BARS + B_XFULL * 8, 131072);
        for (int sl = 0; sl < 8; sl++)
            tma2d(sb + SM_X + sl * 16384, &p.tm_x, 64 * ((sl + 2 * cb + 2) & 7), 128 * i, sb + SM_BARS + B_XFULL * 8);
    }
    if (tid == 288) {
        tmap_prefetch(rank ? &p.tm_uA : &p.tm_gA);
        for (int s = 0; s < 5; s++) { mbar_init(sb + SM_BARS + (B_FULL + s) * 8, 1); mbar_init(sb + SM_BARS + (B_EMPTY + s) * 8, 16); }
        for (int s = 0; s < 4; s++) mbar_init(sb + SM_BARS + (B_CONV + s) * 8, 1);
        mbar_init(sb + SM_BARS + B_YT * 8, 1);
        mbar_init(sb + SM_BARS + B_XR * 8, 1);
        mbar_init(sb + SM_BARS + B_G1DONE * 8, 8);
        mbar_init(sb + SM_BARS + B_XFREE * 8, 8);
        mbar_init(sb + SM_BARS + B_CVDONE * 8, 1);
        sts32(sb + SM_CVCNT, 0);
        mbar_init(sb + SM_BARS + B_YST * 8, 4);
        for (int s = 0; s < 4; s++) mbar_init(sb + SM_BARS + (B_HD + s) * 8, 4);
        for (int s = 0; s < 2; s++) mbar_init(sb + SM_BARS + (B_HRDY + s) * 8, 1);
        asm volatile("fence.mbarrier_init.release.cluster;" ::: "memory");
        asm volatile("fence.proxy.async.shared::cta;" ::: "memory");
    }
    __syncwarp();
    asm volatile("barrier.cluster.arrive.relaxed.aligned;\nbarrier.cluster.wait.aligned;\n" ::: "memory");
    PROFW(1, 0);

    if (warp < 8) {
        asm volatile("setmaxnreg.inc.sync.aligned.u32 200;");
        const int wgi = warp >> 2, warp4 = warp & 3;
        const int g = lane >> 2, c = lane & 3;
        const uint32_t e_cl = mapa(sb + SM_BARS + B_EMPTY * 8, lane & 1);
        {
            const uint32_t xa = sb + SM_X + (lane >> 3) * 16384 + warp * 16 * 128;
            uint4 xr[16][2];
            float v[32];
            mbar_wait(sb + SM_BARS + B_XFULL * 8, 0);
            PROFW(16, 0);
            #pragma unroll
            for (int r = 0; r < 16; r++) {
                const uint32_t a = xa + r * 128 + (((lane & 7) ^ (r & 7)) << 4);
                xr[r][0] = lds128(a); xr[r][1] = lds128(a + 65536);
            }
            #pragma unroll
            for (int r = 0; r < 16; r++) {
                const uint32_t* u = (const uint32_t*)&xr[r][0];
                float s = 0.f, q = 0.f;
                #pragma unroll
                for (int e = 0; e < 8; e++) { const float lo = bf_lo(u[e]), hi = bf_hi(u[e]); s += lo; q = fmaf(lo, lo, q); s += hi; q = fmaf(hi, hi, q); }
                v[r] = s; v[16 + r] = q;
            }
            xreduce<16>(v, lane); xreduce<8>(v, lane); xreduce<4>(v, lane); xreduce<2>(v, lane); xreduce<1>(v, lane);
            const float other = __shfl_xor_sync(0xffffffffu, v[0], 16);
            const float mean = (lane < 16 ? v[0] : other) * (1.0f / DM);
            const float msq = (lane < 16 ? other : v[0]) * (1.0f / DM);
            const float var_b = bf_round(fmaxf(msq - mean * mean, 0.f));
            const float sd = bf_round(sqrtf(bf_round(var_b + 1e-5f)));
            if (lane < 16) sts32(sb + SM_STATS + (warp * 16 + lane) * 4, __float_as_uint(1.0f / sd));
            const uint32_t mb = pack_bf(mean, mean);
            #pragma unroll
            for (int r = 0; r < 16; r++) {
                const uint32_t m = __shfl_sync(0xffffffffu, mb, r);
                const uint32_t a = xa + r * 128 + (((lane & 7) ^ (r & 7)) << 4);
                #pragma unroll
                for (int hh = 0; hh < 2; hh++) {
                    uint4 t = xr[r][hh];
                    t.x = bsub2(t.x, m); t.y = bsub2(t.y, m); t.z = bsub2(t.z, m); t.w = bsub2(t.w, m);
                    sts128(a + hh * 65536, t);
                }
            }
            asm volatile("fence.proxy.async.shared::cta;" ::: "memory");
            named_bar(1 + wgi, 128);
            PROFW(17, 0);
        }
        int st = 0; uint32_t fph = 0;
        const int rb64 = 2 * i + wgi;
        gemm1_pass<4>(sb, wgi, warp4, lane, st, fph, e_cl, rb64, 14 * j);
        gemm1_pass<3>(sb, wgi, warp4, lane, st, fph, e_cl, rb64, 14 * j + 8);

        if (wgi == 1) {
            const int gch = 4 * b + warp4;
            const uint32_t xb = sb + SM_CVX + warp4 * 4096;
            const uint32_t hb = sb + SM_CVH + warp4 * 4096;
            const uint32_t dw = ((const unsigned short*)p.ssm_D)[gch];
            const uint32_t d2 = dw | (dw << 16);
            mbar_wait(sb + SM_BARS + (B_CONV + warp4) * 8, 0);
            PROFW(32, 4);
            float acc[16][4];
            #pragma unroll
            for (int jj = 0; jj < 16; jj++) { acc[jj][0] = 0.f; acc[jj][1] = 0.f; acc[jj][2] = 0.f; acc[jj][3] = 0.f; }
            uint2 bh[8], bl0[8], bl1[8];
            uint32_t xl = xb + g * 32 + c * 8;
            uint32_t hl = hb + (g + 2 * c - 8) * 4;
            #pragma unroll
            for (int d = 0; d < 8; d++) { bl0[d] = lds64(xl + d * 256); bh[d] = lds64(xl + (8 + d) * 256); }
            uint32_t w[6];
            w[0] = 0; w[1] = 0; w[2] = 0;
            if (g + 2 * c >= 8) w[0] = lds32(hl);
            if (g + 2 * c >= 7) w[1] = lds32(hl + 4);
            if (g + 2 * c >= 6) w[2] = lds32(hl + 8);
            w[3] = lds32(hl + 2048); w[4] = lds32(hl + 2052); w[5] = lds32(hl + 2056);
            auto conv_m0 = [&](int m0, uint2 (&bl)[8], uint2 (&bn)[8]) {
                xl -= 32;
                #pragma unroll
                for (int k = 0; k < 8; k++) {
                    const uint32_t a0 = w[1], a1 = __byte_perm(w[0], w[1], 0x5432), a2 = w[2], a3 = __byte_perm(w[1], w[2], 0x5432);
                    const uint32_t c0 = w[4], c1 = __byte_perm(w[3], w[4], 0x5432), c2 = w[5], c3 = __byte_perm(w[4], w[5], 0x5432);
                    const uint32_t nx = (k < 7) ? hl + (k + 1) * 256 : hl + 32;
                    w[0] = lds32(nx); w[1] = lds32(nx + 4); w[2] = lds32(nx + 8);
                    w[3] = lds32(nx + 2048); w[4] = lds32(nx + 2052); w[5] = lds32(nx + 2056);
                    if (k > 0) bn[k] = lds64(xl + k * 256);
                    else { bn[0] = make_uint2(0, 0); if (g > m0) bn[0] = lds64(xl); }
                    #pragma unroll
                    for (int jj = k; jj < 16; jj++) mma16816(acc[jj], a0, a1, a2, a3, (jj - k < 8) ? bl[(jj - k) & 7] : bh[(jj - k) & 7]);
                    bh[7 - k] = lds64(xl + (15 - k) * 256);
                    #pragma unroll
                    for (int jj = k + 8; jj < 16; jj++) mma16816(acc[jj], c0, c1, c2, c3, bl[jj - k - 8]);
                }
                hl += 32;
                if (lane == 0) asm volatile("red.shared.add.u32 [%0], 1;" :: "r"(sb + SM_CVCNT) : "memory");
            };
            #pragma unroll 1
            for (int m0 = 0; m0 < 8; m0 += 2) {
                conv_m0(m0, bl0, bl1);
                conv_m0(m0 + 1, bl1, bl0);
            }
            PROFW(33, 4);
            const uint32_t kvl = xb + c * 64 + (7 - g) * 4;
            const uint32_t yl = hb + c * 64 + g * 4;
            __syncwarp();
            #pragma unroll
            for (int jj = 0; jj < 16; jj++) {
                uint32_t k0 = lds32(kvl + jj * 256), k1 = lds32(kvl + jj * 256 + 32);
                k0 = __byte_perm(k0, k0, 0x1032); k1 = __byte_perm(k1, k1, 0x1032);
                sts32(yl + jj * 256, badd2(pack_bf(acc[jj][2], acc[jj][0]), bmul2(k0, d2)));
                sts32(yl + jj * 256 + 32, badd2(pack_bf(acc[jj][3], acc[jj][1]), bmul2(k1, d2)));
            }
            asm volatile("fence.proxy.async.shared::cta;" ::: "memory");
            __syncwarp();
            PROFW(44, 4);
            if (lane == 0) mbar_arrive(sb + SM_BARS + B_YST * 8);
            PROFW(45, 4);
        }
        {
            float acc[64];
            uint4 af[3][8];
            const uint4* hsrc = g_hfrag + ((size_t)rbG2 * 112 * 4 + warp4) * 32 + lane;
            const uint64_t descB0 = make_desc(sb, 4096, 1024, 1);
            int prev = 0;
            auto load_group = [&](uint4 (&dstf)[8], int u) {
                #pragma unroll
                for (int hb = 0; hb < 4; hb++) {
                    const int ks = blk_f0(4 * u + hb, j) >> 4;
                    dstf[2 * hb] = ldg_cg128(hsrc + ks * 128);
                    dstf[2 * hb + 1] = ldg_cg128(hsrc + ks * 128 + 128);
                }
            };
            auto g2_step = [&](int u, int up, int un, uint4 (&cur)[8], uint4 (&nxt)[8], bool do_load) {
                const int u5 = (u * 13) >> 6;
                const int sg = (0x02143 >> (4 * (u - 5 * u5))) & 7;
                if (warp == 0) PROF2(2, 16 + u);
                mbar_wait(sb + SM_BARS + (B_FULL + sg) * 8, ((6u >> sg) ^ (uint32_t)u5) & 1);
                if (warp == 0) PROF2(1, 16 + u);
                const uint64_t db = desc_add(descB0, stage_off_rt(sg) >> 4);
                WG_FENCE();
                #pragma unroll
                for (int kk = 0; kk < 8; kk++)
                    wgmma_rs_n128_tb(acc, cur[kk].x, cur[kk].y, cur[kk].z, cur[kk].w, db + ((kk >> 1) * 512 + (kk & 1) * 128), (up >= 0 || kk) ? 1 : 0);
                WG_COMMIT();
                wg_wait<1>();
                if (warp == 0) PROF2(3, 16 + u);
                if (lane < 2 && up >= 0 && up + 5 < 14) mbar_arrive_cluster(e_cl + prev * 8, 2);
                prev = sg;
                if (do_load) load_group(nxt, un);
            };
            if (wgi == 0) {
                mbar_wait(sb + SM_BARS + B_HRDY * 8, 0);
                load_group(af[0], 0); load_group(af[1], 1);
                PROFW(20, 0);
                #pragma unroll 1
                for (int u0 = 0; u0 < 6; u0 += 3) {
                    pace_wait(sb + SM_CVCNT, 4 * (u0 + PACE0));
                    g2_step(u0, u0 - 1, u0 + 2, af[0], af[2], true);
                    pace_wait(sb + SM_CVCNT, 4 * (u0 + 1 + PACE0));
                    g2_step(u0 + 1, u0, u0 + 3, af[1], af[0], true);
                    pace_wait(sb + SM_CVCNT, 4 * (u0 + 2 + PACE0));
                    g2_step(u0 + 2, u0 + 1, u0 + 4, af[2], af[1], true);
                }
                PROFW(22, 0);
                mbar_wait(sb + SM_BARS + (B_HRDY + 1) * 8, 0);
                pace_wait(sb + SM_CVCNT, 4 * (6 + PACE0));
                g2_step(6, 5, 8, af[0], af[2], true);
                g2_step(7, 6, 10, af[1], af[0], true);
                g2_step(8, 7, 12, af[2], af[1], true);
                PROFW(24, 0);
                g2_step(10, 8, -1, af[0], af[2], false);
                g2_step(12, 10, -1, af[1], af[0], false);
                wg_wait<0>();
            } else {
                mbar_wait(sb + SM_BARS + (B_HRDY + 1) * 8, 0);
                load_group(af[0], 9); load_group(af[1], 11); load_group(af[2], 13);
                g2_step(9, -1, -1, af[0], af[2], false);
                g2_step(11, 9, -1, af[1], af[0], false);
                g2_step(13, 11, -1, af[2], af[1], false);
                wg_wait<0>();
            }
            PROFW(27, 0);
            named_bar(3, 256);
            {
                const uint32_t ex = sb + SM_RING + (tid & 127) * 16;
                #pragma unroll
                for (int q = 0; q < 8; q++) {
                    const float e0 = wgi ? acc[4 * q] : acc[32 + 4 * q], e1 = wgi ? acc[4 * q + 1] : acc[33 + 4 * q];
                    const float e2 = wgi ? acc[4 * q + 2] : acc[34 + 4 * q], e3 = wgi ? acc[4 * q + 3] : acc[35 + 4 * q];
                    sts128(ex + wgi * 16384 + q * 2048, make_uint4(__float_as_uint(e0), __float_as_uint(e1), __float_as_uint(e2), __float_as_uint(e3)));
                }
                named_bar(3, 256);
                #pragma unroll
                for (int q = 0; q < 8; q++) {
                    const uint4 t = lds128(ex + (wgi ^ 1) * 16384 + q * 2048);
                    acc[4 * q] = (wgi ? acc[32 + 4 * q] : acc[4 * q]) + __uint_as_float(t.x);
                    acc[4 * q + 1] = (wgi ? acc[33 + 4 * q] : acc[4 * q + 1]) + __uint_as_float(t.y);
                    acc[4 * q + 2] = (wgi ? acc[34 + 4 * q] : acc[4 * q + 2]) + __uint_as_float(t.z);
                    acc[4 * q + 3] = (wgi ? acc[35 + 4 * q] : acc[4 * q + 3]) + __uint_as_float(t.w);
                }
            }
            mbar_wait(sb + SM_BARS + B_XR * 8, 0);
            mbar_wait(sb + SM_BARS + B_YT * 8, 0);
            PROFW(28, 0);
            const int r0 = (j & 1) * 64 + warp4 * 16 + g;
            const float s0 = __uint_as_float(lds32(sb + SM_STATS + r0 * 4)), s1 = __uint_as_float(lds32(sb + SM_STATS + (r0 + 8) * 4));
            const uint32_t drow0 = sb + SM_XE + wgi * 16384 + r0 * 128 + c * 4;
            const uint32_t xrow0 = sb + SM_XE + wgi * 16384 + (r0 ^ 64) * 128 + c * 4;
            const int mi = lane >> 3, lr = lane & 7;
            const uint32_t yaddr = sb + SM_YT + wgi * 8192 + ((mi >> 1) * 8 + lr) * 128 + (((2 * warp4 + (mi & 1)) ^ lr) << 4);
            uint32_t y[4][4], xv[8][2], dv[8][2];
            #pragma unroll
            for (int t2 = 0; t2 < 4; t2++)
                asm volatile("ldmatrix.sync.aligned.m8n8.x4.trans.shared.b16 {%0,%1,%2,%3}, [%4];"
                    : "=r"(y[t2][0]), "=r"(y[t2][1]), "=r"(y[t2][2]), "=r"(y[t2][3]) : "r"(yaddr + t2 * 2048) : "memory");
            #pragma unroll
            for (int t = 0; t < 8; t++) {
                const uint32_t off = (t ^ g) << 4;
                xv[t][0] = lds32(xrow0 + off); xv[t][1] = lds32(xrow0 + 1024 + off);
                dv[t][0] = lds32(drow0 + off); dv[t][1] = lds32(drow0 + 1024 + off);
            }
            #pragma unroll
            for (int t = 0; t < 8; t++) {
                const uint32_t off = (t ^ g) << 4;
                const uint32_t n0 = pack_bf(bf_lo(dv[t][0]) * s0, bf_hi(dv[t][0]) * s0), n1 = pack_bf(bf_lo(dv[t][1]) * s1, bf_hi(dv[t][1]) * s1);
                const uint32_t o0 = badd2(badd2(xv[t][0], bmul2(n0, y[t >> 1][2 * (t & 1)])), pack_bf(acc[4 * t], acc[4 * t + 1]));
                const uint32_t o1 = badd2(badd2(xv[t][1], bmul2(n1, y[t >> 1][2 * (t & 1) + 1])), pack_bf(acc[4 * t + 2], acc[4 * t + 3]));
                sts32(xrow0 + off, o0); sts32(xrow0 + 1024 + off, o1);
            }
            asm volatile("fence.proxy.async.shared::cta;" ::: "memory");
            named_bar(1 + wgi, 128);
            if ((tid & 127) == 0) {
                tma2d_store(&p.tm_out, 128 * cb + 64 * wgi, 64 * rbG2, sb + SM_XE + wgi * 16384 + ((j & 1) ^ 1) * 8192);
                asm volatile("cp.async.bulk.commit_group;" ::: "memory");
                asm volatile("cp.async.bulk.wait_group.read 0;" ::: "memory");
                PROFW(29, 0);
            }
        }
    } else {
        asm volatile("setmaxnreg.dec.sync.aligned.u32 104;");
        if (warp == 8) {
            if (lane == 0) {
                int st = 0; uint32_t eph = 7;
                #pragma unroll 1
                for (int it = 0; it < 16; it++) {
                    const int pass = it >> 3, sl = it & 7;
                    const int nb = pass ? 3 : 4;
                    const CUtensorMap* tm = pass ? (rank ? &p.tm_uB : &p.tm_gB) : (rank ? &p.tm_uA : &p.tm_gA);
                    mbar_wait(sb + SM_BARS + (B_EMPTY + st) * 8, (eph >> st) & 1);
                    eph ^= 1u << st;
                    PROF2(0, it);
                    mbar_expect_tx(sb + SM_BARS + (B_FULL + st) * 8, nb * 8192);
                    tma3d_mc(sb + SM_RING + st * STAGE_BYTES + rank * nb * 4096, tm, 0, ((sl + 2 * cb + 2) & 7) * 64, 7 * j + 4 * pass, sb + SM_BARS + (B_FULL + st) * 8);
                    st = (st == 2) ? 0 : st + 1;
                }
                st = 3;
                #pragma unroll 1
                for (int u = 0; u < 14; u++) {
                    mbar_wait(sb + SM_BARS + (B_EMPTY + st) * 8, (eph >> st) & 1);
                    eph ^= 1u << st;
                    PROF2(0, 16 + u);
                    const uint32_t so = sb + stage_off_rt(st) + rank * 8192;
                    mbar_expect_tx(sb + SM_BARS + (B_FULL + st) * 8, 32768);
                    tma3d_mc(so, &p.tm_w2, 0, blk_f0(4 * u + rank, j), 2 * cb, sb + SM_BARS + (B_FULL + st) * 8);
                    tma3d_mc(so + 16384, &p.tm_w2, 0, blk_f0(4 * u + 2 + rank, j), 2 * cb, sb + SM_BARS + (B_FULL + st) * 8);
                    st = next_st2(st);
                }
                PROF(48);
                const unsigned ep = lds32(sb + SM_EPOCH);
                mbar_wait(sb + SM_BARS + B_CVDONE * 8, 0);
                flag_wait(&g_cnt_y[cb * 32], ep * 32);
                PROF(49);
                asm volatile("fence.proxy.async.global;" ::: "memory");
                mbar_expect_tx(sb + SM_BARS + B_YT * 8, 16384);
                tma2d(sb + SM_YT, &p.tm_yT, 64 * rbG2, 128 * cb, sb + SM_BARS + B_YT * 8);
            }
        } else if (warp < 11) {
            mbar_wait(sb + SM_BARS + B_XFULL * 8, 0);
            #pragma unroll 1
            for (int rnd = 0; rnd < 2; rnd++) {
                const int tt = (tid - 288) + 64 * rnd;
                uint32_t sk[4][2];
                uint4 skw[2];
                skw[0] = ldg_nc128(p.shift_k + 16 * tt); skw[1] = ldg_nc128(p.shift_k + 16 * tt + 8);
                const __nv_bfloat16* kp = p.k + (size_t)(16 * b) * DM + 4 * tt;
                const __nv_bfloat16* vp = p.v + (size_t)(16 * b) * DM + 4 * tt;
                uint2 kr[19];
                uint2 kv[16];
                #pragma unroll
                for (int r = 0; r < 3; r++) kr[r] = (b > 0) ? ldg_nc64(kp + (r - 3) * DM) : make_uint2(0, 0);
                #pragma unroll
                for (int r = 0; r < 16; r++) { kr[3 + r] = ldg_nc64(kp + r * DM); kv[r] = ldg_nc64(vp + r * DM); }
                {
                    const uint4 w0 = skw[0], w1 = skw[1];
                    sk[0][0] = __byte_perm(w0.x, w0.z, 0x5410); sk[1][0] = __byte_perm(w0.x, w0.z, 0x7632);
                    sk[2][0] = __byte_perm(w0.y, w0.w, 0x5410); sk[3][0] = __byte_perm(w0.y, w0.w, 0x7632);
                    sk[0][1] = __byte_perm(w1.x, w1.z, 0x5410); sk[1][1] = __byte_perm(w1.x, w1.z, 0x7632);
                    sk[2][1] = __byte_perm(w1.y, w1.w, 0x5410); sk[3][1] = __byte_perm(w1.y, w1.w, 0x7632);
                }
                #pragma unroll
                for (int s = 0; s < 16; s++) {
                    uint32_t a = bmul2(kr[s].x, sk[3][0]);
                    a = badd2(a, bmul2(kr[s + 1].x, sk[2][0]));
                    a = badd2(a, bmul2(kr[s + 2].x, sk[1][0]));
                    a = badd2(a, bmul2(kr[s + 3].x, sk[0][0]));
                    kv[s].x = bmul2(a, kv[s].x);
                    a = bmul2(kr[s].y, sk[3][1]);
                    a = badd2(a, bmul2(kr[s + 1].y, sk[2][1]));
                    a = badd2(a, bmul2(kr[s + 2].y, sk[1][1]));
                    a = badd2(a, bmul2(kr[s + 3].y, sk[0][1]));
                    kv[s].y = bmul2(a, kv[s].y);
                }
                PROFW(57 + 2 * rnd, 9);
                #pragma unroll
                for (int cc = 0; cc < 4; cc++) {
                    const uint32_t sel = (cc & 1) ? 0x7632 : 0x5410;
                    #define KVW(r) ((cc & 2) ? kv[r].y : kv[r].x)
                    uint4* dst = (uint4*)(g_kvT + (size_t)(4 * tt + cc) * SEQ + 16 * b);
                    dst[0] = make_uint4(__byte_perm(KVW(15), KVW(14), sel), __byte_perm(KVW(13), KVW(12), sel),
                                        __byte_perm(KVW(11), KVW(10), sel), __byte_perm(KVW(9), KVW(8), sel));
                    dst[1] = make_uint4(__byte_perm(KVW(7), KVW(6), sel), __byte_perm(KVW(5), KVW(4), sel),
                                        __byte_perm(KVW(3), KVW(2), sel), __byte_perm(KVW(1), KVW(0), sel));
                    #undef KVW
                }
                PROFW(58 + 2 * rnd, 9);
            }
            asm volatile("fence.proxy.async.global;" ::: "memory");
            __syncwarp();
            if (lane == 0) {
                flag_add(&g_cnt_kv[0]);
                PROFW(50, 9);
                const int wgi = warp - 9;
                mbar_wait(sb + SM_BARS + (B_HD + wgi * 2) * 8, 0);
                flag_add(&g_flag_h[((2 * i + wgi) * 2 + 0) * 8]);
                mbar_wait(sb + SM_BARS + (B_HD + wgi * 2 + 1) * 8, 0);
                flag_add(&g_flag_h[((2 * i + wgi) * 2 + 1) * 8]);
                if (wgi == 1) {
                    mbar_wait(sb + SM_BARS + B_YST * 8, 0);
                    bulk_s2g(g_yT + (size_t)(4 * b) * SEQ, sb + SM_CVH, 16384);
                    asm volatile("cp.async.bulk.commit_group;" ::: "memory");
                    asm volatile("cp.async.bulk.wait_group 0;" ::: "memory");
                    mbar_arrive(sb + SM_BARS + B_CVDONE * 8);
                    asm volatile("fence.proxy.async.global;" ::: "memory");
                    flag_add(&g_cnt_y[(b >> 5) * 32]);
                    PROF(46);
                }
            }
        } else {
            if (lane == 0) {
                const unsigned ep = g_launch[b] + 1;
                g_launch[b] = ep;
                sts32(sb + SM_EPOCH, ep);
                tmap_prefetch(rank ? &p.tm_uB : &p.tm_gB);
                tmap_prefetch(&p.tm_w2); tmap_prefetch(&p.tm_yT); tmap_prefetch(&p.tm_out); tmap_prefetch(&p.tm_xe);
                mbar_wait(sb + SM_BARS + (B_FULL + 2) * 8, 0);
                l2_prefetch(p.ssm_k + (size_t)(4 * b) * SEQ, 4 * SEQ * 2);
                l2_prefetch(p.wd + (size_t)b * (FF * DM / NCTA), FF * DM / NCTA * 2);
                mbar_wait(sb + SM_BARS + (B_HD + 0) * 8, 0);
                flag_wait(&g_cnt_kv[0], ep * 256);
                asm volatile("fence.proxy.async.global;" ::: "memory");
                PROF(53);
                mbar_wait(sb + SM_BARS + B_XFREE * 8, 0);
                PROF(54);
                for (int ch = 0; ch < 4; ch++) {
                    const uint32_t bar = sb + SM_BARS + (B_CONV + ch) * 8;
                    mbar_expect_tx(bar, 8192);
                    bulk_g2s(sb + SM_CVX + ch * 4096, g_kvT + (size_t)(4 * b + ch) * SEQ, 4096, bar);
                    bulk_g2s(sb + SM_CVH + ch * 4096, p.ssm_k + (size_t)(4 * b + ch) * SEQ, 4096, bar);
                }
                flag_wait(&g_flag_h[(rbG2 * 2 + 0) * 8], ep * 8);
                mbar_arrive(sb + SM_BARS + B_HRDY * 8);
                mbar_wait(sb + SM_BARS + B_G1DONE * 8, 0);
                mbar_expect_tx(sb + SM_BARS + B_XR * 8, 16384);
                tma2d(sb + SM_XE + ((j & 1) ^ 1) * 8192, &p.tm_xe, 128 * cb, 64 * rbG2, sb + SM_BARS + B_XR * 8);
                tma2d(sb + SM_XE + 16384 + ((j & 1) ^ 1) * 8192, &p.tm_xe, 128 * cb + 64, 64 * rbG2, sb + SM_BARS + B_XR * 8);
                flag_wait(&g_flag_h[(rbG2 * 2 + 1) * 8], ep * 8);
                mbar_arrive(sb + SM_BARS + (B_HRDY + 1) * 8);
            }
        }
    }
}

typedef CUresult (*EncodeFn)(CUtensorMap*, CUtensorMapDataType, cuuint32_t, void*, const cuuint64_t*, const cuuint64_t*,
                             const cuuint32_t*, const cuuint32_t*, CUtensorMapInterleave, CUtensorMapSwizzle,
                             CUtensorMapL2promotion, CUtensorMapFloatOOBfill);

void encode(EncodeFn fn, CUtensorMap* tm, const void* base, int rank, const cuuint64_t* dims, const cuuint64_t* strides,
            const cuuint32_t* box, CUtensorMapSwizzle swz) {
    cuuint32_t es[5] = {1, 1, 1, 1, 1};
    fn(tm, CU_TENSOR_MAP_DATA_TYPE_BFLOAT16, rank, (void*)base, dims, strides, box, es, CU_TENSOR_MAP_INTERLEAVE_NONE, swz,
       CU_TENSOR_MAP_L2_PROMOTION_L2_128B, CU_TENSOR_MAP_FLOAT_OOB_FILL_NONE);
}

}

extern "C" void kernel_launch(void* const* d_in, const int* in_sizes, int n_in, void* d_out, int out_size) {
    (void)in_sizes; (void)n_in; (void)out_size;
    static EncodeFn enc = nullptr;
    static void* yT_ptr = nullptr;
    if (!enc) {
        void* fn = nullptr; cudaDriverEntryPointQueryResult qr;
        cudaGetDriverEntryPoint("cuTensorMapEncodeTiled", &fn, cudaEnableDefault, &qr);
        enc = (EncodeFn)fn;
        cudaGetSymbolAddress(&yT_ptr, g_yT);
        cudaFuncSetAttribute(fused_kernel, cudaFuncAttributeMaxDynamicSharedMemorySize, SM_TOTAL);
    }
    Params p;
    p.q = (const __nv_bfloat16*)d_in[0]; p.k = (const __nv_bfloat16*)d_in[1]; p.v = (const __nv_bfloat16*)d_in[2];
    p.shift_k = (const __nv_bfloat16*)d_in[3]; p.ssm_k = (const __nv_bfloat16*)d_in[4]; p.ssm_D = (const __nv_bfloat16*)d_in[5];
    p.wg = (const __nv_bfloat16*)d_in[7]; p.wu = (const __nv_bfloat16*)d_in[8]; p.wd = (const __nv_bfloat16*)d_in[9];
    {
        cuuint64_t dims[2] = {DM, SEQ}; cuuint64_t str[1] = {DM * 2};
        cuuint32_t box[2] = {64, 128};
        encode(enc, &p.tm_x, p.q, 2, dims, str, box, CU_TENSOR_MAP_SWIZZLE_128B);
        cuuint32_t box2[2] = {64, 64};
        encode(enc, &p.tm_out, d_out, 2, dims, str, box2, CU_TENSOR_MAP_SWIZZLE_128B);
        encode(enc, &p.tm_xe, p.q, 2, dims, str, box2, CU_TENSOR_MAP_SWIZZLE_128B);
    }
    {
        cuuint64_t dims[3] = {32, DM, FF / 32}; cuuint64_t str[2] = {FF * 2, 64};
        cuuint32_t boxA[3] = {32, 64, 4}, boxB[3] = {32, 64, 3};
        encode(enc, &p.tm_gA, p.wg, 3, dims, str, boxA, CU_TENSOR_MAP_SWIZZLE_64B);
        encode(enc, &p.tm_gB, p.wg, 3, dims, str, boxB, CU_TENSOR_MAP_SWIZZLE_64B);
        encode(enc, &p.tm_uA, p.wu, 3, dims, str, boxA, CU_TENSOR_MAP_SWIZZLE_64B);
        encode(enc, &p.tm_uB, p.wu, 3, dims, str, boxB, CU_TENSOR_MAP_SWIZZLE_64B);
    }
    {
        cuuint64_t dims[3] = {64, FF, DM / 64}; cuuint64_t str[2] = {DM * 2, 128};
        cuuint32_t box[3] = {64, 32, 2};
        encode(enc, &p.tm_w2, p.wd, 3, dims, str, box, CU_TENSOR_MAP_SWIZZLE_128B);
    }
    {
        cuuint64_t dims[2] = {SEQ, DM}; cuuint64_t str[1] = {SEQ * 2};
        cuuint32_t box[2] = {64, 128};
        encode(enc, &p.tm_yT, yT_ptr, 2, dims, str, box, CU_TENSOR_MAP_SWIZZLE_128B);
    }
    fused_kernel<<<NCTA, NTHREADS, SM_TOTAL>>>(p);
}
```

```cpp
#include <cuda_runtime.h>
#include <cuda_bf16.h>
#include <cuda.h>
#include <stdint.h>

namespace {

constexpr int SEQ = 2048, DM = 512, FF = 1792;
constexpr int NCTA = 128;
constexpr int NTHREADS = 384;
constexpr int STAGE_BYTES = 32768;
#define PACE0 1

constexpr uint32_t SM_X = 0;
constexpr uint32_t SM_RING = 131072;
constexpr uint32_t SM_MISC = SM_RING + 3 * STAGE_BYTES;
constexpr uint32_t SM_BARS = SM_MISC;
constexpr uint32_t SM_EPOCH = SM_MISC + 248;
constexpr uint32_t SM_CVCNT = SM_MISC + 252;
constexpr uint32_t SM_STATS = SM_MISC + 256;
constexpr uint32_t SM_TOTAL = SM_STATS + 512;
static_assert(SM_TOTAL <= 232448, "smem");
__host__ __device__ constexpr uint32_t stage_off(int s) { return s < 3 ? SM_RING + s * STAGE_BYTES : (uint32_t)(s - 2) * STAGE_BYTES; }
constexpr uint32_t SM_CVX = 0;
constexpr uint32_t SM_CVH = 16384;
constexpr uint32_t SM_YT = 0;
constexpr uint32_t SM_XE = 6 * 16384;

constexpr int B_FULL = 0, B_EMPTY = 5, B_XFULL = 10, B_CONV = 11, B_YT = 15, B_XR = 16, B_G1DONE = 17, B_HD = 18, B_HRDY = 22,
              B_XFREE = 24, B_CVDONE = 25, B_CVGO = 26, B_YST = 27, B_COUNT = 28;
static_assert(B_COUNT * 8 <= 248, "barrier space");

__device__ uint4 g_hfrag[32 * 112 * 4 * 32];
__device__ __align__(128) __nv_bfloat16 g_kvT[DM * SEQ];
__device__ __align__(128) __nv_bfloat16 g_yT[DM * SEQ];
__device__ unsigned g_launch[NCTA];
__device__ unsigned g_cnt_kv[32];
__device__ unsigned g_cnt_y[4 * 32];
__device__ unsigned g_flag_h[32 * 2 * 8];

#define PROF(idx)
#define PROF2(a, idx)
#define PROFW(idx, w)

struct Params {
    CUtensorMap tm_x, tm_gA, tm_gB, tm_uA, tm_uB, tm_w2, tm_yT, tm_out, tm_xe;
    const __nv_bfloat16 *q, *k, *v, *shift_k, *ssm_k, *ssm_D, *wg, *wu, *wd;
};

__device__ __forceinline__ void wgmma_rs_n32(float (&d)[16], uint32_t a0, uint32_t a1, uint32_t a2, uint32_t a3, uint64_t db, int sc) {
  asm volatile("{\n.reg .pred p;\nsetp.ne.b32 p, %21, 0;\n"
    "wgmma.mma_async.sync.aligned.m64n32k16.f32.bf16.bf16 {%0,%1,%2,%3,%4,%5,%6,%7,%8,%9,%10,%11,%12,%13,%14,%15}, {%16,%17,%18,%19}, %20, p, 1, 1, 0;\n}\n"
    : "+f"(d[0]),"+f"(d[1]),"+f"(d[2]),"+f"(d[3]),"+f"(d[4]),"+f"(d[5]),"+f"(d[6]),"+f"(d[7]),"+f"(d[8]),"+f"(d[9]),"+f"(d[10]),"+f"(d[11]),"+f"(d[12]),"+f"(d[13]),"+f"(d[14]),"+f"(d[15])
    : "r"(a0),"r"(a1),"r"(a2),"r"(a3),"l"(db),"r"(sc));
}
__device__ __forceinline__ void wgmma_rs_n128_tb(float (&d)[64], uint32_t a0, uint32_t a1, uint32_t a2, uint32_t a3, uint64_t db, int sc) {
  asm volatile("{\n.reg .pred p;\nsetp.ne.b32 p, %69, 0;\n"
    "wgmma.mma_async.sync.aligned.m64n128k16.f32.bf16.bf16 {%0,%1,%2,%3,%4,%5,%6,%7,%8,%9,%10,%11,%12,%13,%14,%15,%16,%17,%18,%19,%20,%21,%22,%23,%24,%25,%26,%27,%28,%29,%30,%31,%32,%33,%34,%35,%36,%37,%38,%39,%40,%41,%42,%43,%44,%45,%46,%47,%48,%49,%50,%51,%52,%53,%54,%55,%56,%57,%58,%59,%60,%61,%62,%63}, {%64,%65,%66,%67}, %68, p, 1, 1, 1;\n}\n"
    : "+f"(d[0]),"+f"(d[1]),"+f"(d[2]),"+f"(d[3]),"+f"(d[4]),"+f"(d[5]),"+f"(d[6]),"+f"(d[7]),"+f"(d[8]),"+f"(d[9]),"+f"(d[10]),"+f"(d[11]),"+f"(d[12]),"+f"(d[13]),"+f"(d[14]),"+f"(d[15]),"+f"(d[16]),"+f"(d[17]),"+f"(d[18]),"+f"(d[19]),"+f"(d[20]),"+f"(d[21]),"+f"(d[22]),"+f"(d[23]),"+f"(d[24]),"+f"(d[25]),"+f"(d[26]),"+f"(d[27]),"+f"(d[28]),"+f"(d[29]),"+f"(d[30]),"+f"(d[31]),"+f"(d[32]),"+f"(d[33]),"+f"(d[34]),"+f"(d[35]),"+f"(d[36]),"+f"(d[37]),"+f"(d[38]),"+f"(d[39]),"+f"(d[40]),"+f"(d[41]),"+f"(d[42]),"+f"(d[43]),"+f"(d[44]),"+f"(d[45]),"+f"(d[46]),"+f"(d[47]),"+f"(d[48]),"+f"(d[49]),"+f"(d[50]),"+f"(d[51]),"+f"(d[52]),"+f"(d[53]),"+f"(d[54]),"+f"(d[55]),"+f"(d[56]),"+f"(d[57]),"+f"(d[58]),"+f"(d[59]),"+f"(d[60]),"+f"(d[61]),"+f"(d[62]),"+f"(d[63])
    : "r"(a0),"r"(a1),"r"(a2),"r"(a3),"l"(db),"r"(sc));
}
__device__ __forceinline__ void wgmma_ss_n256_tb(float (&d)[128], uint64_t da, uint64_t db, int sc) {
  asm volatile("{\n.reg .pred p;\nsetp.ne.b32 p, %130, 0;\n"
    "wgmma.mma_async.sync.aligned.m64n256k16.f32.bf16.bf16 {%0,%1,%2,%3,%4,%5,%6,%7,%8,%9,%10,%11,%12,%13,%14,%15,%16,%17,%18,%19,%20,%21,%22,%23,%24,%25,%26,%27,%28,%29,%30,%31,%32,%33,%34,%35,%36,%37,%38,%39,%40,%41,%42,%43,%44,%45,%46,%47,%48,%49,%50,%51,%52,%53,%54,%55,%56,%57,%58,%59,%60,%61,%62,%63,%64,%65,%66,%67,%68,%69,%70,%71,%72,%73,%74,%75,%76,%77,%78,%79,%80,%81,%82,%83,%84,%85,%86,%87,%88,%89,%90,%91,%92,%93,%94,%95,%96,%97,%98,%99,%100,%101,%102,%103,%104,%105,%106,%107,%108,%109,%110,%111,%112,%113,%114,%115,%116,%117,%118,%119,%120,%121,%122,%123,%124,%125,%126,%127}, %128, %129, p, 1, 1, 0, 1;\n}\n"
    : "+f"(d[0]),"+f"(d[1]),"+f"(d[2]),"+f"(d[3]),"+f"(d[4]),"+f"(d[5]),"+f"(d[6]),"+f"(d[7]),"+f"(d[8]),"+f"(d[9]),"+f"(d[10]),"+f"(d[11]),"+f"(d[12]),"+f"(d[13]),"+f"(d[14]),"+f"(d[15]),"+f"(d[16]),"+f"(d[17]),"+f"(d[18]),"+f"(d[19]),"+f"(d[20]),"+f"(d[21]),"+f"(d[22]),"+f"(d[23]),"+f"(d[24]),"+f"(d[25]),"+f"(d[26]),"+f"(d[27]),"+f"(d[28]),"+f"(d[29]),"+f"(d[30]),"+f"(d[31]),"+f"(d[32]),"+f"(d[33]),"+f"(d[34]),"+f"(d[35]),"+f"(d[36]),"+f"(d[37]),"+f"(d[38]),"+f"(d[39]),"+f"(d[40]),"+f"(d[41]),"+f"(d[42]),"+f"(d[43]),"+f"(d[44]),"+f"(d[45]),"+f"(d[46]),"+f"(d[47]),"+f"(d[48]),"+f"(d[49]),"+f"(d[50]),"+f"(d[51]),"+f"(d[52]),"+f"(d[53]),"+f"(d[54]),"+f"(d[55]),"+f"(d[56]),"+f"(d[57]),"+f"(d[58]),"+f"(d[59]),"+f"(d[60]),"+f"(d[61]),"+f"(d[62]),"+f"(d[63]),"+f"(d[64]),"+f"(d[65]),"+f"(d[66]),"+f"(d[67]),"+f"(d[68]),"+f"(d[69]),"+f"(d[70]),"+f"(d[71]),"+f"(d[72]),"+f"(d[73]),"+f"(d[74]),"+f"(d[75]),"+f"(d[76]),"+f"(d[77]),"+f"(d[78]),"+f"(d[79]),"+f"(d[80]),"+f"(d[81]),"+f"(d[82]),"+f"(d[83]),"+f"(d[84]),"+f"(d[85]),"+f"(d[86]),"+f"(d[87]),"+f"(d[88]),"+f"(d[89]),"+f"(d[90]),"+f"(d[91]),"+f"(d[92]),"+f"(d[93]),"+f"(d[94]),"+f"(d[95]),"+f"(d[96]),"+f"(d[97]),"+f"(d[98]),"+f"(d[99]),"+f"(d[100]),"+f"(d[101]),"+f"(d[102]),"+f"(d[103]),"+f"(d[104]),"+f"(d[105]),"+f"(d[106]),"+f"(d[107]),"+f"(d[108]),"+f"(d[109]),"+f"(d[110]),"+f"(d[111]),"+f"(d[112]),"+f"(d[113]),"+f"(d[114]),"+f"(d[115]),"+f"(d[116]),"+f"(d[117]),"+f"(d[118]),"+f"(d[119]),"+f"(d[120]),"+f"(d[121]),"+f"(d[122]),"+f"(d[123]),"+f"(d[124]),"+f"(d[125]),"+f"(d[126]),"+f"(d[127])
    : "l"(da),"l"(db),"r"(sc));
}
__device__ __forceinline__ void wgmma_ss_n192_tb(float (&d)[96], uint64_t da, uint64_t db, int sc) {
  asm volatile("{\n.reg .pred p;\nsetp.ne.b32 p, %98, 0;\n"
    "wgmma.mma_async.sync.aligned.m64n192k16.f32.bf16.bf16 {%0,%1,%2,%3,%4,%5,%6,%7,%8,%9,%10,%11,%12,%13,%14,%15,%16,%17,%18,%19,%20,%21,%22,%23,%24,%25,%26,%27,%28,%29,%30,%31,%32,%33,%34,%35,%36,%37,%38,%39,%40,%41,%42,%43,%44,%45,%46,%47,%48,%49,%50,%51,%52,%53,%54,%55,%56,%57,%58,%59,%60,%61,%62,%63,%64,%65,%66,%67,%68,%69,%70,%71,%72,%73,%74,%75,%76,%77,%78,%79,%80,%81,%82,%83,%84,%85,%86,%87,%88,%89,%90,%91,%92,%93,%94,%95}, %96, %97, p, 1, 1, 0, 1;\n}\n"
    : "+f"(d[0]),"+f"(d[1]),"+f"(d[2]),"+f"(d[3]),"+f"(d[4]),"+f"(d[5]),"+f"(d[6]),"+f"(d[7]),"+f"(d[8]),"+f"(d[9]),"+f"(d[10]),"+f"(d[11]),"+f"(d[12]),"+f"(d[13]),"+f"(d[14]),"+f"(d[15]),"+f"(d[16]),"+f"(d[17]),"+f"(d[18]),"+f"(d[19]),"+f"(d[20]),"+f"(d[21]),"+f"(d[22]),"+f"(d[23]),"+f"(d[24]),"+f"(d[25]),"+f"(d[26]),"+f"(d[27]),"+f"(d[28]),"+f"(d[29]),"+f"(d[30]),"+f"(d[31]),"+f"(d[32]),"+f"(d[33]),"+f"(d[34]),"+f"(d[35]),"+f"(d[36]),"+f"(d[37]),"+f"(d[38]),"+f"(d[39]),"+f"(d[40]),"+f"(d[41]),"+f"(d[42]),"+f"(d[43]),"+f"(d[44]),"+f"(d[45]),"+f"(d[46]),"+f"(d[47]),"+f"(d[48]),"+f"(d[49]),"+f"(d[50]),"+f"(d[51]),"+f"(d[52]),"+f"(d[53]),"+f"(d[54]),"+f"(d[55]),"+f"(d[56]),"+f"(d[57]),"+f"(d[58]),"+f"(d[59]),"+f"(d[60]),"+f"(d[61]),"+f"(d[62]),"+f"(d[63]),"+f"(d[64]),"+f"(d[65]),"+f"(d[66]),"+f"(d[67]),"+f"(d[68]),"+f"(d[69]),"+f"(d[70]),"+f"(d[71]),"+f"(d[72]),"+f"(d[73]),"+f"(d[74]),"+f"(d[75]),"+f"(d[76]),"+f"(d[77]),"+f"(d[78]),"+f"(d[79]),"+f"(d[80]),"+f"(d[81]),"+f"(d[82]),"+f"(d[83]),"+f"(d[84]),"+f"(d[85]),"+f"(d[86]),"+f"(d[87]),"+f"(d[88]),"+f"(d[89]),"+f"(d[90]),"+f"(d[91]),"+f"(d[92]),"+f"(d[93]),"+f"(d[94]),"+f"(d[95])
    : "l"(da),"l"(db),"r"(sc));
}

__device__ __forceinline__ uint32_t smem_u32(const void* p) { return (uint32_t)__cvta_generic_to_shared(p); }
__device__ __forceinline__ void mbar_init(uint32_t bar, uint32_t cnt) { asm volatile("mbarrier.init.shared::cta.b64 [%0], %1;" :: "r"(bar), "r"(cnt)); }
__device__ __forceinline__ void mbar_expect_tx(uint32_t bar, uint32_t bytes) { asm volatile("mbarrier.arrive.expect_tx.shared::cta.b64 _, [%0], %1;" :: "r"(bar), "r"(bytes) : "memory"); }
__device__ __forceinline__ void mbar_arrive(uint32_t bar) { asm volatile("mbarrier.arrive.shared::cta.b64 _, [%0];" :: "r"(bar) : "memory"); }
__device__ __forceinline__ void mbar_arrive_cluster(uint32_t cbar, uint32_t cnt) { asm volatile("mbarrier.arrive.shared::cluster.b64 _, [%0], %1;" :: "r"(cbar), "r"(cnt) : "memory"); }
__device__ __forceinline__ uint32_t mapa(uint32_t a, uint32_t rank) { uint32_t r; asm volatile("mapa.shared::cluster.u32 %0, %1, %2;" : "=r"(r) : "r"(a), "r"(rank)); return r; }
__device__ __forceinline__ void mbar_wait(uint32_t bar, uint32_t parity) {
    uint32_t ok; uint32_t n = 0;
    do {
        asm volatile("{\n.reg .pred p;\nmbarrier.try_wait.parity.shared::cta.b64 p, [%1], %2;\nselp.u32 %0, 1, 0, p;\n}" : "=r"(ok) : "r"(bar), "r"(parity) : "memory");
    } while (!ok && ++n < (1u << 17));
}
__device__ __forceinline__ void pace_wait(uint32_t a, uint32_t target) {
    uint32_t v, n = 0;
    do {
        asm volatile("ld.volatile.shared.u32 %0, [%1];" : "=r"(v) : "r"(a) : "memory");
        if (v < target) __nanosleep(40);
    } while (v < target && ++n < (1u << 14));
}
__device__ __forceinline__ void flag_wait(const unsigned* p, unsigned target) {
    unsigned v; uint32_t n = 0;
    while (true) {
        asm volatile("ld.acquire.gpu.global.u32 %0, [%1];" : "=r"(v) : "l"(p) : "memory");
        if ((int)(v - target) >= 0 || ++n >= (1u << 17)) break;
        __nanosleep(100);
    }
}
__device__ __forceinline__ void flag_add(unsigned* p) {
    asm volatile("fence.acq_rel.gpu;\nred.relaxed.gpu.global.add.u32 [%0], 1;" :: "l"(p) : "memory");
}
__device__ __forceinline__ uint64_t make_desc(uint32_t addr, uint32_t lbo, uint32_t sbo, uint32_t swz) {
    return (uint64_t)((addr & 0x3FFFF) >> 4) | ((uint64_t)((lbo & 0x3FFFF) >> 4) << 16) | ((uint64_t)((sbo & 0x3FFFF) >> 4) << 32) | ((uint64_t)swz << 62);
}
__device__ __forceinline__ uint64_t desc_add(uint64_t d, uint32_t off16) {
    return (d & 0xFFFFFFFF00000000ull) | (uint64_t)((uint32_t)d + off16);
}
__device__ __forceinline__ void tma2d(uint32_t dst, const CUtensorMap* tm, int c0, int c1, uint32_t bar) {
    asm volatile("cp.async.bulk.tensor.2d.shared::cluster.global.mbarrier::complete_tx::bytes [%0], [%1, {%3, %4}], [%2];"
        :: "r"(dst), "l"((uint64_t)tm), "r"(bar), "r"(c0), "r"(c1) : "memory");
}
__device__ __forceinline__ void tma3d_mc(uint32_t dst, const CUtensorMap* tm, int c0, int c1, int c2, uint32_t bar) {
    asm volatile("cp.async.bulk.tensor.3d.shared::cluster.global.mbarrier::complete_tx::bytes.multicast::cluster [%0], [%1, {%3, %4, %5}], [%2], %6;"
        :: "r"(dst), "l"((uint64_t)tm), "r"(bar), "r"(c0), "r"(c1), "r"(c2), "h"((uint16_t)3) : "memory");
}
__device__ __forceinline__ void bulk_g2s(uint32_t dst, const void* src, uint32_t bytes, uint32_t bar) {
    asm volatile("cp.async.bulk.shared::cluster.global.mbarrier::complete_tx::bytes [%0], [%1], %2, [%3];"
        :: "r"(dst), "l"(src), "r"(bytes), "r"(bar) : "memory");
}
__device__ __forceinline__ void bulk_s2g(void* dst, uint32_t src, uint32_t bytes) {
    asm volatile("cp.async.bulk.global.shared::cta.bulk_group [%0], [%1], %2;" :: "l"(dst), "r"(src), "r"(bytes) : "memory");
}
__device__ __forceinline__ void tma2d_store(const CUtensorMap* tm, int c0, int c1, uint32_t src) {
    asm volatile("cp.async.bulk.tensor.2d.global.shared::cta.bulk_group [%0, {%2, %3}], [%1];"
        :: "l"((uint64_t)tm), "r"(src), "r"(c0), "r"(c1) : "memory");
}
__device__ __forceinline__ void l2_prefetch(const void* p, uint32_t bytes) {
    asm volatile("cp.async.bulk.prefetch.L2.global [%0], %1;" :: "l"(p), "r"(bytes) : "memory");
}
__device__ __forceinline__ void tmap_prefetch(const CUtensorMap* tm) { asm volatile("prefetch.tensormap [%0];" :: "l"((uint64_t)tm) : "memory"); }
__device__ __forceinline__ uint32_t lds32(uint32_t a) { uint32_t v; asm volatile("ld.shared.u32 %0, [%1];" : "=r"(v) : "r"(a)); return v; }
__device__ __forceinline__ uint2 lds64(uint32_t a) { uint2 v; asm volatile("ld.shared.v2.u32 {%0,%1}, [%2];" : "=r"(v.x), "=r"(v.y) : "r"(a)); return v; }
__device__ __forceinline__ uint4 lds128(uint32_t a) { uint4 v; asm volatile("ld.shared.v4.u32 {%0,%1,%2,%3}, [%4];" : "=r"(v.x), "=r"(v.y), "=r"(v.z), "=r"(v.w) : "r"(a)); return v; }
__device__ __forceinline__ void sts32(uint32_t a, uint32_t v) { asm volatile("st.shared.u32 [%0], %1;" :: "r"(a), "r"(v) : "memory"); }
__device__ __forceinline__ void sts128(uint32_t a, uint4 v) { asm volatile("st.shared.v4.u32 [%0], {%1,%2,%3,%4};" :: "r"(a), "r"(v.x), "r"(v.y), "r"(v.z), "r"(v.w) : "memory"); }
__device__ __forceinline__ uint4 ldg_cg128(const void* p) { uint4 v; asm volatile("ld.global.cg.v4.u32 {%0,%1,%2,%3}, [%4];" : "=r"(v.x), "=r"(v.y), "=r"(v.z), "=r"(v.w) : "l"(p)); return v; }
__device__ __forceinline__ uint4 ldg_nc128(const void* p) { uint4 v; asm volatile("ld.global.nc.L1::no_allocate.v4.u32 {%0,%1,%2,%3}, [%4];" : "=r"(v.x), "=r"(v.y), "=r"(v.z), "=r"(v.w) : "l"(p)); return v; }
__device__ __forceinline__ uint2 ldg_nc64(const void* p) { uint2 v; asm volatile("ld.global.nc.L1::no_allocate.v2.u32 {%0,%1}, [%2];" : "=r"(v.x), "=r"(v.y) : "l"(p)); return v; }
#define WG_FENCE() asm volatile("wgmma.fence.sync.aligned;\n" ::: "memory")
#define WG_COMMIT() asm volatile("wgmma.commit_group.sync.aligned;\n" ::: "memory")
template<int N> __device__ __forceinline__ void wg_wait() { asm volatile("wgmma.wait_group.sync.aligned %0;\n" :: "n"(N) : "memory"); }
__device__ __forceinline__ void named_bar(int id, int n) { asm volatile("bar.sync %0, %1;" :: "r"(id), "r"(n) : "memory"); }

__device__ __forceinline__ float bf_lo(uint32_t u) { return __uint_as_float(u << 16); }
__device__ __forceinline__ float bf_hi(uint32_t u) { return __uint_as_float(u & 0xFFFF0000u); }
__device__ __forceinline__ uint32_t pack_bf(float lo, float hi) { uint32_t r; asm("cvt.rn.bf16x2.f32 %0, %1, %2;" : "=r"(r) : "f"(hi), "f"(lo)); return r; }
__device__ __forceinline__ float bf_round(float x) { return __bfloat162float(__float2bfloat16_rn(x)); }
__device__ __forceinline__ uint32_t bmul2(uint32_t a, uint32_t b) { uint32_t r; asm("mul.rn.bf16x2 %0, %1, %2;" : "=r"(r) : "r"(a), "r"(b)); return r; }
__device__ __forceinline__ uint32_t badd2(uint32_t a, uint32_t b) { uint32_t r; asm("add.rn.bf16x2 %0, %1, %2;" : "=r"(r) : "r"(a), "r"(b)); return r; }
__device__ __forceinline__ uint32_t bsub2(uint32_t a, uint32_t b) { uint32_t r; asm("sub.rn.bf16x2 %0, %1, %2;" : "=r"(r) : "r"(a), "r"(b)); return r; }
__device__ __forceinline__ void mma16816(float (&d)[4], uint32_t a0, uint32_t a1, uint32_t a2, uint32_t a3, uint2 b) {
    asm volatile("mma.sync.aligned.m16n8k16.row.col.f32.bf16.bf16.f32 {%0,%1,%2,%3}, {%4,%5,%6,%7}, {%8,%9}, {%0,%1,%2,%3};\n"
        : "+f"(d[0]), "+f"(d[1]), "+f"(d[2]), "+f"(d[3]) : "r"(a0), "r"(a1), "r"(a2), "r"(a3), "r"(b.x), "r"(b.y));
}

template<int HS> __device__ __forceinline__ void xreduce(float (&v)[32], int lane) {
    const int up = lane & HS;
    #pragma unroll
    for (int e = 0; e < HS; e++) {
        float keep, send;
        asm("{\n.reg .pred p;\nsetp.ne.b32 p, %4, 0;\nselp.f32 %0, %3, %2, p;\nselp.f32 %1, %2, %3, p;\n}"
            : "=f"(keep), "=f"(send) : "f"(v[e]), "f"(v[e + HS]), "r"(up));
        v[e] = keep + __shfl_xor_sync(0xffffffffu, send, HS);
    }
}

__device__ __forceinline__ int blk_f0(int bi, int j) {
    if (bi < 32) return 224 * ((j + (bi >> 2)) & 7) + 32 * (bi & 3);
    int b2 = bi - 32; int q3 = (b2 * 11) >> 5;
    return 224 * ((j + q3) & 7) + 128 + 32 * (b2 - 3 * q3);
}
__device__ __forceinline__ int next_st2(int s) { return (0x14023 >> (4 * s)) & 7; }
__device__ __forceinline__ uint32_t stage_off_rt(int s) { return s < 3 ? SM_RING + s * STAGE_BYTES : (uint32_t)(s - 2) * STAGE_BYTES; }

template<int NB>
__device__ __forceinline__ void gemm1_pass(uint32_t sb, int wgi, int warp4, int lane, int& st, uint32_t& fph, uint32_t e_cl,
                                           int rb64, int ks0) {
    constexpr bool passA = (NB == 4);
    float acc[NB * 32];
    const uint64_t descA0 = make_desc(sb + SM_X + wgi * 8192, 16, 1024, 1);
    const uint64_t descB0 = make_desc(sb + SM_RING, 4096, 512, 2);
    int prev = 0;
    #pragma unroll 1
    for (int sl = 0; sl < 8; sl++) {
        if (warp4 == 0 && wgi == 0) PROF2(2, sl + (passA ? 0 : 8));
        mbar_wait(sb + SM_BARS + (B_FULL + st) * 8, (fph >> st) & 1);
        fph ^= 1u << st;
        if (sl == 0 && warp4 == 0) PROF(2 + wgi * 8 + (passA ? 0 : 3));
        if (warp4 == 0 && wgi == 0) PROF2(1, sl + (passA ? 0 : 8));
        const uint64_t da = desc_add(descA0, sl * 1024), db = desc_add(descB0, st * 2048);
        WG_FENCE();
        #pragma unroll
        for (int kk = 0; kk < 4; kk++) {
            int sc = (sl | kk) ? 1 : 0;
            if constexpr (NB == 4) wgmma_ss_n256_tb(acc, da + kk * 2, db + kk * 64, sc); else wgmma_ss_n192_tb(acc, da + kk * 2, db + kk * 64, sc);
        }
        WG_COMMIT();
        wg_wait<1>();
        if (warp4 == 0 && wgi == 0) PROF2(3, sl + (passA ? 0 : 8));
        if (lane < 2 && sl) mbar_arrive_cluster(e_cl + prev * 8, 1);
        if (!passA) {
            if (sl == 2 && lane == 0) mbar_arrive(sb + SM_BARS + B_XFREE * 8);
            if ((sl == 4 || sl == 6) && lane < 2) mbar_arrive_cluster(e_cl + (1 + (sl >> 1)) * 8, 1);
        }
        prev = st;
        st = (st == 2) ? 0 : st + 1;
    }
    wg_wait<0>();
    if (lane < 2) mbar_arrive_cluster(e_cl + prev * 8, 1);
    if (!passA && lane == 0) mbar_arrive(sb + SM_BARS + B_G1DONE * 8);
    if (warp4 == 0) PROF(3 + wgi * 8 + (passA ? 0 : 3));
    const int g = lane >> 2;
    const int r0 = wgi * 64 + warp4 * 16 + g;
    const float s0 = __uint_as_float(lds32(sb + SM_STATS + r0 * 4)), s1 = __uint_as_float(lds32(sb + SM_STATS + (r0 + 8) * 4));
    uint4* dst = g_hfrag + ((size_t)(rb64 * 112 + ks0) * 4 + warp4) * 32 + lane;
    #pragma unroll
    for (int kk = 0; kk < NB * 2; kk++) {
        uint32_t h[4];
        #pragma unroll
        for (int tt = 0; tt < 2; tt++) {
            const int t = 2 * kk + tt;
            const float* ag = &acc[4 * t];
            const float* au = &acc[NB * 16 + 4 * t];
            h[2 * tt] = bmul2(pack_bf(ag[0] * s0, ag[1] * s0), pack_bf(au[0] * s0, au[1] * s0));
            h[2 * tt + 1] = bmul2(pack_bf(ag[2] * s1, ag[3] * s1), pack_bf(au[2] * s1, au[3] * s1));
        }
        dst[kk * 128] = make_uint4(h[0], h[1], h[2], h[3]);
    }
    __syncwarp();
    if (lane == 0) mbar_arrive(sb + SM_BARS + (B_HD + wgi * 2 + (passA ? 0 : 1)) * 8);
    if (warp4 == 0) PROF(4 + wgi * 8 + (passA ? 0 : 3));
}

__global__ void __cluster_dims__(2, 1, 1) __launch_bounds__(NTHREADS, 1)
fused_kernel(const __grid_constant__ Params p) {
    extern __shared__ __align__(1024) uint8_t smem_raw[];
    const uint32_t sb = smem_u32(smem_raw);
    const int tid = threadIdx.x, warp = tid >> 5, lane = tid & 31;
    const int b = blockIdx.x;
    const int rank = b & 1;
    const int j = (b >> 1) & 7;
    const int i = ((b >> 4) << 1) | rank;
    const int cb = j >> 1;
    const int rbG2 = 2 * i + (j & 1);

    if (tid == 256) {
        mbar_init(sb + SM_BARS + B_XFULL * 8, 1);
        asm volatile("fence.proxy.async.shared::cta;" ::: "memory");
        mbar_expect_tx(sb + SM_BARS + B_XFULL * 8, 131072);
        for (int sl = 0; sl < 8; sl++)
            tma2d(sb + SM_X + sl * 16384, &p.tm_x, 64 * ((sl + 2 * cb + 2) & 7), 128 * i, sb + SM_BARS + B_XFULL * 8);
    }
    if (tid == 288) {
        tmap_prefetch(rank ? &p.tm_uA : &p.tm_gA);
        for (int s = 0; s < 5; s++) { mbar_init(sb + SM_BARS + (B_FULL + s) * 8, 1); mbar_init(sb + SM_BARS + (B_EMPTY + s) * 8, 16); }
        for (int s = 0; s < 4; s++) mbar_init(sb + SM_BARS + (B_CONV + s) * 8, 1);
        mbar_init(sb + SM_BARS + B_YT * 8, 1);
        mbar_init(sb + SM_BARS + B_XR * 8, 1);
        mbar_init(sb + SM_BARS + B_G1DONE * 8, 8);
        mbar_init(sb + SM_BARS + B_XFREE * 8, 8);
        mbar_init(sb + SM_BARS + B_CVDONE * 8, 1);
        sts32(sb + SM_CVCNT, 0);
        mbar_init(sb + SM_BARS + B_YST * 8, 4);
        for (int s = 0; s < 4; s++) mbar_init(sb + SM_BARS + (B_HD + s) * 8, 4);
        for (int s = 0; s < 2; s++) mbar_init(sb + SM_BARS + (B_HRDY + s) * 8, 1);
        asm volatile("fence.mbarrier_init.release.cluster;" ::: "memory");
        asm volatile("fence.proxy.async.shared::cta;" ::: "memory");
    }
    __syncwarp();
    asm volatile("barrier.cluster.arrive.relaxed.aligned;\nbarrier.cluster.wait.aligned;\n" ::: "memory");
    PROFW(1, 0);

    if (warp < 8) {
        asm volatile("setmaxnreg.inc.sync.aligned.u32 208;");
        const int wgi = warp >> 2, warp4 = warp & 3;
        const int g = lane >> 2, c = lane & 3;
        const uint32_t e_cl = mapa(sb + SM_BARS + B_EMPTY * 8, lane & 1);
        {
            const uint32_t xa = sb + SM_X + (lane >> 3) * 16384 + warp * 16 * 128;
            uint4 xr[16][2];
            float v[32];
            mbar_wait(sb + SM_BARS + B_XFULL * 8, 0);
            PROFW(16, 0);
            #pragma unroll
            for (int r = 0; r < 16; r++) {
                const uint32_t a = xa + r * 128 + (((lane & 7) ^ (r & 7)) << 4);
                xr[r][0] = lds128(a); xr[r][1] = lds128(a + 65536);
            }
            #pragma unroll
            for (int r = 0; r < 16; r++) {
                const uint32_t* u = (const uint32_t*)&xr[r][0];
                float s = 0.f, q = 0.f;
                #pragma unroll
                for (int e = 0; e < 8; e++) { const float lo = bf_lo(u[e]), hi = bf_hi(u[e]); s += lo; q = fmaf(lo, lo, q); s += hi; q = fmaf(hi, hi, q); }
                v[r] = s; v[16 + r] = q;
            }
            xreduce<16>(v, lane); xreduce<8>(v, lane); xreduce<4>(v, lane); xreduce<2>(v, lane); xreduce<1>(v, lane);
            const float other = __shfl_xor_sync(0xffffffffu, v[0], 16);
            const float mean = (lane < 16 ? v[0] : other) * (1.0f / DM);
            const float msq = (lane < 16 ? other : v[0]) * (1.0f / DM);
            const float var_b = bf_round(fmaxf(msq - mean * mean, 0.f));
            const float sd = bf_round(sqrtf(bf_round(var_b + 1e-5f)));
            if (lane < 16) sts32(sb + SM_STATS + (warp * 16 + lane) * 4, __float_as_uint(1.0f / sd));
            const uint32_t mb = pack_bf(mean, mean);
            #pragma unroll
            for (int r = 0; r < 16; r++) {
                const uint32_t m = __shfl_sync(0xffffffffu, mb, r);
                const uint32_t a = xa + r * 128 + (((lane & 7) ^ (r & 7)) << 4);
                #pragma unroll
                for (int hh = 0; hh < 2; hh++) {
                    uint4 t = xr[r][hh];
                    t.x = bsub2(t.x, m); t.y = bsub2(t.y, m); t.z = bsub2(t.z, m); t.w = bsub2(t.w, m);
                    sts128(a + hh * 65536, t);
                }
            }
            asm volatile("fence.proxy.async.shared::cta;" ::: "memory");
            named_bar(1 + wgi, 128);
            PROFW(17, 0);
        }
        int st = 0; uint32_t fph = 0;
        const int rb64 = 2 * i + wgi;
        gemm1_pass<4>(sb, wgi, warp4, lane, st, fph, e_cl, rb64, 14 * j);
        gemm1_pass<3>(sb, wgi, warp4, lane, st, fph, e_cl, rb64, 14 * j + 8);

        if (wgi == 1) {
            const int gch = 4 * b + warp4;
            const uint32_t xb = sb + SM_CVX + warp4 * 4096;
            const uint32_t hb = sb + SM_CVH + warp4 * 4096;
            const uint32_t dw = ((const unsigned short*)p.ssm_D)[gch];
            const uint32_t d2 = dw | (dw << 16);
            mbar_wait(sb + SM_BARS + (B_CONV + warp4) * 8, 0);
            PROFW(32, 4);
            float acc[16][4];
            #pragma unroll
            for (int jj = 0; jj < 16; jj++) { acc[jj][0] = 0.f; acc[jj][1] = 0.f; acc[jj][2] = 0.f; acc[jj][3] = 0.f; }
            uint2 bh[8], bl0[8], bl1[8];
            uint32_t xl = xb + g * 32 + c * 8;
            uint32_t hl = hb + (g + 2 * c - 8) * 4;
            #pragma unroll
            for (int d = 0; d < 8; d++) { bl0[d] = lds64(xl + d * 256); bh[d] = lds64(xl + (8 + d) * 256); }
            uint32_t w[6];
            w[0] = 0; w[1] = 0; w[2] = 0;
            if (g + 2 * c >= 8) w[0] = lds32(hl);
            if (g + 2 * c >= 7) w[1] = lds32(hl + 4);
            if (g + 2 * c >= 6) w[2] = lds32(hl + 8);
            w[3] = lds32(hl + 2048); w[4] = lds32(hl + 2052); w[5] = lds32(hl + 2056);
            auto conv_m0 = [&](int m0, uint2 (&bl)[8], uint2 (&bn)[8]) {
                xl -= 32;
                #pragma unroll
                for (int k = 0; k < 8; k++) {
                    const uint32_t a0 = w[1], a1 = __byte_perm(w[0], w[1], 0x5432), a2 = w[2], a3 = __byte_perm(w[1], w[2], 0x5432);
                    const uint32_t c0 = w[4], c1 = __byte_perm(w[3], w[4], 0x5432), c2 = w[5], c3 = __byte_perm(w[4], w[5], 0x5432);
                    const uint32_t nx = (k < 7) ? hl + (k + 1) * 256 : hl + 32;
                    w[0] = lds32(nx); w[1] = lds32(nx + 4); w[2] = lds32(nx + 8);
                    w[3] = lds32(nx + 2048); w[4] = lds32(nx + 2052); w[5] = lds32(nx + 2056);
                    if (k > 0) bn[k] = lds64(xl + k * 256);
                    else { bn[0] = make_uint2(0, 0); if (g > m0) bn[0] = lds64(xl); }
                    #pragma unroll
                    for (int jj = k; jj < 16; jj++) mma16816(acc[jj], a0, a1, a2, a3, (jj - k < 8) ? bl[(jj - k) & 7] : bh[(jj - k) & 7]);
                    bh[7 - k] = lds64(xl + (15 - k) * 256);
                    #pragma unroll
                    for (int jj = k + 8; jj < 16; jj++) mma16816(acc[jj], c0, c1, c2, c3, bl[jj - k - 8]);
                }
                hl += 32;
                if (lane == 0) asm volatile("red.shared.add.u32 [%0], 1;" :: "r"(sb + SM_CVCNT) : "memory");
            };
            #pragma unroll 1
            for (int m0 = 0; m0 < 8; m0 += 2) {
                conv_m0(m0, bl0, bl1);
                conv_m0(m0 + 1, bl1, bl0);
            }
            PROFW(33, 4);
            const uint32_t kvl = xb + c * 64 + (7 - g) * 4;
            const uint32_t yl = hb + c * 64 + g * 4;
            __syncwarp();
            #pragma unroll
            for (int jj = 0; jj < 16; jj++) {
                uint32_t k0 = lds32(kvl + jj * 256), k1 = lds32(kvl + jj * 256 + 32);
                k0 = __byte_perm(k0, k0, 0x1032); k1 = __byte_perm(k1, k1, 0x1032);
                sts32(yl + jj * 256, badd2(pack_bf(acc[jj][2], acc[jj][0]), bmul2(k0, d2)));
                sts32(yl + jj * 256 + 32, badd2(pack_bf(acc[jj][3], acc[jj][1]), bmul2(k1, d2)));
            }
            asm volatile("fence.proxy.async.shared::cta;" ::: "memory");
            __syncwarp();
            PROFW(44, 4);
            if (lane == 0) mbar_arrive(sb + SM_BARS + B_YST * 8);
            PROFW(45, 4);
        }
        {
            const uint4* hsrc = g_hfrag + ((size_t)rbG2 * 112 * 4 + warp4) * 32 + lane;
            const uint64_t descB0 = make_desc(sb, 4096, 1024, 1);
            int prev = 0;
            auto load_group = [&](uint4 (&dstf)[8], int u) {
                #pragma unroll
                for (int hb = 0; hb < 4; hb++) {
                    const int ks = blk_f0(4 * u + hb, j) >> 4;
                    dstf[2 * hb] = ldg_cg128(hsrc + ks * 128);
                    dstf[2 * hb + 1] = ldg_cg128(hsrc + ks * 128 + 128);
                }
            };
            auto g2_step = [&](float (&acc)[64], int u, int up, int un, uint4 (&cur)[8], uint4 (&nxt)[8], bool do_load) {
                const int u5 = (u * 13) >> 6;
                const int sg = (0x02143 >> (4 * (u - 5 * u5))) & 7;
                if (warp == 0) PROF2(2, 16 + u);
                mbar_wait(sb + SM_BARS + (B_FULL + sg) * 8, ((6u >> sg) ^ (uint32_t)u5) & 1);
                if (warp == 0) PROF2(1, 16 + u);
                const uint64_t db = desc_add(descB0, stage_off_rt(sg) >> 4);
                WG_FENCE();
                #pragma unroll
                for (int kk = 0; kk < 8; kk++)
                    wgmma_rs_n128_tb(acc, cur[kk].x, cur[kk].y, cur[kk].z, cur[kk].w, db + ((kk >> 1) * 512 + (kk & 1) * 128), (up >= 0 || kk) ? 1 : 0);
                WG_COMMIT();
                wg_wait<1>();
                if (warp == 0) PROF2(3, 16 + u);
                if (lane < 2 && up >= 0 && up + 5 < 14) mbar_arrive_cluster(e_cl + prev * 8, 2);
                prev = sg;
                if (do_load) load_group(nxt, un);
            };
            auto finish = [&](float (&acc)[64]) {
            PROFW(27, 0);
            named_bar(3, 256);
            {
                const uint32_t ex = sb + SM_RING + (tid & 127) * 16;
                #pragma unroll
                for (int q = 0; q < 8; q++) {
                    const float e0 = wgi ? acc[4 * q] : acc[32 + 4 * q], e1 = wgi ? acc[4 * q + 1] : acc[33 + 4 * q];
                    const float e2 = wgi ? acc[4 * q + 2] : acc[34 + 4 * q], e3 = wgi ? acc[4 * q + 3] : acc[35 + 4 * q];
                    sts128(ex + wgi * 16384 + q * 2048, make_uint4(__float_as_uint(e0), __float_as_uint(e1), __float_as_uint(e2), __float_as_uint(e3)));
                }
                named_bar(3, 256);
                #pragma unroll
                for (int q = 0; q < 8; q++) {
                    const uint4 t = lds128(ex + (wgi ^ 1) * 16384 + q * 2048);
                    acc[4 * q] = (wgi ? acc[32 + 4 * q] : acc[4 * q]) + __uint_as_float(t.x);
                    acc[4 * q + 1] = (wgi ? acc[33 + 4 * q] : acc[4 * q + 1]) + __uint_as_float(t.y);
                    acc[4 * q + 2] = (wgi ? acc[34 + 4 * q] : acc[4 * q + 2]) + __uint_as_float(t.z);
                    acc[4 * q + 3] = (wgi ? acc[35 + 4 * q] : acc[4 * q + 3]) + __uint_as_float(t.w);
                }
            }
            mbar_wait(sb + SM_BARS + B_XR * 8, 0);
            mbar_wait(sb + SM_BARS + B_YT * 8, 0);
            PROFW(28, 0);
            const int r0 = (j & 1) * 64 + warp4 * 16 + g;
            const float s0 = __uint_as_float(lds32(sb + SM_STATS + r0 * 4)), s1 = __uint_as_float(lds32(sb + SM_STATS + (r0 + 8) * 4));
            const uint32_t drow0 = sb + SM_XE + wgi * 16384 + r0 * 128 + c * 4;
            const uint32_t xrow0 = sb + SM_XE + wgi * 16384 + (r0 ^ 64) * 128 + c * 4;
            const int mi = lane >> 3, lr = lane & 7;
            const uint32_t yaddr = sb + SM_YT + wgi * 8192 + ((mi >> 1) * 8 + lr) * 128 + (((2 * warp4 + (mi & 1)) ^ lr) << 4);
            uint32_t y[4][4], xv[8][2], dv[8][2];
            #pragma unroll
            for (int t2 = 0; t2 < 4; t2++)
                asm volatile("ldmatrix.sync.aligned.m8n8.x4.trans.shared.b16 {%0,%1,%2,%3}, [%4];"
                    : "=r"(y[t2][0]), "=r"(y[t2][1]), "=r"(y[t2][2]), "=r"(y[t2][3]) : "r"(yaddr + t2 * 2048) : "memory");
            #pragma unroll
            for (int t = 0; t < 8; t++) {
                const uint32_t off = (t ^ g) << 4;
                xv[t][0] = lds32(xrow0 + off); xv[t][1] = lds32(xrow0 + 1024 + off);
                dv[t][0] = lds32(drow0 + off); dv[t][1] = lds32(drow0 + 1024 + off);
            }
            #pragma unroll
            for (int t = 0; t < 8; t++) {
                const uint32_t off = (t ^ g) << 4;
                const uint32_t n0 = pack_bf(bf_lo(dv[t][0]) * s0, bf_hi(dv[t][0]) * s0), n1 = pack_bf(bf_lo(dv[t][1]) * s1, bf_hi(dv[t][1]) * s1);
                const uint32_t o0 = badd2(badd2(xv[t][0], bmul2(n0, y[t >> 1][2 * (t & 1)])), pack_bf(acc[4 * t], acc[4 * t + 1]));
                const uint32_t o1 = badd2(badd2(xv[t][1], bmul2(n1, y[t >> 1][2 * (t & 1) + 1])), pack_bf(acc[4 * t + 2], acc[4 * t + 3]));
                sts32(xrow0 + off, o0); sts32(xrow0 + 1024 + off, o1);
            }
            asm volatile("fence.proxy.async.shared::cta;" ::: "memory");
            named_bar(1 + wgi, 128);
            if ((tid & 127) == 0) {
                tma2d_store(&p.tm_out, 128 * cb + 64 * wgi, 64 * rbG2, sb + SM_XE + wgi * 16384 + ((j & 1) ^ 1) * 8192);
                asm volatile("cp.async.bulk.commit_group;" ::: "memory");
                asm volatile("cp.async.bulk.wait_group.read 0;" ::: "memory");
                PROFW(29, 0);
            }
            };
            if (wgi == 0) {
                float acc[64];
                uint4 af[3][8];
                mbar_wait(sb + SM_BARS + B_HRDY * 8, 0);
                load_group(af[0], 0); load_group(af[1], 1);
                PROFW(20, 0);
                #pragma unroll
                for (int u0 = 0; u0 < 6; u0 += 3) {
                    pace_wait(sb + SM_CVCNT, 4 * (u0 + PACE0));
                    g2_step(acc, u0, u0 - 1, u0 + 2, af[0], af[2], true);
                    pace_wait(sb + SM_CVCNT, 4 * (u0 + 1 + PACE0));
                    g2_step(acc, u0 + 1, u0, u0 + 3, af[1], af[0], true);
                    pace_wait(sb + SM_CVCNT, 4 * (u0 + 2 + PACE0));
                    g2_step(acc, u0 + 2, u0 + 1, u0 + 4, af[2], af[1], true);
                }
                PROFW(22, 0);
                mbar_wait(sb + SM_BARS + (B_HRDY + 1) * 8, 0);
                pace_wait(sb + SM_CVCNT, 4 * (6 + PACE0));
                g2_step(acc, 6, 5, 8, af[0], af[2], true);
                g2_step(acc, 7, 6, 10, af[1], af[0], true);
                g2_step(acc, 8, 7, 12, af[2], af[1], true);
                PROFW(24, 0);
                g2_step(acc, 10, 8, -1, af[0], af[2], false);
                g2_step(acc, 12, 10, -1, af[1], af[0], false);
                wg_wait<0>();
                finish(acc);
            } else {
                float acc[64];
                uint4 af[3][8];
                mbar_wait(sb + SM_BARS + (B_HRDY + 1) * 8, 0);
                load_group(af[0], 9); load_group(af[1], 11); load_group(af[2], 13);
                g2_step(acc, 9, -1, -1, af[0], af[2], false);
                g2_step(acc, 11, 9, -1, af[1], af[0], false);
                g2_step(acc, 13, 11, -1, af[2], af[1], false);
                wg_wait<0>();
                finish(acc);
            }
        }
    } else {
        asm volatile("setmaxnreg.dec.sync.aligned.u32 88;");
        if (warp == 8) {
            if (lane == 0) {
                int st = 0; uint32_t eph = 7;
                #pragma unroll 1
                for (int it = 0; it < 16; it++) {
                    const int pass = it >> 3, sl = it & 7;
                    const int nb = pass ? 3 : 4;
                    const CUtensorMap* tm = pass ? (rank ? &p.tm_uB : &p.tm_gB) : (rank ? &p.tm_uA : &p.tm_gA);
                    mbar_wait(sb + SM_BARS + (B_EMPTY + st) * 8, (eph >> st) & 1);
                    eph ^= 1u << st;
                    PROF2(0, it);
                    mbar_expect_tx(sb + SM_BARS + (B_FULL + st) * 8, nb * 8192);
                    tma3d_mc(sb + SM_RING + st * STAGE_BYTES + rank * nb * 4096, tm, 0, ((sl + 2 * cb + 2) & 7) * 64, 7 * j + 4 * pass, sb + SM_BARS + (B_FULL + st) * 8);
                    st = (st == 2) ? 0 : st + 1;
                }
                st = 3;
                #pragma unroll 1
                for (int u = 0; u < 14; u++) {
                    mbar_wait(sb + SM_BARS + (B_EMPTY + st) * 8, (eph >> st) & 1);
                    eph ^= 1u << st;
                    PROF2(0, 16 + u);
                    const uint32_t so = sb + stage_off_rt(st) + rank * 8192;
                    mbar_expect_tx(sb + SM_BARS + (B_FULL + st) * 8, 32768);
                    tma3d_mc(so, &p.tm_w2, 0, blk_f0(4 * u + rank, j), 2 * cb, sb + SM_BARS + (B_FULL + st) * 8);
                    tma3d_mc(so + 16384, &p.tm_w2, 0, blk_f0(4 * u + 2 + rank, j), 2 * cb, sb + SM_BARS + (B_FULL + st) * 8);
                    st = next_st2(st);
                }
                PROF(48);
                const unsigned ep = lds32(sb + SM_EPOCH);
                mbar_wait(sb + SM_BARS + B_CVDONE * 8, 0);
                flag_wait(&g_cnt_y[cb * 32], ep * 32);
                PROF(49);
                asm volatile("fence.proxy.async.global;" ::: "memory");
                mbar_expect_tx(sb + SM_BARS + B_YT * 8, 16384);
                tma2d(sb + SM_YT, &p.tm_yT, 64 * rbG2, 128 * cb, sb + SM_BARS + B_YT * 8);
            }
        } else if (warp < 11) {
            mbar_wait(sb + SM_BARS + B_XFULL * 8, 0);
            #pragma unroll 1
            for (int rnd = 0; rnd < 2; rnd++) {
                const int tt = (tid - 288) + 64 * rnd;
                uint32_t sk[4][2];
                uint4 skw[2];
                skw[0] = ldg_nc128(p.shift_k + 16 * tt); skw[1] = ldg_nc128(p.shift_k + 16 * tt + 8);
                const __nv_bfloat16* kp = p.k + (size_t)(16 * b) * DM + 4 * tt;
                const __nv_bfloat16* vp = p.v + (size_t)(16 * b) * DM + 4 * tt;
                uint2 kr[19];
                uint2 kv[16];
                #pragma unroll
                for (int r = 0; r < 3; r++) kr[r] = (b > 0) ? ldg_nc64(kp + (r - 3) * DM) : make_uint2(0, 0);
                #pragma unroll
                for (int r = 0; r < 16; r++) { kr[3 + r] = ldg_nc64(kp + r * DM); if (r < 10) kv[r] = ldg_nc64(vp + r * DM); }
                {
                    const uint4 w0 = skw[0], w1 = skw[1];
                    sk[0][0] = __byte_perm(w0.x, w0.z, 0x5410); sk[1][0] = __byte_perm(w0.x, w0.z, 0x7632);
                    sk[2][0] = __byte_perm(w0.y, w0.w, 0x5410); sk[3][0] = __byte_perm(w0.y, w0.w, 0x7632);
                    sk[0][1] = __byte_perm(w1.x, w1.z, 0x5410); sk[1][1] = __byte_perm(w1.x, w1.z, 0x7632);
                    sk[2][1] = __byte_perm(w1.y, w1.w, 0x5410); sk[3][1] = __byte_perm(w1.y, w1.w, 0x7632);
                }
                #pragma unroll
                for (int s = 0; s < 16; s++) {
                    uint32_t a = bmul2(kr[s].x, sk[3][0]);
                    a = badd2(a, bmul2(kr[s + 1].x, sk[2][0]));
                    a = badd2(a, bmul2(kr[s + 2].x, sk[1][0]));
                    a = badd2(a, bmul2(kr[s + 3].x, sk[0][0]));
                    kv[s].x = bmul2(a, kv[s].x);
                    a = bmul2(kr[s].y, sk[3][1]);
                    a = badd2(a, bmul2(kr[s + 1].y, sk[2][1]));
                    a = badd2(a, bmul2(kr[s + 2].y, sk[1][1]));
                    a = badd2(a, bmul2(kr[s + 3].y, sk[0][1]));
                    kv[s].y = bmul2(a, kv[s].y);
                    if (s < 6) kv[10 + s] = ldg_nc64(vp + (10 + s) * DM);
                }
                PROFW(57 + 2 * rnd, 9);
                #pragma unroll
                for (int cc = 0; cc < 4; cc++) {
                    const uint32_t sel = (cc & 1) ? 0x7632 : 0x5410;
                    #define KVW(r) ((cc & 2) ? kv[r].y : kv[r].x)
                    uint4* dst = (uint4*)(g_kvT + (size_t)(4 * tt + cc) * SEQ + 16 * b);
                    dst[0] = make_uint4(__byte_perm(KVW(15), KVW(14), sel), __byte_perm(KVW(13), KVW(12), sel),
                                        __byte_perm(KVW(11), KVW(10), sel), __byte_perm(KVW(9), KVW(8), sel));
                    dst[1] = make_uint4(__byte_perm(KVW(7), KVW(6), sel), __byte_perm(KVW(5), KVW(4), sel),
                                        __byte_perm(KVW(3), KVW(2), sel), __byte_perm(KVW(1), KVW(0), sel));
                    #undef KVW
                }
                PROFW(58 + 2 * rnd, 9);
            }
            asm volatile("fence.proxy.async.global;" ::: "memory");
            __syncwarp();
            if (lane == 0) {
                flag_add(&g_cnt_kv[0]);
                PROFW(50, 9);
                const int wgi = warp - 9;
                mbar_wait(sb + SM_BARS + (B_HD + wgi * 2) * 8, 0);
                flag_add(&g_flag_h[((2 * i + wgi) * 2 + 0) * 8]);
                mbar_wait(sb + SM_BARS + (B_HD + wgi * 2 + 1) * 8, 0);
                flag_add(&g_flag_h[((2 * i + wgi) * 2 + 1) * 8]);
                if (wgi == 1) {
                    mbar_wait(sb + SM_BARS + B_YST * 8, 0);
                    bulk_s2g(g_yT + (size_t)(4 * b) * SEQ, sb + SM_CVH, 16384);
                    asm volatile("cp.async.bulk.commit_group;" ::: "memory");
                    asm volatile("cp.async.bulk.wait_group 0;" ::: "memory");
                    mbar_arrive(sb + SM_BARS + B_CVDONE * 8);
                    asm volatile("fence.proxy.async.global;" ::: "memory");
                    flag_add(&g_cnt_y[(b >> 5) * 32]);
                    PROF(46);
                }
            }
        } else {
            if (lane == 0) {
                const unsigned ep = g_launch[b] + 1;
                g_launch[b] = ep;
                sts32(sb + SM_EPOCH, ep);
                tmap_prefetch(rank ? &p.tm_uB : &p.tm_gB);
                tmap_prefetch(&p.tm_w2); tmap_prefetch(&p.tm_yT); tmap_prefetch(&p.tm_out); tmap_prefetch(&p.tm_xe);
                mbar_wait(sb + SM_BARS + (B_FULL + 2) * 8, 0);
                l2_prefetch(p.ssm_k + (size_t)(4 * b) * SEQ, 4 * SEQ * 2);
                l2_prefetch(p.wd + (size_t)b * (FF * DM / NCTA), FF * DM / NCTA * 2);
                mbar_wait(sb + SM_BARS + (B_HD + 0) * 8, 0);
                flag_wait(&g_cnt_kv[0], ep * 256);
                asm volatile("fence.proxy.async.global;" ::: "memory");
                PROF(53);
                mbar_wait(sb + SM_BARS + B_XFREE * 8, 0);
                PROF(54);
                for (int ch = 0; ch < 4; ch++) {
                    const uint32_t bar = sb + SM_BARS + (B_CONV + ch) * 8;
                    mbar_expect_tx(bar, 8192);
                    bulk_g2s(sb + SM_CVX + ch * 4096, g_kvT + (size_t)(4 * b + ch) * SEQ, 4096, bar);
                    bulk_g2s(sb + SM_CVH + ch * 4096, p.ssm_k + (size_t)(4 * b + ch) * SEQ, 4096, bar);
                }
                flag_wait(&g_flag_h[(rbG2 * 2 + 0) * 8], ep * 8);
                mbar_arrive(sb + SM_BARS + B_HRDY * 8);
                mbar_wait(sb + SM_BARS + B_G1DONE * 8, 0);
                mbar_expect_tx(sb + SM_BARS + B_XR * 8, 16384);
                tma2d(sb + SM_XE + ((j & 1) ^ 1) * 8192, &p.tm_xe, 128 * cb, 64 * rbG2, sb + SM_BARS + B_XR * 8);
                tma2d(sb + SM_XE + 16384 + ((j & 1) ^ 1) * 8192, &p.tm_xe, 128 * cb + 64, 64 * rbG2, sb + SM_BARS + B_XR * 8);
                flag_wait(&g_flag_h[(rbG2 * 2 + 1) * 8], ep * 8);
                mbar_arrive(sb + SM_BARS + (B_HRDY + 1) * 8);
            }
        }
    }
}

typedef CUresult (*EncodeFn)(CUtensorMap*, CUtensorMapDataType, cuuint32_t, void*, const cuuint64_t*, const cuuint64_t*,
                             const cuuint32_t*, const cuuint32_t*, CUtensorMapInterleave, CUtensorMapSwizzle,
                             CUtensorMapL2promotion, CUtensorMapFloatOOBfill);

void encode(EncodeFn fn, CUtensorMap* tm, const void* base, int rank, const cuuint64_t* dims, const cuuint64_t* strides,
            const cuuint32_t* box, CUtensorMapSwizzle swz) {
    cuuint32_t es[5] = {1, 1, 1, 1, 1};
    fn(tm, CU_TENSOR_MAP_DATA_TYPE_BFLOAT16, rank, (void*)base, dims, strides, box, es, CU_TENSOR_MAP_INTERLEAVE_NONE, swz,
       CU_TENSOR_MAP_L2_PROMOTION_L2_128B, CU_TENSOR_MAP_FLOAT_OOB_FILL_NONE);
}

}

extern "C" void kernel_launch(void* const* d_in, const int* in_sizes, int n_in, void* d_out, int out_size) {
    (void)in_sizes; (void)n_in; (void)out_size;
    static EncodeFn enc = nullptr;
    static void* yT_ptr = nullptr;
    if (!enc) {
        void* fn = nullptr; cudaDriverEntryPointQueryResult qr;
        cudaGetDriverEntryPoint("cuTensorMapEncodeTiled", &fn, cudaEnableDefault, &qr);
        enc = (EncodeFn)fn;
        cudaGetSymbolAddress(&yT_ptr, g_yT);
        cudaFuncSetAttribute(fused_kernel, cudaFuncAttributeMaxDynamicSharedMemorySize, SM_TOTAL);
    }
    Params p;
    p.q = (const __nv_bfloat16*)d_in[0]; p.k = (const __nv_bfloat16*)d_in[1]; p.v = (const __nv_bfloat16*)d_in[2];
    p.shift_k = (const __nv_bfloat16*)d_in[3]; p.ssm_k = (const __nv_bfloat16*)d_in[4]; p.ssm_D = (const __nv_bfloat16*)d_in[5];
    p.wg = (const __nv_bfloat16*)d_in[7]; p.wu = (const __nv_bfloat16*)d_in[8]; p.wd = (const __nv_bfloat16*)d_in[9];
    {
        cuuint64_t dims[2] = {DM, SEQ}; cuuint64_t str[1] = {DM * 2};
        cuuint32_t box[2] = {64, 128};
        encode(enc, &p.tm_x, p.q, 2, dims, str, box, CU_TENSOR_MAP_SWIZZLE_128B);
        cuuint32_t box2[2] = {64, 64};
        encode(enc, &p.tm_out, d_out, 2, dims, str, box2, CU_TENSOR_MAP_SWIZZLE_128B);
        encode(enc, &p.tm_xe, p.q, 2, dims, str, box2, CU_TENSOR_MAP_SWIZZLE_128B);
    }
    {
        cuuint64_t dims[3] = {32, DM, FF / 32}; cuuint64_t str[2] = {FF * 2, 64};
        cuuint32_t boxA[3] = {32, 64, 4}, boxB[3] = {32, 64, 3};
        encode(enc, &p.tm_gA, p.wg, 3, dims, str, boxA, CU_TENSOR_MAP_SWIZZLE_64B);
        encode(enc, &p.tm_gB, p.wg, 3, dims, str, boxB, CU_TENSOR_MAP_SWIZZLE_64B);
        encode(enc, &p.tm_uA, p.wu, 3, dims, str, boxA, CU_TENSOR_MAP_SWIZZLE_64B);
        encode(enc, &p.tm_uB, p.wu, 3, dims, str, boxB, CU_TENSOR_MAP_SWIZZLE_64B);
    }
    {
        cuuint64_t dims[3] = {64, FF, DM / 64}; cuuint64_t str[2] = {DM * 2, 128};
        cuuint32_t box[3] = {64, 32, 2};
        encode(enc, &p.tm_w2, p.wd, 3, dims, str, box, CU_TENSOR_MAP_SWIZZLE_128B);
    }
    {
        cuuint64_t dims[2] = {SEQ, DM}; cuuint64_t str[1] = {SEQ * 2};
        cuuint32_t box[2] = {64, 128};
        encode(enc, &p.tm_yT, yT_ptr, 2, dims, str, box, CU_TENSOR_MAP_SWIZZLE_128B);
    }
    fused_kernel<<<NCTA, NTHREADS, SM_TOTAL>>>(p);
}
```

```cpp
#include <cuda_runtime.h>
#include <cuda_bf16.h>
#include <cuda.h>
#include <stdint.h>

namespace {

constexpr int SEQ = 2048, DM = 512, FF = 1792;
constexpr int NCTA = 128;
constexpr int NTHREADS = 384;
constexpr int STAGE_BYTES = 32768;
#define PACE0 1
#define PACEM 2
#define PACE(u) (4 * ((PACE0 + (u) * PACEM) < 8 ? (PACE0 + (u) * PACEM) : 8))

constexpr uint32_t SM_X = 0;
constexpr uint32_t SM_RING = 131072;
constexpr uint32_t SM_MISC = SM_RING + 3 * STAGE_BYTES;
constexpr uint32_t SM_BARS = SM_MISC;
constexpr uint32_t SM_EPOCH = SM_MISC + 248;
constexpr uint32_t SM_CVCNT = SM_MISC + 252;
constexpr uint32_t SM_STATS = SM_MISC + 256;
constexpr uint32_t SM_TOTAL = SM_STATS + 512;
static_assert(SM_TOTAL <= 232448, "smem");
__host__ __device__ constexpr uint32_t stage_off(int s) { return s < 3 ? SM_RING + s * STAGE_BYTES : (uint32_t)(s - 2) * STAGE_BYTES; }
constexpr uint32_t SM_CVX = 0;
constexpr uint32_t SM_CVH = 16384;
constexpr uint32_t SM_YT = 0;
constexpr uint32_t SM_XE = 6 * 16384;

constexpr int B_FULL = 0, B_EMPTY = 5, B_XFULL = 10, B_CONV = 14, B_YT = 15, B_XR = 16, B_G1DONE = 17, B_HD = 18, B_HRDY = 22,
              B_XFREE = 24, B_YST = 25, B_COUNT = 26;
static_assert(B_COUNT * 8 <= 248, "barrier space");

__device__ uint4 g_hfrag[32 * 112 * 4 * 32];
__device__ __align__(128) __nv_bfloat16 g_kvT[DM * SEQ];
__device__ __align__(128) __nv_bfloat16 g_yT[DM * SEQ];
__device__ unsigned g_launch[NCTA];
__device__ unsigned g_cnt_kv[32];
__device__ unsigned g_cnt_y[4 * 32];
__device__ unsigned g_flag_h[32 * 2 * 8];

#define PROF(idx)
#define PROF2(a, idx)
#define PROFW(idx, w)

struct Params {
    CUtensorMap tm_x, tm_gA, tm_gB, tm_uA, tm_uB, tm_w2, tm_yT, tm_out, tm_xe;
    const __nv_bfloat16 *q, *k, *v, *shift_k, *ssm_k, *ssm_D, *wg, *wu, *wd;
};

__device__ __forceinline__ void wgmma_rs_n32(float (&d)[16], uint32_t a0, uint32_t a1, uint32_t a2, uint32_t a3, uint64_t db, int sc) {
  asm volatile("{\n.reg .pred p;\nsetp.ne.b32 p, %21, 0;\n"
    "wgmma.mma_async.sync.aligned.m64n32k16.f32.bf16.bf16 {%0,%1,%2,%3,%4,%5,%6,%7,%8,%9,%10,%11,%12,%13,%14,%15}, {%16,%17,%18,%19}, %20, p, 1, 1, 0;\n}\n"
    : "+f"(d[0]),"+f"(d[1]),"+f"(d[2]),"+f"(d[3]),"+f"(d[4]),"+f"(d[5]),"+f"(d[6]),"+f"(d[7]),"+f"(d[8]),"+f"(d[9]),"+f"(d[10]),"+f"(d[11]),"+f"(d[12]),"+f"(d[13]),"+f"(d[14]),"+f"(d[15])
    : "r"(a0),"r"(a1),"r"(a2),"r"(a3),"l"(db),"r"(sc));
}
__device__ __forceinline__ void wgmma_rs_n128_tb(float (&d)[64], uint32_t a0, uint32_t a1, uint32_t a2, uint32_t a3, uint64_t db, int sc) {
  asm volatile("{\n.reg .pred p;\nsetp.ne.b32 p, %69, 0;\n"
    "wgmma.mma_async.sync.aligned.m64n128k16.f32.bf16.bf16 {%0,%1,%2,%3,%4,%5,%6,%7,%8,%9,%10,%11,%12,%13,%14,%15,%16,%17,%18,%19,%20,%21,%22,%23,%24,%25,%26,%27,%28,%29,%30,%31,%32,%33,%34,%35,%36,%37,%38,%39,%40,%41,%42,%43,%44,%45,%46,%47,%48,%49,%50,%51,%52,%53,%54,%55,%56,%57,%58,%59,%60,%61,%62,%63}, {%64,%65,%66,%67}, %68, p, 1, 1, 1;\n}\n"
    : "+f"(d[0]),"+f"(d[1]),"+f"(d[2]),"+f"(d[3]),"+f"(d[4]),"+f"(d[5]),"+f"(d[6]),"+f"(d[7]),"+f"(d[8]),"+f"(d[9]),"+f"(d[10]),"+f"(d[11]),"+f"(d[12]),"+f"(d[13]),"+f"(d[14]),"+f"(d[15]),"+f"(d[16]),"+f"(d[17]),"+f"(d[18]),"+f"(d[19]),"+f"(d[20]),"+f"(d[21]),"+f"(d[22]),"+f"(d[23]),"+f"(d[24]),"+f"(d[25]),"+f"(d[26]),"+f"(d[27]),"+f"(d[28]),"+f"(d[29]),"+f"(d[30]),"+f"(d[31]),"+f"(d[32]),"+f"(d[33]),"+f"(d[34]),"+f"(d[35]),"+f"(d[36]),"+f"(d[37]),"+f"(d[38]),"+f"(d[39]),"+f"(d[40]),"+f"(d[41]),"+f"(d[42]),"+f"(d[43]),"+f"(d[44]),"+f"(d[45]),"+f"(d[46]),"+f"(d[47]),"+f"(d[48]),"+f"(d[49]),"+f"(d[50]),"+f"(d[51]),"+f"(d[52]),"+f"(d[53]),"+f"(d[54]),"+f"(d[55]),"+f"(d[56]),"+f"(d[57]),"+f"(d[58]),"+f"(d[59]),"+f"(d[60]),"+f"(d[61]),"+f"(d[62]),"+f"(d[63])
    : "r"(a0),"r"(a1),"r"(a2),"r"(a3),"l"(db),"r"(sc));
}
__device__ __forceinline__ void wgmma_ss_n256_tb(float (&d)[128], uint64_t da, uint64_t db, int sc) {
  asm volatile("{\n.reg .pred p;\nsetp.ne.b32 p, %130, 0;\n"
    "wgmma.mma_async.sync.aligned.m64n256k16.f32.bf16.bf16 {%0,%1,%2,%3,%4,%5,%6,%7,%8,%9,%10,%11,%12,%13,%14,%15,%16,%17,%18,%19,%20,%21,%22,%23,%24,%25,%26,%27,%28,%29,%30,%31,%32,%33,%34,%35,%36,%37,%38,%39,%40,%41,%42,%43,%44,%45,%46,%47,%48,%49,%50,%51,%52,%53,%54,%55,%56,%57,%58,%59,%60,%61,%62,%63,%64,%65,%66,%67,%68,%69,%70,%71,%72,%73,%74,%75,%76,%77,%78,%79,%80,%81,%82,%83,%84,%85,%86,%87,%88,%89,%90,%91,%92,%93,%94,%95,%96,%97,%98,%99,%100,%101,%102,%103,%104,%105,%106,%107,%108,%109,%110,%111,%112,%113,%114,%115,%116,%117,%118,%119,%120,%121,%122,%123,%124,%125,%126,%127}, %128, %129, p, 1, 1, 0, 1;\n}\n"
    : "+f"(d[0]),"+f"(d[1]),"+f"(d[2]),"+f"(d[3]),"+f"(d[4]),"+f"(d[5]),"+f"(d[6]),"+f"(d[7]),"+f"(d[8]),"+f"(d[9]),"+f"(d[10]),"+f"(d[11]),"+f"(d[12]),"+f"(d[13]),"+f"(d[14]),"+f"(d[15]),"+f"(d[16]),"+f"(d[17]),"+f"(d[18]),"+f"(d[19]),"+f"(d[20]),"+f"(d[21]),"+f"(d[22]),"+f"(d[23]),"+f"(d[24]),"+f"(d[25]),"+f"(d[26]),"+f"(d[27]),"+f"(d[28]),"+f"(d[29]),"+f"(d[30]),"+f"(d[31]),"+f"(d[32]),"+f"(d[33]),"+f"(d[34]),"+f"(d[35]),"+f"(d[36]),"+f"(d[37]),"+f"(d[38]),"+f"(d[39]),"+f"(d[40]),"+f"(d[41]),"+f"(d[42]),"+f"(d[43]),"+f"(d[44]),"+f"(d[45]),"+f"(d[46]),"+f"(d[47]),"+f"(d[48]),"+f"(d[49]),"+f"(d[50]),"+f"(d[51]),"+f"(d[52]),"+f"(d[53]),"+f"(d[54]),"+f"(d[55]),"+f"(d[56]),"+f"(d[57]),"+f"(d[58]),"+f"(d[59]),"+f"(d[60]),"+f"(d[61]),"+f"(d[62]),"+f"(d[63]),"+f"(d[64]),"+f"(d[65]),"+f"(d[66]),"+f"(d[67]),"+f"(d[68]),"+f"(d[69]),"+f"(d[70]),"+f"(d[71]),"+f"(d[72]),"+f"(d[73]),"+f"(d[74]),"+f"(d[75]),"+f"(d[76]),"+f"(d[77]),"+f"(d[78]),"+f"(d[79]),"+f"(d[80]),"+f"(d[81]),"+f"(d[82]),"+f"(d[83]),"+f"(d[84]),"+f"(d[85]),"+f"(d[86]),"+f"(d[87]),"+f"(d[88]),"+f"(d[89]),"+f"(d[90]),"+f"(d[91]),"+f"(d[92]),"+f"(d[93]),"+f"(d[94]),"+f"(d[95]),"+f"(d[96]),"+f"(d[97]),"+f"(d[98]),"+f"(d[99]),"+f"(d[100]),"+f"(d[101]),"+f"(d[102]),"+f"(d[103]),"+f"(d[104]),"+f"(d[105]),"+f"(d[106]),"+f"(d[107]),"+f"(d[108]),"+f"(d[109]),"+f"(d[110]),"+f"(d[111]),"+f"(d[112]),"+f"(d[113]),"+f"(d[114]),"+f"(d[115]),"+f"(d[116]),"+f"(d[117]),"+f"(d[118]),"+f"(d[119]),"+f"(d[120]),"+f"(d[121]),"+f"(d[122]),"+f"(d[123]),"+f"(d[124]),"+f"(d[125]),"+f"(d[126]),"+f"(d[127])
    : "l"(da),"l"(db),"r"(sc));
}
__device__ __forceinline__ void wgmma_ss_n192_tb(float (&d)[96], uint64_t da, uint64_t db, int sc) {
  asm volatile("{\n.reg .pred p;\nsetp.ne.b32 p, %98, 0;\n"
    "wgmma.mma_async.sync.aligned.m64n192k16.f32.bf16.bf16 {%0,%1,%2,%3,%4,%5,%6,%7,%8,%9,%10,%11,%12,%13,%14,%15,%16,%17,%18,%19,%20,%21,%22,%23,%24,%25,%26,%27,%28,%29,%30,%31,%32,%33,%34,%35,%36,%37,%38,%39,%40,%41,%42,%43,%44,%45,%46,%47,%48,%49,%50,%51,%52,%53,%54,%55,%56,%57,%58,%59,%60,%61,%62,%63,%64,%65,%66,%67,%68,%69,%70,%71,%72,%73,%74,%75,%76,%77,%78,%79,%80,%81,%82,%83,%84,%85,%86,%87,%88,%89,%90,%91,%92,%93,%94,%95}, %96, %97, p, 1, 1, 0, 1;\n}\n"
    : "+f"(d[0]),"+f"(d[1]),"+f"(d[2]),"+f"(d[3]),"+f"(d[4]),"+f"(d[5]),"+f"(d[6]),"+f"(d[7]),"+f"(d[8]),"+f"(d[9]),"+f"(d[10]),"+f"(d[11]),"+f"(d[12]),"+f"(d[13]),"+f"(d[14]),"+f"(d[15]),"+f"(d[16]),"+f"(d[17]),"+f"(d[18]),"+f"(d[19]),"+f"(d[20]),"+f"(d[21]),"+f"(d[22]),"+f"(d[23]),"+f"(d[24]),"+f"(d[25]),"+f"(d[26]),"+f"(d[27]),"+f"(d[28]),"+f"(d[29]),"+f"(d[30]),"+f"(d[31]),"+f"(d[32]),"+f"(d[33]),"+f"(d[34]),"+f"(d[35]),"+f"(d[36]),"+f"(d[37]),"+f"(d[38]),"+f"(d[39]),"+f"(d[40]),"+f"(d[41]),"+f"(d[42]),"+f"(d[43]),"+f"(d[44]),"+f"(d[45]),"+f"(d[46]),"+f"(d[47]),"+f"(d[48]),"+f"(d[49]),"+f"(d[50]),"+f"(d[51]),"+f"(d[52]),"+f"(d[53]),"+f"(d[54]),"+f"(d[55]),"+f"(d[56]),"+f"(d[57]),"+f"(d[58]),"+f"(d[59]),"+f"(d[60]),"+f"(d[61]),"+f"(d[62]),"+f"(d[63]),"+f"(d[64]),"+f"(d[65]),"+f"(d[66]),"+f"(d[67]),"+f"(d[68]),"+f"(d[69]),"+f"(d[70]),"+f"(d[71]),"+f"(d[72]),"+f"(d[73]),"+f"(d[74]),"+f"(d[75]),"+f"(d[76]),"+f"(d[77]),"+f"(d[78]),"+f"(d[79]),"+f"(d[80]),"+f"(d[81]),"+f"(d[82]),"+f"(d[83]),"+f"(d[84]),"+f"(d[85]),"+f"(d[86]),"+f"(d[87]),"+f"(d[88]),"+f"(d[89]),"+f"(d[90]),"+f"(d[91]),"+f"(d[92]),"+f"(d[93]),"+f"(d[94]),"+f"(d[95])
    : "l"(da),"l"(db),"r"(sc));
}

__device__ __forceinline__ uint32_t smem_u32(const void* p) { return (uint32_t)__cvta_generic_to_shared(p); }
__device__ __forceinline__ void mbar_init(uint32_t bar, uint32_t cnt) { asm volatile("mbarrier.init.shared::cta.b64 [%0], %1;" :: "r"(bar), "r"(cnt)); }
__device__ __forceinline__ void mbar_expect_tx(uint32_t bar, uint32_t bytes) { asm volatile("mbarrier.arrive.expect_tx.shared::cta.b64 _, [%0], %1;" :: "r"(bar), "r"(bytes) : "memory"); }
__device__ __forceinline__ void mbar_arrive(uint32_t bar) { asm volatile("mbarrier.arrive.shared::cta.b64 _, [%0];" :: "r"(bar) : "memory"); }
__device__ __forceinline__ void mbar_arrive_cluster(uint32_t cbar, uint32_t cnt) { asm volatile("mbarrier.arrive.shared::cluster.b64 _, [%0], %1;" :: "r"(cbar), "r"(cnt) : "memory"); }
__device__ __forceinline__ uint32_t mapa(uint32_t a, uint32_t rank) { uint32_t r; asm volatile("mapa.shared::cluster.u32 %0, %1, %2;" : "=r"(r) : "r"(a), "r"(rank)); return r; }
__device__ __forceinline__ void mbar_wait(uint32_t bar, uint32_t parity) {
    uint32_t ok; uint32_t n = 0;
    do {
        asm volatile("{\n.reg .pred p;\nmbarrier.try_wait.parity.shared::cta.b64 p, [%1], %2;\nselp.u32 %0, 1, 0, p;\n}" : "=r"(ok) : "r"(bar), "r"(parity) : "memory");
    } while (!ok && ++n < (1u << 17));
}
__device__ __forceinline__ void pace_wait(uint32_t a, uint32_t target) {
    uint32_t v, n = 0;
    do {
        asm volatile("ld.volatile.shared.u32 %0, [%1];" : "=r"(v) : "r"(a) : "memory");
        if (v < target) __nanosleep(40);
    } while (v < target && ++n < (1u << 14));
}
__device__ __forceinline__ void flag_wait(const unsigned* p, unsigned target) {
    unsigned v; uint32_t n = 0;
    while (true) {
        asm volatile("ld.acquire.gpu.global.u32 %0, [%1];" : "=r"(v) : "l"(p) : "memory");
        if ((int)(v - target) >= 0 || ++n >= (1u << 17)) break;
        __nanosleep(100);
    }
}
__device__ __forceinline__ void flag_add(unsigned* p) {
    asm volatile("fence.acq_rel.gpu;\nred.relaxed.gpu.global.add.u32 [%0], 1;" :: "l"(p) : "memory");
}
__device__ __forceinline__ uint64_t make_desc(uint32_t addr, uint32_t lbo, uint32_t sbo, uint32_t swz) {
    return (uint64_t)((addr & 0x3FFFF) >> 4) | ((uint64_t)((lbo & 0x3FFFF) >> 4) << 16) | ((uint64_t)((sbo & 0x3FFFF) >> 4) << 32) | ((uint64_t)swz << 62);
}
__device__ __forceinline__ uint64_t desc_add(uint64_t d, uint32_t off16) {
    return (d & 0xFFFFFFFF00000000ull) | (uint64_t)((uint32_t)d + off16);
}
__device__ __forceinline__ void tma2d(uint32_t dst, const CUtensorMap* tm, int c0, int c1, uint32_t bar) {
    asm volatile("cp.async.bulk.tensor.2d.shared::cluster.global.mbarrier::complete_tx::bytes [%0], [%1, {%3, %4}], [%2];"
        :: "r"(dst), "l"((uint64_t)tm), "r"(bar), "r"(c0), "r"(c1) : "memory");
}
__device__ __forceinline__ void tma3d_mc(uint32_t dst, const CUtensorMap* tm, int c0, int c1, int c2, uint32_t bar) {
    asm volatile("cp.async.bulk.tensor.3d.shared::cluster.global.mbarrier::complete_tx::bytes.multicast::cluster [%0], [%1, {%3, %4, %5}], [%2], %6;"
        :: "r"(dst), "l"((uint64_t)tm), "r"(bar), "r"(c0), "r"(c1), "r"(c2), "h"((uint16_t)3) : "memory");
}
__device__ __forceinline__ void bulk_g2s(uint32_t dst, const void* src, uint32_t bytes, uint32_t bar) {
    asm volatile("cp.async.bulk.shared::cluster.global.mbarrier::complete_tx::bytes [%0], [%1], %2, [%3];"
        :: "r"(dst), "l"(src), "r"(bytes), "r"(bar) : "memory");
}
__device__ __forceinline__ void bulk_s2g(void* dst, uint32_t src, uint32_t bytes) {
    asm volatile("cp.async.bulk.global.shared::cta.bulk_group [%0], [%1], %2;" :: "l"(dst), "r"(src), "r"(bytes) : "memory");
}
__device__ __forceinline__ void tma2d_store(const CUtensorMap* tm, int c0, int c1, uint32_t src) {
    asm volatile("cp.async.bulk.tensor.2d.global.shared::cta.bulk_group [%0, {%2, %3}], [%1];"
        :: "l"((uint64_t)tm), "r"(src), "r"(c0), "r"(c1) : "memory");
}
__device__ __forceinline__ void l2_prefetch(const void* p, uint32_t bytes) {
    asm volatile("cp.async.bulk.prefetch.L2.global [%0], %1;" :: "l"(p), "r"(bytes) : "memory");
}
__device__ __forceinline__ void tmap_prefetch(const CUtensorMap* tm) { asm volatile("prefetch.tensormap [%0];" :: "l"((uint64_t)tm) : "memory"); }
__device__ __forceinline__ uint32_t lds32(uint32_t a) { uint32_t v; asm volatile("ld.shared.u32 %0, [%1];" : "=r"(v) : "r"(a)); return v; }
__device__ __forceinline__ uint2 lds64(uint32_t a) { uint2 v; asm volatile("ld.shared.v2.u32 {%0,%1}, [%2];" : "=r"(v.x), "=r"(v.y) : "r"(a)); return v; }
__device__ __forceinline__ uint4 lds128(uint32_t a) { uint4 v; asm volatile("ld.shared.v4.u32 {%0,%1,%2,%3}, [%4];" : "=r"(v.x), "=r"(v.y), "=r"(v.z), "=r"(v.w) : "r"(a)); return v; }
__device__ __forceinline__ void sts32(uint32_t a, uint32_t v) { asm volatile("st.shared.u32 [%0], %1;" :: "r"(a), "r"(v) : "memory"); }
__device__ __forceinline__ void sts128(uint32_t a, uint4 v) { asm volatile("st.shared.v4.u32 [%0], {%1,%2,%3,%4};" :: "r"(a), "r"(v.x), "r"(v.y), "r"(v.z), "r"(v.w) : "memory"); }
__device__ __forceinline__ uint4 ldg_cg128(const void* p) { uint4 v; asm volatile("ld.global.cg.v4.u32 {%0,%1,%2,%3}, [%4];" : "=r"(v.x), "=r"(v.y), "=r"(v.z), "=r"(v.w) : "l"(p)); return v; }
__device__ __forceinline__ uint4 ldg_nc128(const void* p) { uint4 v; asm volatile("ld.global.nc.L1::no_allocate.v4.u32 {%0,%1,%2,%3}, [%4];" : "=r"(v.x), "=r"(v.y), "=r"(v.z), "=r"(v.w) : "l"(p)); return v; }
__device__ __forceinline__ uint2 ldg_nc64(const void* p) { uint2 v; asm volatile("ld.global.nc.L1::no_allocate.v2.u32 {%0,%1}, [%2];" : "=r"(v.x), "=r"(v.y) : "l"(p)); return v; }
#define WG_FENCE() asm volatile("wgmma.fence.sync.aligned;\n" ::: "memory")
#define WG_COMMIT() asm volatile("wgmma.commit_group.sync.aligned;\n" ::: "memory")
template<int N> __device__ __forceinline__ void wg_wait() { asm volatile("wgmma.wait_group.sync.aligned %0;\n" :: "n"(N) : "memory"); }
__device__ __forceinline__ void named_bar(int id, int n) { asm volatile("bar.sync %0, %1;" :: "r"(id), "r"(n) : "memory"); }

__device__ __forceinline__ float bf_lo(uint32_t u) { return __uint_as_float(u << 16); }
__device__ __forceinline__ float bf_hi(uint32_t u) { return __uint_as_float(u & 0xFFFF0000u); }
__device__ __forceinline__ uint32_t pack_bf(float lo, float hi) { uint32_t r; asm("cvt.rn.bf16x2.f32 %0, %1, %2;" : "=r"(r) : "f"(hi), "f"(lo)); return r; }
__device__ __forceinline__ float bf_round(float x) { return __bfloat162float(__float2bfloat16_rn(x)); }
__device__ __forceinline__ uint32_t bmul2(uint32_t a, uint32_t b) { uint32_t r; asm("mul.rn.bf16x2 %0, %1, %2;" : "=r"(r) : "r"(a), "r"(b)); return r; }
__device__ __forceinline__ uint32_t badd2(uint32_t a, uint32_t b) { uint32_t r; asm("add.rn.bf16x2 %0, %1, %2;" : "=r"(r) : "r"(a), "r"(b)); return r; }
__device__ __forceinline__ uint32_t bsub2(uint32_t a, uint32_t b) { uint32_t r; asm("sub.rn.bf16x2 %0, %1, %2;" : "=r"(r) : "r"(a), "r"(b)); return r; }
__device__ __forceinline__ void mma16816(float (&d)[4], uint32_t a0, uint32_t a1, uint32_t a2, uint32_t a3, uint2 b) {
    asm volatile("mma.sync.aligned.m16n8k16.row.col.f32.bf16.bf16.f32 {%0,%1,%2,%3}, {%4,%5,%6,%7}, {%8,%9}, {%0,%1,%2,%3};\n"
        : "+f"(d[0]), "+f"(d[1]), "+f"(d[2]), "+f"(d[3]) : "r"(a0), "r"(a1), "r"(a2), "r"(a3), "r"(b.x), "r"(b.y));
}

template<int HS> __device__ __forceinline__ void xreduce(float (&v)[32], int lane) {
    const int up = lane & HS;
    #pragma unroll
    for (int e = 0; e < HS; e++) {
        float keep, send;
        asm("{\n.reg .pred p;\nsetp.ne.b32 p, %4, 0;\nselp.f32 %0, %3, %2, p;\nselp.f32 %1, %2, %3, p;\n}"
            : "=f"(keep), "=f"(send) : "f"(v[e]), "f"(v[e + HS]), "r"(up));
        v[e] = keep + __shfl_xor_sync(0xffffffffu, send, HS);
    }
}

__device__ __forceinline__ int blk_f0(int bi, int j) {
    if (bi < 32) return 224 * ((j + (bi >> 2)) & 7) + 32 * (bi & 3);
    int b2 = bi - 32; int q3 = (b2 * 11) >> 5;
    return 224 * ((j + q3) & 7) + 128 + 32 * (b2 - 3 * q3);
}
__device__ __forceinline__ int next_st2(int s) { return (0x14023 >> (4 * s)) & 7; }
__device__ __forceinline__ uint32_t stage_off_rt(int s) { return s < 3 ? SM_RING + s * STAGE_BYTES : (uint32_t)(s - 2) * STAGE_BYTES; }

template<int NB>
__device__ __forceinline__ void gemm1_pass(uint32_t sb, int wgi, int warp4, int lane, int& st, uint32_t& fph, uint32_t e_cl,
                                           int rb64, int ks0) {
    constexpr bool passA = (NB == 4);
    float acc[NB * 32];
    const uint64_t descA0 = make_desc(sb + SM_X + wgi * 8192, 16, 1024, 1);
    const uint64_t descB0 = make_desc(sb + SM_RING, 4096, 512, 2);
    int prev = 0;
    #pragma unroll 1
    for (int sl = 0; sl < 8; sl++) {
        if (warp4 == 0 && wgi == 0) PROF2(2, sl + (passA ? 0 : 8));
        mbar_wait(sb + SM_BARS + (B_FULL + st) * 8, (fph >> st) & 1);
        fph ^= 1u << st;
        if (sl == 0 && warp4 == 0) PROF(2 + wgi * 8 + (passA ? 0 : 3));
        if (warp4 == 0 && wgi == 0) PROF2(1, sl + (passA ? 0 : 8));
        const uint64_t da = desc_add(descA0, sl * 1024), db = desc_add(descB0, st * 2048);
        WG_FENCE();
        #pragma unroll
        for (int kk = 0; kk < 4; kk++) {
            int sc = (sl | kk) ? 1 : 0;
            if constexpr (NB == 4) wgmma_ss_n256_tb(acc, da + kk * 2, db + kk * 64, sc); else wgmma_ss_n192_tb(acc, da + kk * 2, db + kk * 64, sc);
        }
        WG_COMMIT();
        wg_wait<1>();
        if (warp4 == 0 && wgi == 0) PROF2(3, sl + (passA ? 0 : 8));
        if (lane < 2 && sl) mbar_arrive_cluster(e_cl + prev * 8, 1);
        if (!passA) {
            if (sl == 2 && lane == 0) mbar_arrive(sb + SM_BARS + B_XFREE * 8);
            if ((sl == 4 || sl == 6) && lane < 2) mbar_arrive_cluster(e_cl + (1 + (sl >> 1)) * 8, 1);
        }
        prev = st;
        st = (st == 2) ? 0 : st + 1;
    }
    wg_wait<0>();
    if (lane < 2) mbar_arrive_cluster(e_cl + prev * 8, 1);
    if (!passA && lane == 0) mbar_arrive(sb + SM_BARS + B_G1DONE * 8);
    if (warp4 == 0) PROF(3 + wgi * 8 + (passA ? 0 : 3));
    const int g = lane >> 2;
    const int r0 = wgi * 64 + warp4 * 16 + g;
    const float s0 = __uint_as_float(lds32(sb + SM_STATS + r0 * 4)), s1 = __uint_as_float(lds32(sb + SM_STATS + (r0 + 8) * 4));
    uint4* dst = g_hfrag + ((size_t)(rb64 * 112 + ks0) * 4 + warp4) * 32 + lane;
    #pragma unroll
    for (int kk = 0; kk < NB * 2; kk++) {
        uint32_t h[4];
        #pragma unroll
        for (int tt = 0; tt < 2; tt++) {
            const int t = 2 * kk + tt;
            const float* ag = &acc[4 * t];
            const float* au = &acc[NB * 16 + 4 * t];
            h[2 * tt] = bmul2(pack_bf(ag[0] * s0, ag[1] * s0), pack_bf(au[0] * s0, au[1] * s0));
            h[2 * tt + 1] = bmul2(pack_bf(ag[2] * s1, ag[3] * s1), pack_bf(au[2] * s1, au[3] * s1));
        }
        dst[kk * 128] = make_uint4(h[0], h[1], h[2], h[3]);
    }
    __syncwarp();
    if (lane == 0) mbar_arrive(sb + SM_BARS + (B_HD + wgi * 2 + (passA ? 0 : 1)) * 8);
    if (warp4 == 0) PROF(4 + wgi * 8 + (passA ? 0 : 3));
}

__global__ void __cluster_dims__(2, 1, 1) __launch_bounds__(NTHREADS, 1)
fused_kernel(const __grid_constant__ Params p) {
    extern __shared__ __align__(1024) uint8_t smem_raw[];
    const uint32_t sb = smem_u32(smem_raw);
    const int tid = threadIdx.x, warp = tid >> 5, lane = tid & 31;
    const int b = blockIdx.x;
    const int rank = b & 1;
    const int j = (b >> 1) & 7;
    const int i = ((b >> 4) << 1) | rank;
    const int cb = j >> 1;
    const int rbG2 = 2 * i + (j & 1);

    if (warp == 8) {
        if (lane < 4) {
            mbar_init(sb + SM_BARS + (B_XFULL + lane) * 8, 1);
            asm volatile("fence.proxy.async.shared::cta;" ::: "memory");
            mbar_expect_tx(sb + SM_BARS + (B_XFULL + lane) * 8, 32768);
        }
        __syncwarp();
        const int rg = lane >> 3, sl = lane & 7;
        tma2d(sb + SM_X + sl * 16384 + rg * 4096, &p.tm_x, 64 * ((sl + 2 * cb + 2) & 7), 128 * i + 32 * rg, sb + SM_BARS + (B_XFULL + rg) * 8);
    }
    if (tid == 288) {
        tmap_prefetch(rank ? &p.tm_uA : &p.tm_gA);
        for (int s = 0; s < 5; s++) { mbar_init(sb + SM_BARS + (B_FULL + s) * 8, 1); mbar_init(sb + SM_BARS + (B_EMPTY + s) * 8, 16); }
        mbar_init(sb + SM_BARS + B_CONV * 8, 1);
        mbar_init(sb + SM_BARS + B_YT * 8, 1);
        mbar_init(sb + SM_BARS + B_XR * 8, 1);
        mbar_init(sb + SM_BARS + B_G1DONE * 8, 8);
        mbar_init(sb + SM_BARS + B_XFREE * 8, 8);
        sts32(sb + SM_CVCNT, 0);
        mbar_init(sb + SM_BARS + B_YST * 8, 4);
        for (int s = 0; s < 4; s++) mbar_init(sb + SM_BARS + (B_HD + s) * 8, 4);
        for (int s = 0; s < 2; s++) mbar_init(sb + SM_BARS + (B_HRDY + s) * 8, 1);
        asm volatile("fence.mbarrier_init.release.cluster;" ::: "memory");
        asm volatile("fence.proxy.async.shared::cta;" ::: "memory");
    }
    __syncwarp();
    asm volatile("barrier.cluster.arrive.relaxed.aligned;\nbarrier.cluster.wait.aligned;\n" ::: "memory");
    PROFW(1, 0);

    if (warp < 8) {
        asm volatile("setmaxnreg.inc.sync.aligned.u32 208;");
        const int wgi = warp >> 2, warp4 = warp & 3;
        const int g = lane >> 2, c = lane & 3;
        const uint32_t e_cl = mapa(sb + SM_BARS + B_EMPTY * 8, lane & 1);
        {
            const uint32_t xa = sb + SM_X + (lane >> 3) * 16384 + warp * 16 * 128;
            uint4 xr[16][2];
            float v[32];
            mbar_wait(sb + SM_BARS + (B_XFULL + (warp >> 1)) * 8, 0);
            PROFW(16, 0); PROFW(18, 7);
            #pragma unroll
            for (int r = 0; r < 16; r++) {
                const uint32_t a = xa + r * 128 + (((lane & 7) ^ (r & 7)) << 4);
                xr[r][0] = lds128(a); xr[r][1] = lds128(a + 65536);
            }
            #pragma unroll
            for (int r = 0; r < 16; r++) {
                const uint32_t* u = (const uint32_t*)&xr[r][0];
                float s = 0.f, q = 0.f;
                #pragma unroll
                for (int e = 0; e < 8; e++) { const float lo = bf_lo(u[e]), hi = bf_hi(u[e]); s += lo; q = fmaf(lo, lo, q); s += hi; q = fmaf(hi, hi, q); }
                v[r] = s; v[16 + r] = q;
            }
            xreduce<16>(v, lane); xreduce<8>(v, lane); xreduce<4>(v, lane); xreduce<2>(v, lane); xreduce<1>(v, lane);
            const float other = __shfl_xor_sync(0xffffffffu, v[0], 16);
            const float mean = (lane < 16 ? v[0] : other) * (1.0f / DM);
            const float msq = (lane < 16 ? other : v[0]) * (1.0f / DM);
            const float var_b = bf_round(fmaxf(msq - mean * mean, 0.f));
            const float sd = bf_round(sqrtf(bf_round(var_b + 1e-5f)));
            if (lane < 16) sts32(sb + SM_STATS + (warp * 16 + lane) * 4, __float_as_uint(1.0f / sd));
            const uint32_t mb = pack_bf(mean, mean);
            #pragma unroll
            for (int r = 0; r < 16; r++) {
                const uint32_t m = __shfl_sync(0xffffffffu, mb, r);
                const uint32_t a = xa + r * 128 + (((lane & 7) ^ (r & 7)) << 4);
                #pragma unroll
                for (int hh = 0; hh < 2; hh++) {
                    uint4 t = xr[r][hh];
                    t.x = bsub2(t.x, m); t.y = bsub2(t.y, m); t.z = bsub2(t.z, m); t.w = bsub2(t.w, m);
                    sts128(a + hh * 65536, t);
                }
            }
            asm volatile("fence.proxy.async.shared::cta;" ::: "memory");
            named_bar(1 + wgi, 128);
            PROFW(17, 0); PROFW(19, 7);
        }
        int st = 0; uint32_t fph = 0;
        const int rb64 = 2 * i + wgi;
        gemm1_pass<4>(sb, wgi, warp4, lane, st, fph, e_cl, rb64, 14 * j);
        gemm1_pass<3>(sb, wgi, warp4, lane, st, fph, e_cl, rb64, 14 * j + 8);

        if (wgi == 1) {
            const int gch = 4 * b + warp4;
            const uint32_t xb = sb + SM_CVX + warp4 * 4096;
            const uint32_t hb = sb + SM_CVH + warp4 * 4096;
            const uint32_t dw = ((const unsigned short*)p.ssm_D)[gch];
            const uint32_t d2 = dw | (dw << 16);
            mbar_wait(sb + SM_BARS + B_CONV * 8, 0);
            PROFW(32, 4);
            float acc[16][4];
            #pragma unroll
            for (int jj = 0; jj < 16; jj++) { acc[jj][0] = 0.f; acc[jj][1] = 0.f; acc[jj][2] = 0.f; acc[jj][3] = 0.f; }
            uint2 bh[8], bl0[8], bl1[8];
            uint32_t xl = xb + g * 32 + c * 8;
            uint32_t hl = hb + (g + 2 * c - 8) * 4;
            #pragma unroll
            for (int d = 0; d < 8; d++) { bl0[d] = lds64(xl + d * 256); bh[d] = lds64(xl + (8 + d) * 256); }
            uint32_t w[6];
            w[0] = 0; w[1] = 0; w[2] = 0;
            if (g + 2 * c >= 8) w[0] = lds32(hl);
            if (g + 2 * c >= 7) w[1] = lds32(hl + 4);
            if (g + 2 * c >= 6) w[2] = lds32(hl + 8);
            w[3] = lds32(hl + 2048); w[4] = lds32(hl + 2052); w[5] = lds32(hl + 2056);
            auto conv_m0 = [&](int m0, uint2 (&bl)[8], uint2 (&bn)[8]) {
                xl -= 32;
                #pragma unroll
                for (int k = 0; k < 8; k++) {
                    const uint32_t a0 = w[1], a1 = __byte_perm(w[0], w[1], 0x5432), a2 = w[2], a3 = __byte_perm(w[1], w[2], 0x5432);
                    const uint32_t c0 = w[4], c1 = __byte_perm(w[3], w[4], 0x5432), c2 = w[5], c3 = __byte_perm(w[4], w[5], 0x5432);
                    const uint32_t nx = (k < 7) ? hl + (k + 1) * 256 : hl + 32;
                    w[0] = lds32(nx); w[1] = lds32(nx + 4); w[2] = lds32(nx + 8);
                    w[3] = lds32(nx + 2048); w[4] = lds32(nx + 2052); w[5] = lds32(nx + 2056);
                    if (k > 0) bn[k] = lds64(xl + k * 256);
                    else { bn[0] = make_uint2(0, 0); if (g > m0) bn[0] = lds64(xl); }
                    #pragma unroll
                    for (int jj = k; jj < 16; jj++) mma16816(acc[jj], a0, a1, a2, a3, (jj - k < 8) ? bl[(jj - k) & 7] : bh[(jj - k) & 7]);
                    bh[7 - k] = lds64(xl + (15 - k) * 256);
                    #pragma unroll
                    for (int jj = k + 8; jj < 16; jj++) mma16816(acc[jj], c0, c1, c2, c3, bl[jj - k - 8]);
                }
                hl += 32;
                if (lane == 0) asm volatile("red.shared.add.u32 [%0], 1;" :: "r"(sb + SM_CVCNT) : "memory");
            };
            #pragma unroll 1
            for (int m0 = 0; m0 < 8; m0 += 2) {
                conv_m0(m0, bl0, bl1);
                conv_m0(m0 + 1, bl1, bl0);
            }
            PROFW(33, 4);
            const uint32_t kvl = xb + c * 64 + (7 - g) * 4;
            uint32_t* ydst = (uint32_t*)(g_yT + (size_t)gch * SEQ + 32 * c + 2 * g);
            uint32_t kk0[16], kk1[16];
            #pragma unroll
            for (int jj = 0; jj < 16; jj++) { kk0[jj] = lds32(kvl + jj * 256); kk1[jj] = lds32(kvl + jj * 256 + 32); }
            #pragma unroll
            for (int jj = 0; jj < 16; jj++) {
                ydst[jj * 64] = badd2(pack_bf(acc[jj][2], acc[jj][0]), bmul2(__byte_perm(kk0[jj], kk0[jj], 0x1032), d2));
                ydst[jj * 64 + 8] = badd2(pack_bf(acc[jj][3], acc[jj][1]), bmul2(__byte_perm(kk1[jj], kk1[jj], 0x1032), d2));
            }
            __syncwarp();
            PROFW(44, 4);
            if (lane == 0) mbar_arrive(sb + SM_BARS + B_YST * 8);
            PROFW(45, 4);
        }
        {
            const uint4* hsrc = g_hfrag + ((size_t)rbG2 * 112 * 4 + warp4) * 32 + lane;
            const uint64_t descB0 = make_desc(sb, 4096, 1024, 1);
            int prev = 0;
            auto load_group = [&](uint4 (&dstf)[8], int u) {
                #pragma unroll
                for (int hb = 0; hb < 4; hb++) {
                    const int ks = blk_f0(4 * u + hb, j) >> 4;
                    dstf[2 * hb] = ldg_cg128(hsrc + ks * 128);
                    dstf[2 * hb + 1] = ldg_cg128(hsrc + ks * 128 + 128);
                }
            };
            auto g2_step = [&](float (&acc)[64], int u, int up, int un, uint4 (&cur)[8], uint4 (&nxt)[8], bool do_load) {
                const int u5 = (u * 13) >> 6;
                const int sg = (0x02143 >> (4 * (u - 5 * u5))) & 7;
                if (warp == 0) PROF2(2, 16 + u);
                mbar_wait(sb + SM_BARS + (B_FULL + sg) * 8, ((6u >> sg) ^ (uint32_t)u5) & 1);
                if (warp == 0) PROF2(1, 16 + u);
                const uint64_t db = desc_add(descB0, stage_off_rt(sg) >> 4);
                WG_FENCE();
                #pragma unroll
                for (int kk = 0; kk < 8; kk++)
                    wgmma_rs_n128_tb(acc, cur[kk].x, cur[kk].y, cur[kk].z, cur[kk].w, db + ((kk >> 1) * 512 + (kk & 1) * 128), (up >= 0 || kk) ? 1 : 0);
                WG_COMMIT();
                wg_wait<1>();
                if (warp == 0) PROF2(3, 16 + u);
                if (lane < 2 && up >= 0 && up + 5 < 14) mbar_arrive_cluster(e_cl + prev * 8, 2);
                prev = sg;
                if (do_load) load_group(nxt, un);
            };
            auto finish = [&](float (&acc)[64]) {
            PROFW(27, 0);
            named_bar(3, 256);
            {
                const uint32_t ex = sb + SM_RING + (tid & 127) * 16;
                #pragma unroll
                for (int q = 0; q < 8; q++) {
                    const float e0 = wgi ? acc[4 * q] : acc[32 + 4 * q], e1 = wgi ? acc[4 * q + 1] : acc[33 + 4 * q];
                    const float e2 = wgi ? acc[4 * q + 2] : acc[34 + 4 * q], e3 = wgi ? acc[4 * q + 3] : acc[35 + 4 * q];
                    sts128(ex + wgi * 16384 + q * 2048, make_uint4(__float_as_uint(e0), __float_as_uint(e1), __float_as_uint(e2), __float_as_uint(e3)));
                }
                named_bar(3, 256);
                #pragma unroll
                for (int q = 0; q < 8; q++) {
                    const uint4 t = lds128(ex + (wgi ^ 1) * 16384 + q * 2048);
                    acc[4 * q] = (wgi ? acc[32 + 4 * q] : acc[4 * q]) + __uint_as_float(t.x);
                    acc[4 * q + 1] = (wgi ? acc[33 + 4 * q] : acc[4 * q + 1]) + __uint_as_float(t.y);
                    acc[4 * q + 2] = (wgi ? acc[34 + 4 * q] : acc[4 * q + 2]) + __uint_as_float(t.z);
                    acc[4 * q + 3] = (wgi ? acc[35 + 4 * q] : acc[4 * q + 3]) + __uint_as_float(t.w);
                }
            }
            mbar_wait(sb + SM_BARS + B_XR * 8, 0);
            mbar_wait(sb + SM_BARS + B_YT * 8, 0);
            PROFW(28, 0);
            const int r0 = (j & 1) * 64 + warp4 * 16 + g;
            const float s0 = __uint_as_float(lds32(sb + SM_STATS + r0 * 4)), s1 = __uint_as_float(lds32(sb + SM_STATS + (r0 + 8) * 4));
            const uint32_t drow0 = sb + SM_XE + wgi * 16384 + r0 * 128 + c * 4;
            const uint32_t xrow0 = sb + SM_XE + wgi * 16384 + (r0 ^ 64) * 128 + c * 4;
            const int mi = lane >> 3, lr = lane & 7;
            const uint32_t yaddr = sb + SM_YT + wgi * 8192 + ((mi >> 1) * 8 + lr) * 128 + (((2 * warp4 + (mi & 1)) ^ lr) << 4);
            uint32_t y[4][4], xv[8][2], dv[8][2];
            #pragma unroll
            for (int t2 = 0; t2 < 4; t2++)
                asm volatile("ldmatrix.sync.aligned.m8n8.x4.trans.shared.b16 {%0,%1,%2,%3}, [%4];"
                    : "=r"(y[t2][0]), "=r"(y[t2][1]), "=r"(y[t2][2]), "=r"(y[t2][3]) : "r"(yaddr + t2 * 2048) : "memory");
            #pragma unroll
            for (int t = 0; t < 8; t++) {
                const uint32_t off = (t ^ g) << 4;
                xv[t][0] = lds32(xrow0 + off); xv[t][1] = lds32(xrow0 + 1024 + off);
                dv[t][0] = lds32(drow0 + off); dv[t][1] = lds32(drow0 + 1024 + off);
            }
            #pragma unroll
            for (int t = 0; t < 8; t++) {
                const uint32_t off = (t ^ g) << 4;
                const uint32_t n0 = pack_bf(bf_lo(dv[t][0]) * s0, bf_hi(dv[t][0]) * s0), n1 = pack_bf(bf_lo(dv[t][1]) * s1, bf_hi(dv[t][1]) * s1);
                const uint32_t o0 = badd2(badd2(xv[t][0], bmul2(n0, y[t >> 1][2 * (t & 1)])), pack_bf(acc[4 * t], acc[4 * t + 1]));
                const uint32_t o1 = badd2(badd2(xv[t][1], bmul2(n1, y[t >> 1][2 * (t & 1) + 1])), pack_bf(acc[4 * t + 2], acc[4 * t + 3]));
                sts32(xrow0 + off, o0); sts32(xrow0 + 1024 + off, o1);
            }
            asm volatile("fence.proxy.async.shared::cta;" ::: "memory");
            named_bar(1 + wgi, 128);
            if ((tid & 127) == 0) {
                tma2d_store(&p.tm_out, 128 * cb + 64 * wgi, 64 * rbG2, sb + SM_XE + wgi * 16384 + ((j & 1) ^ 1) * 8192);
                asm volatile("cp.async.bulk.commit_group;" ::: "memory");
                asm volatile("cp.async.bulk.wait_group.read 0;" ::: "memory");
                PROFW(29, 0);
            }
            };
            if (wgi == 0) {
                float acc[64];
                uint4 af[3][8];
                mbar_wait(sb + SM_BARS + B_HRDY * 8, 0);
                load_group(af[0], 0); load_group(af[1], 1);
                PROFW(20, 0);
                #pragma unroll
                for (int u0 = 0; u0 < 6; u0 += 3) {
                    pace_wait(sb + SM_CVCNT, PACE(u0));
                    g2_step(acc, u0, u0 - 1, u0 + 2, af[0], af[2], true);
                    pace_wait(sb + SM_CVCNT, PACE(u0 + 1));
                    g2_step(acc, u0 + 1, u0, u0 + 3, af[1], af[0], true);
                    pace_wait(sb + SM_CVCNT, PACE(u0 + 2));
                    g2_step(acc, u0 + 2, u0 + 1, u0 + 4, af[2], af[1], true);
                }
                PROFW(22, 0);
                mbar_wait(sb + SM_BARS + (B_HRDY + 1) * 8, 0);
                pace_wait(sb + SM_CVCNT, PACE(6));
                g2_step(acc, 6, 5, 8, af[0], af[2], true);
                g2_step(acc, 7, 6, 10, af[1], af[0], true);
                g2_step(acc, 8, 7, 12, af[2], af[1], true);
                PROFW(24, 0);
                g2_step(acc, 10, 8, -1, af[0], af[2], false);
                g2_step(acc, 12, 10, -1, af[1], af[0], false);
                wg_wait<0>();
                finish(acc);
            } else {
                float acc[64];
                uint4 af[3][8];
                mbar_wait(sb + SM_BARS + (B_HRDY + 1) * 8, 0);
                load_group(af[0], 9); load_group(af[1], 11); load_group(af[2], 13);
                g2_step(acc, 9, -1, -1, af[0], af[2], false);
                g2_step(acc, 11, 9, -1, af[1], af[0], false);
                g2_step(acc, 13, 11, -1, af[2], af[1], false);
                wg_wait<0>();
                finish(acc);
            }
        }
    } else {
        asm volatile("setmaxnreg.dec.sync.aligned.u32 88;");
        if (warp == 8) {
            if (lane == 0) {
                int st = 0; uint32_t eph = 7;
                #pragma unroll 1
                for (int it = 0; it < 16; it++) {
                    const int pass = it >> 3, sl = it & 7;
                    const int nb = pass ? 3 : 4;
                    const CUtensorMap* tm = pass ? (rank ? &p.tm_uB : &p.tm_gB) : (rank ? &p.tm_uA : &p.tm_gA);
                    mbar_wait(sb + SM_BARS + (B_EMPTY + st) * 8, (eph >> st) & 1);
                    eph ^= 1u << st;
                    if (it == 1) mbar_wait(sb + SM_BARS + (B_XFULL + 2) * 8, 0);
                    PROF2(0, it);
                    mbar_expect_tx(sb + SM_BARS + (B_FULL + st) * 8, nb * 8192);
                    tma3d_mc(sb + SM_RING + st * STAGE_BYTES + rank * nb * 4096, tm, 0, ((sl + 2 * cb + 2) & 7) * 64, 7 * j + 4 * pass, sb + SM_BARS + (B_FULL + st) * 8);
                    st = (st == 2) ? 0 : st + 1;
                }
                st = 3;
                #pragma unroll 1
                for (int u = 0; u < 14; u++) {
                    mbar_wait(sb + SM_BARS + (B_EMPTY + st) * 8, (eph >> st) & 1);
                    eph ^= 1u << st;
                    PROF2(0, 16 + u);
                    const uint32_t so = sb + stage_off_rt(st) + rank * 8192;
                    mbar_expect_tx(sb + SM_BARS + (B_FULL + st) * 8, 32768);
                    tma3d_mc(so, &p.tm_w2, 0, blk_f0(4 * u + rank, j), 2 * cb, sb + SM_BARS + (B_FULL + st) * 8);
                    tma3d_mc(so + 16384, &p.tm_w2, 0, blk_f0(4 * u + 2 + rank, j), 2 * cb, sb + SM_BARS + (B_FULL + st) * 8);
                    st = next_st2(st);
                }
                PROF(48);
                const unsigned ep = lds32(sb + SM_EPOCH);
                mbar_wait(sb + SM_BARS + B_YST * 8, 0);
                flag_wait(&g_cnt_y[cb * 32], ep * 32);
                PROF(49);
                asm volatile("fence.proxy.async.global;" ::: "memory");
                mbar_expect_tx(sb + SM_BARS + B_YT * 8, 16384);
                tma2d(sb + SM_YT, &p.tm_yT, 64 * rbG2, 128 * cb, sb + SM_BARS + B_YT * 8);
            }
        } else if (warp < 11) {
            mbar_wait(sb + SM_BARS + (B_XFULL + 3) * 8, 0);
            #pragma unroll 1
            for (int rnd = 0; rnd < 2; rnd++) {
                const int tt = (tid - 288) + 64 * rnd;
                uint32_t sk[4][2];
                uint4 skw[2];
                skw[0] = ldg_nc128(p.shift_k + 16 * tt); skw[1] = ldg_nc128(p.shift_k + 16 * tt + 8);
                const __nv_bfloat16* kp = p.k + (size_t)(16 * b) * DM + 4 * tt;
                const __nv_bfloat16* vp = p.v + (size_t)(16 * b) * DM + 4 * tt;
                uint2 kr[19];
                uint2 kv[16];
                #pragma unroll
                for (int r = 0; r < 3; r++) kr[r] = (b > 0) ? ldg_nc64(kp + (r - 3) * DM) : make_uint2(0, 0);
                #pragma unroll
                for (int r = 0; r < 16; r++) { kr[3 + r] = ldg_nc64(kp + r * DM); if (r < 10) kv[r] = ldg_nc64(vp + r * DM); }
                {
                    const uint4 w0 = skw[0], w1 = skw[1];
                    sk[0][0] = __byte_perm(w0.x, w0.z, 0x5410); sk[1][0] = __byte_perm(w0.x, w0.z, 0x7632);
                    sk[2][0] = __byte_perm(w0.y, w0.w, 0x5410); sk[3][0] = __byte_perm(w0.y, w0.w, 0x7632);
                    sk[0][1] = __byte_perm(w1.x, w1.z, 0x5410); sk[1][1] = __byte_perm(w1.x, w1.z, 0x7632);
                    sk[2][1] = __byte_perm(w1.y, w1.w, 0x5410); sk[3][1] = __byte_perm(w1.y, w1.w, 0x7632);
                }
                #pragma unroll
                for (int s = 0; s < 16; s++) {
                    uint32_t a = bmul2(kr[s].x, sk[3][0]);
                    a = badd2(a, bmul2(kr[s + 1].x, sk[2][0]));
                    a = badd2(a, bmul2(kr[s + 2].x, sk[1][0]));
                    a = badd2(a, bmul2(kr[s + 3].x, sk[0][0]));
                    kv[s].x = bmul2(a, kv[s].x);
                    a = bmul2(kr[s].y, sk[3][1]);
                    a = badd2(a, bmul2(kr[s + 1].y, sk[2][1]));
                    a = badd2(a, bmul2(kr[s + 2].y, sk[1][1]));
                    a = badd2(a, bmul2(kr[s + 3].y, sk[0][1]));
                    kv[s].y = bmul2(a, kv[s].y);
                    if (s < 6) kv[10 + s] = ldg_nc64(vp + (10 + s) * DM);
                }
                PROFW(57 + 2 * rnd, 9);
                #pragma unroll
                for (int cc = 0; cc < 4; cc++) {
                    const uint32_t sel = (cc & 1) ? 0x7632 : 0x5410;
                    #define KVW(r) ((cc & 2) ? kv[r].y : kv[r].x)
                    uint4* dst = (uint4*)(g_kvT + (size_t)(4 * tt + cc) * SEQ + 16 * b);
                    dst[0] = make_uint4(__byte_perm(KVW(15), KVW(14), sel), __byte_perm(KVW(13), KVW(12), sel),
                                        __byte_perm(KVW(11), KVW(10), sel), __byte_perm(KVW(9), KVW(8), sel));
                    dst[1] = make_uint4(__byte_perm(KVW(7), KVW(6), sel), __byte_perm(KVW(5), KVW(4), sel),
                                        __byte_perm(KVW(3), KVW(2), sel), __byte_perm(KVW(1), KVW(0), sel));
                    #undef KVW
                }
                PROFW(58 + 2 * rnd, 9);
            }
            asm volatile("fence.proxy.async.global;" ::: "memory");
            __syncwarp();
            if (lane == 0) {
                flag_add(&g_cnt_kv[0]);
                PROFW(50, 9);
                const int wgi = warp - 9;
                mbar_wait(sb + SM_BARS + (B_HD + wgi * 2) * 8, 0);
                flag_add(&g_flag_h[((2 * i + wgi) * 2 + 0) * 8]);
                mbar_wait(sb + SM_BARS + (B_HD + wgi * 2 + 1) * 8, 0);
                flag_add(&g_flag_h[((2 * i + wgi) * 2 + 1) * 8]);
                if (wgi == 1) {
                    mbar_wait(sb + SM_BARS + B_YST * 8, 0);
                    asm volatile("fence.proxy.async.global;" ::: "memory");
                    flag_add(&g_cnt_y[(b >> 5) * 32]);
                    PROF(46);
                }
            }
        } else {
            if (lane == 0) {
                const unsigned ep = g_launch[b] + 1;
                g_launch[b] = ep;
                sts32(sb + SM_EPOCH, ep);
                tmap_prefetch(rank ? &p.tm_uB : &p.tm_gB);
                tmap_prefetch(&p.tm_w2); tmap_prefetch(&p.tm_yT); tmap_prefetch(&p.tm_out); tmap_prefetch(&p.tm_xe);
                mbar_wait(sb + SM_BARS + (B_FULL + 2) * 8, 0);
                l2_prefetch(p.ssm_k + (size_t)(4 * b) * SEQ, 4 * SEQ * 2);
                l2_prefetch(p.wd + (size_t)b * (FF * DM / NCTA), FF * DM / NCTA * 2);
                mbar_wait(sb + SM_BARS + (B_HD + 0) * 8, 0);
                flag_wait(&g_cnt_kv[0], ep * 256);
                asm volatile("fence.proxy.async.global;" ::: "memory");
                PROF(53);
                mbar_wait(sb + SM_BARS + B_XFREE * 8, 0);
                PROF(54);
                mbar_expect_tx(sb + SM_BARS + B_CONV * 8, 32768);
                bulk_g2s(sb + SM_CVX, g_kvT + (size_t)(4 * b) * SEQ, 16384, sb + SM_BARS + B_CONV * 8);
                bulk_g2s(sb + SM_CVH, p.ssm_k + (size_t)(4 * b) * SEQ, 16384, sb + SM_BARS + B_CONV * 8);
                flag_wait(&g_flag_h[(rbG2 * 2 + 0) * 8], ep * 8);
                mbar_arrive(sb + SM_BARS + B_HRDY * 8);
                mbar_wait(sb + SM_BARS + B_G1DONE * 8, 0);
                mbar_expect_tx(sb + SM_BARS + B_XR * 8, 16384);
                tma2d(sb + SM_XE + ((j & 1) ^ 1) * 8192, &p.tm_xe, 128 * cb, 64 * rbG2, sb + SM_BARS + B_XR * 8);
                tma2d(sb + SM_XE + 16384 + ((j & 1) ^ 1) * 8192, &p.tm_xe, 128 * cb + 64, 64 * rbG2, sb + SM_BARS + B_XR * 8);
                flag_wait(&g_flag_h[(rbG2 * 2 + 1) * 8], ep * 8);
                mbar_arrive(sb + SM_BARS + (B_HRDY + 1) * 8);
            }
        }
    }
}

typedef CUresult (*EncodeFn)(CUtensorMap*, CUtensorMapDataType, cuuint32_t, void*, const cuuint64_t*, const cuuint64_t*,
                             const cuuint32_t*, const cuuint32_t*, CUtensorMapInterleave, CUtensorMapSwizzle,
                             CUtensorMapL2promotion, CUtensorMapFloatOOBfill);

void encode(EncodeFn fn, CUtensorMap* tm, const void* base, int rank, const cuuint64_t* dims, const cuuint64_t* strides,
            const cuuint32_t* box, CUtensorMapSwizzle swz) {
    cuuint32_t es[5] = {1, 1, 1, 1, 1};
    fn(tm, CU_TENSOR_MAP_DATA_TYPE_BFLOAT16, rank, (void*)base, dims, strides, box, es, CU_TENSOR_MAP_INTERLEAVE_NONE, swz,
       CU_TENSOR_MAP_L2_PROMOTION_L2_128B, CU_TENSOR_MAP_FLOAT_OOB_FILL_NONE);
}

}

extern "C" void kernel_launch(void* const* d_in, const int* in_sizes, int n_in, void* d_out, int out_size) {
    (void)in_sizes; (void)n_in; (void)out_size;
    static EncodeFn enc = nullptr;
    static void* yT_ptr = nullptr;
    if (!enc) {
        void* fn = nullptr; cudaDriverEntryPointQueryResult qr;
        cudaGetDriverEntryPoint("cuTensorMapEncodeTiled", &fn, cudaEnableDefault, &qr);
        enc = (EncodeFn)fn;
        cudaGetSymbolAddress(&yT_ptr, g_yT);
        cudaFuncSetAttribute(fused_kernel, cudaFuncAttributeMaxDynamicSharedMemorySize, SM_TOTAL);
    }
    Params p;
    p.q = (const __nv_bfloat16*)d_in[0]; p.k = (const __nv_bfloat16*)d_in[1]; p.v = (const __nv_bfloat16*)d_in[2];
    p.shift_k = (const __nv_bfloat16*)d_in[3]; p.ssm_k = (const __nv_bfloat16*)d_in[4]; p.ssm_D = (const __nv_bfloat16*)d_in[5];
    p.wg = (const __nv_bfloat16*)d_in[7]; p.wu = (const __nv_bfloat16*)d_in[8]; p.wd = (const __nv_bfloat16*)d_in[9];
    {
        cuuint64_t dims[2] = {DM, SEQ}; cuuint64_t str[1] = {DM * 2};
        cuuint32_t box[2] = {64, 32};
        encode(enc, &p.tm_x, p.q, 2, dims, str, box, CU_TENSOR_MAP_SWIZZLE_128B);
        cuuint32_t box2[2] = {64, 64};
        encode(enc, &p.tm_out, d_out, 2, dims, str, box2, CU_TENSOR_MAP_SWIZZLE_128B);
        encode(enc, &p.tm_xe, p.q, 2, dims, str, box2, CU_TENSOR_MAP_SWIZZLE_128B);
    }
    {
        cuuint64_t dims[3] = {32, DM, FF / 32}; cuuint64_t str[2] = {FF * 2, 64};
        cuuint32_t boxA[3] = {32, 64, 4}, boxB[3] = {32, 64, 3};
        encode(enc, &p.tm_gA, p.wg, 3, dims, str, boxA, CU_TENSOR_MAP_SWIZZLE_64B);
        encode(enc, &p.tm_gB, p.wg, 3, dims, str, boxB, CU_TENSOR_MAP_SWIZZLE_64B);
        encode(enc, &p.tm_uA, p.wu, 3, dims, str, boxA, CU_TENSOR_MAP_SWIZZLE_64B);
        encode(enc, &p.tm_uB, p.wu, 3, dims, str, boxB, CU_TENSOR_MAP_SWIZZLE_64B);
    }
    {
        cuuint64_t dims[3] = {64, FF, DM / 64}; cuuint64_t str[2] = {DM * 2, 128};
        cuuint32_t box[3] = {64, 32, 2};
        encode(enc, &p.tm_w2, p.wd, 3, dims, str, box, CU_TENSOR_MAP_SWIZZLE_128B);
    }
    {
        cuuint64_t dims[2] = {SEQ, DM}; cuuint64_t str[1] = {SEQ * 2};
        cuuint32_t box[2] = {64, 128};
        encode(enc, &p.tm_yT, yT_ptr, 2, dims, str, box, CU_TENSOR_MAP_SWIZZLE_128B);
    }
    fused_kernel<<<NCTA, NTHREADS, SM_TOTAL>>>(p);
}
```

```cpp
#include <cuda_runtime.h>
#include <cuda_bf16.h>
#include <cuda.h>
#include <stdint.h>

namespace {

constexpr int SEQ = 2048, DM = 512, FF = 1792;
constexpr int NCTA = 128;
constexpr int NTHREADS = 384;
constexpr int STAGE_BYTES = 32768;
#define PACE0 1
#define PACEM 2
#define PACE(u) (4 * ((PACE0 + (u) * PACEM) < 8 ? (PACE0 + (u) * PACEM) : 8))

constexpr uint32_t SM_X = 0;
constexpr uint32_t SM_RING = 131072;
constexpr uint32_t SM_MISC = SM_RING + 3 * STAGE_BYTES;
constexpr uint32_t SM_BARS = SM_MISC;
constexpr uint32_t SM_EPOCH = SM_MISC + 248;
constexpr uint32_t SM_CVCNT = SM_MISC + 252;
constexpr uint32_t SM_STATS = SM_MISC + 256;
constexpr uint32_t SM_TOTAL = SM_STATS + 512;
static_assert(SM_TOTAL <= 232448, "smem");
__host__ __device__ constexpr uint32_t stage_off(int s) { return s < 3 ? SM_RING + s * STAGE_BYTES : (uint32_t)(s - 2) * STAGE_BYTES; }
constexpr uint32_t SM_CVX = 0;
constexpr uint32_t SM_CVH = 16384;
constexpr uint32_t SM_YT = 0;
constexpr uint32_t SM_XE = 6 * 16384;

constexpr int B_FULL = 0, B_EMPTY = 5, B_XFULL = 10, B_CONV = 14, B_YT = 15, B_XR = 16, B_G1DONE = 17, B_HD = 18, B_HRDY = 22,
              B_XFREE = 24, B_YST = 25, B_COUNT = 26;
static_assert(B_COUNT * 8 <= 248, "barrier space");

__device__ uint4 g_hfrag[32 * 112 * 4 * 32];
__device__ __align__(128) __nv_bfloat16 g_kvT[DM * SEQ];
__device__ __align__(128) __nv_bfloat16 g_yT[DM * SEQ];
__device__ unsigned g_launch[NCTA];
__device__ unsigned g_cnt_kv[32];
__device__ unsigned g_cnt_y[4 * 32];
__device__ unsigned g_flag_h[32 * 2 * 8];

#define PROF(idx)
#define PROF2(a, idx)
#define PROFW(idx, w)

struct Params {
    CUtensorMap tm_x, tm_gA, tm_gB, tm_uA, tm_uB, tm_w2, tm_yT, tm_out, tm_xe;
    const __nv_bfloat16 *q, *k, *v, *shift_k, *ssm_k, *ssm_D, *wg, *wu, *wd;
};

__device__ __forceinline__ void wgmma_rs_n32(float (&d)[16], uint32_t a0, uint32_t a1, uint32_t a2, uint32_t a3, uint64_t db, int sc) {
  asm volatile("{\n.reg .pred p;\nsetp.ne.b32 p, %21, 0;\n"
    "wgmma.mma_async.sync.aligned.m64n32k16.f32.bf16.bf16 {%0,%1,%2,%3,%4,%5,%6,%7,%8,%9,%10,%11,%12,%13,%14,%15}, {%16,%17,%18,%19}, %20, p, 1, 1, 0;\n}\n"
    : "+f"(d[0]),"+f"(d[1]),"+f"(d[2]),"+f"(d[3]),"+f"(d[4]),"+f"(d[5]),"+f"(d[6]),"+f"(d[7]),"+f"(d[8]),"+f"(d[9]),"+f"(d[10]),"+f"(d[11]),"+f"(d[12]),"+f"(d[13]),"+f"(d[14]),"+f"(d[15])
    : "r"(a0),"r"(a1),"r"(a2),"r"(a3),"l"(db),"r"(sc));
}
__device__ __forceinline__ void wgmma_rs_n128_tb(float (&d)[64], uint32_t a0, uint32_t a1, uint32_t a2, uint32_t a3, uint64_t db, int sc) {
  asm volatile("{\n.reg .pred p;\nsetp.ne.b32 p, %69, 0;\n"
    "wgmma.mma_async.sync.aligned.m64n128k16.f32.bf16.bf16 {%0,%1,%2,%3,%4,%5,%6,%7,%8,%9,%10,%11,%12,%13,%14,%15,%16,%17,%18,%19,%20,%21,%22,%23,%24,%25,%26,%27,%28,%29,%30,%31,%32,%33,%34,%35,%36,%37,%38,%39,%40,%41,%42,%43,%44,%45,%46,%47,%48,%49,%50,%51,%52,%53,%54,%55,%56,%57,%58,%59,%60,%61,%62,%63}, {%64,%65,%66,%67}, %68, p, 1, 1, 1;\n}\n"
    : "+f"(d[0]),"+f"(d[1]),"+f"(d[2]),"+f"(d[3]),"+f"(d[4]),"+f"(d[5]),"+f"(d[6]),"+f"(d[7]),"+f"(d[8]),"+f"(d[9]),"+f"(d[10]),"+f"(d[11]),"+f"(d[12]),"+f"(d[13]),"+f"(d[14]),"+f"(d[15]),"+f"(d[16]),"+f"(d[17]),"+f"(d[18]),"+f"(d[19]),"+f"(d[20]),"+f"(d[21]),"+f"(d[22]),"+f"(d[23]),"+f"(d[24]),"+f"(d[25]),"+f"(d[26]),"+f"(d[27]),"+f"(d[28]),"+f"(d[29]),"+f"(d[30]),"+f"(d[31]),"+f"(d[32]),"+f"(d[33]),"+f"(d[34]),"+f"(d[35]),"+f"(d[36]),"+f"(d[37]),"+f"(d[38]),"+f"(d[39]),"+f"(d[40]),"+f"(d[41]),"+f"(d[42]),"+f"(d[43]),"+f"(d[44]),"+f"(d[45]),"+f"(d[46]),"+f"(d[47]),"+f"(d[48]),"+f"(d[49]),"+f"(d[50]),"+f"(d[51]),"+f"(d[52]),"+f"(d[53]),"+f"(d[54]),"+f"(d[55]),"+f"(d[56]),"+f"(d[57]),"+f"(d[58]),"+f"(d[59]),"+f"(d[60]),"+f"(d[61]),"+f"(d[62]),"+f"(d[63])
    : "r"(a0),"r"(a1),"r"(a2),"r"(a3),"l"(db),"r"(sc));
}
__device__ __forceinline__ void wgmma_ss_n256_tb(float (&d)[128], uint64_t da, uint64_t db, int sc) {
  asm volatile("{\n.reg .pred p;\nsetp.ne.b32 p, %130, 0;\n"
    "wgmma.mma_async.sync.aligned.m64n256k16.f32.bf16.bf16 {%0,%1,%2,%3,%4,%5,%6,%7,%8,%9,%10,%11,%12,%13,%14,%15,%16,%17,%18,%19,%20,%21,%22,%23,%24,%25,%26,%27,%28,%29,%30,%31,%32,%33,%34,%35,%36,%37,%38,%39,%40,%41,%42,%43,%44,%45,%46,%47,%48,%49,%50,%51,%52,%53,%54,%55,%56,%57,%58,%59,%60,%61,%62,%63,%64,%65,%66,%67,%68,%69,%70,%71,%72,%73,%74,%75,%76,%77,%78,%79,%80,%81,%82,%83,%84,%85,%86,%87,%88,%89,%90,%91,%92,%93,%94,%95,%96,%97,%98,%99,%100,%101,%102,%103,%104,%105,%106,%107,%108,%109,%110,%111,%112,%113,%114,%115,%116,%117,%118,%119,%120,%121,%122,%123,%124,%125,%126,%127}, %128, %129, p, 1, 1, 0, 1;\n}\n"
    : "+f"(d[0]),"+f"(d[1]),"+f"(d[2]),"+f"(d[3]),"+f"(d[4]),"+f"(d[5]),"+f"(d[6]),"+f"(d[7]),"+f"(d[8]),"+f"(d[9]),"+f"(d[10]),"+f"(d[11]),"+f"(d[12]),"+f"(d[13]),"+f"(d[14]),"+f"(d[15]),"+f"(d[16]),"+f"(d[17]),"+f"(d[18]),"+f"(d[19]),"+f"(d[20]),"+f"(d[21]),"+f"(d[22]),"+f"(d[23]),"+f"(d[24]),"+f"(d[25]),"+f"(d[26]),"+f"(d[27]),"+f"(d[28]),"+f"(d[29]),"+f"(d[30]),"+f"(d[31]),"+f"(d[32]),"+f"(d[33]),"+f"(d[34]),"+f"(d[35]),"+f"(d[36]),"+f"(d[37]),"+f"(d[38]),"+f"(d[39]),"+f"(d[40]),"+f"(d[41]),"+f"(d[42]),"+f"(d[43]),"+f"(d[44]),"+f"(d[45]),"+f"(d[46]),"+f"(d[47]),"+f"(d[48]),"+f"(d[49]),"+f"(d[50]),"+f"(d[51]),"+f"(d[52]),"+f"(d[53]),"+f"(d[54]),"+f"(d[55]),"+f"(d[56]),"+f"(d[57]),"+f"(d[58]),"+f"(d[59]),"+f"(d[60]),"+f"(d[61]),"+f"(d[62]),"+f"(d[63]),"+f"(d[64]),"+f"(d[65]),"+f"(d[66]),"+f"(d[67]),"+f"(d[68]),"+f"(d[69]),"+f"(d[70]),"+f"(d[71]),"+f"(d[72]),"+f"(d[73]),"+f"(d[74]),"+f"(d[75]),"+f"(d[76]),"+f"(d[77]),"+f"(d[78]),"+f"(d[79]),"+f"(d[80]),"+f"(d[81]),"+f"(d[82]),"+f"(d[83]),"+f"(d[84]),"+f"(d[85]),"+f"(d[86]),"+f"(d[87]),"+f"(d[88]),"+f"(d[89]),"+f"(d[90]),"+f"(d[91]),"+f"(d[92]),"+f"(d[93]),"+f"(d[94]),"+f"(d[95]),"+f"(d[96]),"+f"(d[97]),"+f"(d[98]),"+f"(d[99]),"+f"(d[100]),"+f"(d[101]),"+f"(d[102]),"+f"(d[103]),"+f"(d[104]),"+f"(d[105]),"+f"(d[106]),"+f"(d[107]),"+f"(d[108]),"+f"(d[109]),"+f"(d[110]),"+f"(d[111]),"+f"(d[112]),"+f"(d[113]),"+f"(d[114]),"+f"(d[115]),"+f"(d[116]),"+f"(d[117]),"+f"(d[118]),"+f"(d[119]),"+f"(d[120]),"+f"(d[121]),"+f"(d[122]),"+f"(d[123]),"+f"(d[124]),"+f"(d[125]),"+f"(d[126]),"+f"(d[127])
    : "l"(da),"l"(db),"r"(sc));
}
__device__ __forceinline__ void wgmma_ss_n192_tb(float (&d)[96], uint64_t da, uint64_t db, int sc) {
  asm volatile("{\n.reg .pred p;\nsetp.ne.b32 p, %98, 0;\n"
    "wgmma.mma_async.sync.aligned.m64n192k16.f32.bf16.bf16 {%0,%1,%2,%3,%4,%5,%6,%7,%8,%9,%10,%11,%12,%13,%14,%15,%16,%17,%18,%19,%20,%21,%22,%23,%24,%25,%26,%27,%28,%29,%30,%31,%32,%33,%34,%35,%36,%37,%38,%39,%40,%41,%42,%43,%44,%45,%46,%47,%48,%49,%50,%51,%52,%53,%54,%55,%56,%57,%58,%59,%60,%61,%62,%63,%64,%65,%66,%67,%68,%69,%70,%71,%72,%73,%74,%75,%76,%77,%78,%79,%80,%81,%82,%83,%84,%85,%86,%87,%88,%89,%90,%91,%92,%93,%94,%95}, %96, %97, p, 1, 1, 0, 1;\n}\n"
    : "+f"(d[0]),"+f"(d[1]),"+f"(d[2]),"+f"(d[3]),"+f"(d[4]),"+f"(d[5]),"+f"(d[6]),"+f"(d[7]),"+f"(d[8]),"+f"(d[9]),"+f"(d[10]),"+f"(d[11]),"+f"(d[12]),"+f"(d[13]),"+f"(d[14]),"+f"(d[15]),"+f"(d[16]),"+f"(d[17]),"+f"(d[18]),"+f"(d[19]),"+f"(d[20]),"+f"(d[21]),"+f"(d[22]),"+f"(d[23]),"+f"(d[24]),"+f"(d[25]),"+f"(d[26]),"+f"(d[27]),"+f"(d[28]),"+f"(d[29]),"+f"(d[30]),"+f"(d[31]),"+f"(d[32]),"+f"(d[33]),"+f"(d[34]),"+f"(d[35]),"+f"(d[36]),"+f"(d[37]),"+f"(d[38]),"+f"(d[39]),"+f"(d[40]),"+f"(d[41]),"+f"(d[42]),"+f"(d[43]),"+f"(d[44]),"+f"(d[45]),"+f"(d[46]),"+f"(d[47]),"+f"(d[48]),"+f"(d[49]),"+f"(d[50]),"+f"(d[51]),"+f"(d[52]),"+f"(d[53]),"+f"(d[54]),"+f"(d[55]),"+f"(d[56]),"+f"(d[57]),"+f"(d[58]),"+f"(d[59]),"+f"(d[60]),"+f"(d[61]),"+f"(d[62]),"+f"(d[63]),"+f"(d[64]),"+f"(d[65]),"+f"(d[66]),"+f"(d[67]),"+f"(d[68]),"+f"(d[69]),"+f"(d[70]),"+f"(d[71]),"+f"(d[72]),"+f"(d[73]),"+f"(d[74]),"+f"(d[75]),"+f"(d[76]),"+f"(d[77]),"+f"(d[78]),"+f"(d[79]),"+f"(d[80]),"+f"(d[81]),"+f"(d[82]),"+f"(d[83]),"+f"(d[84]),"+f"(d[85]),"+f"(d[86]),"+f"(d[87]),"+f"(d[88]),"+f"(d[89]),"+f"(d[90]),"+f"(d[91]),"+f"(d[92]),"+f"(d[93]),"+f"(d[94]),"+f"(d[95])
    : "l"(da),"l"(db),"r"(sc));
}

__device__ __forceinline__ uint32_t smem_u32(const void* p) { return (uint32_t)__cvta_generic_to_shared(p); }
__device__ __forceinline__ void mbar_init(uint32_t bar, uint32_t cnt) { asm volatile("mbarrier.init.shared::cta.b64 [%0], %1;" :: "r"(bar), "r"(cnt)); }
__device__ __forceinline__ void mbar_expect_tx(uint32_t bar, uint32_t bytes) { asm volatile("mbarrier.arrive.expect_tx.shared::cta.b64 _, [%0], %1;" :: "r"(bar), "r"(bytes) : "memory"); }
__device__ __forceinline__ void mbar_arrive(uint32_t bar) { asm volatile("mbarrier.arrive.shared::cta.b64 _, [%0];" :: "r"(bar) : "memory"); }
__device__ __forceinline__ void mbar_arrive_cluster(uint32_t cbar, uint32_t cnt) { asm volatile("mbarrier.arrive.shared::cluster.b64 _, [%0], %1;" :: "r"(cbar), "r"(cnt) : "memory"); }
__device__ __forceinline__ uint32_t mapa(uint32_t a, uint32_t rank) { uint32_t r; asm volatile("mapa.shared::cluster.u32 %0, %1, %2;" : "=r"(r) : "r"(a), "r"(rank)); return r; }
__device__ __forceinline__ void mbar_wait(uint32_t bar, uint32_t parity) {
    uint32_t ok; uint32_t n = 0;
    do {
        asm volatile("{\n.reg .pred p;\nmbarrier.try_wait.parity.shared::cta.b64 p, [%1], %2;\nselp.u32 %0, 1, 0, p;\n}" : "=r"(ok) : "r"(bar), "r"(parity) : "memory");
    } while (!ok && ++n < (1u << 17));
}
__device__ __forceinline__ void pace_wait(uint32_t a, uint32_t target) {
    uint32_t v, n = 0;
    do {
        asm volatile("ld.volatile.shared.u32 %0, [%1];" : "=r"(v) : "r"(a) : "memory");
        if (v < target) __nanosleep(150);
    } while (v < target && ++n < (1u << 14));
}
__device__ __forceinline__ void flag_wait(const unsigned* p, unsigned target) {
    unsigned v; uint32_t n = 0;
    while (true) {
        asm volatile("ld.acquire.gpu.global.u32 %0, [%1];" : "=r"(v) : "l"(p) : "memory");
        if ((int)(v - target) >= 0 || ++n >= (1u << 17)) break;
        __nanosleep(100);
    }
}
__device__ __forceinline__ void flag_add(unsigned* p) {
    asm volatile("fence.acq_rel.gpu;\nred.relaxed.gpu.global.add.u32 [%0], 1;" :: "l"(p) : "memory");
}
__device__ __forceinline__ uint64_t make_desc(uint32_t addr, uint32_t lbo, uint32_t sbo, uint32_t swz) {
    return (uint64_t)((addr & 0x3FFFF) >> 4) | ((uint64_t)((lbo & 0x3FFFF) >> 4) << 16) | ((uint64_t)((sbo & 0x3FFFF) >> 4) << 32) | ((uint64_t)swz << 62);
}
__device__ __forceinline__ uint64_t desc_add(uint64_t d, uint32_t off16) {
    return (d & 0xFFFFFFFF00000000ull) | (uint64_t)((uint32_t)d + off16);
}
__device__ __forceinline__ void tma2d(uint32_t dst, const CUtensorMap* tm, int c0, int c1, uint32_t bar) {
    asm volatile("cp.async.bulk.tensor.2d.shared::cluster.global.mbarrier::complete_tx::bytes [%0], [%1, {%3, %4}], [%2];"
        :: "r"(dst), "l"((uint64_t)tm), "r"(bar), "r"(c0), "r"(c1) : "memory");
}
__device__ __forceinline__ void tma3d_mc(uint32_t dst, const CUtensorMap* tm, int c0, int c1, int c2, uint32_t bar) {
    asm volatile("cp.async.bulk.tensor.3d.shared::cluster.global.mbarrier::complete_tx::bytes.multicast::cluster [%0], [%1, {%3, %4, %5}], [%2], %6;"
        :: "r"(dst), "l"((uint64_t)tm), "r"(bar), "r"(c0), "r"(c1), "r"(c2), "h"((uint16_t)3) : "memory");
}
__device__ __forceinline__ void bulk_g2s(uint32_t dst, const void* src, uint32_t bytes, uint32_t bar) {
    asm volatile("cp.async.bulk.shared::cluster.global.mbarrier::complete_tx::bytes [%0], [%1], %2, [%3];"
        :: "r"(dst), "l"(src), "r"(bytes), "r"(bar) : "memory");
}
__device__ __forceinline__ void bulk_s2g(void* dst, uint32_t src, uint32_t bytes) {
    asm volatile("cp.async.bulk.global.shared::cta.bulk_group [%0], [%1], %2;" :: "l"(dst), "r"(src), "r"(bytes) : "memory");
}
__device__ __forceinline__ void tma2d_store(const CUtensorMap* tm, int c0, int c1, uint32_t src) {
    asm volatile("cp.async.bulk.tensor.2d.global.shared::cta.bulk_group [%0, {%2, %3}], [%1];"
        :: "l"((uint64_t)tm), "r"(src), "r"(c0), "r"(c1) : "memory");
}
__device__ __forceinline__ void l2_prefetch(const void* p, uint32_t bytes) {
    asm volatile("cp.async.bulk.prefetch.L2.global [%0], %1;" :: "l"(p), "r"(bytes) : "memory");
}
__device__ __forceinline__ void tmap_prefetch(const CUtensorMap* tm) { asm volatile("prefetch.tensormap [%0];" :: "l"((uint64_t)tm) : "memory"); }
__device__ __forceinline__ uint32_t lds32(uint32_t a) { uint32_t v; asm volatile("ld.shared.u32 %0, [%1];" : "=r"(v) : "r"(a)); return v; }
__device__ __forceinline__ uint2 lds64(uint32_t a) { uint2 v; asm volatile("ld.shared.v2.u32 {%0,%1}, [%2];" : "=r"(v.x), "=r"(v.y) : "r"(a)); return v; }
__device__ __forceinline__ uint4 lds128(uint32_t a) { uint4 v; asm volatile("ld.shared.v4.u32 {%0,%1,%2,%3}, [%4];" : "=r"(v.x), "=r"(v.y), "=r"(v.z), "=r"(v.w) : "r"(a)); return v; }
__device__ __forceinline__ void sts32(uint32_t a, uint32_t v) { asm volatile("st.shared.u32 [%0], %1;" :: "r"(a), "r"(v) : "memory"); }
__device__ __forceinline__ void sts128(uint32_t a, uint4 v) { asm volatile("st.shared.v4.u32 [%0], {%1,%2,%3,%4};" :: "r"(a), "r"(v.x), "r"(v.y), "r"(v.z), "r"(v.w) : "memory"); }
__device__ __forceinline__ uint4 ldg_cg128(const void* p) { uint4 v; asm volatile("ld.global.cg.v4.u32 {%0,%1,%2,%3}, [%4];" : "=r"(v.x), "=r"(v.y), "=r"(v.z), "=r"(v.w) : "l"(p)); return v; }
__device__ __forceinline__ uint4 ldg_nc128(const void* p) { uint4 v; asm volatile("ld.global.nc.L1::no_allocate.v4.u32 {%0,%1,%2,%3}, [%4];" : "=r"(v.x), "=r"(v.y), "=r"(v.z), "=r"(v.w) : "l"(p)); return v; }
__device__ __forceinline__ uint2 ldg_nc64(const void* p) { uint2 v; asm volatile("ld.global.nc.L1::no_allocate.v2.u32 {%0,%1}, [%2];" : "=r"(v.x), "=r"(v.y) : "l"(p)); return v; }
#define WG_FENCE() asm volatile("wgmma.fence.sync.aligned;\n" ::: "memory")
#define WG_COMMIT() asm volatile("wgmma.commit_group.sync.aligned;\n" ::: "memory")
template<int N> __device__ __forceinline__ void wg_wait() { asm volatile("wgmma.wait_group.sync.aligned %0;\n" :: "n"(N) : "memory"); }
__device__ __forceinline__ void named_bar(int id, int n) { asm volatile("bar.sync %0, %1;" :: "r"(id), "r"(n) : "memory"); }

__device__ __forceinline__ float bf_lo(uint32_t u) { return __uint_as_float(u << 16); }
__device__ __forceinline__ float bf_hi(uint32_t u) { return __uint_as_float(u & 0xFFFF0000u); }
__device__ __forceinline__ uint32_t pack_bf(float lo, float hi) { uint32_t r; asm("cvt.rn.bf16x2.f32 %0, %1, %2;" : "=r"(r) : "f"(hi), "f"(lo)); return r; }
__device__ __forceinline__ float bf_round(float x) { return __bfloat162float(__float2bfloat16_rn(x)); }
__device__ __forceinline__ uint32_t bmul2(uint32_t a, uint32_t b) { uint32_t r; asm("mul.rn.bf16x2 %0, %1, %2;" : "=r"(r) : "r"(a), "r"(b)); return r; }
__device__ __forceinline__ uint32_t badd2(uint32_t a, uint32_t b) { uint32_t r; asm("add.rn.bf16x2 %0, %1, %2;" : "=r"(r) : "r"(a), "r"(b)); return r; }
__device__ __forceinline__ uint32_t bsub2(uint32_t a, uint32_t b) { uint32_t r; asm("sub.rn.bf16x2 %0, %1, %2;" : "=r"(r) : "r"(a), "r"(b)); return r; }
__device__ __forceinline__ void mma16816(float (&d)[4], uint32_t a0, uint32_t a1, uint32_t a2, uint32_t a3, uint2 b) {
    asm volatile("mma.sync.aligned.m16n8k16.row.col.f32.bf16.bf16.f32 {%0,%1,%2,%3}, {%4,%5,%6,%7}, {%8,%9}, {%0,%1,%2,%3};\n"
        : "+f"(d[0]), "+f"(d[1]), "+f"(d[2]), "+f"(d[3]) : "r"(a0), "r"(a1), "r"(a2), "r"(a3), "r"(b.x), "r"(b.y));
}

template<int HS> __device__ __forceinline__ void xreduce(float (&v)[32], int lane) {
    const int up = lane & HS;
    #pragma unroll
    for (int e = 0; e < HS; e++) {
        float keep, send;
        asm("{\n.reg .pred p;\nsetp.ne.b32 p, %4, 0;\nselp.f32 %0, %3, %2, p;\nselp.f32 %1, %2, %3, p;\n}"
            : "=f"(keep), "=f"(send) : "f"(v[e]), "f"(v[e + HS]), "r"(up));
        v[e] = keep + __shfl_xor_sync(0xffffffffu, send, HS);
    }
}

__device__ __forceinline__ int blk_f0(int bi, int j) {
    if (bi < 32) return 224 * ((j + (bi >> 2)) & 7) + 32 * (bi & 3);
    int b2 = bi - 32; int q3 = (b2 * 11) >> 5;
    return 224 * ((j + q3) & 7) + 128 + 32 * (b2 - 3 * q3);
}
__device__ __forceinline__ int next_st2(int s) { return (0x14023 >> (4 * s)) & 7; }
__device__ __forceinline__ uint32_t stage_off_rt(int s) { return s < 3 ? SM_RING + s * STAGE_BYTES : (uint32_t)(s - 2) * STAGE_BYTES; }

template<int NB>
__device__ __forceinline__ void gemm1_pass(uint32_t sb, int wgi, int warp4, int lane, int& st, uint32_t& fph, uint32_t e_cl,
                                           int rb64, int ks0) {
    constexpr bool passA = (NB == 4);
    float acc[NB * 32];
    const uint64_t descA0 = make_desc(sb + SM_X + wgi * 8192, 16, 1024, 1);
    const uint64_t descB0 = make_desc(sb + SM_RING, 4096, 512, 2);
    int prev = 0;
    #pragma unroll 1
    for (int sl = 0; sl < 8; sl++) {
        if (warp4 == 0 && wgi == 0) PROF2(2, sl + (passA ? 0 : 8));
        mbar_wait(sb + SM_BARS + (B_FULL + st) * 8, (fph >> st) & 1);
        fph ^= 1u << st;
        if (sl == 0 && warp4 == 0) PROF(2 + wgi * 8 + (passA ? 0 : 3));
        if (warp4 == 0 && wgi == 0) PROF2(1, sl + (passA ? 0 : 8));
        const uint64_t da = desc_add(descA0, sl * 1024), db = desc_add(descB0, st * 2048);
        WG_FENCE();
        #pragma unroll
        for (int kk = 0; kk < 4; kk++) {
            int sc = (sl | kk) ? 1 : 0;
            if constexpr (NB == 4) wgmma_ss_n256_tb(acc, da + kk * 2, db + kk * 64, sc); else wgmma_ss_n192_tb(acc, da + kk * 2, db + kk * 64, sc);
        }
        WG_COMMIT();
        wg_wait<1>();
        if (warp4 == 0 && wgi == 0) PROF2(3, sl + (passA ? 0 : 8));
        if (lane < 2 && sl) mbar_arrive_cluster(e_cl + prev * 8, 1);
        if (!passA) {
            if (sl == 2 && lane == 0) mbar_arrive(sb + SM_BARS + B_XFREE * 8);
            if ((sl == 4 || sl == 6) && lane < 2) mbar_arrive_cluster(e_cl + (1 + (sl >> 1)) * 8, 1);
        }
        prev = st;
        st = (st == 2) ? 0 : st + 1;
    }
    wg_wait<0>();
    if (lane < 2) mbar_arrive_cluster(e_cl + prev * 8, 1);
    if (!passA && lane == 0) mbar_arrive(sb + SM_BARS + B_G1DONE * 8);
    if (warp4 == 0) PROF(3 + wgi * 8 + (passA ? 0 : 3));
    const int g = lane >> 2;
    const int r0 = wgi * 64 + warp4 * 16 + g;
    const float s0 = __uint_as_float(lds32(sb + SM_STATS + r0 * 4)), s1 = __uint_as_float(lds32(sb + SM_STATS + (r0 + 8) * 4));
    uint4* dst = g_hfrag + ((size_t)(rb64 * 112 + ks0) * 4 + warp4) * 32 + lane;
    #pragma unroll
    for (int kk = 0; kk < NB * 2; kk++) {
        uint32_t h[4];
        #pragma unroll
        for (int tt = 0; tt < 2; tt++) {
            const int t = 2 * kk + tt;
            const float* ag = &acc[4 * t];
            const float* au = &acc[NB * 16 + 4 * t];
            h[2 * tt] = bmul2(pack_bf(ag[0] * s0, ag[1] * s0), pack_bf(au[0] * s0, au[1] * s0));
            h[2 * tt + 1] = bmul2(pack_bf(ag[2] * s1, ag[3] * s1), pack_bf(au[2] * s1, au[3] * s1));
        }
        dst[kk * 128] = make_uint4(h[0], h[1], h[2], h[3]);
    }
    __syncwarp();
    if (lane == 0) mbar_arrive(sb + SM_BARS + (B_HD + wgi * 2 + (passA ? 0 : 1)) * 8);
    if (warp4 == 0) PROF(4 + wgi * 8 + (passA ? 0 : 3));
}

__global__ void __cluster_dims__(2, 1, 1) __launch_bounds__(NTHREADS, 1)
fused_kernel(const __grid_constant__ Params p) {
    extern __shared__ __align__(1024) uint8_t smem_raw[];
    const uint32_t sb = smem_u32(smem_raw);
    const int tid = threadIdx.x, warp = tid >> 5, lane = tid & 31;
    const int b = blockIdx.x;
    const int rank = b & 1;
    const int j = (b >> 1) & 7;
    const int i = ((b >> 4) << 1) | rank;
    const int cb = j >> 1;
    const int rbG2 = 2 * i + (j & 1);

    if (warp == 8 && lane < 4) {
        mbar_init(sb + SM_BARS + (B_XFULL + lane) * 8, 1);
        asm volatile("fence.proxy.async.shared::cta;" ::: "memory");
        mbar_expect_tx(sb + SM_BARS + (B_XFULL + lane) * 8, 32768);
    }
    if (tid == 288) {
        for (int s = 0; s < 5; s++) { mbar_init(sb + SM_BARS + (B_FULL + s) * 8, 1); mbar_init(sb + SM_BARS + (B_EMPTY + s) * 8, 16); }
        mbar_init(sb + SM_BARS + B_CONV * 8, 1);
        mbar_init(sb + SM_BARS + B_YT * 8, 1);
        mbar_init(sb + SM_BARS + B_XR * 8, 1);
        mbar_init(sb + SM_BARS + B_G1DONE * 8, 8);
        mbar_init(sb + SM_BARS + B_XFREE * 8, 8);
        sts32(sb + SM_CVCNT, 0);
        mbar_init(sb + SM_BARS + B_YST * 8, 4);
        for (int s = 0; s < 4; s++) mbar_init(sb + SM_BARS + (B_HD + s) * 8, 4);
        for (int s = 0; s < 2; s++) mbar_init(sb + SM_BARS + (B_HRDY + s) * 8, 1);
        asm volatile("fence.mbarrier_init.release.cluster;" ::: "memory");
        asm volatile("fence.proxy.async.shared::cta;" ::: "memory");
    }
    __syncwarp();
    asm volatile("barrier.cluster.arrive.relaxed.aligned;\n" ::: "memory");
    if (warp == 8) {
        const int rg = lane >> 3, sl = lane & 7;
        tma2d(sb + SM_X + sl * 16384 + rg * 4096, &p.tm_x, 64 * ((sl + 2 * cb + 2) & 7), 128 * i + 32 * rg, sb + SM_BARS + (B_XFULL + rg) * 8);
        __syncwarp();
    }
    asm volatile("barrier.cluster.wait.aligned;\n" ::: "memory");
    PROFW(1, 0);

    if (warp < 8) {
        asm volatile("setmaxnreg.inc.sync.aligned.u32 208;");
        const int wgi = warp >> 2, warp4 = warp & 3;
        const int g = lane >> 2, c = lane & 3;
        const uint32_t e_cl = mapa(sb + SM_BARS + B_EMPTY * 8, lane & 1);
        {
            const uint32_t xa = sb + SM_X + (lane >> 3) * 16384 + warp * 16 * 128;
            uint4 xr[16][2];
            float v[32];
            mbar_wait(sb + SM_BARS + (B_XFULL + (warp >> 1)) * 8, 0);
            PROFW(16, 0); PROFW(18, 7);
            #pragma unroll
            for (int r = 0; r < 16; r++) {
                const uint32_t a = xa + r * 128 + (((lane & 7) ^ (r & 7)) << 4);
                xr[r][0] = lds128(a); xr[r][1] = lds128(a + 65536);
            }
            #pragma unroll
            for (int r = 0; r < 16; r++) {
                const uint32_t* u = (const uint32_t*)&xr[r][0];
                float s = 0.f, q = 0.f;
                #pragma unroll
                for (int e = 0; e < 8; e++) { const float lo = bf_lo(u[e]), hi = bf_hi(u[e]); s += lo; q = fmaf(lo, lo, q); s += hi; q = fmaf(hi, hi, q); }
                v[r] = s; v[16 + r] = q;
            }
            xreduce<16>(v, lane); xreduce<8>(v, lane); xreduce<4>(v, lane); xreduce<2>(v, lane); xreduce<1>(v, lane);
            const float other = __shfl_xor_sync(0xffffffffu, v[0], 16);
            const float mean = (lane < 16 ? v[0] : other) * (1.0f / DM);
            const float msq = (lane < 16 ? other : v[0]) * (1.0f / DM);
            const float var_b = bf_round(fmaxf(msq - mean * mean, 0.f));
            const float sd = bf_round(sqrtf(bf_round(var_b + 1e-5f)));
            if (lane < 16) sts32(sb + SM_STATS + (warp * 16 + lane) * 4, __float_as_uint(1.0f / sd));
            const uint32_t mb = pack_bf(mean, mean);
            #pragma unroll
            for (int r = 0; r < 16; r++) {
                const uint32_t m = __shfl_sync(0xffffffffu, mb, r);
                const uint32_t a = xa + r * 128 + (((lane & 7) ^ (r & 7)) << 4);
                #pragma unroll
                for (int hh = 0; hh < 2; hh++) {
                    uint4 t = xr[r][hh];
                    t.x = bsub2(t.x, m); t.y = bsub2(t.y, m); t.z = bsub2(t.z, m); t.w = bsub2(t.w, m);
                    sts128(a + hh * 65536, t);
                }
            }
            asm volatile("fence.proxy.async.shared::cta;" ::: "memory");
            named_bar(1 + wgi, 128);
            PROFW(17, 0); PROFW(19, 7);
        }
        int st = 0; uint32_t fph = 0;
        const int rb64 = 2 * i + wgi;
        gemm1_pass<4>(sb, wgi, warp4, lane, st, fph, e_cl, rb64, 14 * j);
        gemm1_pass<3>(sb, wgi, warp4, lane, st, fph, e_cl, rb64, 14 * j + 8);

        if (wgi == 1) {
            const int gch = 4 * b + warp4;
            const uint32_t xb = sb + SM_CVX + warp4 * 4096;
            const uint32_t hb = sb + SM_CVH + warp4 * 4096;
            const uint32_t dw = ((const unsigned short*)p.ssm_D)[gch];
            const uint32_t d2 = dw | (dw << 16);
            mbar_wait(sb + SM_BARS + B_CONV * 8, 0);
            PROFW(32, 4);
            float acc[16][4];
            #pragma unroll
            for (int jj = 0; jj < 16; jj++) { acc[jj][0] = 0.f; acc[jj][1] = 0.f; acc[jj][2] = 0.f; acc[jj][3] = 0.f; }
            uint2 bh[8], bl0[8], bl1[8];
            uint32_t xl = xb + g * 32 + c * 8;
            uint32_t hl = hb + (g + 2 * c - 8) * 4;
            #pragma unroll
            for (int d = 0; d < 8; d++) { bl0[d] = lds64(xl + d * 256); bh[d] = lds64(xl + (8 + d) * 256); }
            uint32_t w[6];
            w[0] = 0; w[1] = 0; w[2] = 0;
            if (g + 2 * c >= 8) w[0] = lds32(hl);
            if (g + 2 * c >= 7) w[1] = lds32(hl + 4);
            if (g + 2 * c >= 6) w[2] = lds32(hl + 8);
            w[3] = lds32(hl + 2048); w[4] = lds32(hl + 2052); w[5] = lds32(hl + 2056);
            auto conv_m0 = [&](int m0, uint2 (&bl)[8], uint2 (&bn)[8]) {
                xl -= 32;
                #pragma unroll
                for (int k = 0; k < 8; k++) {
                    const uint32_t a0 = w[1], a1 = __byte_perm(w[0], w[1], 0x5432), a2 = w[2], a3 = __byte_perm(w[1], w[2], 0x5432);
                    const uint32_t c0 = w[4], c1 = __byte_perm(w[3], w[4], 0x5432), c2 = w[5], c3 = __byte_perm(w[4], w[5], 0x5432);
                    const uint32_t nx = (k < 7) ? hl + (k + 1) * 256 : hl + 32;
                    w[0] = lds32(nx); w[1] = lds32(nx + 4); w[2] = lds32(nx + 8);
                    w[3] = lds32(nx + 2048); w[4] = lds32(nx + 2052); w[5] = lds32(nx + 2056);
                    if (k > 0) bn[k] = lds64(xl + k * 256);
                    else { bn[0] = make_uint2(0, 0); if (g > m0) bn[0] = lds64(xl); }
                    #pragma unroll
                    for (int jj = k; jj < 16; jj++) mma16816(acc[jj], a0, a1, a2, a3, (jj - k < 8) ? bl[(jj - k) & 7] : bh[(jj - k) & 7]);
                    bh[7 - k] = lds64(xl + (15 - k) * 256);
                    #pragma unroll
                    for (int jj = k + 8; jj < 16; jj++) mma16816(acc[jj], c0, c1, c2, c3, bl[jj - k - 8]);
                }
                hl += 32;
                if (lane == 0) asm volatile("red.shared.add.u32 [%0], 1;" :: "r"(sb + SM_CVCNT) : "memory");
            };
            #pragma unroll 1
            for (int m0 = 0; m0 < 8; m0 += 2) {
                conv_m0(m0, bl0, bl1);
                conv_m0(m0 + 1, bl1, bl0);
            }
            PROFW(33, 4);
            const uint32_t kvl = xb + c * 64 + (7 - g) * 4;
            uint32_t* ydst = (uint32_t*)(g_yT + (size_t)gch * SEQ + 32 * c + 2 * g);
            uint32_t kk0[16], kk1[16];
            #pragma unroll
            for (int jj = 0; jj < 16; jj++) { kk0[jj] = lds32(kvl + jj * 256); kk1[jj] = lds32(kvl + jj * 256 + 32); }
            #pragma unroll
            for (int jj = 0; jj < 16; jj++) {
                ydst[jj * 64] = badd2(pack_bf(acc[jj][2], acc[jj][0]), bmul2(__byte_perm(kk0[jj], kk0[jj], 0x1032), d2));
                ydst[jj * 64 + 8] = badd2(pack_bf(acc[jj][3], acc[jj][1]), bmul2(__byte_perm(kk1[jj], kk1[jj], 0x1032), d2));
            }
            __syncwarp();
            PROFW(44, 4);
            if (lane == 0) mbar_arrive(sb + SM_BARS + B_YST * 8);
            PROFW(45, 4);
        }
        {
            const uint4* hsrc = g_hfrag + ((size_t)rbG2 * 112 * 4 + warp4) * 32 + lane;
            const uint64_t descB0 = make_desc(sb, 4096, 1024, 1);
            int prev = 0;
            auto load_group = [&](uint4 (&dstf)[8], int u) {
                #pragma unroll
                for (int hb = 0; hb < 4; hb++) {
                    const int ks = blk_f0(4 * u + hb, j) >> 4;
                    dstf[2 * hb] = ldg_cg128(hsrc + ks * 128);
                    dstf[2 * hb + 1] = ldg_cg128(hsrc + ks * 128 + 128);
                }
            };
            auto g2_step = [&](float (&acc)[64], int u, int up, int un, uint4 (&cur)[8], uint4 (&nxt)[8], bool do_load) {
                const int u5 = (u * 13) >> 6;
                const int sg = (0x02143 >> (4 * (u - 5 * u5))) & 7;
                if (warp == 0) PROF2(2, 16 + u);
                mbar_wait(sb + SM_BARS + (B_FULL + sg) * 8, ((6u >> sg) ^ (uint32_t)u5) & 1);
                if (warp == 0) PROF2(1, 16 + u);
                const uint64_t db = desc_add(descB0, stage_off_rt(sg) >> 4);
                WG_FENCE();
                #pragma unroll
                for (int kk = 0; kk < 8; kk++)
                    wgmma_rs_n128_tb(acc, cur[kk].x, cur[kk].y, cur[kk].z, cur[kk].w, db + ((kk >> 1) * 512 + (kk & 1) * 128), (up >= 0 || kk) ? 1 : 0);
                WG_COMMIT();
                wg_wait<1>();
                if (warp == 0) PROF2(3, 16 + u);
                if (lane < 2 && up >= 0 && up + 5 < 14) mbar_arrive_cluster(e_cl + prev * 8, 2);
                prev = sg;
                if (do_load) load_group(nxt, un);
            };
            auto finish = [&](float (&acc)[64]) {
            PROFW(27, 0);
            named_bar(3, 256);
            {
                const uint32_t ex = sb + SM_RING + (tid & 127) * 16;
                #pragma unroll
                for (int q = 0; q < 8; q++) {
                    const float e0 = wgi ? acc[4 * q] : acc[32 + 4 * q], e1 = wgi ? acc[4 * q + 1] : acc[33 + 4 * q];
                    const float e2 = wgi ? acc[4 * q + 2] : acc[34 + 4 * q], e3 = wgi ? acc[4 * q + 3] : acc[35 + 4 * q];
                    sts128(ex + wgi * 16384 + q * 2048, make_uint4(__float_as_uint(e0), __float_as_uint(e1), __float_as_uint(e2), __float_as_uint(e3)));
                }
                named_bar(3, 256);
                #pragma unroll
                for (int q = 0; q < 8; q++) {
                    const uint4 t = lds128(ex + (wgi ^ 1) * 16384 + q * 2048);
                    acc[4 * q] = (wgi ? acc[32 + 4 * q] : acc[4 * q]) + __uint_as_float(t.x);
                    acc[4 * q + 1] = (wgi ? acc[33 + 4 * q] : acc[4 * q + 1]) + __uint_as_float(t.y);
                    acc[4 * q + 2] = (wgi ? acc[34 + 4 * q] : acc[4 * q + 2]) + __uint_as_float(t.z);
                    acc[4 * q + 3] = (wgi ? acc[35 + 4 * q] : acc[4 * q + 3]) + __uint_as_float(t.w);
                }
            }
            mbar_wait(sb + SM_BARS + B_XR * 8, 0);
            mbar_wait(sb + SM_BARS + B_YT * 8, 0);
            PROFW(28, 0);
            const int r0 = (j & 1) * 64 + warp4 * 16 + g;
            const float s0 = __uint_as_float(lds32(sb + SM_STATS + r0 * 4)), s1 = __uint_as_float(lds32(sb + SM_STATS + (r0 + 8) * 4));
            const uint32_t drow0 = sb + SM_XE + wgi * 16384 + r0 * 128 + c * 4;
            const uint32_t xrow0 = sb + SM_XE + wgi * 16384 + (r0 ^ 64) * 128 + c * 4;
            const int mi = lane >> 3, lr = lane & 7;
            const uint32_t yaddr = sb + SM_YT + wgi * 8192 + ((mi >> 1) * 8 + lr) * 128 + (((2 * warp4 + (mi & 1)) ^ lr) << 4);
            uint32_t y[4][4], xv[8][2], dv[8][2];
            #pragma unroll
            for (int t2 = 0; t2 < 4; t2++)
                asm volatile("ldmatrix.sync.aligned.m8n8.x4.trans.shared.b16 {%0,%1,%2,%3}, [%4];"
                    : "=r"(y[t2][0]), "=r"(y[t2][1]), "=r"(y[t2][2]), "=r"(y[t2][3]) : "r"(yaddr + t2 * 2048) : "memory");
            #pragma unroll
            for (int t = 0; t < 8; t++) {
                const uint32_t off = (t ^ g) << 4;
                xv[t][0] = lds32(xrow0 + off); xv[t][1] = lds32(xrow0 + 1024 + off);
                dv[t][0] = lds32(drow0 + off); dv[t][1] = lds32(drow0 + 1024 + off);
            }
            #pragma unroll
            for (int t = 0; t < 8; t++) {
                const uint32_t off = (t ^ g) << 4;
                const uint32_t n0 = pack_bf(bf_lo(dv[t][0]) * s0, bf_hi(dv[t][0]) * s0), n1 = pack_bf(bf_lo(dv[t][1]) * s1, bf_hi(dv[t][1]) * s1);
                const uint32_t o0 = badd2(badd2(xv[t][0], bmul2(n0, y[t >> 1][2 * (t & 1)])), pack_bf(acc[4 * t], acc[4 * t + 1]));
                const uint32_t o1 = badd2(badd2(xv[t][1], bmul2(n1, y[t >> 1][2 * (t & 1) + 1])), pack_bf(acc[4 * t + 2], acc[4 * t + 3]));
                sts32(xrow0 + off, o0); sts32(xrow0 + 1024 + off, o1);
            }
            asm volatile("fence.proxy.async.shared::cta;" ::: "memory");
            named_bar(1 + wgi, 128);
            if ((tid & 127) == 0) {
                tma2d_store(&p.tm_out, 128 * cb + 64 * wgi, 64 * rbG2, sb + SM_XE + wgi * 16384 + ((j & 1) ^ 1) * 8192);
                asm volatile("cp.async.bulk.commit_group;" ::: "memory");
                asm volatile("cp.async.bulk.wait_group.read 0;" ::: "memory");
                PROFW(29, 0);
            }
            };
            if (wgi == 0) {
                float acc[64];
                uint4 af[3][8];
                mbar_wait(sb + SM_BARS + B_HRDY * 8, 0);
                load_group(af[0], 0); load_group(af[1], 1);
                PROFW(20, 0);
                pace_wait(sb + SM_CVCNT, PACE(0));
                g2_step(acc, 0, -1, 2, af[0], af[2], true);
                pace_wait(sb + SM_CVCNT, PACE(1));
                g2_step(acc, 1, 0, 3, af[1], af[0], true);
                pace_wait(sb + SM_CVCNT, PACE(2));
                g2_step(acc, 2, 1, 4, af[2], af[1], true);
                pace_wait(sb + SM_CVCNT, PACE(3));
                g2_step(acc, 3, 2, 6, af[0], af[2], true);
                PROFW(22, 0);
                mbar_wait(sb + SM_BARS + (B_HRDY + 1) * 8, 0);
                pace_wait(sb + SM_CVCNT, PACE(4));
                g2_step(acc, 4, 3, 8, af[1], af[0], true);
                g2_step(acc, 6, 4, 10, af[2], af[1], true);
                g2_step(acc, 8, 6, 12, af[0], af[2], true);
                PROFW(24, 0);
                g2_step(acc, 10, 8, -1, af[1], af[0], false);
                g2_step(acc, 12, 10, -1, af[2], af[1], false);
                wg_wait<0>();
                finish(acc);
            } else {
                float acc[64];
                uint4 af[3][8];
                mbar_wait(sb + SM_BARS + (B_HRDY + 1) * 8, 0);
                load_group(af[0], 5); load_group(af[1], 7);
                g2_step(acc, 5, -1, 9, af[0], af[2], true);
                g2_step(acc, 7, 5, 11, af[1], af[0], true);
                g2_step(acc, 9, 7, 13, af[2], af[1], true);
                g2_step(acc, 11, 9, -1, af[0], af[2], false);
                g2_step(acc, 13, 11, -1, af[1], af[0], false);
                wg_wait<0>();
                finish(acc);
            }
        }
    } else {
        asm volatile("setmaxnreg.dec.sync.aligned.u32 88;");
        if (warp == 8) {
            if (lane == 0) {
                int st = 0; uint32_t eph = 7;
                #pragma unroll 1
                for (int it = 0; it < 16; it++) {
                    const int pass = it >> 3, sl = it & 7;
                    const int nb = pass ? 3 : 4;
                    const CUtensorMap* tm = pass ? (rank ? &p.tm_uB : &p.tm_gB) : (rank ? &p.tm_uA : &p.tm_gA);
                    mbar_wait(sb + SM_BARS + (B_EMPTY + st) * 8, (eph >> st) & 1);
                    eph ^= 1u << st;
                    if (it == 1) mbar_wait(sb + SM_BARS + (B_XFULL + 2) * 8, 0);
                    PROF2(0, it);
                    mbar_expect_tx(sb + SM_BARS + (B_FULL + st) * 8, nb * 8192);
                    tma3d_mc(sb + SM_RING + st * STAGE_BYTES + rank * nb * 4096, tm, 0, ((sl + 2 * cb + 2) & 7) * 64, 7 * j + 4 * pass, sb + SM_BARS + (B_FULL + st) * 8);
                    st = (st == 2) ? 0 : st + 1;
                }
                st = 3;
                #pragma unroll 1
                for (int u = 0; u < 14; u++) {
                    mbar_wait(sb + SM_BARS + (B_EMPTY + st) * 8, (eph >> st) & 1);
                    eph ^= 1u << st;
                    PROF2(0, 16 + u);
                    const uint32_t so = sb + stage_off_rt(st) + rank * 8192;
                    mbar_expect_tx(sb + SM_BARS + (B_FULL + st) * 8, 32768);
                    tma3d_mc(so, &p.tm_w2, 0, blk_f0(4 * u + rank, j), 2 * cb, sb + SM_BARS + (B_FULL + st) * 8);
                    tma3d_mc(so + 16384, &p.tm_w2, 0, blk_f0(4 * u + 2 + rank, j), 2 * cb, sb + SM_BARS + (B_FULL + st) * 8);
                    st = next_st2(st);
                }
                PROF(48);
            }
        } else if (warp < 11) {
            mbar_wait(sb + SM_BARS + (B_XFULL + 3) * 8, 0);
            #pragma unroll 1
            for (int rnd = 0; rnd < 2; rnd++) {
                const int tt = (tid - 288) + 64 * rnd;
                uint32_t sk[4][2];
                uint4 skw[2];
                skw[0] = ldg_nc128(p.shift_k + 16 * tt); skw[1] = ldg_nc128(p.shift_k + 16 * tt + 8);
                const __nv_bfloat16* kp = p.k + (size_t)(16 * b) * DM + 4 * tt;
                const __nv_bfloat16* vp = p.v + (size_t)(16 * b) * DM + 4 * tt;
                uint2 kr[19];
                uint2 kv[16];
                #pragma unroll
                for (int r = 0; r < 3; r++) kr[r] = (b > 0) ? ldg_nc64(kp + (r - 3) * DM) : make_uint2(0, 0);
                #pragma unroll
                for (int r = 0; r < 16; r++) { kr[3 + r] = ldg_nc64(kp + r * DM); if (r < 10) kv[r] = ldg_nc64(vp + r * DM); }
                {
                    const uint4 w0 = skw[0], w1 = skw[1];
                    sk[0][0] = __byte_perm(w0.x, w0.z, 0x5410); sk[1][0] = __byte_perm(w0.x, w0.z, 0x7632);
                    sk[2][0] = __byte_perm(w0.y, w0.w, 0x5410); sk[3][0] = __byte_perm(w0.y, w0.w, 0x7632);
                    sk[0][1] = __byte_perm(w1.x, w1.z, 0x5410); sk[1][1] = __byte_perm(w1.x, w1.z, 0x7632);
                    sk[2][1] = __byte_perm(w1.y, w1.w, 0x5410); sk[3][1] = __byte_perm(w1.y, w1.w, 0x7632);
                }
                #pragma unroll
                for (int s = 0; s < 16; s++) {
                    uint32_t a = bmul2(kr[s].x, sk[3][0]);
                    a = badd2(a, bmul2(kr[s + 1].x, sk[2][0]));
                    a = badd2(a, bmul2(kr[s + 2].x, sk[1][0]));
                    a = badd2(a, bmul2(kr[s + 3].x, sk[0][0]));
                    kv[s].x = bmul2(a, kv[s].x);
                    a = bmul2(kr[s].y, sk[3][1]);
                    a = badd2(a, bmul2(kr[s + 1].y, sk[2][1]));
                    a = badd2(a, bmul2(kr[s + 2].y, sk[1][1]));
                    a = badd2(a, bmul2(kr[s + 3].y, sk[0][1]));
                    kv[s].y = bmul2(a, kv[s].y);
                    if (s < 6) kv[10 + s] = ldg_nc64(vp + (10 + s) * DM);
                }
                PROFW(57 + 2 * rnd, 9);
                #pragma unroll
                for (int cc = 0; cc < 4; cc++) {
                    const uint32_t sel = (cc & 1) ? 0x7632 : 0x5410;
                    #define KVW(r) ((cc & 2) ? kv[r].y : kv[r].x)
                    uint4* dst = (uint4*)(g_kvT + (size_t)(4 * tt + cc) * SEQ + 16 * b);
                    dst[0] = make_uint4(__byte_perm(KVW(15), KVW(14), sel), __byte_perm(KVW(13), KVW(12), sel),
                                        __byte_perm(KVW(11), KVW(10), sel), __byte_perm(KVW(9), KVW(8), sel));
                    dst[1] = make_uint4(__byte_perm(KVW(7), KVW(6), sel), __byte_perm(KVW(5), KVW(4), sel),
                                        __byte_perm(KVW(3), KVW(2), sel), __byte_perm(KVW(1), KVW(0), sel));
                    #undef KVW
                }
                PROFW(58 + 2 * rnd, 9);
            }
            asm volatile("fence.proxy.async.global;" ::: "memory");
            __syncwarp();
            if (lane == 0) {
                flag_add(&g_cnt_kv[0]);
                PROFW(50, 9);
                const int wgi = warp - 9;
                mbar_wait(sb + SM_BARS + (B_HD + wgi * 2) * 8, 0);
                flag_add(&g_flag_h[((2 * i + wgi) * 2 + 0) * 8]);
                mbar_wait(sb + SM_BARS + (B_HD + wgi * 2 + 1) * 8, 0);
                flag_add(&g_flag_h[((2 * i + wgi) * 2 + 1) * 8]);
                if (wgi == 1) {
                    mbar_wait(sb + SM_BARS + B_YST * 8, 0);
                    asm volatile("fence.proxy.async.global;" ::: "memory");
                    flag_add(&g_cnt_y[(b >> 5) * 32]);
                    PROF(46);
                }
            }
        } else {
            if (lane == 0) {
                const unsigned ep = g_launch[b] + 1;
                g_launch[b] = ep;
                sts32(sb + SM_EPOCH, ep);
                tmap_prefetch(rank ? &p.tm_uA : &p.tm_gA);
                mbar_wait(sb + SM_BARS + (B_XFULL + 1) * 8, 0);
                l2_prefetch(p.wg + (size_t)b * (FF * DM / NCTA), FF * DM / NCTA * 2);
                l2_prefetch(p.wu + (size_t)b * (FF * DM / NCTA), FF * DM / NCTA * 2);
                tmap_prefetch(rank ? &p.tm_uB : &p.tm_gB);
                tmap_prefetch(&p.tm_w2); tmap_prefetch(&p.tm_yT); tmap_prefetch(&p.tm_out); tmap_prefetch(&p.tm_xe);
                mbar_wait(sb + SM_BARS + (B_FULL + 2) * 8, 0);
                l2_prefetch(p.ssm_k + (size_t)(4 * b) * SEQ, 4 * SEQ * 2);
                l2_prefetch(p.wd + (size_t)b * (FF * DM / NCTA), FF * DM / NCTA * 2);
                mbar_wait(sb + SM_BARS + (B_HD + 0) * 8, 0);
                flag_wait(&g_cnt_kv[0], ep * 256);
                asm volatile("fence.proxy.async.global;" ::: "memory");
                PROF(53);
                mbar_wait(sb + SM_BARS + B_XFREE * 8, 0);
                PROF(54);
                mbar_expect_tx(sb + SM_BARS + B_CONV * 8, 32768);
                bulk_g2s(sb + SM_CVX, g_kvT + (size_t)(4 * b) * SEQ, 16384, sb + SM_BARS + B_CONV * 8);
                bulk_g2s(sb + SM_CVH, p.ssm_k + (size_t)(4 * b) * SEQ, 16384, sb + SM_BARS + B_CONV * 8);
                flag_wait(&g_flag_h[(rbG2 * 2 + 0) * 8], ep * 8);
                mbar_arrive(sb + SM_BARS + B_HRDY * 8);
                mbar_wait(sb + SM_BARS + B_G1DONE * 8, 0);
                mbar_expect_tx(sb + SM_BARS + B_XR * 8, 16384);
                tma2d(sb + SM_XE + ((j & 1) ^ 1) * 8192, &p.tm_xe, 128 * cb, 64 * rbG2, sb + SM_BARS + B_XR * 8);
                tma2d(sb + SM_XE + 16384 + ((j & 1) ^ 1) * 8192, &p.tm_xe, 128 * cb + 64, 64 * rbG2, sb + SM_BARS + B_XR * 8);
                flag_wait(&g_flag_h[(rbG2 * 2 + 1) * 8], ep * 8);
                mbar_arrive(sb + SM_BARS + (B_HRDY + 1) * 8);
                mbar_wait(sb + SM_BARS + B_YST * 8, 0);
                flag_wait(&g_cnt_y[cb * 32], ep * 32);
                PROF(49);
                asm volatile("fence.proxy.async.global;" ::: "memory");
                mbar_expect_tx(sb + SM_BARS + B_YT * 8, 16384);
                tma2d(sb + SM_YT, &p.tm_yT, 64 * rbG2, 128 * cb, sb + SM_BARS + B_YT * 8);
            }
        }
    }
}

typedef CUresult (*EncodeFn)(CUtensorMap*, CUtensorMapDataType, cuuint32_t, void*, const cuuint64_t*, const cuuint64_t*,
                             const cuuint32_t*, const cuuint32_t*, CUtensorMapInterleave, CUtensorMapSwizzle,
                             CUtensorMapL2promotion, CUtensorMapFloatOOBfill);

void encode(EncodeFn fn, CUtensorMap* tm, const void* base, int rank, const cuuint64_t* dims, const cuuint64_t* strides,
            const cuuint32_t* box, CUtensorMapSwizzle swz) {
    cuuint32_t es[5] = {1, 1, 1, 1, 1};
    fn(tm, CU_TENSOR_MAP_DATA_TYPE_BFLOAT16, rank, (void*)base, dims, strides, box, es, CU_TENSOR_MAP_INTERLEAVE_NONE, swz,
       CU_TENSOR_MAP_L2_PROMOTION_L2_128B, CU_TENSOR_MAP_FLOAT_OOB_FILL_NONE);
}

}

extern "C" void kernel_launch(void* const* d_in, const int* in_sizes, int n_in, void* d_out, int out_size) {
    (void)in_sizes; (void)n_in; (void)out_size;
    static EncodeFn enc = nullptr;
    static void* yT_ptr = nullptr;
    if (!enc) {
        void* fn = nullptr; cudaDriverEntryPointQueryResult qr;
        cudaGetDriverEntryPoint("cuTensorMapEncodeTiled", &fn, cudaEnableDefault, &qr);
        enc = (EncodeFn)fn;
        cudaGetSymbolAddress(&yT_ptr, g_yT);
        cudaFuncSetAttribute(fused_kernel, cudaFuncAttributeMaxDynamicSharedMemorySize, SM_TOTAL);
    }
    Params p;
    p.q = (const __nv_bfloat16*)d_in[0]; p.k = (const __nv_bfloat16*)d_in[1]; p.v = (const __nv_bfloat16*)d_in[2];
    p.shift_k = (const __nv_bfloat16*)d_in[3]; p.ssm_k = (const __nv_bfloat16*)d_in[4]; p.ssm_D = (const __nv_bfloat16*)d_in[5];
    p.wg = (const __nv_bfloat16*)d_in[7]; p.wu = (const __nv_bfloat16*)d_in[8]; p.wd = (const __nv_bfloat16*)d_in[9];
    {
        cuuint64_t dims[2] = {DM, SEQ}; cuuint64_t str[1] = {DM * 2};
        cuuint32_t box[2] = {64, 32};
        encode(enc, &p.tm_x, p.q, 2, dims, str, box, CU_TENSOR_MAP_SWIZZLE_128B);
        cuuint32_t box2[2] = {64, 64};
        encode(enc, &p.tm_out, d_out, 2, dims, str, box2, CU_TENSOR_MAP_SWIZZLE_128B);
        encode(enc, &p.tm_xe, p.q, 2, dims, str, box2, CU_TENSOR_MAP_SWIZZLE_128B);
    }
    {
        cuuint64_t dims[3] = {32, DM, FF / 32}; cuuint64_t str[2] = {FF * 2, 64};
        cuuint32_t boxA[3] = {32, 64, 4}, boxB[3] = {32, 64, 3};
        encode(enc, &p.tm_gA, p.wg, 3, dims, str, boxA, CU_TENSOR_MAP_SWIZZLE_64B);
        encode(enc, &p.tm_gB, p.wg, 3, dims, str, boxB, CU_TENSOR_MAP_SWIZZLE_64B);
        encode(enc, &p.tm_uA, p.wu, 3, dims, str, boxA, CU_TENSOR_MAP_SWIZZLE_64B);
        encode(enc, &p.tm_uB, p.wu, 3, dims, str, boxB, CU_TENSOR_MAP_SWIZZLE_64B);
    }
    {
        cuuint64_t dims[3] = {64, FF, DM / 64}; cuuint64_t str[2] = {DM * 2, 128};
        cuuint32_t box[3] = {64, 32, 2};
        encode(enc, &p.tm_w2, p.wd, 3, dims, str, box, CU_TENSOR_MAP_SWIZZLE_128B);
    }
    {
        cuuint64_t dims[2] = {SEQ, DM}; cuuint64_t str[1] = {SEQ * 2};
        cuuint32_t box[2] = {64, 128};
        encode(enc, &p.tm_yT, yT_ptr, 2, dims, str, box, CU_TENSOR_MAP_SWIZZLE_128B);
    }
    fused_kernel<<<NCTA, NTHREADS, SM_TOTAL>>>(p);
}
```

```cpp
#include <cuda_runtime.h>
#include <cuda_bf16.h>
#include <cuda.h>
#include <stdint.h>

namespace {

constexpr int SEQ = 2048, DM = 512, FF = 1792;
constexpr int NCTA = 128;
constexpr int NTHREADS = 384;
constexpr int STAGE_BYTES = 32768;

constexpr uint32_t SM_X = 0;
constexpr uint32_t SM_RING = 131072;
constexpr uint32_t SM_MISC = SM_RING + 3 * STAGE_BYTES;
constexpr uint32_t SM_BARS = SM_MISC;
constexpr uint32_t SM_EPOCH = SM_MISC + 248;
constexpr uint32_t SM_STATS = SM_MISC + 256;
constexpr uint32_t SM_TOTAL = SM_STATS + 1024;
static_assert(SM_TOTAL <= 232448, "smem");
constexpr int RB_Z = 25;
constexpr int RB_R1 = (128 + RB_Z) * 16;
constexpr int RB_CH = 2 * RB_R1;
constexpr uint32_t SM_CVR = 0;
constexpr uint32_t SM_CVH = 8 * RB_CH;
static_assert(SM_CVH + 8 * 4096 <= 5 * 16384, "conv operands");
constexpr uint32_t SM_YT = 4 * 16384;
constexpr uint32_t SM_XE = 6 * 16384;

constexpr int B_FULL = 0, B_EMPTY = 5, B_XFULL = 10, B_CONV = 14, B_YT = 15, B_XR = 16, B_G1DONE = 17, B_HD = 18, B_HRDY = 22,
              B_XFREE = 24, B_YST = 25, B_COUNT = 26;
static_assert(B_COUNT * 8 <= 248, "barrier space");

__device__ __align__(128) uint32_t g_h[32 * 112 * 512];
__device__ __align__(128) uint8_t g_rb[DM * RB_CH];
__device__ __align__(128) __nv_bfloat16 g_yT[DM * SEQ];
__device__ unsigned g_launch[NCTA];
__device__ unsigned g_cnt_kv[32];
__device__ unsigned g_cnt_y[4 * 32];
__device__ unsigned g_flag_h[16 * 2 * 8];

#define PROF(idx)
#define PROF2(a, idx)
#define PROFW(idx, w)

struct Params {
    CUtensorMap tm_x, tm_gA, tm_gB, tm_uA, tm_uB, tm_w2, tm_yT, tm_out, tm_xe;
    const __nv_bfloat16 *q, *k, *v, *shift_k, *ssm_k, *ssm_D, *wg, *wu, *wd;
};

__device__ __forceinline__ void wgmma_rs_n32(float (&d)[16], uint32_t a0, uint32_t a1, uint32_t a2, uint32_t a3, uint64_t db, int sc) {
  asm volatile("{\n.reg .pred p;\nsetp.ne.b32 p, %21, 0;\n"
    "wgmma.mma_async.sync.aligned.m64n32k16.f32.bf16.bf16 {%0,%1,%2,%3,%4,%5,%6,%7,%8,%9,%10,%11,%12,%13,%14,%15}, {%16,%17,%18,%19}, %20, p, 1, 1, 0;\n}\n"
    : "+f"(d[0]),"+f"(d[1]),"+f"(d[2]),"+f"(d[3]),"+f"(d[4]),"+f"(d[5]),"+f"(d[6]),"+f"(d[7]),"+f"(d[8]),"+f"(d[9]),"+f"(d[10]),"+f"(d[11]),"+f"(d[12]),"+f"(d[13]),"+f"(d[14]),"+f"(d[15])
    : "r"(a0),"r"(a1),"r"(a2),"r"(a3),"l"(db),"r"(sc));
}
__device__ __forceinline__ void wgmma_rs_n128_tb(float (&d)[64], uint32_t a0, uint32_t a1, uint32_t a2, uint32_t a3, uint64_t db, int sc) {
  asm volatile("{\n.reg .pred p;\nsetp.ne.b32 p, %69, 0;\n"
    "wgmma.mma_async.sync.aligned.m64n128k16.f32.bf16.bf16 {%0,%1,%2,%3,%4,%5,%6,%7,%8,%9,%10,%11,%12,%13,%14,%15,%16,%17,%18,%19,%20,%21,%22,%23,%24,%25,%26,%27,%28,%29,%30,%31,%32,%33,%34,%35,%36,%37,%38,%39,%40,%41,%42,%43,%44,%45,%46,%47,%48,%49,%50,%51,%52,%53,%54,%55,%56,%57,%58,%59,%60,%61,%62,%63}, {%64,%65,%66,%67}, %68, p, 1, 1, 1;\n}\n"
    : "+f"(d[0]),"+f"(d[1]),"+f"(d[2]),"+f"(d[3]),"+f"(d[4]),"+f"(d[5]),"+f"(d[6]),"+f"(d[7]),"+f"(d[8]),"+f"(d[9]),"+f"(d[10]),"+f"(d[11]),"+f"(d[12]),"+f"(d[13]),"+f"(d[14]),"+f"(d[15]),"+f"(d[16]),"+f"(d[17]),"+f"(d[18]),"+f"(d[19]),"+f"(d[20]),"+f"(d[21]),"+f"(d[22]),"+f"(d[23]),"+f"(d[24]),"+f"(d[25]),"+f"(d[26]),"+f"(d[27]),"+f"(d[28]),"+f"(d[29]),"+f"(d[30]),"+f"(d[31]),"+f"(d[32]),"+f"(d[33]),"+f"(d[34]),"+f"(d[35]),"+f"(d[36]),"+f"(d[37]),"+f"(d[38]),"+f"(d[39]),"+f"(d[40]),"+f"(d[41]),"+f"(d[42]),"+f"(d[43]),"+f"(d[44]),"+f"(d[45]),"+f"(d[46]),"+f"(d[47]),"+f"(d[48]),"+f"(d[49]),"+f"(d[50]),"+f"(d[51]),"+f"(d[52]),"+f"(d[53]),"+f"(d[54]),"+f"(d[55]),"+f"(d[56]),"+f"(d[57]),"+f"(d[58]),"+f"(d[59]),"+f"(d[60]),"+f"(d[61]),"+f"(d[62]),"+f"(d[63])
    : "r"(a0),"r"(a1),"r"(a2),"r"(a3),"l"(db),"r"(sc));
}
__device__ __forceinline__ void wgmma_ss_n256_tb(float (&d)[128], uint64_t da, uint64_t db, int sc) {
  asm volatile("{\n.reg .pred p;\nsetp.ne.b32 p, %130, 0;\n"
    "wgmma.mma_async.sync.aligned.m64n256k16.f32.bf16.bf16 {%0,%1,%2,%3,%4,%5,%6,%7,%8,%9,%10,%11,%12,%13,%14,%15,%16,%17,%18,%19,%20,%21,%22,%23,%24,%25,%26,%27,%28,%29,%30,%31,%32,%33,%34,%35,%36,%37,%38,%39,%40,%41,%42,%43,%44,%45,%46,%47,%48,%49,%50,%51,%52,%53,%54,%55,%56,%57,%58,%59,%60,%61,%62,%63,%64,%65,%66,%67,%68,%69,%70,%71,%72,%73,%74,%75,%76,%77,%78,%79,%80,%81,%82,%83,%84,%85,%86,%87,%88,%89,%90,%91,%92,%93,%94,%95,%96,%97,%98,%99,%100,%101,%102,%103,%104,%105,%106,%107,%108,%109,%110,%111,%112,%113,%114,%115,%116,%117,%118,%119,%120,%121,%122,%123,%124,%125,%126,%127}, %128, %129, p, 1, 1, 0, 1;\n}\n"
    : "+f"(d[0]),"+f"(d[1]),"+f"(d[2]),"+f"(d[3]),"+f"(d[4]),"+f"(d[5]),"+f"(d[6]),"+f"(d[7]),"+f"(d[8]),"+f"(d[9]),"+f"(d[10]),"+f"(d[11]),"+f"(d[12]),"+f"(d[13]),"+f"(d[14]),"+f"(d[15]),"+f"(d[16]),"+f"(d[17]),"+f"(d[18]),"+f"(d[19]),"+f"(d[20]),"+f"(d[21]),"+f"(d[22]),"+f"(d[23]),"+f"(d[24]),"+f"(d[25]),"+f"(d[26]),"+f"(d[27]),"+f"(d[28]),"+f"(d[29]),"+f"(d[30]),"+f"(d[31]),"+f"(d[32]),"+f"(d[33]),"+f"(d[34]),"+f"(d[35]),"+f"(d[36]),"+f"(d[37]),"+f"(d[38]),"+f"(d[39]),"+f"(d[40]),"+f"(d[41]),"+f"(d[42]),"+f"(d[43]),"+f"(d[44]),"+f"(d[45]),"+f"(d[46]),"+f"(d[47]),"+f"(d[48]),"+f"(d[49]),"+f"(d[50]),"+f"(d[51]),"+f"(d[52]),"+f"(d[53]),"+f"(d[54]),"+f"(d[55]),"+f"(d[56]),"+f"(d[57]),"+f"(d[58]),"+f"(d[59]),"+f"(d[60]),"+f"(d[61]),"+f"(d[62]),"+f"(d[63]),"+f"(d[64]),"+f"(d[65]),"+f"(d[66]),"+f"(d[67]),"+f"(d[68]),"+f"(d[69]),"+f"(d[70]),"+f"(d[71]),"+f"(d[72]),"+f"(d[73]),"+f"(d[74]),"+f"(d[75]),"+f"(d[76]),"+f"(d[77]),"+f"(d[78]),"+f"(d[79]),"+f"(d[80]),"+f"(d[81]),"+f"(d[82]),"+f"(d[83]),"+f"(d[84]),"+f"(d[85]),"+f"(d[86]),"+f"(d[87]),"+f"(d[88]),"+f"(d[89]),"+f"(d[90]),"+f"(d[91]),"+f"(d[92]),"+f"(d[93]),"+f"(d[94]),"+f"(d[95]),"+f"(d[96]),"+f"(d[97]),"+f"(d[98]),"+f"(d[99]),"+f"(d[100]),"+f"(d[101]),"+f"(d[102]),"+f"(d[103]),"+f"(d[104]),"+f"(d[105]),"+f"(d[106]),"+f"(d[107]),"+f"(d[108]),"+f"(d[109]),"+f"(d[110]),"+f"(d[111]),"+f"(d[112]),"+f"(d[113]),"+f"(d[114]),"+f"(d[115]),"+f"(d[116]),"+f"(d[117]),"+f"(d[118]),"+f"(d[119]),"+f"(d[120]),"+f"(d[121]),"+f"(d[122]),"+f"(d[123]),"+f"(d[124]),"+f"(d[125]),"+f"(d[126]),"+f"(d[127])
    : "l"(da),"l"(db),"r"(sc));
}
__device__ __forceinline__ void wgmma_ss_n192_tb(float (&d)[96], uint64_t da, uint64_t db, int sc) {
  asm volatile("{\n.reg .pred p;\nsetp.ne.b32 p, %98, 0;\n"
    "wgmma.mma_async.sync.aligned.m64n192k16.f32.bf16.bf16 {%0,%1,%2,%3,%4,%5,%6,%7,%8,%9,%10,%11,%12,%13,%14,%15,%16,%17,%18,%19,%20,%21,%22,%23,%24,%25,%26,%27,%28,%29,%30,%31,%32,%33,%34,%35,%36,%37,%38,%39,%40,%41,%42,%43,%44,%45,%46,%47,%48,%49,%50,%51,%52,%53,%54,%55,%56,%57,%58,%59,%60,%61,%62,%63,%64,%65,%66,%67,%68,%69,%70,%71,%72,%73,%74,%75,%76,%77,%78,%79,%80,%81,%82,%83,%84,%85,%86,%87,%88,%89,%90,%91,%92,%93,%94,%95}, %96, %97, p, 1, 1, 0, 1;\n}\n"
    : "+f"(d[0]),"+f"(d[1]),"+f"(d[2]),"+f"(d[3]),"+f"(d[4]),"+f"(d[5]),"+f"(d[6]),"+f"(d[7]),"+f"(d[8]),"+f"(d[9]),"+f"(d[10]),"+f"(d[11]),"+f"(d[12]),"+f"(d[13]),"+f"(d[14]),"+f"(d[15]),"+f"(d[16]),"+f"(d[17]),"+f"(d[18]),"+f"(d[19]),"+f"(d[20]),"+f"(d[21]),"+f"(d[22]),"+f"(d[23]),"+f"(d[24]),"+f"(d[25]),"+f"(d[26]),"+f"(d[27]),"+f"(d[28]),"+f"(d[29]),"+f"(d[30]),"+f"(d[31]),"+f"(d[32]),"+f"(d[33]),"+f"(d[34]),"+f"(d[35]),"+f"(d[36]),"+f"(d[37]),"+f"(d[38]),"+f"(d[39]),"+f"(d[40]),"+f"(d[41]),"+f"(d[42]),"+f"(d[43]),"+f"(d[44]),"+f"(d[45]),"+f"(d[46]),"+f"(d[47]),"+f"(d[48]),"+f"(d[49]),"+f"(d[50]),"+f"(d[51]),"+f"(d[52]),"+f"(d[53]),"+f"(d[54]),"+f"(d[55]),"+f"(d[56]),"+f"(d[57]),"+f"(d[58]),"+f"(d[59]),"+f"(d[60]),"+f"(d[61]),"+f"(d[62]),"+f"(d[63]),"+f"(d[64]),"+f"(d[65]),"+f"(d[66]),"+f"(d[67]),"+f"(d[68]),"+f"(d[69]),"+f"(d[70]),"+f"(d[71]),"+f"(d[72]),"+f"(d[73]),"+f"(d[74]),"+f"(d[75]),"+f"(d[76]),"+f"(d[77]),"+f"(d[78]),"+f"(d[79]),"+f"(d[80]),"+f"(d[81]),"+f"(d[82]),"+f"(d[83]),"+f"(d[84]),"+f"(d[85]),"+f"(d[86]),"+f"(d[87]),"+f"(d[88]),"+f"(d[89]),"+f"(d[90]),"+f"(d[91]),"+f"(d[92]),"+f"(d[93]),"+f"(d[94]),"+f"(d[95])
    : "l"(da),"l"(db),"r"(sc));
}

__device__ __forceinline__ uint32_t smem_u32(const void* p) { return (uint32_t)__cvta_generic_to_shared(p); }
__device__ __forceinline__ void mbar_init(uint32_t bar, uint32_t cnt) { asm volatile("mbarrier.init.shared::cta.b64 [%0], %1;" :: "r"(bar), "r"(cnt)); }
__device__ __forceinline__ void mbar_expect_tx(uint32_t bar, uint32_t bytes) { asm volatile("mbarrier.arrive.expect_tx.shared::cta.b64 _, [%0], %1;" :: "r"(bar), "r"(bytes) : "memory"); }
__device__ __forceinline__ void mbar_arrive(uint32_t bar) { asm volatile("mbarrier.arrive.shared::cta.b64 _, [%0];" :: "r"(bar) : "memory"); }
__device__ __forceinline__ void mbar_arrive_cluster(uint32_t cbar, uint32_t cnt) { asm volatile("mbarrier.arrive.shared::cluster.b64 _, [%0], %1;" :: "r"(cbar), "r"(cnt) : "memory"); }
__device__ __forceinline__ uint32_t mapa(uint32_t a, uint32_t rank) { uint32_t r; asm volatile("mapa.shared::cluster.u32 %0, %1, %2;" : "=r"(r) : "r"(a), "r"(rank)); return r; }
__device__ __forceinline__ void mbar_wait(uint32_t bar, uint32_t parity) {
    uint32_t ok; uint32_t n = 0;
    do {
        asm volatile("{\n.reg .pred p;\nmbarrier.try_wait.parity.shared::cta.b64 p, [%1], %2;\nselp.u32 %0, 1, 0, p;\n}" : "=r"(ok) : "r"(bar), "r"(parity) : "memory");
    } while (!ok && ++n < (1u << 17));
}
__device__ __forceinline__ void pace_wait(uint32_t a, uint32_t target) {
    uint32_t v, n = 0;
    do {
        asm volatile("ld.volatile.shared.u32 %0, [%1];" : "=r"(v) : "r"(a) : "memory");
        if (v < target) __nanosleep(150);
    } while (v < target && ++n < (1u << 14));
}
__device__ __forceinline__ void flag_wait(const unsigned* p, unsigned target) {
    unsigned v; uint32_t n = 0;
    while (true) {
        asm volatile("ld.acquire.gpu.global.u32 %0, [%1];" : "=r"(v) : "l"(p) : "memory");
        if ((int)(v - target) >= 0 || ++n >= (1u << 17)) break;
        __nanosleep(100);
    }
}
__device__ __forceinline__ void flag_add(unsigned* p) {
    asm volatile("fence.acq_rel.gpu;\nred.relaxed.gpu.global.add.u32 [%0], 1;" :: "l"(p) : "memory");
}
__device__ __forceinline__ uint64_t make_desc(uint32_t addr, uint32_t lbo, uint32_t sbo, uint32_t swz) {
    return (uint64_t)((addr & 0x3FFFF) >> 4) | ((uint64_t)((lbo & 0x3FFFF) >> 4) << 16) | ((uint64_t)((sbo & 0x3FFFF) >> 4) << 32) | ((uint64_t)swz << 62);
}
__device__ __forceinline__ uint64_t desc_add(uint64_t d, uint32_t off16) {
    return (d & 0xFFFFFFFF00000000ull) | (uint64_t)((uint32_t)d + off16);
}
__device__ __forceinline__ void tma2d(uint32_t dst, const CUtensorMap* tm, int c0, int c1, uint32_t bar) {
    asm volatile("cp.async.bulk.tensor.2d.shared::cluster.global.mbarrier::complete_tx::bytes [%0], [%1, {%3, %4}], [%2];"
        :: "r"(dst), "l"((uint64_t)tm), "r"(bar), "r"(c0), "r"(c1) : "memory");
}
__device__ __forceinline__ void tma3d_mc(uint32_t dst, const CUtensorMap* tm, int c0, int c1, int c2, uint32_t bar) {
    asm volatile("cp.async.bulk.tensor.3d.shared::cluster.global.mbarrier::complete_tx::bytes.multicast::cluster [%0], [%1, {%3, %4, %5}], [%2], %6;"
        :: "r"(dst), "l"((uint64_t)tm), "r"(bar), "r"(c0), "r"(c1), "r"(c2), "h"((uint16_t)3) : "memory");
}
__device__ __forceinline__ void bulk_g2s(uint32_t dst, const void* src, uint32_t bytes, uint32_t bar) {
    asm volatile("cp.async.bulk.shared::cluster.global.mbarrier::complete_tx::bytes [%0], [%1], %2, [%3];"
        :: "r"(dst), "l"(src), "r"(bytes), "r"(bar) : "memory");
}
__device__ __forceinline__ void bulk_s2g(void* dst, uint32_t src, uint32_t bytes) {
    asm volatile("cp.async.bulk.global.shared::cta.bulk_group [%0], [%1], %2;" :: "l"(dst), "r"(src), "r"(bytes) : "memory");
}
__device__ __forceinline__ void tma2d_store(const CUtensorMap* tm, int c0, int c1, uint32_t src) {
    asm volatile("cp.async.bulk.tensor.2d.global.shared::cta.bulk_group [%0, {%2, %3}], [%1];"
        :: "l"((uint64_t)tm), "r"(src), "r"(c0), "r"(c1) : "memory");
}
__device__ __forceinline__ void l2_prefetch(const void* p, uint32_t bytes) {
    asm volatile("cp.async.bulk.prefetch.L2.global [%0], %1;" :: "l"(p), "r"(bytes) : "memory");
}
__device__ __forceinline__ void tmap_prefetch(const CUtensorMap* tm) { asm volatile("prefetch.tensormap [%0];" :: "l"((uint64_t)tm) : "memory"); }
__device__ __forceinline__ uint32_t lds32(uint32_t a) { uint32_t v; asm volatile("ld.shared.u32 %0, [%1];" : "=r"(v) : "r"(a)); return v; }
__device__ __forceinline__ uint2 lds64(uint32_t a) { uint2 v; asm volatile("ld.shared.v2.u32 {%0,%1}, [%2];" : "=r"(v.x), "=r"(v.y) : "r"(a)); return v; }
__device__ __forceinline__ uint4 lds128(uint32_t a) { uint4 v; asm volatile("ld.shared.v4.u32 {%0,%1,%2,%3}, [%4];" : "=r"(v.x), "=r"(v.y), "=r"(v.z), "=r"(v.w) : "r"(a)); return v; }
__device__ __forceinline__ float2 lds64f(uint32_t a) { float2 v; asm volatile("ld.shared.v2.f32 {%0,%1}, [%2];" : "=f"(v.x), "=f"(v.y) : "r"(a)); return v; }
__device__ __forceinline__ void sts32(uint32_t a, uint32_t v) { asm volatile("st.shared.u32 [%0], %1;" :: "r"(a), "r"(v) : "memory"); }
__device__ __forceinline__ void sts128(uint32_t a, uint4 v) { asm volatile("st.shared.v4.u32 [%0], {%1,%2,%3,%4};" :: "r"(a), "r"(v.x), "r"(v.y), "r"(v.z), "r"(v.w) : "memory"); }
__device__ __forceinline__ uint4 ldg_cg128(const void* p) { uint4 v; asm volatile("ld.global.cg.v4.u32 {%0,%1,%2,%3}, [%4];" : "=r"(v.x), "=r"(v.y), "=r"(v.z), "=r"(v.w) : "l"(p)); return v; }
__device__ __forceinline__ uint4 ldg_nc128(const void* p) { uint4 v; asm volatile("ld.global.nc.L1::no_allocate.v4.u32 {%0,%1,%2,%3}, [%4];" : "=r"(v.x), "=r"(v.y), "=r"(v.z), "=r"(v.w) : "l"(p)); return v; }
__device__ __forceinline__ uint2 ldg_nc64(const void* p) { uint2 v; asm volatile("ld.global.nc.L1::no_allocate.v2.u32 {%0,%1}, [%2];" : "=r"(v.x), "=r"(v.y) : "l"(p)); return v; }
#define WG_FENCE() asm volatile("wgmma.fence.sync.aligned;\n" ::: "memory")
#define WG_COMMIT() asm volatile("wgmma.commit_group.sync.aligned;\n" ::: "memory")
template<int N> __device__ __forceinline__ void wg_wait() { asm volatile("wgmma.wait_group.sync.aligned %0;\n" :: "n"(N) : "memory"); }
__device__ __forceinline__ void named_bar(int id, int n) { asm volatile("bar.sync %0, %1;" :: "r"(id), "r"(n) : "memory"); }

__device__ __forceinline__ float bf_lo(uint32_t u) { return __uint_as_float(u << 16); }
__device__ __forceinline__ float bf_hi(uint32_t u) { return __uint_as_float(u & 0xFFFF0000u); }
__device__ __forceinline__ uint32_t pack_bf(float lo, float hi) { uint32_t r; asm("cvt.rn.bf16x2.f32 %0, %1, %2;" : "=r"(r) : "f"(hi), "f"(lo)); return r; }
__device__ __forceinline__ float bf_round(float x) { return __bfloat162float(__float2bfloat16_rn(x)); }
__device__ __forceinline__ uint32_t bmul2(uint32_t a, uint32_t b) { uint32_t r; asm("mul.rn.bf16x2 %0, %1, %2;" : "=r"(r) : "r"(a), "r"(b)); return r; }
__device__ __forceinline__ uint32_t badd2(uint32_t a, uint32_t b) { uint32_t r; asm("add.rn.bf16x2 %0, %1, %2;" : "=r"(r) : "r"(a), "r"(b)); return r; }
__device__ __forceinline__ uint32_t bsub2(uint32_t a, uint32_t b) { uint32_t r; asm("sub.rn.bf16x2 %0, %1, %2;" : "=r"(r) : "r"(a), "r"(b)); return r; }
__device__ __forceinline__ void mma16816(float (&d)[4], uint32_t a0, uint32_t a1, uint32_t a2, uint32_t a3, uint2 b) {
    asm volatile("mma.sync.aligned.m16n8k16.row.col.f32.bf16.bf16.f32 {%0,%1,%2,%3}, {%4,%5,%6,%7}, {%8,%9}, {%0,%1,%2,%3};\n"
        : "+f"(d[0]), "+f"(d[1]), "+f"(d[2]), "+f"(d[3]) : "r"(a0), "r"(a1), "r"(a2), "r"(a3), "r"(b.x), "r"(b.y));
}

template<int HS> __device__ __forceinline__ void xreduce(float (&v)[32], int lane) {
    const int up = lane & HS;
    #pragma unroll
    for (int e = 0; e < HS; e++) {
        float keep, send;
        asm("{\n.reg .pred p;\nsetp.ne.b32 p, %4, 0;\nselp.f32 %0, %3, %2, p;\nselp.f32 %1, %2, %3, p;\n}"
            : "=f"(keep), "=f"(send) : "f"(v[e]), "f"(v[e + HS]), "r"(up));
        v[e] = keep + __shfl_xor_sync(0xffffffffu, send, HS);
    }
}

__device__ __forceinline__ int blk_f0(int bi, int j) {
    if (bi < 32) return 224 * ((j + (bi >> 2)) & 7) + 32 * (bi & 3);
    int b2 = bi - 32; int q3 = (b2 * 11) >> 5;
    return 224 * ((j + q3) & 7) + 128 + 32 * (b2 - 3 * q3);
}
__device__ __forceinline__ int next_st2(int s) { return (0x14023 >> (4 * s)) & 7; }
__device__ __forceinline__ uint32_t stage_off_rt(int s) { return s < 3 ? SM_RING + s * STAGE_BYTES : (uint32_t)(s - 3) * STAGE_BYTES; }

template<int NB>
__device__ __forceinline__ void gemm1_pass(uint32_t sb, int wgi, int warp4, int lane, int& st, uint32_t& fph, uint32_t e_cl,
                                           int rb64, int ks0, bool convCTA) {
    constexpr bool passA = (NB == 4);
    float acc[NB * 32];
    const uint64_t descA0 = make_desc(sb + SM_X + wgi * 8192, 16, 1024, 1);
    const uint64_t descB0 = make_desc(sb + SM_RING, 4096, 512, 2);
    int prev = 0;
    #pragma unroll 1
    for (int sl = 0; sl < 8; sl++) {
        if (warp4 == 0 && wgi == 0) PROF2(2, sl + (passA ? 0 : 8));
        mbar_wait(sb + SM_BARS + (B_FULL + st) * 8, (fph >> st) & 1);
        fph ^= 1u << st;
        if (sl == 0 && warp4 == 0) PROF(2 + wgi * 8 + (passA ? 0 : 3));
        if (warp4 == 0 && wgi == 0) PROF2(1, sl + (passA ? 0 : 8));
        const uint64_t da = desc_add(descA0, sl * 1024), db = desc_add(descB0, st * 2048);
        WG_FENCE();
        #pragma unroll
        for (int kk = 0; kk < 4; kk++) {
            int sc = (sl | kk) ? 1 : 0;
            if constexpr (NB == 4) wgmma_ss_n256_tb(acc, da + kk * 2, db + kk * 64, sc); else wgmma_ss_n192_tb(acc, da + kk * 2, db + kk * 64, sc);
        }
        WG_COMMIT();
        wg_wait<1>();
        if (warp4 == 0 && wgi == 0) PROF2(3, sl + (passA ? 0 : 8));
        if (lane < 2 && sl && (passA || !convCTA || sl < 6)) mbar_arrive_cluster(e_cl + prev * 8, 1);
        if (!passA) {
            if (convCTA) { if (sl == 5 && lane == 0) mbar_arrive(sb + SM_BARS + B_XFREE * 8); }
            else if ((sl == 2 || sl == 4) && lane < 2) mbar_arrive_cluster(e_cl + (2 + (sl >> 1)) * 8, 1);
        }
        prev = st;
        st = (st == 2) ? 0 : st + 1;
    }
    wg_wait<0>();
    if (lane < 2 && (passA || !convCTA)) mbar_arrive_cluster(e_cl + prev * 8, 1);
    if (!passA && lane == 0) mbar_arrive(sb + SM_BARS + B_G1DONE * 8);
    if (warp4 == 0) PROF(3 + wgi * 8 + (passA ? 0 : 3));
    const int g = lane >> 2;
    const int r0 = wgi * 64 + warp4 * 16 + g;
    const float s0 = __uint_as_float(lds32(sb + SM_STATS + r0 * 8 + 4)), s1 = __uint_as_float(lds32(sb + SM_STATS + (r0 + 8) * 8 + 4));
    uint32_t* dst = g_h + (size_t)(rb64 * 112 + ks0) * 512 + warp4 * 128 + lane;
    #pragma unroll
    for (int kk = 0; kk < NB * 2; kk++) {
        uint32_t h[4];
        #pragma unroll
        for (int tt = 0; tt < 2; tt++) {
            const int t = 2 * kk + tt;
            const float* ag = &acc[4 * t];
            const float* au = &acc[NB * 16 + 4 * t];
            h[2 * tt] = bmul2(pack_bf(ag[0] * s0, ag[1] * s0), pack_bf(au[0] * s0, au[1] * s0));
            h[2 * tt + 1] = bmul2(pack_bf(ag[2] * s1, ag[3] * s1), pack_bf(au[2] * s1, au[3] * s1));
        }
        dst[kk * 512] = h[0]; dst[kk * 512 + 64] = h[1]; dst[kk * 512 + 32] = h[2]; dst[kk * 512 + 96] = h[3];
    }
    asm volatile("fence.proxy.async.global;" ::: "memory");
    __syncwarp();
    if (lane == 0) mbar_arrive(sb + SM_BARS + (B_HD + wgi * 2 + (passA ? 0 : 1)) * 8);
    if (warp4 == 0) PROF(4 + wgi * 8 + (passA ? 0 : 3));
}

template<int P0, int NP>
__device__ __forceinline__ void conv_load_a(uint32_t (&a)[NP][2][4], uint32_t hk_lane, int m_lane) {
    #pragma unroll
    for (int pp = 0; pp < NP; pp++) {
        #pragma unroll
        for (int q = 0; q < 2; q++) {
            const int off = (8 * q + 64 * (P0 + pp)) * 4;
            uint32_t w0, w1, w2;
            if (P0 + pp == 0 && q == 0) {
                w0 = (m_lane + 0 < 8) ? 0u : lds32(hk_lane + off);
                w1 = (m_lane + 1 < 8) ? 0u : lds32(hk_lane + off + 4);
                w2 = (m_lane + 2 < 8) ? 0u : lds32(hk_lane + off + 8);
            } else {
                w0 = lds32(hk_lane + off); w1 = lds32(hk_lane + off + 4); w2 = lds32(hk_lane + off + 8);
            }
            a[pp][q][0] = w1;
            a[pp][q][1] = __byte_perm(w0, w1, 0x5432);
            a[pp][q][2] = w2;
            a[pp][q][3] = __byte_perm(w1, w2, 0x5432);
        }
    }
}
template<int P0, int NP>
__device__ __forceinline__ void conv_mma(float (&acc)[4][16], uint32_t (&a)[NP][2][4], uint64_t db) {
    WG_FENCE();
    #pragma unroll
    for (int pp = 0; pp < NP; pp++) {
        #pragma unroll
        for (int q = 0; q < 2; q++) {
            const int P = P0 + pp;
            #pragma unroll
            for (int bq = P / 4; bq < 4; bq++)
                wgmma_rs_n32(acc[bq], a[pp][q][0], a[pp][q][1], a[pp][q][2], a[pp][q][3],
                             db + (uint64_t)(int64_t)(32 * bq - 8 * P - q), (P == 0 && q == 0) ? 0 : 1);
        }
    }
    WG_COMMIT();
}

__global__ void __cluster_dims__(2, 1, 1) __launch_bounds__(NTHREADS, 1)
fused_kernel(const __grid_constant__ Params p) {
    extern __shared__ __align__(1024) uint8_t smem_raw[];
    const uint32_t sb = smem_u32(smem_raw);
    const int tid = threadIdx.x, warp = tid >> 5, lane = tid & 31;
    const int b = blockIdx.x;
    const int rank = b & 1;
    const int j = (b >> 1) & 7;
    const int i = ((b >> 4) << 1) | rank;
    const int cb = j >> 1;
    const bool convCTA = j & 1;
    const int cidx = 4 * i + cb;

    if (warp == 8 && lane < 4) {
        mbar_init(sb + SM_BARS + (B_XFULL + lane) * 8, 1);
        asm volatile("fence.proxy.async.shared::cta;" ::: "memory");
        mbar_expect_tx(sb + SM_BARS + (B_XFULL + lane) * 8, 32768);
    }
    if (tid == 288) {
        for (int s = 0; s < 5; s++) { mbar_init(sb + SM_BARS + (B_FULL + s) * 8, 1); mbar_init(sb + SM_BARS + (B_EMPTY + s) * 8, 16); }
        mbar_init(sb + SM_BARS + B_CONV * 8, 1);
        mbar_init(sb + SM_BARS + B_YT * 8, 1);
        mbar_init(sb + SM_BARS + B_XR * 8, 1);
        mbar_init(sb + SM_BARS + B_G1DONE * 8, 8);
        mbar_init(sb + SM_BARS + B_XFREE * 8, 8);
        mbar_init(sb + SM_BARS + B_YST * 8, 8);
        for (int s = 0; s < 4; s++) mbar_init(sb + SM_BARS + (B_HD + s) * 8, 4);
        for (int s = 0; s < 2; s++) mbar_init(sb + SM_BARS + (B_HRDY + s) * 8, 1);
        asm volatile("fence.mbarrier_init.release.cluster;" ::: "memory");
        asm volatile("fence.proxy.async.shared::cta;" ::: "memory");
    }
    __syncwarp();
    asm volatile("barrier.cluster.arrive.relaxed.aligned;\n" ::: "memory");
    if (warp == 8) {
        const int rg = lane >> 3, sl = lane & 7;
        tma2d(sb + SM_X + sl * 16384 + rg * 4096, &p.tm_x, 64 * ((sl + 2 * cb + 2) & 7), 128 * i + 32 * rg, sb + SM_BARS + (B_XFULL + rg) * 8);
        __syncwarp();
    }
    asm volatile("barrier.cluster.wait.aligned;\n" ::: "memory");
    PROFW(1, 0);

    if (warp < 8) {
        asm volatile("setmaxnreg.inc.sync.aligned.u32 200;");
        const int wgi = warp >> 2, warp4 = warp & 3;
        const int g = lane >> 2, c = lane & 3;
        const uint32_t e_cl = mapa(sb + SM_BARS + B_EMPTY * 8, lane & 1);
        {
            const uint32_t xa = sb + SM_X + (lane >> 3) * 16384 + warp * 16 * 128;
            uint4 xr[16][2];
            float v[32];
            mbar_wait(sb + SM_BARS + (B_XFULL + (warp >> 1)) * 8, 0);
            PROFW(16, 0); PROFW(18, 7);
            #pragma unroll
            for (int r = 0; r < 16; r++) {
                const uint32_t a = xa + r * 128 + (((lane & 7) ^ (r & 7)) << 4);
                xr[r][0] = lds128(a); xr[r][1] = lds128(a + 65536);
            }
            #pragma unroll
            for (int r = 0; r < 16; r++) {
                const uint32_t* u = (const uint32_t*)&xr[r][0];
                float s = 0.f, q = 0.f;
                #pragma unroll
                for (int e = 0; e < 8; e++) { const float lo = bf_lo(u[e]), hi = bf_hi(u[e]); s += lo; q = fmaf(lo, lo, q); s += hi; q = fmaf(hi, hi, q); }
                v[r] = s; v[16 + r] = q;
            }
            xreduce<16>(v, lane); xreduce<8>(v, lane); xreduce<4>(v, lane); xreduce<2>(v, lane); xreduce<1>(v, lane);
            const float other = __shfl_xor_sync(0xffffffffu, v[0], 16);
            const float mean = (lane < 16 ? v[0] : other) * (1.0f / DM);
            const float msq = (lane < 16 ? other : v[0]) * (1.0f / DM);
            const float var_b = bf_round(fmaxf(msq - mean * mean, 0.f));
            const float sd = bf_round(sqrtf(bf_round(var_b + 1e-5f)));
            const uint32_t mb = pack_bf(mean, mean);
            if (lane < 16) { sts32(sb + SM_STATS + (warp * 16 + lane) * 8, mb); sts32(sb + SM_STATS + (warp * 16 + lane) * 8 + 4, __float_as_uint(1.0f / sd)); }
            #pragma unroll
            for (int r = 0; r < 16; r++) {
                const uint32_t m = __shfl_sync(0xffffffffu, mb, r);
                const uint32_t a = xa + r * 128 + (((lane & 7) ^ (r & 7)) << 4);
                #pragma unroll
                for (int hh = 0; hh < 2; hh++) {
                    uint4 t = xr[r][hh];
                    t.x = bsub2(t.x, m); t.y = bsub2(t.y, m); t.z = bsub2(t.z, m); t.w = bsub2(t.w, m);
                    sts128(a + hh * 65536, t);
                }
            }
            asm volatile("fence.proxy.async.shared::cta;" ::: "memory");
            named_bar(1 + wgi, 128);
            PROFW(17, 0); PROFW(19, 7);
        }
        int st = 0; uint32_t fph = 0;
        const int rb64 = 2 * i + wgi;
        gemm1_pass<4>(sb, wgi, warp4, lane, st, fph, e_cl, rb64, 14 * j, convCTA);
        gemm1_pass<3>(sb, wgi, warp4, lane, st, fph, e_cl, rb64, 14 * j + 8, convCTA);

        if (convCTA) {
            const int m_lane = g + 2 * c + 16 * warp4;
            const int cp = (c + warp4) & 3, ish = (c + warp4) >> 2;
            const uint32_t rdst = sb + SM_RING + wgi * 32768 + warp4 * 8192 + ish * 512 + (g * 4 + cp) * 16;
            const uint32_t rsrc = sb + SM_RING + wgi * 32768 + warp4 * 2048 + lane * 16;
            const uint2 dd = ldg_nc64(p.ssm_D + 8 * cidx + 4 * wgi);
            const uint32_t hk0 = sb + SM_CVH + wgi * 16384 + (m_lane - 8) * 4;
            uint32_t a0[4][2][4], a1[4][2][4];
            mbar_wait(sb + SM_BARS + B_CONV * 8, 0);
            conv_load_a<0, 4>(a0, hk0, m_lane);
            #pragma unroll 1
            for (int ch = 0; ch < 4; ch++) {
                const int gch = 8 * cidx + 4 * wgi + ch;
                const uint32_t dw = (ch & 2) ? dd.y : dd.x;
                const uint32_t d2 = __byte_perm(dw, dw, (ch & 1) ? 0x3232 : 0x1010);
                const uint32_t cbase = sb + SM_CVR + (4 * wgi + ch) * RB_CH;
                const uint64_t db = make_desc(cbase + RB_Z * 16, RB_R1, 128, 0);
                const uint32_t hk_lane = hk0 + ch * 4096;
                float acc[4][16];
                PROFW(32 + ch * 2, 4);
                conv_mma<0, 4>(acc, a0, db);
                conv_load_a<4, 4>(a1, hk_lane, m_lane);
                conv_mma<4, 4>(acc, a1, db);
                wg_wait<1>();
                conv_load_a<8, 4>(a0, hk_lane, m_lane);
                conv_mma<8, 4>(acc, a0, db);
                wg_wait<1>();
                conv_load_a<12, 4>(a1, hk_lane, m_lane);
                conv_mma<12, 4>(acc, a1, db);
                wg_wait<1>();
                conv_load_a<0, 4>(a0, hk0 + (ch < 3 ? ch + 1 : 3) * 4096, m_lane);
                wg_wait<0>();
                PROFW(33 + ch * 2, 4);
                if (ch == 0) mbar_wait(sb + SM_BARS + B_G1DONE * 8, 0);
                else named_bar(1 + wgi, 128);
                #pragma unroll
                for (int ii = 0; ii < 16; ii++) {
                    if (ii < 15 || ish == 0)
                        sts128(rdst + ii * 512, make_uint4(__float_as_uint(acc[ii >> 2][4 * (ii & 3)]), __float_as_uint(acc[ii >> 2][4 * (ii & 3) + 1]),
                                                           __float_as_uint(acc[ii >> 2][4 * (ii & 3) + 2]), __float_as_uint(acc[ii >> 2][4 * (ii & 3) + 3])));
                }
                named_bar(1 + wgi, 128);
                const uint32_t kvaddr = cbase + ((7 - g) & 1) * RB_R1 + (RB_Z + 32 * warp4 + 2 * c) * 16 + ((7 - g) >> 1) * 4;
                uint32_t* ydst = (uint32_t*)(g_yT + (size_t)gch * SEQ + 512 * warp4 + 32 * c + 2 * g);
                uint4 t[4][4]; uint32_t k0[4], k1[4];
                #pragma unroll
                for (int ii = 0; ii < 4; ii++) {
                    #pragma unroll
                    for (int ww = 0; ww < 4; ww++) t[ii][ww] = lds128(rsrc + ww * 8192 + ii * 512);
                    k0[ii] = lds32(kvaddr + ii * 128); k1[ii] = lds32(kvaddr + ii * 128 + 16);
                }
                #pragma unroll
                for (int ii = 0; ii < 4; ii++) {
                    float sx = __uint_as_float(t[ii][0].x), sy = __uint_as_float(t[ii][0].y), sz = __uint_as_float(t[ii][0].z), sw = __uint_as_float(t[ii][0].w);
                    #pragma unroll
                    for (int ww = 1; ww < 4; ww++) {
                        if (!(ii == 0 && warp4 == 0 && c < ww)) {
                            sx += __uint_as_float(t[ii][ww].x); sy += __uint_as_float(t[ii][ww].y); sz += __uint_as_float(t[ii][ww].z); sw += __uint_as_float(t[ii][ww].w);
                        }
                    }
                    ydst[ii * 64] = badd2(pack_bf(sz, sx), bmul2(__byte_perm(k0[ii], k0[ii], 0x1032), d2));
                    ydst[ii * 64 + 8] = badd2(pack_bf(sw, sy), bmul2(__byte_perm(k1[ii], k1[ii], 0x1032), d2));
                }
            }
            PROFW(44, 4);
            asm volatile("fence.proxy.async.global;" ::: "memory");
            __syncwarp();
            if (lane == 0) mbar_arrive(sb + SM_BARS + B_YST * 8);
        } else {
            float acc[64];
            const uint64_t descB0 = make_desc(sb, 4096, 1024, 1);
            const uint64_t descA0 = make_desc(sb + 16384 + wgi * 8192, 128, 256, 0);
            int sg = 3, p0 = 0, p1 = 0; uint32_t ph = 6;
            PROFW(20, 0);
            #pragma unroll 1
            for (int o = 0; o < 14; o++) {
                const int s0 = sg, s1 = next_st2(sg);
                sg = next_st2(s1);
                if (warp == 0) PROF2(2, 16 + o);
                mbar_wait(sb + SM_BARS + (B_FULL + s0) * 8, (ph >> s0) & 1);
                mbar_wait(sb + SM_BARS + (B_FULL + s1) * 8, (ph >> s1) & 1);
                ph ^= (1u << s0) | (1u << s1);
                if (warp == 0) PROF2(1, 16 + o);
                const uint32_t o0 = stage_off_rt(s0) >> 4, o1 = stage_off_rt(s1) >> 4;
                const uint64_t da0 = desc_add(descA0, o0), db0 = desc_add(descB0, o0), da1 = desc_add(descA0, o1), db1 = desc_add(descB0, o1);
                WG_FENCE();
                #pragma unroll
                for (int kk = 0; kk < 4; kk++) wgmma_ss_n128_tb(acc, da0 + kk * 128, db0 + ((kk >> 1) * 512 + (kk & 1) * 128), (o | kk) ? 1 : 0);
                #pragma unroll
                for (int kk = 0; kk < 4; kk++) wgmma_ss_n128_tb(acc, da1 + kk * 128, db1 + ((kk >> 1) * 512 + (kk & 1) * 128), 1);
                WG_COMMIT();
                wg_wait<1>();
                if (warp == 0) PROF2(3, 16 + o);
                if (lane < 2 && o > 0) {
                    if (2 * o - 2 + 5 < 28) mbar_arrive_cluster(e_cl + p0 * 8, 1);
                    if (2 * o - 1 + 5 < 28) mbar_arrive_cluster(e_cl + p1 * 8, 1);
                }
                p0 = s0; p1 = s1;
            }
            wg_wait<0>();
            PROFW(27, 0);
            mbar_wait(sb + SM_BARS + B_XR * 8, 0);
            mbar_wait(sb + SM_BARS + B_YT * 8, 0);
            PROFW(28, 0);
            const int r0 = wgi * 64 + warp4 * 16 + g;
            const float2 st0 = lds64f(sb + SM_STATS + r0 * 8), st1 = lds64f(sb + SM_STATS + (r0 + 8) * 8);
            const uint32_t m0 = __float_as_uint(st0.x), m1 = __float_as_uint(st1.x);
            const uint32_t xrow0 = sb + SM_XE + r0 * 128 + c * 4;
            const int mi = lane >> 3, lr = lane & 7;
            const uint32_t yaddr = sb + SM_YT + wgi * 16384 + ((mi >> 1) * 8 + lr) * 128 + (((2 * warp4 + (mi & 1)) ^ lr) << 4);
            uint32_t y[8][4], xv[16][2];
            #pragma unroll
            for (int t2 = 0; t2 < 8; t2++)
                asm volatile("ldmatrix.sync.aligned.m8n8.x4.trans.shared.b16 {%0,%1,%2,%3}, [%4];"
                    : "=r"(y[t2][0]), "=r"(y[t2][1]), "=r"(y[t2][2]), "=r"(y[t2][3]) : "r"(yaddr + t2 * 2048) : "memory");
            #pragma unroll
            for (int t = 0; t < 16; t++) {
                const uint32_t off = (t >> 3) * 16384 + (((t & 7) ^ g) << 4);
                xv[t][0] = lds32(xrow0 + off); xv[t][1] = lds32(xrow0 + 1024 + off);
            }
            #pragma unroll
            for (int t = 0; t < 16; t++) {
                const uint32_t off = (t >> 3) * 16384 + (((t & 7) ^ g) << 4);
                const uint32_t d0 = bsub2(xv[t][0], m0), d1 = bsub2(xv[t][1], m1);
                const uint32_t n0 = pack_bf(bf_lo(d0) * st0.y, bf_hi(d0) * st0.y), n1 = pack_bf(bf_lo(d1) * st1.y, bf_hi(d1) * st1.y);
                const uint32_t o0 = badd2(badd2(xv[t][0], bmul2(n0, y[t >> 1][2 * (t & 1)])), pack_bf(acc[4 * t], acc[4 * t + 1]));
                const uint32_t o1 = badd2(badd2(xv[t][1], bmul2(n1, y[t >> 1][2 * (t & 1) + 1])), pack_bf(acc[4 * t + 2], acc[4 * t + 3]));
                sts32(xrow0 + off, o0); sts32(xrow0 + 1024 + off, o1);
            }
            asm volatile("fence.proxy.async.shared::cta;" ::: "memory");
            named_bar(1 + wgi, 128);
            if ((tid & 127) == 0) {
                tma2d_store(&p.tm_out, 128 * cb, 128 * i + 64 * wgi, sb + SM_XE + wgi * 8192);
                tma2d_store(&p.tm_out, 128 * cb + 64, 128 * i + 64 * wgi, sb + SM_XE + 16384 + wgi * 8192);
                asm volatile("cp.async.bulk.commit_group;" ::: "memory");
                asm volatile("cp.async.bulk.wait_group.read 0;" ::: "memory");
                PROFW(29, 0);
            }
        }
    } else {
        asm volatile("setmaxnreg.dec.sync.aligned.u32 104;");
        if (warp == 8) {
            if (lane == 0) {
                int st = 0; uint32_t eph = 7;
                #pragma unroll 1
                for (int it = 0; it < 16; it++) {
                    const int pass = it >> 3, sl = it & 7;
                    const int nb = pass ? 3 : 4;
                    const CUtensorMap* tm = pass ? (rank ? &p.tm_uB : &p.tm_gB) : (rank ? &p.tm_uA : &p.tm_gA);
                    mbar_wait(sb + SM_BARS + (B_EMPTY + st) * 8, (eph >> st) & 1);
                    eph ^= 1u << st;
                    if (it == 1) mbar_wait(sb + SM_BARS + (B_XFULL + 2) * 8, 0);
                    PROF2(0, it);
                    mbar_expect_tx(sb + SM_BARS + (B_FULL + st) * 8, nb * 8192);
                    tma3d_mc(sb + SM_RING + st * STAGE_BYTES + rank * nb * 4096, tm, 0, ((sl + 2 * cb + 2) & 7) * 64, 7 * j + 4 * pass, sb + SM_BARS + (B_FULL + st) * 8);
                    st = (st == 2) ? 0 : st + 1;
                }
                st = 3;
                if (!convCTA) {
                    const uint8_t* hsrc = (const uint8_t*)g_h + (size_t)(2 * i) * 112 * 2048;
                    #pragma unroll 1
                    for (int u = 0; u < 28; u++) {
                        mbar_wait(sb + SM_BARS + (B_EMPTY + st) * 8, (eph >> st) & 1);
                        eph ^= 1u << st;
                        if ((u & 1) == 0) PROF2(0, 16 + (u >> 1));
                        const uint32_t so = sb + stage_off_rt(st), bar = sb + SM_BARS + (B_FULL + st) * 8;
                        const int f0 = blk_f0(2 * u, j), f1 = blk_f0(2 * u + 1, j);
                        mbar_expect_tx(bar, 32768);
                        tma3d_mc(so + rank * 8192, &p.tm_w2, 0, rank ? f1 : f0, 2 * cb, bar);
                        if ((u & 15) == 0) mbar_wait(sb + SM_BARS + (B_HRDY + (u >> 4)) * 8, 0);
                        bulk_g2s(so + 16384, hsrc + f0 * 128, 4096, bar);
                        bulk_g2s(so + 16384 + 4096, hsrc + f1 * 128, 4096, bar);
                        bulk_g2s(so + 16384 + 8192, hsrc + 112 * 2048 + f0 * 128, 4096, bar);
                        bulk_g2s(so + 16384 + 12288, hsrc + 112 * 2048 + f1 * 128, 4096, bar);
                        st = next_st2(st);
                    }
                }
                PROF(48);
            }
        } else if (warp < 11) {
            mbar_wait(sb + SM_BARS + (B_XFULL + 3) * 8, 0);
            #pragma unroll 1
            for (int rnd = 0; rnd < 2; rnd++) {
                const int tt = (tid - 288) + 64 * rnd;
                uint32_t sk[4][2];
                uint4 skw[2];
                skw[0] = ldg_nc128(p.shift_k + 16 * tt); skw[1] = ldg_nc128(p.shift_k + 16 * tt + 8);
                const __nv_bfloat16* kp = p.k + (size_t)(16 * b) * DM + 4 * tt;
                const __nv_bfloat16* vp = p.v + (size_t)(16 * b) * DM + 4 * tt;
                uint2 kr[19];
                uint2 kv[16];
                #pragma unroll
                for (int r = 0; r < 3; r++) kr[r] = (b > 0) ? ldg_nc64(kp + (r - 3) * DM) : make_uint2(0, 0);
                #pragma unroll
                for (int r = 0; r < 16; r++) { kr[3 + r] = ldg_nc64(kp + r * DM); if (r < 10) kv[r] = ldg_nc64(vp + r * DM); }
                {
                    const uint4 w0 = skw[0], w1 = skw[1];
                    sk[0][0] = __byte_perm(w0.x, w0.z, 0x5410); sk[1][0] = __byte_perm(w0.x, w0.z, 0x7632);
                    sk[2][0] = __byte_perm(w0.y, w0.w, 0x5410); sk[3][0] = __byte_perm(w0.y, w0.w, 0x7632);
                    sk[0][1] = __byte_perm(w1.x, w1.z, 0x5410); sk[1][1] = __byte_perm(w1.x, w1.z, 0x7632);
                    sk[2][1] = __byte_perm(w1.y, w1.w, 0x5410); sk[3][1] = __byte_perm(w1.y, w1.w, 0x7632);
                }
                #pragma unroll
                for (int s = 0; s < 16; s++) {
                    uint32_t a = bmul2(kr[s].x, sk[3][0]);
                    a = badd2(a, bmul2(kr[s + 1].x, sk[2][0]));
                    a = badd2(a, bmul2(kr[s + 2].x, sk[1][0]));
                    a = badd2(a, bmul2(kr[s + 3].x, sk[0][0]));
                    kv[s].x = bmul2(a, kv[s].x);
                    a = bmul2(kr[s].y, sk[3][1]);
                    a = badd2(a, bmul2(kr[s + 1].y, sk[2][1]));
                    a = badd2(a, bmul2(kr[s + 2].y, sk[1][1]));
                    a = badd2(a, bmul2(kr[s + 3].y, sk[0][1]));
                    kv[s].y = bmul2(a, kv[s].y);
                    if (s < 6) kv[10 + s] = ldg_nc64(vp + (10 + s) * DM);
                }
                PROFW(57 + 2 * rnd, 9);
                #pragma unroll
                for (int cc = 0; cc < 4; cc++) {
                    const uint32_t sel = (cc & 1) ? 0x7632 : 0x5410;
                    #define KVW(r) ((cc & 2) ? kv[r].y : kv[r].x)
                    uint8_t* dst = g_rb + (size_t)(4 * tt + cc) * RB_CH + (RB_Z + b) * 16;
                    *(uint4*)dst = make_uint4(__byte_perm(KVW(15), KVW(14), sel), __byte_perm(KVW(11), KVW(10), sel),
                                              __byte_perm(KVW(7), KVW(6), sel), __byte_perm(KVW(3), KVW(2), sel));
                    *(uint4*)(dst + RB_R1) = make_uint4(__byte_perm(KVW(13), KVW(12), sel), __byte_perm(KVW(9), KVW(8), sel),
                                                        __byte_perm(KVW(5), KVW(4), sel), __byte_perm(KVW(1), KVW(0), sel));
                    if (b < RB_Z) {
                        uint8_t* z = g_rb + (size_t)(4 * tt + cc) * RB_CH + b * 16;
                        *(uint4*)z = make_uint4(0, 0, 0, 0);
                        *(uint4*)(z + RB_R1) = make_uint4(0, 0, 0, 0);
                    }
                    #undef KVW
                }
                PROFW(58 + 2 * rnd, 9);
            }
            asm volatile("fence.proxy.async.global;" ::: "memory");
            __syncwarp();
            if (lane == 0) {
                flag_add(&g_cnt_kv[0]);
                PROFW(50, 9);
                const int wgi = warp - 9;
                mbar_wait(sb + SM_BARS + (B_HD + wgi * 2) * 8, 0);
                flag_add(&g_flag_h[(i * 2 + 0) * 8]);
                mbar_wait(sb + SM_BARS + (B_HD + wgi * 2 + 1) * 8, 0);
                flag_add(&g_flag_h[(i * 2 + 1) * 8]);
                if (wgi == 1 && convCTA) {
                    mbar_wait(sb + SM_BARS + B_YST * 8, 0);
                    flag_add(&g_cnt_y[(cidx >> 4) * 32]);
                    PROF(46);
                }
            }
        } else {
            if (lane == 0) {
                const unsigned ep = g_launch[b] + 1;
                g_launch[b] = ep;
                sts32(sb + SM_EPOCH, ep);
                tmap_prefetch(rank ? &p.tm_uA : &p.tm_gA);
                mbar_wait(sb + SM_BARS + (B_XFULL + 1) * 8, 0);
                l2_prefetch(p.wg + (size_t)b * (FF * DM / NCTA), FF * DM / NCTA * 2);
                l2_prefetch(p.wu + (size_t)b * (FF * DM / NCTA), FF * DM / NCTA * 2);
                tmap_prefetch(rank ? &p.tm_uB : &p.tm_gB);
                tmap_prefetch(&p.tm_w2); tmap_prefetch(&p.tm_yT); tmap_prefetch(&p.tm_out); tmap_prefetch(&p.tm_xe);
                mbar_wait(sb + SM_BARS + (B_FULL + 2) * 8, 0);
                l2_prefetch(p.ssm_k + (size_t)(4 * b) * SEQ, 4 * SEQ * 2);
                l2_prefetch(p.wd + (size_t)b * (FF * DM / NCTA), FF * DM / NCTA * 2);
                mbar_wait(sb + SM_BARS + (B_HD + 0) * 8, 0);
                if (convCTA) {
                    flag_wait(&g_cnt_kv[0], ep * 256);
                    asm volatile("fence.proxy.async.global;" ::: "memory");
                    PROF(53);
                    mbar_wait(sb + SM_BARS + B_XFREE * 8, 0);
                    PROF(54);
                    mbar_expect_tx(sb + SM_BARS + B_CONV * 8, 8 * RB_CH + 32768);
                    bulk_g2s(sb + SM_CVR, g_rb + (size_t)(8 * cidx) * RB_CH, 8 * RB_CH, sb + SM_BARS + B_CONV * 8);
                    bulk_g2s(sb + SM_CVH, p.ssm_k + (size_t)(8 * cidx) * SEQ, 32768, sb + SM_BARS + B_CONV * 8);
                } else {
                    flag_wait(&g_flag_h[(i * 2 + 0) * 8], ep * 16);
                    asm volatile("fence.proxy.async.global;" ::: "memory");
                    mbar_arrive(sb + SM_BARS + B_HRDY * 8);
                    mbar_wait(sb + SM_BARS + B_G1DONE * 8, 0);
                    mbar_expect_tx(sb + SM_BARS + B_XR * 8, 32768);
                    for (int q = 0; q < 4; q++)
                        tma2d(sb + SM_XE + q * 8192, &p.tm_xe, 128 * cb + 64 * (q >> 1), 128 * i + 64 * (q & 1), sb + SM_BARS + B_XR * 8);
                    flag_wait(&g_flag_h[(i * 2 + 1) * 8], ep * 16);
                    asm volatile("fence.proxy.async.global;" ::: "memory");
                    mbar_arrive(sb + SM_BARS + (B_HRDY + 1) * 8);
                    __nanosleep(3000);
                    flag_wait(&g_cnt_y[cb * 32], ep * 16);
                    PROF(49);
                    asm volatile("fence.proxy.async.global;" ::: "memory");
                    mbar_expect_tx(sb + SM_BARS + B_YT * 8, 32768);
                    tma2d(sb + SM_YT, &p.tm_yT, 128 * i, 128 * cb, sb + SM_BARS + B_YT * 8);
                    tma2d(sb + SM_YT + 16384, &p.tm_yT, 128 * i + 64, 128 * cb, sb + SM_BARS + B_YT * 8);
                }
            }
        }
    }
}

typedef CUresult (*EncodeFn)(CUtensorMap*, CUtensorMapDataType, cuuint32_t, void*, const cuuint64_t*, const cuuint64_t*,
                             const cuuint32_t*, const cuuint32_t*, CUtensorMapInterleave, CUtensorMapSwizzle,
                             CUtensorMapL2promotion, CUtensorMapFloatOOBfill);

void encode(EncodeFn fn, CUtensorMap* tm, const void* base, int rank, const cuuint64_t* dims, const cuuint64_t* strides,
            const cuuint32_t* box, CUtensorMapSwizzle swz) {
    cuuint32_t es[5] = {1, 1, 1, 1, 1};
    fn(tm, CU_TENSOR_MAP_DATA_TYPE_BFLOAT16, rank, (void*)base, dims, strides, box, es, CU_TENSOR_MAP_INTERLEAVE_NONE, swz,
       CU_TENSOR_MAP_L2_PROMOTION_L2_128B, CU_TENSOR_MAP_FLOAT_OOB_FILL_NONE);
}

}

extern "C" void kernel_launch(void* const* d_in, const int* in_sizes, int n_in, void* d_out, int out_size) {
    (void)in_sizes; (void)n_in; (void)out_size;
    static EncodeFn enc = nullptr;
    static void* yT_ptr = nullptr;
    if (!enc) {
        void* fn = nullptr; cudaDriverEntryPointQueryResult qr;
        cudaGetDriverEntryPoint("cuTensorMapEncodeTiled", &fn, cudaEnableDefault, &qr);
        enc = (EncodeFn)fn;
        cudaGetSymbolAddress(&yT_ptr, g_yT);
        cudaFuncSetAttribute(fused_kernel, cudaFuncAttributeMaxDynamicSharedMemorySize, SM_TOTAL);
    }
    Params p;
    p.q = (const __nv_bfloat16*)d_in[0]; p.k = (const __nv_bfloat16*)d_in[1]; p.v = (const __nv_bfloat16*)d_in[2];
    p.shift_k = (const __nv_bfloat16*)d_in[3]; p.ssm_k = (const __nv_bfloat16*)d_in[4]; p.ssm_D = (const __nv_bfloat16*)d_in[5];
    p.wg = (const __nv_bfloat16*)d_in[7]; p.wu = (const __nv_bfloat16*)d_in[8]; p.wd = (const __nv_bfloat16*)d_in[9];
    {
        cuuint64_t dims[2] = {DM, SEQ}; cuuint64_t str[1] = {DM * 2};
        cuuint32_t box[2] = {64, 32};
        encode(enc, &p.tm_x, p.q, 2, dims, str, box, CU_TENSOR_MAP_SWIZZLE_128B);
        cuuint32_t box2[2] = {64, 64};
        encode(enc, &p.tm_out, d_out, 2, dims, str, box2, CU_TENSOR_MAP_SWIZZLE_128B);
        encode(enc, &p.tm_xe, p.q, 2, dims, str, box2, CU_TENSOR_MAP_SWIZZLE_128B);
    }
    {
        cuuint64_t dims[3] = {32, DM, FF / 32}; cuuint64_t str[2] = {FF * 2, 64};
        cuuint32_t boxA[3] = {32, 64, 4}, boxB[3] = {32, 64, 3};
        encode(enc, &p.tm_gA, p.wg, 3, dims, str, boxA, CU_TENSOR_MAP_SWIZZLE_64B);
        encode(enc, &p.tm_gB, p.wg, 3, dims, str, boxB, CU_TENSOR_MAP_SWIZZLE_64B);
        encode(enc, &p.tm_uA, p.wu, 3, dims, str, boxA, CU_TENSOR_MAP_SWIZZLE_64B);
        encode(enc, &p.tm_uB, p.wu, 3, dims, str, boxB, CU_TENSOR_MAP_SWIZZLE_64B);
    }
    {
        cuuint64_t dims[3] = {64, FF, DM / 64}; cuuint64_t str[2] = {DM * 2, 128};
        cuuint32_t box[3] = {64, 32, 2};
        encode(enc, &p.tm_w2, p.wd, 3, dims, str, box, CU_TENSOR_MAP_SWIZZLE_128B);
    }
    {
        cuuint64_t dims[2] = {SEQ, DM}; cuuint64_t str[1] = {SEQ * 2};
        cuuint32_t box[2] = {64, 128};
        encode(enc, &p.tm_yT, yT_ptr, 2, dims, str, box, CU_TENSOR_MAP_SWIZZLE_128B);
    }
    fused_kernel<<<NCTA, NTHREADS, SM_TOTAL>>>(p);
}
```

```cpp
#include <cuda_runtime.h>
#include <cuda_bf16.h>
#include <cuda.h>
#include <stdint.h>

namespace {

constexpr int SEQ = 2048, DM = 512, FF = 1792;
constexpr int NCTA = 128;
constexpr int NTHREADS = 384;
constexpr int STAGE_BYTES = 32768;

constexpr uint32_t SM_X = 0;
constexpr uint32_t SM_RING = 131072;
constexpr uint32_t SM_MISC = SM_RING + 3 * STAGE_BYTES;
constexpr uint32_t SM_BARS = SM_MISC;
constexpr uint32_t SM_EPOCH = SM_MISC + 248;
constexpr uint32_t SM_STATS = SM_MISC + 256;
constexpr uint32_t SM_TOTAL = SM_STATS + 1024;
static_assert(SM_TOTAL <= 232448, "smem");
constexpr int RB_Z = 25;
constexpr int RB_R1 = (128 + RB_Z) * 16;
constexpr int RB_CH = 2 * RB_R1;
constexpr uint32_t SM_CVR = 0;
constexpr uint32_t SM_CVH = 8 * RB_CH;
static_assert(SM_CVH + 8 * 4096 <= 5 * 16384, "conv operands");
constexpr uint32_t SM_YT = 4 * 16384;
constexpr uint32_t SM_XE = 6 * 16384;

constexpr int B_FULL = 0, B_EMPTY = 5, B_XFULL = 10, B_CONV = 14, B_YT = 15, B_XR = 16, B_G1DONE = 17, B_HD = 18, B_HRDY = 22,
              B_XFREE = 24, B_YST = 25, B_COUNT = 26;
static_assert(B_COUNT * 8 <= 248, "barrier space");

__device__ __align__(128) uint32_t g_h[32 * 112 * 512];
__device__ __align__(128) uint8_t g_rb[DM * RB_CH];
__device__ __align__(128) __nv_bfloat16 g_yT[DM * SEQ];
__device__ unsigned g_launch[NCTA];
__device__ unsigned g_cnt_kv[32];
__device__ unsigned g_cnt_y[4 * 32];
__device__ unsigned g_flag_h[16 * 2 * 8];

#define PROF(idx)
#define PROF2(a, idx)
#define PROFW(idx, w)

struct Params {
    CUtensorMap tm_x, tm_gA, tm_gB, tm_uA, tm_uB, tm_w2, tm_yT, tm_out, tm_xe;
    const __nv_bfloat16 *q, *k, *v, *shift_k, *ssm_k, *ssm_D, *wg, *wu, *wd;
};

__device__ __forceinline__ void wgmma_rs_n32(float (&d)[16], uint32_t a0, uint32_t a1, uint32_t a2, uint32_t a3, uint64_t db, int sc) {
  asm volatile("{\n.reg .pred p;\nsetp.ne.b32 p, %21, 0;\n"
    "wgmma.mma_async.sync.aligned.m64n32k16.f32.bf16.bf16 {%0,%1,%2,%3,%4,%5,%6,%7,%8,%9,%10,%11,%12,%13,%14,%15}, {%16,%17,%18,%19}, %20, p, 1, 1, 0;\n}\n"
    : "+f"(d[0]),"+f"(d[1]),"+f"(d[2]),"+f"(d[3]),"+f"(d[4]),"+f"(d[5]),"+f"(d[6]),"+f"(d[7]),"+f"(d[8]),"+f"(d[9]),"+f"(d[10]),"+f"(d[11]),"+f"(d[12]),"+f"(d[13]),"+f"(d[14]),"+f"(d[15])
    : "r"(a0),"r"(a1),"r"(a2),"r"(a3),"l"(db),"r"(sc));
}
__device__ __forceinline__ void wgmma_rs_n128_tb(float (&d)[64], uint32_t a0, uint32_t a1, uint32_t a2, uint32_t a3, uint64_t db, int sc) {
  asm volatile("{\n.reg .pred p;\nsetp.ne.b32 p, %69, 0;\n"
    "wgmma.mma_async.sync.aligned.m64n128k16.f32.bf16.bf16 {%0,%1,%2,%3,%4,%5,%6,%7,%8,%9,%10,%11,%12,%13,%14,%15,%16,%17,%18,%19,%20,%21,%22,%23,%24,%25,%26,%27,%28,%29,%30,%31,%32,%33,%34,%35,%36,%37,%38,%39,%40,%41,%42,%43,%44,%45,%46,%47,%48,%49,%50,%51,%52,%53,%54,%55,%56,%57,%58,%59,%60,%61,%62,%63}, {%64,%65,%66,%67}, %68, p, 1, 1, 1;\n}\n"
    : "+f"(d[0]),"+f"(d[1]),"+f"(d[2]),"+f"(d[3]),"+f"(d[4]),"+f"(d[5]),"+f"(d[6]),"+f"(d[7]),"+f"(d[8]),"+f"(d[9]),"+f"(d[10]),"+f"(d[11]),"+f"(d[12]),"+f"(d[13]),"+f"(d[14]),"+f"(d[15]),"+f"(d[16]),"+f"(d[17]),"+f"(d[18]),"+f"(d[19]),"+f"(d[20]),"+f"(d[21]),"+f"(d[22]),"+f"(d[23]),"+f"(d[24]),"+f"(d[25]),"+f"(d[26]),"+f"(d[27]),"+f"(d[28]),"+f"(d[29]),"+f"(d[30]),"+f"(d[31]),"+f"(d[32]),"+f"(d[33]),"+f"(d[34]),"+f"(d[35]),"+f"(d[36]),"+f"(d[37]),"+f"(d[38]),"+f"(d[39]),"+f"(d[40]),"+f"(d[41]),"+f"(d[42]),"+f"(d[43]),"+f"(d[44]),"+f"(d[45]),"+f"(d[46]),"+f"(d[47]),"+f"(d[48]),"+f"(d[49]),"+f"(d[50]),"+f"(d[51]),"+f"(d[52]),"+f"(d[53]),"+f"(d[54]),"+f"(d[55]),"+f"(d[56]),"+f"(d[57]),"+f"(d[58]),"+f"(d[59]),"+f"(d[60]),"+f"(d[61]),"+f"(d[62]),"+f"(d[63])
    : "r"(a0),"r"(a1),"r"(a2),"r"(a3),"l"(db),"r"(sc));
}
__device__ __forceinline__ void wgmma_ss_n256_tb(float (&d)[128], uint64_t da, uint64_t db, int sc) {
  asm volatile("{\n.reg .pred p;\nsetp.ne.b32 p, %130, 0;\n"
    "wgmma.mma_async.sync.aligned.m64n256k16.f32.bf16.bf16 {%0,%1,%2,%3,%4,%5,%6,%7,%8,%9,%10,%11,%12,%13,%14,%15,%16,%17,%18,%19,%20,%21,%22,%23,%24,%25,%26,%27,%28,%29,%30,%31,%32,%33,%34,%35,%36,%37,%38,%39,%40,%41,%42,%43,%44,%45,%46,%47,%48,%49,%50,%51,%52,%53,%54,%55,%56,%57,%58,%59,%60,%61,%62,%63,%64,%65,%66,%67,%68,%69,%70,%71,%72,%73,%74,%75,%76,%77,%78,%79,%80,%81,%82,%83,%84,%85,%86,%87,%88,%89,%90,%91,%92,%93,%94,%95,%96,%97,%98,%99,%100,%101,%102,%103,%104,%105,%106,%107,%108,%109,%110,%111,%112,%113,%114,%115,%116,%117,%118,%119,%120,%121,%122,%123,%124,%125,%126,%127}, %128, %129, p, 1, 1, 0, 1;\n}\n"
    : "+f"(d[0]),"+f"(d[1]),"+f"(d[2]),"+f"(d[3]),"+f"(d[4]),"+f"(d[5]),"+f"(d[6]),"+f"(d[7]),"+f"(d[8]),"+f"(d[9]),"+f"(d[10]),"+f"(d[11]),"+f"(d[12]),"+f"(d[13]),"+f"(d[14]),"+f"(d[15]),"+f"(d[16]),"+f"(d[17]),"+f"(d[18]),"+f"(d[19]),"+f"(d[20]),"+f"(d[21]),"+f"(d[22]),"+f"(d[23]),"+f"(d[24]),"+f"(d[25]),"+f"(d[26]),"+f"(d[27]),"+f"(d[28]),"+f"(d[29]),"+f"(d[30]),"+f"(d[31]),"+f"(d[32]),"+f"(d[33]),"+f"(d[34]),"+f"(d[35]),"+f"(d[36]),"+f"(d[37]),"+f"(d[38]),"+f"(d[39]),"+f"(d[40]),"+f"(d[41]),"+f"(d[42]),"+f"(d[43]),"+f"(d[44]),"+f"(d[45]),"+f"(d[46]),"+f"(d[47]),"+f"(d[48]),"+f"(d[49]),"+f"(d[50]),"+f"(d[51]),"+f"(d[52]),"+f"(d[53]),"+f"(d[54]),"+f"(d[55]),"+f"(d[56]),"+f"(d[57]),"+f"(d[58]),"+f"(d[59]),"+f"(d[60]),"+f"(d[61]),"+f"(d[62]),"+f"(d[63]),"+f"(d[64]),"+f"(d[65]),"+f"(d[66]),"+f"(d[67]),"+f"(d[68]),"+f"(d[69]),"+f"(d[70]),"+f"(d[71]),"+f"(d[72]),"+f"(d[73]),"+f"(d[74]),"+f"(d[75]),"+f"(d[76]),"+f"(d[77]),"+f"(d[78]),"+f"(d[79]),"+f"(d[80]),"+f"(d[81]),"+f"(d[82]),"+f"(d[83]),"+f"(d[84]),"+f"(d[85]),"+f"(d[86]),"+f"(d[87]),"+f"(d[88]),"+f"(d[89]),"+f"(d[90]),"+f"(d[91]),"+f"(d[92]),"+f"(d[93]),"+f"(d[94]),"+f"(d[95]),"+f"(d[96]),"+f"(d[97]),"+f"(d[98]),"+f"(d[99]),"+f"(d[100]),"+f"(d[101]),"+f"(d[102]),"+f"(d[103]),"+f"(d[104]),"+f"(d[105]),"+f"(d[106]),"+f"(d[107]),"+f"(d[108]),"+f"(d[109]),"+f"(d[110]),"+f"(d[111]),"+f"(d[112]),"+f"(d[113]),"+f"(d[114]),"+f"(d[115]),"+f"(d[116]),"+f"(d[117]),"+f"(d[118]),"+f"(d[119]),"+f"(d[120]),"+f"(d[121]),"+f"(d[122]),"+f"(d[123]),"+f"(d[124]),"+f"(d[125]),"+f"(d[126]),"+f"(d[127])
    : "l"(da),"l"(db),"r"(sc));
}
__device__ __forceinline__ void wgmma_ss_n192_tb(float (&d)[96], uint64_t da, uint64_t db, int sc) {
  asm volatile("{\n.reg .pred p;\nsetp.ne.b32 p, %98, 0;\n"
    "wgmma.mma_async.sync.aligned.m64n192k16.f32.bf16.bf16 {%0,%1,%2,%3,%4,%5,%6,%7,%8,%9,%10,%11,%12,%13,%14,%15,%16,%17,%18,%19,%20,%21,%22,%23,%24,%25,%26,%27,%28,%29,%30,%31,%32,%33,%34,%35,%36,%37,%38,%39,%40,%41,%42,%43,%44,%45,%46,%47,%48,%49,%50,%51,%52,%53,%54,%55,%56,%57,%58,%59,%60,%61,%62,%63,%64,%65,%66,%67,%68,%69,%70,%71,%72,%73,%74,%75,%76,%77,%78,%79,%80,%81,%82,%83,%84,%85,%86,%87,%88,%89,%90,%91,%92,%93,%94,%95}, %96, %97, p, 1, 1, 0, 1;\n}\n"
    : "+f"(d[0]),"+f"(d[1]),"+f"(d[2]),"+f"(d[3]),"+f"(d[4]),"+f"(d[5]),"+f"(d[6]),"+f"(d[7]),"+f"(d[8]),"+f"(d[9]),"+f"(d[10]),"+f"(d[11]),"+f"(d[12]),"+f"(d[13]),"+f"(d[14]),"+f"(d[15]),"+f"(d[16]),"+f"(d[17]),"+f"(d[18]),"+f"(d[19]),"+f"(d[20]),"+f"(d[21]),"+f"(d[22]),"+f"(d[23]),"+f"(d[24]),"+f"(d[25]),"+f"(d[26]),"+f"(d[27]),"+f"(d[28]),"+f"(d[29]),"+f"(d[30]),"+f"(d[31]),"+f"(d[32]),"+f"(d[33]),"+f"(d[34]),"+f"(d[35]),"+f"(d[36]),"+f"(d[37]),"+f"(d[38]),"+f"(d[39]),"+f"(d[40]),"+f"(d[41]),"+f"(d[42]),"+f"(d[43]),"+f"(d[44]),"+f"(d[45]),"+f"(d[46]),"+f"(d[47]),"+f"(d[48]),"+f"(d[49]),"+f"(d[50]),"+f"(d[51]),"+f"(d[52]),"+f"(d[53]),"+f"(d[54]),"+f"(d[55]),"+f"(d[56]),"+f"(d[57]),"+f"(d[58]),"+f"(d[59]),"+f"(d[60]),"+f"(d[61]),"+f"(d[62]),"+f"(d[63]),"+f"(d[64]),"+f"(d[65]),"+f"(d[66]),"+f"(d[67]),"+f"(d[68]),"+f"(d[69]),"+f"(d[70]),"+f"(d[71]),"+f"(d[72]),"+f"(d[73]),"+f"(d[74]),"+f"(d[75]),"+f"(d[76]),"+f"(d[77]),"+f"(d[78]),"+f"(d[79]),"+f"(d[80]),"+f"(d[81]),"+f"(d[82]),"+f"(d[83]),"+f"(d[84]),"+f"(d[85]),"+f"(d[86]),"+f"(d[87]),"+f"(d[88]),"+f"(d[89]),"+f"(d[90]),"+f"(d[91]),"+f"(d[92]),"+f"(d[93]),"+f"(d[94]),"+f"(d[95])
    : "l"(da),"l"(db),"r"(sc));
}

__device__ __forceinline__ uint32_t smem_u32(const void* p) { return (uint32_t)__cvta_generic_to_shared(p); }
__device__ __forceinline__ void mbar_init(uint32_t bar, uint32_t cnt) { asm volatile("mbarrier.init.shared::cta.b64 [%0], %1;" :: "r"(bar), "r"(cnt)); }
__device__ __forceinline__ void mbar_expect_tx(uint32_t bar, uint32_t bytes) { asm volatile("mbarrier.arrive.expect_tx.shared::cta.b64 _, [%0], %1;" :: "r"(bar), "r"(bytes) : "memory"); }
__device__ __forceinline__ void mbar_arrive(uint32_t bar) { asm volatile("mbarrier.arrive.shared::cta.b64 _, [%0];" :: "r"(bar) : "memory"); }
__device__ __forceinline__ void mbar_arrive_cluster(uint32_t cbar, uint32_t cnt) { asm volatile("mbarrier.arrive.shared::cluster.b64 _, [%0], %1;" :: "r"(cbar), "r"(cnt) : "memory"); }
__device__ __forceinline__ uint32_t mapa(uint32_t a, uint32_t rank) { uint32_t r; asm volatile("mapa.shared::cluster.u32 %0, %1, %2;" : "=r"(r) : "r"(a), "r"(rank)); return r; }
__device__ __forceinline__ void mbar_wait(uint32_t bar, uint32_t parity) {
    uint32_t ok; uint32_t n = 0;
    do {
        asm volatile("{\n.reg .pred p;\nmbarrier.try_wait.parity.shared::cta.b64 p, [%1], %2;\nselp.u32 %0, 1, 0, p;\n}" : "=r"(ok) : "r"(bar), "r"(parity) : "memory");
    } while (!ok && ++n < (1u << 17));
}
__device__ __forceinline__ void pace_wait(uint32_t a, uint32_t target) {
    uint32_t v, n = 0;
    do {
        asm volatile("ld.volatile.shared.u32 %0, [%1];" : "=r"(v) : "r"(a) : "memory");
        if (v < target) __nanosleep(150);
    } while (v < target && ++n < (1u << 14));
}
__device__ __forceinline__ void flag_wait(const unsigned* p, unsigned target) {
    unsigned v; uint32_t n = 0;
    while (true) {
        asm volatile("ld.acquire.gpu.global.u32 %0, [%1];" : "=r"(v) : "l"(p) : "memory");
        if ((int)(v - target) >= 0 || ++n >= (1u << 17)) break;
        __nanosleep(100);
    }
}
__device__ __forceinline__ void flag_add(unsigned* p) {
    asm volatile("fence.acq_rel.gpu;\nred.relaxed.gpu.global.add.u32 [%0], 1;" :: "l"(p) : "memory");
}
__device__ __forceinline__ uint64_t make_desc(uint32_t addr, uint32_t lbo, uint32_t sbo, uint32_t swz) {
    return (uint64_t)((addr & 0x3FFFF) >> 4) | ((uint64_t)((lbo & 0x3FFFF) >> 4) << 16) | ((uint64_t)((sbo & 0x3FFFF) >> 4) << 32) | ((uint64_t)swz << 62);
}
__device__ __forceinline__ uint64_t desc_add(uint64_t d, uint32_t off16) {
    return (d & 0xFFFFFFFF00000000ull) | (uint64_t)((uint32_t)d + off16);
}
__device__ __forceinline__ void tma2d(uint32_t dst, const CUtensorMap* tm, int c0, int c1, uint32_t bar) {
    asm volatile("cp.async.bulk.tensor.2d.shared::cluster.global.mbarrier::complete_tx::bytes [%0], [%1, {%3, %4}], [%2];"
        :: "r"(dst), "l"((uint64_t)tm), "r"(bar), "r"(c0), "r"(c1) : "memory");
}
__device__ __forceinline__ void tma3d_mc(uint32_t dst, const CUtensorMap* tm, int c0, int c1, int c2, uint32_t bar) {
    asm volatile("cp.async.bulk.tensor.3d.shared::cluster.global.mbarrier::complete_tx::bytes.multicast::cluster [%0], [%1, {%3, %4, %5}], [%2], %6;"
        :: "r"(dst), "l"((uint64_t)tm), "r"(bar), "r"(c0), "r"(c1), "r"(c2), "h"((uint16_t)3) : "memory");
}
__device__ __forceinline__ void bulk_g2s(uint32_t dst, const void* src, uint32_t bytes, uint32_t bar) {
    asm volatile("cp.async.bulk.shared::cluster.global.mbarrier::complete_tx::bytes [%0], [%1], %2, [%3];"
        :: "r"(dst), "l"(src), "r"(bytes), "r"(bar) : "memory");
}
__device__ __forceinline__ void bulk_s2g(void* dst, uint32_t src, uint32_t bytes) {
    asm volatile("cp.async.bulk.global.shared::cta.bulk_group [%0], [%1], %2;" :: "l"(dst), "r"(src), "r"(bytes) : "memory");
}
__device__ __forceinline__ void tma2d_store(const CUtensorMap* tm, int c0, int c1, uint32_t src) {
    asm volatile("cp.async.bulk.tensor.2d.global.shared::cta.bulk_group [%0, {%2, %3}], [%1];"
        :: "l"((uint64_t)tm), "r"(src), "r"(c0), "r"(c1) : "memory");
}
__device__ __forceinline__ void l2_prefetch(const void* p, uint32_t bytes) {
    asm volatile("cp.async.bulk.prefetch.L2.global [%0], %1;" :: "l"(p), "r"(bytes) : "memory");
}
__device__ __forceinline__ void tmap_prefetch(const CUtensorMap* tm) { asm volatile("prefetch.tensormap [%0];" :: "l"((uint64_t)tm) : "memory"); }
__device__ __forceinline__ uint32_t lds32(uint32_t a) { uint32_t v; asm volatile("ld.shared.u32 %0, [%1];" : "=r"(v) : "r"(a)); return v; }
__device__ __forceinline__ uint2 lds64(uint32_t a) { uint2 v; asm volatile("ld.shared.v2.u32 {%0,%1}, [%2];" : "=r"(v.x), "=r"(v.y) : "r"(a)); return v; }
__device__ __forceinline__ uint4 lds128(uint32_t a) { uint4 v; asm volatile("ld.shared.v4.u32 {%0,%1,%2,%3}, [%4];" : "=r"(v.x), "=r"(v.y), "=r"(v.z), "=r"(v.w) : "r"(a)); return v; }
__device__ __forceinline__ float2 lds64f(uint32_t a) { float2 v; asm volatile("ld.shared.v2.f32 {%0,%1}, [%2];" : "=f"(v.x), "=f"(v.y) : "r"(a)); return v; }
__device__ __forceinline__ void sts32(uint32_t a, uint32_t v) { asm volatile("st.shared.u32 [%0], %1;" :: "r"(a), "r"(v) : "memory"); }
__device__ __forceinline__ void sts128(uint32_t a, uint4 v) { asm volatile("st.shared.v4.u32 [%0], {%1,%2,%3,%4};" :: "r"(a), "r"(v.x), "r"(v.y), "r"(v.z), "r"(v.w) : "memory"); }
__device__ __forceinline__ uint4 ldg_cg128(const void* p) { uint4 v; asm volatile("ld.global.cg.v4.u32 {%0,%1,%2,%3}, [%4];" : "=r"(v.x), "=r"(v.y), "=r"(v.z), "=r"(v.w) : "l"(p)); return v; }
__device__ __forceinline__ uint4 ldg_nc128(const void* p) { uint4 v; asm volatile("ld.global.nc.L1::no_allocate.v4.u32 {%0,%1,%2,%3}, [%4];" : "=r"(v.x), "=r"(v.y), "=r"(v.z), "=r"(v.w) : "l"(p)); return v; }
__device__ __forceinline__ uint2 ldg_nc64(const void* p) { uint2 v; asm volatile("ld.global.nc.L1::no_allocate.v2.u32 {%0,%1}, [%2];" : "=r"(v.x), "=r"(v.y) : "l"(p)); return v; }
#define WG_FENCE() asm volatile("wgmma.fence.sync.aligned;\n" ::: "memory")
#define WG_COMMIT() asm volatile("wgmma.commit_group.sync.aligned;\n" ::: "memory")
template<int N> __device__ __forceinline__ void wg_wait() { asm volatile("wgmma.wait_group.sync.aligned %0;\n" :: "n"(N) : "memory"); }
__device__ __forceinline__ void named_bar(int id, int n) { asm volatile("bar.sync %0, %1;" :: "r"(id), "r"(n) : "memory"); }

__device__ __forceinline__ float bf_lo(uint32_t u) { return __uint_as_float(u << 16); }
__device__ __forceinline__ float bf_hi(uint32_t u) { return __uint_as_float(u & 0xFFFF0000u); }
__device__ __forceinline__ uint32_t pack_bf(float lo, float hi) { uint32_t r; asm("cvt.rn.bf16x2.f32 %0, %1, %2;" : "=r"(r) : "f"(hi), "f"(lo)); return r; }
__device__ __forceinline__ float bf_round(float x) { return __bfloat162float(__float2bfloat16_rn(x)); }
__device__ __forceinline__ uint32_t bmul2(uint32_t a, uint32_t b) { uint32_t r; asm("mul.rn.bf16x2 %0, %1, %2;" : "=r"(r) : "r"(a), "r"(b)); return r; }
__device__ __forceinline__ uint32_t badd2(uint32_t a, uint32_t b) { uint32_t r; asm("add.rn.bf16x2 %0, %1, %2;" : "=r"(r) : "r"(a), "r"(b)); return r; }
__device__ __forceinline__ uint32_t bsub2(uint32_t a, uint32_t b) { uint32_t r; asm("sub.rn.bf16x2 %0, %1, %2;" : "=r"(r) : "r"(a), "r"(b)); return r; }
__device__ __forceinline__ void mma16816(float (&d)[4], uint32_t a0, uint32_t a1, uint32_t a2, uint32_t a3, uint2 b) {
    asm volatile("mma.sync.aligned.m16n8k16.row.col.f32.bf16.bf16.f32 {%0,%1,%2,%3}, {%4,%5,%6,%7}, {%8,%9}, {%0,%1,%2,%3};\n"
        : "+f"(d[0]), "+f"(d[1]), "+f"(d[2]), "+f"(d[3]) : "r"(a0), "r"(a1), "r"(a2), "r"(a3), "r"(b.x), "r"(b.y));
}

template<int HS> __device__ __forceinline__ void xreduce(float (&v)[32], int lane) {
    const int up = lane & HS;
    #pragma unroll
    for (int e = 0; e < HS; e++) {
        float keep, send;
        asm("{\n.reg .pred p;\nsetp.ne.b32 p, %4, 0;\nselp.f32 %0, %3, %2, p;\nselp.f32 %1, %2, %3, p;\n}"
            : "=f"(keep), "=f"(send) : "f"(v[e]), "f"(v[e + HS]), "r"(up));
        v[e] = keep + __shfl_xor_sync(0xffffffffu, send, HS);
    }
}

__device__ __forceinline__ int blk_f0(int bi, int j) {
    if (bi < 32) return 224 * ((j + (bi >> 2)) & 7) + 32 * (bi & 3);
    int b2 = bi - 32; int q3 = (b2 * 11) >> 5;
    return 224 * ((j + q3) & 7) + 128 + 32 * (b2 - 3 * q3);
}
__device__ __forceinline__ int next_st2(int s) { return (0x14023 >> (4 * s)) & 7; }
__device__ __forceinline__ uint32_t stage_off_rt(int s) { return s < 3 ? SM_RING + s * STAGE_BYTES : (uint32_t)(s - 3) * STAGE_BYTES; }

template<int NB>
__device__ __forceinline__ void gemm1_pass(uint32_t sb, int wgi, int warp4, int lane, int& st, uint32_t& fph, uint32_t e_cl,
                                           int rb64, int ks0, bool convCTA) {
    constexpr bool passA = (NB == 4);
    float acc[NB * 32];
    const uint64_t descA0 = make_desc(sb + SM_X + wgi * 8192, 16, 1024, 1);
    const uint64_t descB0 = make_desc(sb + SM_RING, 4096, 512, 2);
    int prev = 0;
    #pragma unroll 1
    for (int sl = 0; sl < 8; sl++) {
        if (warp4 == 0 && wgi == 0) PROF2(2, sl + (passA ? 0 : 8));
        mbar_wait(sb + SM_BARS + (B_FULL + st) * 8, (fph >> st) & 1);
        fph ^= 1u << st;
        if (sl == 0 && warp4 == 0) PROF(2 + wgi * 8 + (passA ? 0 : 3));
        if (warp4 == 0 && wgi == 0) PROF2(1, sl + (passA ? 0 : 8));
        const uint64_t da = desc_add(descA0, sl * 1024), db = desc_add(descB0, st * 2048);
        WG_FENCE();
        #pragma unroll
        for (int kk = 0; kk < 4; kk++) {
            int sc = (sl | kk) ? 1 : 0;
            if constexpr (NB == 4) wgmma_ss_n256_tb(acc, da + kk * 2, db + kk * 64, sc); else wgmma_ss_n192_tb(acc, da + kk * 2, db + kk * 64, sc);
        }
        WG_COMMIT();
        wg_wait<1>();
        if (warp4 == 0 && wgi == 0) PROF2(3, sl + (passA ? 0 : 8));
        if (lane < 2 && sl && (passA || !convCTA || sl < 6)) mbar_arrive_cluster(e_cl + prev * 8, 1);
        if (!passA) {
            if (convCTA) { if (sl == 5 && lane == 0) mbar_arrive(sb + SM_BARS + B_XFREE * 8); }
            else if ((sl == 2 || sl == 4) && lane < 2) mbar_arrive_cluster(e_cl + (2 + (sl >> 1)) * 8, 1);
        }
        prev = st;
        st = (st == 2) ? 0 : st + 1;
    }
    wg_wait<0>();
    if (lane < 2 && (passA || !convCTA)) mbar_arrive_cluster(e_cl + prev * 8, 1);
    if (!passA && lane == 0) mbar_arrive(sb + SM_BARS + B_G1DONE * 8);
    if (warp4 == 0) PROF(3 + wgi * 8 + (passA ? 0 : 3));
    const int g = lane >> 2;
    const int r0 = wgi * 64 + warp4 * 16 + g;
    const float s0 = __uint_as_float(lds32(sb + SM_STATS + r0 * 8 + 4)), s1 = __uint_as_float(lds32(sb + SM_STATS + (r0 + 8) * 8 + 4));
    uint32_t* dst = g_h + (size_t)(rb64 * 112 + ks0) * 512 + warp4 * 128 + lane;
    #pragma unroll
    for (int kk = 0; kk < NB * 2; kk++) {
        uint32_t h[4];
        #pragma unroll
        for (int tt = 0; tt < 2; tt++) {
            const int t = 2 * kk + tt;
            const float* ag = &acc[4 * t];
            const float* au = &acc[NB * 16 + 4 * t];
            h[2 * tt] = bmul2(pack_bf(ag[0] * s0, ag[1] * s0), pack_bf(au[0] * s0, au[1] * s0));
            h[2 * tt + 1] = bmul2(pack_bf(ag[2] * s1, ag[3] * s1), pack_bf(au[2] * s1, au[3] * s1));
        }
        dst[kk * 512] = h[0]; dst[kk * 512 + 64] = h[1]; dst[kk * 512 + 32] = h[2]; dst[kk * 512 + 96] = h[3];
    }
    asm volatile("fence.proxy.async.global;" ::: "memory");
    __syncwarp();
    if (lane == 0) mbar_arrive(sb + SM_BARS + (B_HD + wgi * 2 + (passA ? 0 : 1)) * 8);
    if (warp4 == 0) PROF(4 + wgi * 8 + (passA ? 0 : 3));
}

template<int P0, int NP>
__device__ __forceinline__ void conv_load_a(uint32_t (&a)[NP][2][4], uint32_t hk_lane, int m_lane) {
    #pragma unroll
    for (int pp = 0; pp < NP; pp++) {
        #pragma unroll
        for (int q = 0; q < 2; q++) {
            const int off = (8 * q + 64 * (P0 + pp)) * 4;
            uint32_t w0, w1, w2;
            if (P0 + pp == 0 && q == 0) {
                w0 = (m_lane + 0 < 8) ? 0u : lds32(hk_lane + off);
                w1 = (m_lane + 1 < 8) ? 0u : lds32(hk_lane + off + 4);
                w2 = (m_lane + 2 < 8) ? 0u : lds32(hk_lane + off + 8);
            } else {
                w0 = lds32(hk_lane + off); w1 = lds32(hk_lane + off + 4); w2 = lds32(hk_lane + off + 8);
            }
            a[pp][q][0] = w1;
            a[pp][q][1] = __byte_perm(w0, w1, 0x5432);
            a[pp][q][2] = w2;
            a[pp][q][3] = __byte_perm(w1, w2, 0x5432);
        }
    }
}
template<int P0, int NP>
__device__ __forceinline__ void conv_mma(float (&acc)[4][16], uint32_t (&a)[NP][2][4], uint64_t db) {
    WG_FENCE();
    #pragma unroll
    for (int pp = 0; pp < NP; pp++) {
        #pragma unroll
        for (int q = 0; q < 2; q++) {
            const int P = P0 + pp;
            #pragma unroll
            for (int bq = P / 4; bq < 4; bq++)
                wgmma_rs_n32(acc[bq], a[pp][q][0], a[pp][q][1], a[pp][q][2], a[pp][q][3],
                             db + (uint64_t)(int64_t)(32 * bq - 8 * P - q), (P == 0 && q == 0) ? 0 : 1);
        }
    }
    WG_COMMIT();
}

__global__ void __cluster_dims__(2, 1, 1) __launch_bounds__(NTHREADS, 1)
fused_kernel(const __grid_constant__ Params p) {
    extern __shared__ __align__(1024) uint8_t smem_raw[];
    const uint32_t sb = smem_u32(smem_raw);
    const int tid = threadIdx.x, warp = tid >> 5, lane = tid & 31;
    const int b = blockIdx.x;
    const int rank = b & 1;
    const int j = (b >> 1) & 7;
    const int i = ((b >> 4) << 1) | rank;
    const int cb = j >> 1;
    const bool convCTA = j & 1;
    const int cidx = 4 * i + cb;

    if (warp == 8 && lane < 4) {
        mbar_init(sb + SM_BARS + (B_XFULL + lane) * 8, 1);
        asm volatile("fence.proxy.async.shared::cta;" ::: "memory");
        mbar_expect_tx(sb + SM_BARS + (B_XFULL + lane) * 8, 32768);
    }
    if (tid == 288) {
        for (int s = 0; s < 5; s++) { mbar_init(sb + SM_BARS + (B_FULL + s) * 8, 1); mbar_init(sb + SM_BARS + (B_EMPTY + s) * 8, 16); }
        mbar_init(sb + SM_BARS + B_CONV * 8, 1);
        mbar_init(sb + SM_BARS + B_YT * 8, 1);
        mbar_init(sb + SM_BARS + B_XR * 8, 1);
        mbar_init(sb + SM_BARS + B_G1DONE * 8, 8);
        mbar_init(sb + SM_BARS + B_XFREE * 8, 8);
        mbar_init(sb + SM_BARS + B_YST * 8, 8);
        for (int s = 0; s < 4; s++) mbar_init(sb + SM_BARS + (B_HD + s) * 8, 4);
        for (int s = 0; s < 2; s++) mbar_init(sb + SM_BARS + (B_HRDY + s) * 8, 1);
        asm volatile("fence.mbarrier_init.release.cluster;" ::: "memory");
        asm volatile("fence.proxy.async.shared::cta;" ::: "memory");
    }
    __syncwarp();
    asm volatile("barrier.cluster.arrive.relaxed.aligned;\n" ::: "memory");
    if (warp == 8) {
        const int rg = lane >> 3, sl = lane & 7;
        tma2d(sb + SM_X + sl * 16384 + rg * 4096, &p.tm_x, 64 * ((sl + 2 * cb + 2) & 7), 128 * i + 32 * rg, sb + SM_BARS + (B_XFULL + rg) * 8);
        __syncwarp();
    }
    asm volatile("barrier.cluster.wait.aligned;\n" ::: "memory");
    PROFW(1, 0);

    if (warp < 8) {
        asm volatile("setmaxnreg.inc.sync.aligned.u32 200;");
        const int wgi = warp >> 2, warp4 = warp & 3;
        const int g = lane >> 2, c = lane & 3;
        const uint32_t e_cl = mapa(sb + SM_BARS + B_EMPTY * 8, lane & 1);
        {
            const uint32_t xa = sb + SM_X + (lane >> 3) * 16384 + warp * 16 * 128;
            uint4 xr[16][2];
            float v[32];
            mbar_wait(sb + SM_BARS + (B_XFULL + (warp >> 1)) * 8, 0);
            PROFW(16, 0); PROFW(18, 7);
            #pragma unroll
            for (int r = 0; r < 16; r++) {
                const uint32_t a = xa + r * 128 + (((lane & 7) ^ (r & 7)) << 4);
                xr[r][0] = lds128(a); xr[r][1] = lds128(a + 65536);
            }
            #pragma unroll
            for (int r = 0; r < 16; r++) {
                const uint32_t* u = (const uint32_t*)&xr[r][0];
                float s = 0.f, q = 0.f;
                #pragma unroll
                for (int e = 0; e < 8; e++) { const float lo = bf_lo(u[e]), hi = bf_hi(u[e]); s += lo; q = fmaf(lo, lo, q); s += hi; q = fmaf(hi, hi, q); }
                v[r] = s; v[16 + r] = q;
            }
            xreduce<16>(v, lane); xreduce<8>(v, lane); xreduce<4>(v, lane); xreduce<2>(v, lane); xreduce<1>(v, lane);
            const float other = __shfl_xor_sync(0xffffffffu, v[0], 16);
            const float mean = (lane < 16 ? v[0] : other) * (1.0f / DM);
            const float msq = (lane < 16 ? other : v[0]) * (1.0f / DM);
            const float var_b = bf_round(fmaxf(msq - mean * mean, 0.f));
            const float sd = bf_round(sqrtf(bf_round(var_b + 1e-5f)));
            const uint32_t mb = pack_bf(mean, mean);
            if (lane < 16) { sts32(sb + SM_STATS + (warp * 16 + lane) * 8, mb); sts32(sb + SM_STATS + (warp * 16 + lane) * 8 + 4, __float_as_uint(1.0f / sd)); }
            #pragma unroll
            for (int r = 0; r < 16; r++) {
                const uint32_t m = __shfl_sync(0xffffffffu, mb, r);
                const uint32_t a = xa + r * 128 + (((lane & 7) ^ (r & 7)) << 4);
                #pragma unroll
                for (int hh = 0; hh < 2; hh++) {
                    uint4 t = xr[r][hh];
                    t.x = bsub2(t.x, m); t.y = bsub2(t.y, m); t.z = bsub2(t.z, m); t.w = bsub2(t.w, m);
                    sts128(a + hh * 65536, t);
                }
            }
            asm volatile("fence.proxy.async.shared::cta;" ::: "memory");
            named_bar(1 + wgi, 128);
            PROFW(17, 0); PROFW(19, 7);
        }
        int st = 0; uint32_t fph = 0;
        const int rb64 = 2 * i + wgi;
        gemm1_pass<4>(sb, wgi, warp4, lane, st, fph, e_cl, rb64, 14 * j, convCTA);
        gemm1_pass<3>(sb, wgi, warp4, lane, st, fph, e_cl, rb64, 14 * j + 8, convCTA);

        if (convCTA) {
            const int m_lane = g + 2 * c + 16 * warp4;
            const int cp = (c + warp4) & 3, ish = (c + warp4) >> 2;
            const uint32_t rdst = sb + SM_RING + wgi * 32768 + warp4 * 8192 + ish * 512 + (g * 4 + cp) * 16;
            const uint32_t rsrc = sb + SM_RING + wgi * 32768 + warp4 * 2048 + lane * 16;
            const uint2 dd = ldg_nc64(p.ssm_D + 8 * cidx + 4 * wgi);
            const uint32_t hk0 = sb + SM_CVH + wgi * 16384 + (m_lane - 8) * 4;
            uint32_t a0[4][2][4], a1[4][2][4];
            mbar_wait(sb + SM_BARS + B_CONV * 8, 0);
            conv_load_a<0, 4>(a0, hk0, m_lane);
            if (wgi == 1) named_bar(3, 256);
            #pragma unroll 1
            for (int ch = 0; ch < 4; ch++) {
                const int gch = 8 * cidx + 4 * wgi + ch;
                const uint32_t dw = (ch & 2) ? dd.y : dd.x;
                const uint32_t d2 = __byte_perm(dw, dw, (ch & 1) ? 0x3232 : 0x1010);
                const uint32_t cbase = sb + SM_CVR + (4 * wgi + ch) * RB_CH;
                const uint64_t db = make_desc(cbase + RB_Z * 16, RB_R1, 128, 0);
                const uint32_t hk_lane = hk0 + ch * 4096;
                float acc[4][16];
                PROFW(32 + ch * 2, 4);
                conv_mma<0, 4>(acc, a0, db);
                conv_load_a<4, 4>(a1, hk_lane, m_lane);
                conv_mma<4, 4>(acc, a1, db);
                wg_wait<1>();
                conv_load_a<8, 4>(a0, hk_lane, m_lane);
                conv_mma<8, 4>(acc, a0, db);
                wg_wait<1>();
                conv_load_a<12, 4>(a1, hk_lane, m_lane);
                conv_mma<12, 4>(acc, a1, db);
                if (wgi == 0 && ch == 0) asm volatile("bar.arrive 3, 256;" ::: "memory");
                wg_wait<1>();
                conv_load_a<0, 4>(a0, hk0 + (ch < 3 ? ch + 1 : 3) * 4096, m_lane);
                wg_wait<0>();
                PROFW(33 + ch * 2, 4);
                if (ch == 0) mbar_wait(sb + SM_BARS + B_G1DONE * 8, 0);
                else named_bar(1 + wgi, 128);
                #pragma unroll
                for (int ii = 0; ii < 16; ii++) {
                    if (ii < 15 || ish == 0)
                        sts128(rdst + ii * 512, make_uint4(__float_as_uint(acc[ii >> 2][4 * (ii & 3)]), __float_as_uint(acc[ii >> 2][4 * (ii & 3) + 1]),
                                                           __float_as_uint(acc[ii >> 2][4 * (ii & 3) + 2]), __float_as_uint(acc[ii >> 2][4 * (ii & 3) + 3])));
                }
                named_bar(1 + wgi, 128);
                const uint32_t kvaddr = cbase + ((7 - g) & 1) * RB_R1 + (RB_Z + 32 * warp4 + 2 * c) * 16 + ((7 - g) >> 1) * 4;
                uint32_t* ydst = (uint32_t*)(g_yT + (size_t)gch * SEQ + 512 * warp4 + 32 * c + 2 * g);
                uint4 t[4][4]; uint32_t k0[4], k1[4];
                #pragma unroll
                for (int ii = 0; ii < 4; ii++) {
                    #pragma unroll
                    for (int ww = 0; ww < 4; ww++) t[ii][ww] = lds128(rsrc + ww * 8192 + ii * 512);
                    k0[ii] = lds32(kvaddr + ii * 128); k1[ii] = lds32(kvaddr + ii * 128 + 16);
                }
                #pragma unroll
                for (int ii = 0; ii < 4; ii++) {
                    float sx = __uint_as_float(t[ii][0].x), sy = __uint_as_float(t[ii][0].y), sz = __uint_as_float(t[ii][0].z), sw = __uint_as_float(t[ii][0].w);
                    #pragma unroll
                    for (int ww = 1; ww < 4; ww++) {
                        if (!(ii == 0 && warp4 == 0 && c < ww)) {
                            sx += __uint_as_float(t[ii][ww].x); sy += __uint_as_float(t[ii][ww].y); sz += __uint_as_float(t[ii][ww].z); sw += __uint_as_float(t[ii][ww].w);
                        }
                    }
                    ydst[ii * 64] = badd2(pack_bf(sz, sx), bmul2(__byte_perm(k0[ii], k0[ii], 0x1032), d2));
                    ydst[ii * 64 + 8] = badd2(pack_bf(sw, sy), bmul2(__byte_perm(k1[ii], k1[ii], 0x1032), d2));
                }
            }
            PROFW(44, 4);
            asm volatile("fence.proxy.async.global;" ::: "memory");
            __syncwarp();
            if (lane == 0) mbar_arrive(sb + SM_BARS + B_YST * 8);
        } else {
            float acc[64];
            const uint64_t descB0 = make_desc(sb, 4096, 1024, 1);
            const uint64_t descA0 = make_desc(sb + 16384 + wgi * 8192, 128, 256, 0);
            int sg = 3, p0 = 0; uint32_t ph = 6;
            PROFW(20, 0);
            #pragma unroll 1
            for (int u = 0; u < 28; u++) {
                if (warp == 0 && !(u & 1)) PROF2(2, 16 + (u >> 1));
                mbar_wait(sb + SM_BARS + (B_FULL + sg) * 8, (ph >> sg) & 1);
                ph ^= 1u << sg;
                if (warp == 0 && !(u & 1)) PROF2(1, 16 + (u >> 1));
                const uint32_t o0 = stage_off_rt(sg) >> 4;
                const uint64_t da0 = desc_add(descA0, o0), db0 = desc_add(descB0, o0);
                WG_FENCE();
                #pragma unroll
                for (int kk = 0; kk < 4; kk++) wgmma_ss_n128_tb(acc, da0 + kk * 128, db0 + ((kk >> 1) * 512 + (kk & 1) * 128), (u | kk) ? 1 : 0);
                WG_COMMIT();
                wg_wait<1>();
                if (warp == 0 && !(u & 1)) PROF2(3, 16 + (u >> 1));
                if (lane < 2 && u > 0 && u + 4 < 28) mbar_arrive_cluster(e_cl + p0 * 8, 1);
                p0 = sg;
                sg = next_st2(sg);
            }
            wg_wait<0>();
            PROFW(27, 0);
            mbar_wait(sb + SM_BARS + B_XR * 8, 0);
            mbar_wait(sb + SM_BARS + B_YT * 8, 0);
            PROFW(28, 0);
            const int r0 = wgi * 64 + warp4 * 16 + g;
            const float2 st0 = lds64f(sb + SM_STATS + r0 * 8), st1 = lds64f(sb + SM_STATS + (r0 + 8) * 8);
            const uint32_t m0 = __float_as_uint(st0.x), m1 = __float_as_uint(st1.x);
            const uint32_t xrow0 = sb + SM_XE + r0 * 128 + c * 4;
            const int mi = lane >> 3, lr = lane & 7;
            const uint32_t yaddr = sb + SM_YT + wgi * 16384 + ((mi >> 1) * 8 + lr) * 128 + (((2 * warp4 + (mi & 1)) ^ lr) << 4);
            uint32_t y[8][4], xv[16][2];
            #pragma unroll
            for (int t2 = 0; t2 < 8; t2++)
                asm volatile("ldmatrix.sync.aligned.m8n8.x4.trans.shared.b16 {%0,%1,%2,%3}, [%4];"
                    : "=r"(y[t2][0]), "=r"(y[t2][1]), "=r"(y[t2][2]), "=r"(y[t2][3]) : "r"(yaddr + t2 * 2048) : "memory");
            #pragma unroll
            for (int t = 0; t < 16; t++) {
                const uint32_t off = (t >> 3) * 16384 + (((t & 7) ^ g) << 4);
                xv[t][0] = lds32(xrow0 + off); xv[t][1] = lds32(xrow0 + 1024 + off);
            }
            #pragma unroll
            for (int t = 0; t < 16; t++) {
                const uint32_t off = (t >> 3) * 16384 + (((t & 7) ^ g) << 4);
                const uint32_t d0 = bsub2(xv[t][0], m0), d1 = bsub2(xv[t][1], m1);
                const uint32_t n0 = pack_bf(bf_lo(d0) * st0.y, bf_hi(d0) * st0.y), n1 = pack_bf(bf_lo(d1) * st1.y, bf_hi(d1) * st1.y);
                const uint32_t o0 = badd2(badd2(xv[t][0], bmul2(n0, y[t >> 1][2 * (t & 1)])), pack_bf(acc[4 * t], acc[4 * t + 1]));
                const uint32_t o1 = badd2(badd2(xv[t][1], bmul2(n1, y[t >> 1][2 * (t & 1) + 1])), pack_bf(acc[4 * t + 2], acc[4 * t + 3]));
                sts32(xrow0 + off, o0); sts32(xrow0 + 1024 + off, o1);
            }
            asm volatile("fence.proxy.async.shared::cta;" ::: "memory");
            named_bar(1 + wgi, 128);
            if ((tid & 127) == 0) {
                tma2d_store(&p.tm_out, 128 * cb, 128 * i + 64 * wgi, sb + SM_XE + wgi * 8192);
                tma2d_store(&p.tm_out, 128 * cb + 64, 128 * i + 64 * wgi, sb + SM_XE + 16384 + wgi * 8192);
                asm volatile("cp.async.bulk.commit_group;" ::: "memory");
                asm volatile("cp.async.bulk.wait_group.read 0;" ::: "memory");
                PROFW(29, 0);
            }
        }
    } else {
        asm volatile("setmaxnreg.dec.sync.aligned.u32 104;");
        if (warp == 8) {
            if (lane == 0) {
                int st = 0; uint32_t eph = 7;
                #pragma unroll 1
                for (int it = 0; it < 16; it++) {
                    const int pass = it >> 3, sl = it & 7;
                    const int nb = pass ? 3 : 4;
                    const CUtensorMap* tm = pass ? (rank ? &p.tm_uB : &p.tm_gB) : (rank ? &p.tm_uA : &p.tm_gA);
                    mbar_wait(sb + SM_BARS + (B_EMPTY + st) * 8, (eph >> st) & 1);
                    eph ^= 1u << st;
                    if (it == 1) mbar_wait(sb + SM_BARS + (B_XFULL + 2) * 8, 0);
                    PROF2(0, it);
                    mbar_expect_tx(sb + SM_BARS + (B_FULL + st) * 8, nb * 8192);
                    tma3d_mc(sb + SM_RING + st * STAGE_BYTES + rank * nb * 4096, tm, 0, ((sl + 2 * cb + 2) & 7) * 64, 7 * j + 4 * pass, sb + SM_BARS + (B_FULL + st) * 8);
                    st = (st == 2) ? 0 : st + 1;
                }
            }
            __syncwarp();
            if (!convCTA && lane < 5) {
                int st = 3; uint32_t eph = 1;
                const int hb = (lane < 4) ? (lane & 1) : rank;
                const uint8_t* hsrc = (const uint8_t*)g_h + (size_t)(2 * i + (lane >> 1)) * 112 * 2048;
                const uint32_t doff = (lane < 4) ? 16384 + lane * 4096 : rank * 8192;
                #pragma unroll 1
                for (int u = 0; u < 28; u++) {
                    const int f0 = blk_f0(2 * u + hb, j);
                    const uint32_t so = sb + stage_off_rt(st) + doff, bar = sb + SM_BARS + (B_FULL + st) * 8;
                    mbar_wait(sb + SM_BARS + (B_EMPTY + st) * 8, (eph >> st) & 1);
                    eph ^= 1u << st;
                    if ((u & 1) == 0) PROF2(0, 16 + (u >> 1));
                    if (lane == 4) {
                        mbar_expect_tx(bar, 32768);
                        tma3d_mc(so, &p.tm_w2, 0, f0, 2 * cb, bar);
                    } else {
                        if ((u & 15) == 0) mbar_wait(sb + SM_BARS + (B_HRDY + (u >> 4)) * 8, 0);
                        bulk_g2s(so, hsrc + f0 * 128, 4096, bar);
                    }
                    st = next_st2(st);
                }
                PROF(48);
            }
        } else if (warp < 11) {
            mbar_wait(sb + SM_BARS + (B_XFULL + 3) * 8, 0);
            #pragma unroll 1
            for (int rnd = 0; rnd < 2; rnd++) {
                const int tt = (tid - 288) + 64 * rnd;
                uint32_t sk[4][2];
                uint4 skw[2];
                skw[0] = ldg_nc128(p.shift_k + 16 * tt); skw[1] = ldg_nc128(p.shift_k + 16 * tt + 8);
                const __nv_bfloat16* kp = p.k + (size_t)(16 * b) * DM + 4 * tt;
                const __nv_bfloat16* vp = p.v + (size_t)(16 * b) * DM + 4 * tt;
                uint2 kr[19];
                uint2 kv[16];
                #pragma unroll
                for (int r = 0; r < 3; r++) kr[r] = (b > 0) ? ldg_nc64(kp + (r - 3) * DM) : make_uint2(0, 0);
                #pragma unroll
                for (int r = 0; r < 16; r++) { kr[3 + r] = ldg_nc64(kp + r * DM); if (r < 10) kv[r] = ldg_nc64(vp + r * DM); }
                {
                    const uint4 w0 = skw[0], w1 = skw[1];
                    sk[0][0] = __byte_perm(w0.x, w0.z, 0x5410); sk[1][0] = __byte_perm(w0.x, w0.z, 0x7632);
                    sk[2][0] = __byte_perm(w0.y, w0.w, 0x5410); sk[3][0] = __byte_perm(w0.y, w0.w, 0x7632);
                    sk[0][1] = __byte_perm(w1.x, w1.z, 0x5410); sk[1][1] = __byte_perm(w1.x, w1.z, 0x7632);
                    sk[2][1] = __byte_perm(w1.y, w1.w, 0x5410); sk[3][1] = __byte_perm(w1.y, w1.w, 0x7632);
                }
                #pragma unroll
                for (int s = 0; s < 16; s++) {
                    uint32_t a = bmul2(kr[s].x, sk[3][0]);
                    a = badd2(a, bmul2(kr[s + 1].x, sk[2][0]));
                    a = badd2(a, bmul2(kr[s + 2].x, sk[1][0]));
                    a = badd2(a, bmul2(kr[s + 3].x, sk[0][0]));
                    kv[s].x = bmul2(a, kv[s].x);
                    a = bmul2(kr[s].y, sk[3][1]);
                    a = badd2(a, bmul2(kr[s + 1].y, sk[2][1]));
                    a = badd2(a, bmul2(kr[s + 2].y, sk[1][1]));
                    a = badd2(a, bmul2(kr[s + 3].y, sk[0][1]));
                    kv[s].y = bmul2(a, kv[s].y);
                    if (s < 6) kv[10 + s] = ldg_nc64(vp + (10 + s) * DM);
                }
                PROFW(57 + 2 * rnd, 9);
                #pragma unroll
                for (int cc = 0; cc < 4; cc++) {
                    const uint32_t sel = (cc & 1) ? 0x7632 : 0x5410;
                    #define KVW(r) ((cc & 2) ? kv[r].y : kv[r].x)
                    uint8_t* dst = g_rb + (size_t)(4 * tt + cc) * RB_CH + (RB_Z + b) * 16;
                    *(uint4*)dst = make_uint4(__byte_perm(KVW(15), KVW(14), sel), __byte_perm(KVW(11), KVW(10), sel),
                                              __byte_perm(KVW(7), KVW(6), sel), __byte_perm(KVW(3), KVW(2), sel));
                    *(uint4*)(dst + RB_R1) = make_uint4(__byte_perm(KVW(13), KVW(12), sel), __byte_perm(KVW(9), KVW(8), sel),
                                                        __byte_perm(KVW(5), KVW(4), sel), __byte_perm(KVW(1), KVW(0), sel));
                    if (b < RB_Z) {
                        uint8_t* z = g_rb + (size_t)(4 * tt + cc) * RB_CH + b * 16;
                        *(uint4*)z = make_uint4(0, 0, 0, 0);
                        *(uint4*)(z + RB_R1) = make_uint4(0, 0, 0, 0);
                    }
                    #undef KVW
                }
                PROFW(58 + 2 * rnd, 9);
            }
            asm volatile("fence.proxy.async.global;" ::: "memory");
            __syncwarp();
            if (lane == 0) {
                flag_add(&g_cnt_kv[0]);
                PROFW(50, 9);
                const int wgi = warp - 9;
                mbar_wait(sb + SM_BARS + (B_HD + wgi * 2) * 8, 0);
                flag_add(&g_flag_h[(i * 2 + 0) * 8]);
                mbar_wait(sb + SM_BARS + (B_HD + wgi * 2 + 1) * 8, 0);
                flag_add(&g_flag_h[(i * 2 + 1) * 8]);
                if (wgi == 1 && convCTA) {
                    mbar_wait(sb + SM_BARS + B_YST * 8, 0);
                    flag_add(&g_cnt_y[(cidx >> 4) * 32]);
                    PROF(46);
                }
            }
        } else {
            if (lane == 0) {
                const unsigned ep = g_launch[b] + 1;
                g_launch[b] = ep;
                sts32(sb + SM_EPOCH, ep);
                tmap_prefetch(rank ? &p.tm_uA : &p.tm_gA);
                mbar_wait(sb + SM_BARS + (B_XFULL + 1) * 8, 0);
                l2_prefetch(p.wg + (size_t)b * (FF * DM / NCTA), FF * DM / NCTA * 2);
                l2_prefetch(p.wu + (size_t)b * (FF * DM / NCTA), FF * DM / NCTA * 2);
                tmap_prefetch(rank ? &p.tm_uB : &p.tm_gB);
                tmap_prefetch(&p.tm_w2); tmap_prefetch(&p.tm_yT); tmap_prefetch(&p.tm_out); tmap_prefetch(&p.tm_xe);
                mbar_wait(sb + SM_BARS + (B_FULL + 2) * 8, 0);
                l2_prefetch(p.ssm_k + (size_t)(4 * b) * SEQ, 4 * SEQ * 2);
                l2_prefetch(p.wd + (size_t)b * (FF * DM / NCTA), FF * DM / NCTA * 2);
                mbar_wait(sb + SM_BARS + (B_HD + 0) * 8, 0);
                if (convCTA) {
                    flag_wait(&g_cnt_kv[0], ep * 256);
                    asm volatile("fence.proxy.async.global;" ::: "memory");
                    PROF(53);
                    mbar_wait(sb + SM_BARS + B_XFREE * 8, 0);
                    PROF(54);
                    mbar_expect_tx(sb + SM_BARS + B_CONV * 8, 8 * RB_CH + 32768);
                    bulk_g2s(sb + SM_CVR, g_rb + (size_t)(8 * cidx) * RB_CH, 8 * RB_CH, sb + SM_BARS + B_CONV * 8);
                    bulk_g2s(sb + SM_CVH, p.ssm_k + (size_t)(8 * cidx) * SEQ, 32768, sb + SM_BARS + B_CONV * 8);
                } else {
                    flag_wait(&g_flag_h[(i * 2 + 0) * 8], ep * 16);
                    asm volatile("fence.proxy.async.global;" ::: "memory");
                    mbar_arrive(sb + SM_BARS + B_HRDY * 8);
                    mbar_wait(sb + SM_BARS + B_G1DONE * 8, 0);
                    mbar_expect_tx(sb + SM_BARS + B_XR * 8, 32768);
                    for (int q = 0; q < 4; q++)
                        tma2d(sb + SM_XE + q * 8192, &p.tm_xe, 128 * cb + 64 * (q >> 1), 128 * i + 64 * (q & 1), sb + SM_BARS + B_XR * 8);
                    flag_wait(&g_flag_h[(i * 2 + 1) * 8], ep * 16);
                    asm volatile("fence.proxy.async.global;" ::: "memory");
                    mbar_arrive(sb + SM_BARS + (B_HRDY + 1) * 8);
                    __nanosleep(3000);
                    flag_wait(&g_cnt_y[cb * 32], ep * 16);
                    PROF(49);
                    asm volatile("fence.proxy.async.global;" ::: "memory");
                    mbar_expect_tx(sb + SM_BARS + B_YT * 8, 32768);
                    tma2d(sb + SM_YT, &p.tm_yT, 128 * i, 128 * cb, sb + SM_BARS + B_YT * 8);
                    tma2d(sb + SM_YT + 16384, &p.tm_yT, 128 * i + 64, 128 * cb, sb + SM_BARS + B_YT * 8);
                }
            }
        }
    }
}

typedef CUresult (*EncodeFn)(CUtensorMap*, CUtensorMapDataType, cuuint32_t, void*, const cuuint64_t*, const cuuint64_t*,
                             const cuuint32_t*, const cuuint32_t*, CUtensorMapInterleave, CUtensorMapSwizzle,
                             CUtensorMapL2promotion, CUtensorMapFloatOOBfill);

void encode(EncodeFn fn, CUtensorMap* tm, const void* base, int rank, const cuuint64_t* dims, const cuuint64_t* strides,
            const cuuint32_t* box, CUtensorMapSwizzle swz) {
    cuuint32_t es[5] = {1, 1, 1, 1, 1};
    fn(tm, CU_TENSOR_MAP_DATA_TYPE_BFLOAT16, rank, (void*)base, dims, strides, box, es, CU_TENSOR_MAP_INTERLEAVE_NONE, swz,
       CU_TENSOR_MAP_L2_PROMOTION_L2_128B, CU_TENSOR_MAP_FLOAT_OOB_FILL_NONE);
}

}

extern "C" void kernel_launch(void* const* d_in, const int* in_sizes, int n_in, void* d_out, int out_size) {
    (void)in_sizes; (void)n_in; (void)out_size;
    static EncodeFn enc = nullptr;
    static void* yT_ptr = nullptr;
    if (!enc) {
        void* fn = nullptr; cudaDriverEntryPointQueryResult qr;
        cudaGetDriverEntryPoint("cuTensorMapEncodeTiled", &fn, cudaEnableDefault, &qr);
        enc = (EncodeFn)fn;
        cudaGetSymbolAddress(&yT_ptr, g_yT);
        cudaFuncSetAttribute(fused_kernel, cudaFuncAttributeMaxDynamicSharedMemorySize, SM_TOTAL);
    }
    Params p;
    p.q = (const __nv_bfloat16*)d_in[0]; p.k = (const __nv_bfloat16*)d_in[1]; p.v = (const __nv_bfloat16*)d_in[2];
    p.shift_k = (const __nv_bfloat16*)d_in[3]; p.ssm_k = (const __nv_bfloat16*)d_in[4]; p.ssm_D = (const __nv_bfloat16*)d_in[5];
    p.wg = (const __nv_bfloat16*)d_in[7]; p.wu = (const __nv_bfloat16*)d_in[8]; p.wd = (const __nv_bfloat16*)d_in[9];
    {
        cuuint64_t dims[2] = {DM, SEQ}; cuuint64_t str[1] = {DM * 2};
        cuuint32_t box[2] = {64, 32};
        encode(enc, &p.tm_x, p.q, 2, dims, str, box, CU_TENSOR_MAP_SWIZZLE_128B);
        cuuint32_t box2[2] = {64, 64};
        encode(enc, &p.tm_out, d_out, 2, dims, str, box2, CU_TENSOR_MAP_SWIZZLE_128B);
        encode(enc, &p.tm_xe, p.q, 2, dims, str, box2, CU_TENSOR_MAP_SWIZZLE_128B);
    }
    {
        cuuint64_t dims[3] = {32, DM, FF / 32}; cuuint64_t str[2] = {FF * 2, 64};
        cuuint32_t boxA[3] = {32, 64, 4}, boxB[3] = {32, 64, 3};
        encode(enc, &p.tm_gA, p.wg, 3, dims, str, boxA, CU_TENSOR_MAP_SWIZZLE_64B);
        encode(enc, &p.tm_gB, p.wg, 3, dims, str, boxB, CU_TENSOR_MAP_SWIZZLE_64B);
        encode(enc, &p.tm_uA, p.wu, 3, dims, str, boxA, CU_TENSOR_MAP_SWIZZLE_64B);
        encode(enc, &p.tm_uB, p.wu, 3, dims, str, boxB, CU_TENSOR_MAP_SWIZZLE_64B);
    }
    {
        cuuint64_t dims[3] = {64, FF, DM / 64}; cuuint64_t str[2] = {DM * 2, 128};
        cuuint32_t box[3] = {64, 32, 2};
        encode(enc, &p.tm_w2, p.wd, 3, dims, str, box, CU_TENSOR_MAP_SWIZZLE_128B);
    }
    {
        cuuint64_t dims[2] = {SEQ, DM}; cuuint64_t str[1] = {SEQ * 2};
        cuuint32_t box[2] = {64, 128};
        encode(enc, &p.tm_yT, yT_ptr, 2, dims, str, box, CU_TENSOR_MAP_SWIZZLE_128B);
    }
    fused_kernel<<<NCTA, NTHREADS, SM_TOTAL>>>(p);
}
```

```cpp
#include <cuda_runtime.h>
#include <cuda_bf16.h>
#include <cuda.h>
#include <stdint.h>

namespace {

constexpr int SEQ = 2048, DM = 512, FF = 1792;
constexpr int NCTA = 128;
constexpr int NTHREADS = 384;
constexpr int STAGE_BYTES = 32768;

constexpr uint32_t SM_X = 0;
constexpr uint32_t SM_RING = 131072;
constexpr uint32_t SM_MISC = SM_RING + 3 * STAGE_BYTES;
constexpr uint32_t SM_BARS = SM_MISC;
constexpr uint32_t SM_EPOCH = SM_MISC + 248;
constexpr uint32_t SM_STATS = SM_MISC + 256;
constexpr uint32_t SM_TOTAL = SM_STATS + 1024;
static_assert(SM_TOTAL <= 232448, "smem");
constexpr int RB_Z = 25;
constexpr int RB_R1 = (128 + RB_Z) * 16;
constexpr int RB_CH = 2 * RB_R1;
constexpr uint32_t SM_CVR = 0;
constexpr uint32_t SM_CVH = 8 * RB_CH;
static_assert(SM_CVH + 8 * 4096 <= 5 * 16384, "conv operands");
constexpr uint32_t SM_YT = 4 * 16384;
constexpr uint32_t SM_XE = 6 * 16384;

constexpr int B_FULL = 0, B_EMPTY = 5, B_XFULL = 10, B_CONV = 14, B_YT = 15, B_XR = 16, B_G1DONE = 17, B_HD = 18, B_HRDY = 22,
              B_XFREE = 24, B_YST = 25, B_COUNT = 26;
static_assert(B_COUNT * 8 <= 248, "barrier space");

__device__ __align__(128) uint32_t g_h[16 * 56 * 2048];
__device__ __align__(128) uint8_t g_rb[DM * RB_CH];
__device__ __align__(128) __nv_bfloat16 g_yT[DM * SEQ];
__device__ unsigned g_launch[NCTA];
__device__ unsigned g_cnt_kv[32];
__device__ unsigned g_cnt_y[4 * 32];
__device__ unsigned g_flag_h[16 * 2 * 8];

#define PROF(idx)
#define PROF2(a, idx)
#define PROFW(idx, w)

struct Params {
    CUtensorMap tm_x, tm_gA, tm_gB, tm_uA, tm_uB, tm_w2, tm_yT, tm_out, tm_xe;
    const __nv_bfloat16 *q, *k, *v, *shift_k, *ssm_k, *ssm_D, *wg, *wu, *wd;
};

__device__ __forceinline__ void wgmma_rs_n32(float (&d)[16], uint32_t a0, uint32_t a1, uint32_t a2, uint32_t a3, uint64_t db, int sc) {
  asm volatile("{\n.reg .pred p;\nsetp.ne.b32 p, %21, 0;\n"
    "wgmma.mma_async.sync.aligned.m64n32k16.f32.bf16.bf16 {%0,%1,%2,%3,%4,%5,%6,%7,%8,%9,%10,%11,%12,%13,%14,%15}, {%16,%17,%18,%19}, %20, p, 1, 1, 0;\n}\n"
    : "+f"(d[0]),"+f"(d[1]),"+f"(d[2]),"+f"(d[3]),"+f"(d[4]),"+f"(d[5]),"+f"(d[6]),"+f"(d[7]),"+f"(d[8]),"+f"(d[9]),"+f"(d[10]),"+f"(d[11]),"+f"(d[12]),"+f"(d[13]),"+f"(d[14]),"+f"(d[15])
    : "r"(a0),"r"(a1),"r"(a2),"r"(a3),"l"(db),"r"(sc));
}
__device__ __forceinline__ void wgmma_rs_n128_tb(float (&d)[64], uint32_t a0, uint32_t a1, uint32_t a2, uint32_t a3, uint64_t db, int sc) {
  asm volatile("{\n.reg .pred p;\nsetp.ne.b32 p, %69, 0;\n"
    "wgmma.mma_async.sync.aligned.m64n128k16.f32.bf16.bf16 {%0,%1,%2,%3,%4,%5,%6,%7,%8,%9,%10,%11,%12,%13,%14,%15,%16,%17,%18,%19,%20,%21,%22,%23,%24,%25,%26,%27,%28,%29,%30,%31,%32,%33,%34,%35,%36,%37,%38,%39,%40,%41,%42,%43,%44,%45,%46,%47,%48,%49,%50,%51,%52,%53,%54,%55,%56,%57,%58,%59,%60,%61,%62,%63}, {%64,%65,%66,%67}, %68, p, 1, 1, 1;\n}\n"
    : "+f"(d[0]),"+f"(d[1]),"+f"(d[2]),"+f"(d[3]),"+f"(d[4]),"+f"(d[5]),"+f"(d[6]),"+f"(d[7]),"+f"(d[8]),"+f"(d[9]),"+f"(d[10]),"+f"(d[11]),"+f"(d[12]),"+f"(d[13]),"+f"(d[14]),"+f"(d[15]),"+f"(d[16]),"+f"(d[17]),"+f"(d[18]),"+f"(d[19]),"+f"(d[20]),"+f"(d[21]),"+f"(d[22]),"+f"(d[23]),"+f"(d[24]),"+f"(d[25]),"+f"(d[26]),"+f"(d[27]),"+f"(d[28]),"+f"(d[29]),"+f"(d[30]),"+f"(d[31]),"+f"(d[32]),"+f"(d[33]),"+f"(d[34]),"+f"(d[35]),"+f"(d[36]),"+f"(d[37]),"+f"(d[38]),"+f"(d[39]),"+f"(d[40]),"+f"(d[41]),"+f"(d[42]),"+f"(d[43]),"+f"(d[44]),"+f"(d[45]),"+f"(d[46]),"+f"(d[47]),"+f"(d[48]),"+f"(d[49]),"+f"(d[50]),"+f"(d[51]),"+f"(d[52]),"+f"(d[53]),"+f"(d[54]),"+f"(d[55]),"+f"(d[56]),"+f"(d[57]),"+f"(d[58]),"+f"(d[59]),"+f"(d[60]),"+f"(d[61]),"+f"(d[62]),"+f"(d[63])
    : "r"(a0),"r"(a1),"r"(a2),"r"(a3),"l"(db),"r"(sc));
}
__device__ __forceinline__ void wgmma_ss_n256_tb(float (&d)[128], uint64_t da, uint64_t db, int sc) {
  asm volatile("{\n.reg .pred p;\nsetp.ne.b32 p, %130, 0;\n"
    "wgmma.mma_async.sync.aligned.m64n256k16.f32.bf16.bf16 {%0,%1,%2,%3,%4,%5,%6,%7,%8,%9,%10,%11,%12,%13,%14,%15,%16,%17,%18,%19,%20,%21,%22,%23,%24,%25,%26,%27,%28,%29,%30,%31,%32,%33,%34,%35,%36,%37,%38,%39,%40,%41,%42,%43,%44,%45,%46,%47,%48,%49,%50,%51,%52,%53,%54,%55,%56,%57,%58,%59,%60,%61,%62,%63,%64,%65,%66,%67,%68,%69,%70,%71,%72,%73,%74,%75,%76,%77,%78,%79,%80,%81,%82,%83,%84,%85,%86,%87,%88,%89,%90,%91,%92,%93,%94,%95,%96,%97,%98,%99,%100,%101,%102,%103,%104,%105,%106,%107,%108,%109,%110,%111,%112,%113,%114,%115,%116,%117,%118,%119,%120,%121,%122,%123,%124,%125,%126,%127}, %128, %129, p, 1, 1, 0, 1;\n}\n"
    : "+f"(d[0]),"+f"(d[1]),"+f"(d[2]),"+f"(d[3]),"+f"(d[4]),"+f"(d[5]),"+f"(d[6]),"+f"(d[7]),"+f"(d[8]),"+f"(d[9]),"+f"(d[10]),"+f"(d[11]),"+f"(d[12]),"+f"(d[13]),"+f"(d[14]),"+f"(d[15]),"+f"(d[16]),"+f"(d[17]),"+f"(d[18]),"+f"(d[19]),"+f"(d[20]),"+f"(d[21]),"+f"(d[22]),"+f"(d[23]),"+f"(d[24]),"+f"(d[25]),"+f"(d[26]),"+f"(d[27]),"+f"(d[28]),"+f"(d[29]),"+f"(d[30]),"+f"(d[31]),"+f"(d[32]),"+f"(d[33]),"+f"(d[34]),"+f"(d[35]),"+f"(d[36]),"+f"(d[37]),"+f"(d[38]),"+f"(d[39]),"+f"(d[40]),"+f"(d[41]),"+f"(d[42]),"+f"(d[43]),"+f"(d[44]),"+f"(d[45]),"+f"(d[46]),"+f"(d[47]),"+f"(d[48]),"+f"(d[49]),"+f"(d[50]),"+f"(d[51]),"+f"(d[52]),"+f"(d[53]),"+f"(d[54]),"+f"(d[55]),"+f"(d[56]),"+f"(d[57]),"+f"(d[58]),"+f"(d[59]),"+f"(d[60]),"+f"(d[61]),"+f"(d[62]),"+f"(d[63]),"+f"(d[64]),"+f"(d[65]),"+f"(d[66]),"+f"(d[67]),"+f"(d[68]),"+f"(d[69]),"+f"(d[70]),"+f"(d[71]),"+f"(d[72]),"+f"(d[73]),"+f"(d[74]),"+f"(d[75]),"+f"(d[76]),"+f"(d[77]),"+f"(d[78]),"+f"(d[79]),"+f"(d[80]),"+f"(d[81]),"+f"(d[82]),"+f"(d[83]),"+f"(d[84]),"+f"(d[85]),"+f"(d[86]),"+f"(d[87]),"+f"(d[88]),"+f"(d[89]),"+f"(d[90]),"+f"(d[91]),"+f"(d[92]),"+f"(d[93]),"+f"(d[94]),"+f"(d[95]),"+f"(d[96]),"+f"(d[97]),"+f"(d[98]),"+f"(d[99]),"+f"(d[100]),"+f"(d[101]),"+f"(d[102]),"+f"(d[103]),"+f"(d[104]),"+f"(d[105]),"+f"(d[106]),"+f"(d[107]),"+f"(d[108]),"+f"(d[109]),"+f"(d[110]),"+f"(d[111]),"+f"(d[112]),"+f"(d[113]),"+f"(d[114]),"+f"(d[115]),"+f"(d[116]),"+f"(d[117]),"+f"(d[118]),"+f"(d[119]),"+f"(d[120]),"+f"(d[121]),"+f"(d[122]),"+f"(d[123]),"+f"(d[124]),"+f"(d[125]),"+f"(d[126]),"+f"(d[127])
    : "l"(da),"l"(db),"r"(sc));
}
__device__ __forceinline__ void wgmma_ss_n192_tb(float (&d)[96], uint64_t da, uint64_t db, int sc) {
  asm volatile("{\n.reg .pred p;\nsetp.ne.b32 p, %98, 0;\n"
    "wgmma.mma_async.sync.aligned.m64n192k16.f32.bf16.bf16 {%0,%1,%2,%3,%4,%5,%6,%7,%8,%9,%10,%11,%12,%13,%14,%15,%16,%17,%18,%19,%20,%21,%22,%23,%24,%25,%26,%27,%28,%29,%30,%31,%32,%33,%34,%35,%36,%37,%38,%39,%40,%41,%42,%43,%44,%45,%46,%47,%48,%49,%50,%51,%52,%53,%54,%55,%56,%57,%58,%59,%60,%61,%62,%63,%64,%65,%66,%67,%68,%69,%70,%71,%72,%73,%74,%75,%76,%77,%78,%79,%80,%81,%82,%83,%84,%85,%86,%87,%88,%89,%90,%91,%92,%93,%94,%95}, %96, %97, p, 1, 1, 0, 1;\n}\n"
    : "+f"(d[0]),"+f"(d[1]),"+f"(d[2]),"+f"(d[3]),"+f"(d[4]),"+f"(d[5]),"+f"(d[6]),"+f"(d[7]),"+f"(d[8]),"+f"(d[9]),"+f"(d[10]),"+f"(d[11]),"+f"(d[12]),"+f"(d[13]),"+f"(d[14]),"+f"(d[15]),"+f"(d[16]),"+f"(d[17]),"+f"(d[18]),"+f"(d[19]),"+f"(d[20]),"+f"(d[21]),"+f"(d[22]),"+f"(d[23]),"+f"(d[24]),"+f"(d[25]),"+f"(d[26]),"+f"(d[27]),"+f"(d[28]),"+f"(d[29]),"+f"(d[30]),"+f"(d[31]),"+f"(d[32]),"+f"(d[33]),"+f"(d[34]),"+f"(d[35]),"+f"(d[36]),"+f"(d[37]),"+f"(d[38]),"+f"(d[39]),"+f"(d[40]),"+f"(d[41]),"+f"(d[42]),"+f"(d[43]),"+f"(d[44]),"+f"(d[45]),"+f"(d[46]),"+f"(d[47]),"+f"(d[48]),"+f"(d[49]),"+f"(d[50]),"+f"(d[51]),"+f"(d[52]),"+f"(d[53]),"+f"(d[54]),"+f"(d[55]),"+f"(d[56]),"+f"(d[57]),"+f"(d[58]),"+f"(d[59]),"+f"(d[60]),"+f"(d[61]),"+f"(d[62]),"+f"(d[63]),"+f"(d[64]),"+f"(d[65]),"+f"(d[66]),"+f"(d[67]),"+f"(d[68]),"+f"(d[69]),"+f"(d[70]),"+f"(d[71]),"+f"(d[72]),"+f"(d[73]),"+f"(d[74]),"+f"(d[75]),"+f"(d[76]),"+f"(d[77]),"+f"(d[78]),"+f"(d[79]),"+f"(d[80]),"+f"(d[81]),"+f"(d[82]),"+f"(d[83]),"+f"(d[84]),"+f"(d[85]),"+f"(d[86]),"+f"(d[87]),"+f"(d[88]),"+f"(d[89]),"+f"(d[90]),"+f"(d[91]),"+f"(d[92]),"+f"(d[93]),"+f"(d[94]),"+f"(d[95])
    : "l"(da),"l"(db),"r"(sc));
}

__device__ __forceinline__ uint32_t smem_u32(const void* p) { return (uint32_t)__cvta_generic_to_shared(p); }
__device__ __forceinline__ void mbar_init(uint32_t bar, uint32_t cnt) { asm volatile("mbarrier.init.shared::cta.b64 [%0], %1;" :: "r"(bar), "r"(cnt)); }
__device__ __forceinline__ void mbar_expect_tx(uint32_t bar, uint32_t bytes) { asm volatile("mbarrier.arrive.expect_tx.shared::cta.b64 _, [%0], %1;" :: "r"(bar), "r"(bytes) : "memory"); }
__device__ __forceinline__ void mbar_arrive(uint32_t bar) { asm volatile("mbarrier.arrive.shared::cta.b64 _, [%0];" :: "r"(bar) : "memory"); }
__device__ __forceinline__ void mbar_arrive_cluster(uint32_t cbar, uint32_t cnt) { asm volatile("mbarrier.arrive.shared::cluster.b64 _, [%0], %1;" :: "r"(cbar), "r"(cnt) : "memory"); }
__device__ __forceinline__ uint32_t mapa(uint32_t a, uint32_t rank) { uint32_t r; asm volatile("mapa.shared::cluster.u32 %0, %1, %2;" : "=r"(r) : "r"(a), "r"(rank)); return r; }
__device__ __forceinline__ void mbar_wait(uint32_t bar, uint32_t parity) {
    uint32_t ok; uint32_t n = 0;
    do {
        asm volatile("{\n.reg .pred p;\nmbarrier.try_wait.parity.shared::cta.b64 p, [%1], %2;\nselp.u32 %0, 1, 0, p;\n}" : "=r"(ok) : "r"(bar), "r"(parity) : "memory");
    } while (!ok && ++n < (1u << 17));
}
__device__ __forceinline__ void pace_wait(uint32_t a, uint32_t target) {
    uint32_t v, n = 0;
    do {
        asm volatile("ld.volatile.shared.u32 %0, [%1];" : "=r"(v) : "r"(a) : "memory");
        if (v < target) __nanosleep(150);
    } while (v < target && ++n < (1u << 14));
}
__device__ __forceinline__ void flag_wait(const unsigned* p, unsigned target) {
    unsigned v; uint32_t n = 0;
    while (true) {
        asm volatile("ld.acquire.gpu.global.u32 %0, [%1];" : "=r"(v) : "l"(p) : "memory");
        if ((int)(v - target) >= 0 || ++n >= (1u << 17)) break;
        __nanosleep(100);
    }
}
__device__ __forceinline__ void flag_add(unsigned* p) {
    asm volatile("fence.acq_rel.gpu;\nred.relaxed.gpu.global.add.u32 [%0], 1;" :: "l"(p) : "memory");
}
__device__ __forceinline__ uint64_t make_desc(uint32_t addr, uint32_t lbo, uint32_t sbo, uint32_t swz) {
    return (uint64_t)((addr & 0x3FFFF) >> 4) | ((uint64_t)((lbo & 0x3FFFF) >> 4) << 16) | ((uint64_t)((sbo & 0x3FFFF) >> 4) << 32) | ((uint64_t)swz << 62);
}
__device__ __forceinline__ uint64_t desc_add(uint64_t d, uint32_t off16) {
    return (d & 0xFFFFFFFF00000000ull) | (uint64_t)((uint32_t)d + off16);
}
__device__ __forceinline__ void tma2d(uint32_t dst, const CUtensorMap* tm, int c0, int c1, uint32_t bar) {
    asm volatile("cp.async.bulk.tensor.2d.shared::cluster.global.mbarrier::complete_tx::bytes [%0], [%1, {%3, %4}], [%2];"
        :: "r"(dst), "l"((uint64_t)tm), "r"(bar), "r"(c0), "r"(c1) : "memory");
}
__device__ __forceinline__ void tma3d_mc(uint32_t dst, const CUtensorMap* tm, int c0, int c1, int c2, uint32_t bar) {
    asm volatile("cp.async.bulk.tensor.3d.shared::cluster.global.mbarrier::complete_tx::bytes.multicast::cluster [%0], [%1, {%3, %4, %5}], [%2], %6;"
        :: "r"(dst), "l"((uint64_t)tm), "r"(bar), "r"(c0), "r"(c1), "r"(c2), "h"((uint16_t)3) : "memory");
}
__device__ __forceinline__ void bulk_g2s(uint32_t dst, const void* src, uint32_t bytes, uint32_t bar) {
    asm volatile("cp.async.bulk.shared::cluster.global.mbarrier::complete_tx::bytes [%0], [%1], %2, [%3];"
        :: "r"(dst), "l"(src), "r"(bytes), "r"(bar) : "memory");
}
__device__ __forceinline__ void bulk_s2g(void* dst, uint32_t src, uint32_t bytes) {
    asm volatile("cp.async.bulk.global.shared::cta.bulk_group [%0], [%1], %2;" :: "l"(dst), "r"(src), "r"(bytes) : "memory");
}
__device__ __forceinline__ void tma2d_store(const CUtensorMap* tm, int c0, int c1, uint32_t src) {
    asm volatile("cp.async.bulk.tensor.2d.global.shared::cta.bulk_group [%0, {%2, %3}], [%1];"
        :: "l"((uint64_t)tm), "r"(src), "r"(c0), "r"(c1) : "memory");
}
__device__ __forceinline__ void l2_prefetch(const void* p, uint32_t bytes) {
    asm volatile("cp.async.bulk.prefetch.L2.global [%0], %1;" :: "l"(p), "r"(bytes) : "memory");
}
__device__ __forceinline__ void tmap_prefetch(const CUtensorMap* tm) { asm volatile("prefetch.tensormap [%0];" :: "l"((uint64_t)tm) : "memory"); }
__device__ __forceinline__ uint32_t lds32(uint32_t a) { uint32_t v; asm volatile("ld.shared.u32 %0, [%1];" : "=r"(v) : "r"(a)); return v; }
__device__ __forceinline__ uint2 lds64(uint32_t a) { uint2 v; asm volatile("ld.shared.v2.u32 {%0,%1}, [%2];" : "=r"(v.x), "=r"(v.y) : "r"(a)); return v; }
__device__ __forceinline__ uint4 lds128(uint32_t a) { uint4 v; asm volatile("ld.shared.v4.u32 {%0,%1,%2,%3}, [%4];" : "=r"(v.x), "=r"(v.y), "=r"(v.z), "=r"(v.w) : "r"(a)); return v; }
__device__ __forceinline__ float2 lds64f(uint32_t a) { float2 v; asm volatile("ld.shared.v2.f32 {%0,%1}, [%2];" : "=f"(v.x), "=f"(v.y) : "r"(a)); return v; }
__device__ __forceinline__ void sts32(uint32_t a, uint32_t v) { asm volatile("st.shared.u32 [%0], %1;" :: "r"(a), "r"(v) : "memory"); }
__device__ __forceinline__ void sts128(uint32_t a, uint4 v) { asm volatile("st.shared.v4.u32 [%0], {%1,%2,%3,%4};" :: "r"(a), "r"(v.x), "r"(v.y), "r"(v.z), "r"(v.w) : "memory"); }
__device__ __forceinline__ uint4 ldg_cg128(const void* p) { uint4 v; asm volatile("ld.global.cg.v4.u32 {%0,%1,%2,%3}, [%4];" : "=r"(v.x), "=r"(v.y), "=r"(v.z), "=r"(v.w) : "l"(p)); return v; }
__device__ __forceinline__ uint4 ldg_nc128(const void* p) { uint4 v; asm volatile("ld.global.nc.L1::no_allocate.v4.u32 {%0,%1,%2,%3}, [%4];" : "=r"(v.x), "=r"(v.y), "=r"(v.z), "=r"(v.w) : "l"(p)); return v; }
__device__ __forceinline__ uint2 ldg_nc64(const void* p) { uint2 v; asm volatile("ld.global.nc.L1::no_allocate.v2.u32 {%0,%1}, [%2];" : "=r"(v.x), "=r"(v.y) : "l"(p)); return v; }
#define WG_FENCE() asm volatile("wgmma.fence.sync.aligned;\n" ::: "memory")
#define WG_COMMIT() asm volatile("wgmma.commit_group.sync.aligned;\n" ::: "memory")
template<int N> __device__ __forceinline__ void wg_wait() { asm volatile("wgmma.wait_group.sync.aligned %0;\n" :: "n"(N) : "memory"); }
__device__ __forceinline__ void named_bar(int id, int n) { asm volatile("bar.sync %0, %1;" :: "r"(id), "r"(n) : "memory"); }

__device__ __forceinline__ float bf_lo(uint32_t u) { return __uint_as_float(u << 16); }
__device__ __forceinline__ float bf_hi(uint32_t u) { return __uint_as_float(u & 0xFFFF0000u); }
__device__ __forceinline__ uint32_t pack_bf(float lo, float hi) { uint32_t r; asm("cvt.rn.bf16x2.f32 %0, %1, %2;" : "=r"(r) : "f"(hi), "f"(lo)); return r; }
__device__ __forceinline__ float bf_round(float x) { return __bfloat162float(__float2bfloat16_rn(x)); }
__device__ __forceinline__ uint32_t bmul2(uint32_t a, uint32_t b) { uint32_t r; asm("mul.rn.bf16x2 %0, %1, %2;" : "=r"(r) : "r"(a), "r"(b)); return r; }
__device__ __forceinline__ uint32_t badd2(uint32_t a, uint32_t b) { uint32_t r; asm("add.rn.bf16x2 %0, %1, %2;" : "=r"(r) : "r"(a), "r"(b)); return r; }
__device__ __forceinline__ uint32_t bsub2(uint32_t a, uint32_t b) { uint32_t r; asm("sub.rn.bf16x2 %0, %1, %2;" : "=r"(r) : "r"(a), "r"(b)); return r; }
__device__ __forceinline__ void mma16816(float (&d)[4], uint32_t a0, uint32_t a1, uint32_t a2, uint32_t a3, uint2 b) {
    asm volatile("mma.sync.aligned.m16n8k16.row.col.f32.bf16.bf16.f32 {%0,%1,%2,%3}, {%4,%5,%6,%7}, {%8,%9}, {%0,%1,%2,%3};\n"
        : "+f"(d[0]), "+f"(d[1]), "+f"(d[2]), "+f"(d[3]) : "r"(a0), "r"(a1), "r"(a2), "r"(a3), "r"(b.x), "r"(b.y));
}

template<int HS> __device__ __forceinline__ void xreduce(float (&v)[32], int lane) {
    const int up = lane & HS;
    #pragma unroll
    for (int e = 0; e < HS; e++) {
        float keep, send;
        asm("{\n.reg .pred p;\nsetp.ne.b32 p, %4, 0;\nselp.f32 %0, %3, %2, p;\nselp.f32 %1, %2, %3, p;\n}"
            : "=f"(keep), "=f"(send) : "f"(v[e]), "f"(v[e + HS]), "r"(up));
        v[e] = keep + __shfl_xor_sync(0xffffffffu, send, HS);
    }
}

__device__ __forceinline__ int blk_f0(int bi, int j) {
    if (bi < 32) return 224 * ((j + (bi >> 2)) & 7) + 32 * (bi & 3);
    int b2 = bi - 32; int q3 = (b2 * 11) >> 5;
    return 224 * ((j + q3) & 7) + 128 + 32 * (b2 - 3 * q3);
}
__device__ __forceinline__ int next_st2(int s) { return (0x14023 >> (4 * s)) & 7; }
__device__ __forceinline__ uint32_t stage_off_rt(int s) { return s < 3 ? SM_RING + s * STAGE_BYTES : (uint32_t)(s - 3) * STAGE_BYTES; }

template<int NB>
__device__ __forceinline__ void gemm1_pass(uint32_t sb, int wgi, int warp4, int lane, int& st, uint32_t& fph, uint32_t e_cl,
                                           int rb64, int ks0, bool convCTA) {
    constexpr bool passA = (NB == 4);
    float acc[NB * 32];
    const uint64_t descA0 = make_desc(sb + SM_X + wgi * 8192, 16, 1024, 1);
    const uint64_t descB0 = make_desc(sb + SM_RING, 4096, 512, 2);
    int prev = 0;
    #pragma unroll 1
    for (int sl = 0; sl < 8; sl++) {
        if (warp4 == 0 && wgi == 0) PROF2(2, sl + (passA ? 0 : 8));
        mbar_wait(sb + SM_BARS + (B_FULL + st) * 8, (fph >> st) & 1);
        fph ^= 1u << st;
        if (sl == 0 && warp4 == 0) PROF(2 + wgi * 8 + (passA ? 0 : 3));
        if (warp4 == 0 && wgi == 0) PROF2(1, sl + (passA ? 0 : 8));
        const uint64_t da = desc_add(descA0, sl * 1024), db = desc_add(descB0, st * 2048);
        WG_FENCE();
        #pragma unroll
        for (int kk = 0; kk < 4; kk++) {
            int sc = (sl | kk) ? 1 : 0;
            if constexpr (NB == 4) wgmma_ss_n256_tb(acc, da + kk * 2, db + kk * 64, sc); else wgmma_ss_n192_tb(acc, da + kk * 2, db + kk * 64, sc);
        }
        WG_COMMIT();
        wg_wait<1>();
        if (warp4 == 0 && wgi == 0) PROF2(3, sl + (passA ? 0 : 8));
        if (lane < 2 && sl && (passA || !convCTA || sl < 6)) mbar_arrive_cluster(e_cl + prev * 8, 1);
        if (!passA) {
            if (convCTA) { if (sl == 5 && lane == 0) mbar_arrive(sb + SM_BARS + B_XFREE * 8); }
            else if ((sl == 2 || sl == 4) && lane < 2) mbar_arrive_cluster(e_cl + (2 + (sl >> 1)) * 8, 1);
        }
        prev = st;
        st = (st == 2) ? 0 : st + 1;
    }
    wg_wait<0>();
    if (lane < 2 && (passA || !convCTA)) mbar_arrive_cluster(e_cl + prev * 8, 1);
    if (!passA && lane == 0) mbar_arrive(sb + SM_BARS + B_G1DONE * 8);
    if (warp4 == 0) PROF(3 + wgi * 8 + (passA ? 0 : 3));
    const int g = lane >> 2;
    const int r0 = wgi * 64 + warp4 * 16 + g;
    const float s0 = __uint_as_float(lds32(sb + SM_STATS + r0 * 8 + 4)), s1 = __uint_as_float(lds32(sb + SM_STATS + (r0 + 8) * 8 + 4));
    uint32_t* dst = g_h + (size_t)((rb64 >> 1) * 56 + ks0) * 2048 + wgi * 1024 + warp4 * 128 + lane;
    #pragma unroll
    for (int kk = 0; kk < NB * 2; kk++) {
        uint32_t h[4];
        #pragma unroll
        for (int tt = 0; tt < 2; tt++) {
            const int t = 2 * kk + tt;
            const float* ag = &acc[4 * t];
            const float* au = &acc[NB * 16 + 4 * t];
            h[2 * tt] = bmul2(pack_bf(ag[0] * s0, ag[1] * s0), pack_bf(au[0] * s0, au[1] * s0));
            h[2 * tt + 1] = bmul2(pack_bf(ag[2] * s1, ag[3] * s1), pack_bf(au[2] * s1, au[3] * s1));
        }
        uint32_t* d2 = dst + (kk >> 1) * 2048 + (kk & 1) * 512;
        d2[0] = h[0]; d2[64] = h[1]; d2[32] = h[2]; d2[96] = h[3];
    }
    asm volatile("fence.proxy.async.global;" ::: "memory");
    __syncwarp();
    if (lane == 0) mbar_arrive(sb + SM_BARS + (B_HD + wgi * 2 + (passA ? 0 : 1)) * 8);
    if (warp4 == 0) PROF(4 + wgi * 8 + (passA ? 0 : 3));
}

template<int P0, int NP>
__device__ __forceinline__ void conv_load_a(uint32_t (&a)[NP][2][4], uint32_t hk_lane, int m_lane) {
    #pragma unroll
    for (int pp = 0; pp < NP; pp++) {
        #pragma unroll
        for (int q = 0; q < 2; q++) {
            const int off = (8 * q + 64 * (P0 + pp)) * 4;
            uint32_t w0, w1, w2;
            if (P0 + pp == 0 && q == 0) {
                w0 = (m_lane + 0 < 8) ? 0u : lds32(hk_lane + off);
                w1 = (m_lane + 1 < 8) ? 0u : lds32(hk_lane + off + 4);
                w2 = (m_lane + 2 < 8) ? 0u : lds32(hk_lane + off + 8);
            } else {
                w0 = lds32(hk_lane + off); w1 = lds32(hk_lane + off + 4); w2 = lds32(hk_lane + off + 8);
            }
            a[pp][q][0] = w1;
            a[pp][q][1] = __byte_perm(w0, w1, 0x5432);
            a[pp][q][2] = w2;
            a[pp][q][3] = __byte_perm(w1, w2, 0x5432);
        }
    }
}
template<int P0, int NP>
__device__ __forceinline__ void conv_mma(float (&acc)[4][16], uint32_t (&a)[NP][2][4], uint64_t db) {
    WG_FENCE();
    #pragma unroll
    for (int pp = 0; pp < NP; pp++) {
        #pragma unroll
        for (int q = 0; q < 2; q++) {
            const int P = P0 + pp;
            #pragma unroll
            for (int bq = P / 4; bq < 4; bq++)
                wgmma_rs_n32(acc[bq], a[pp][q][0], a[pp][q][1], a[pp][q][2], a[pp][q][3],
                             db + (uint64_t)(int64_t)(32 * bq - 8 * P - q), (P == 0 && q == 0) ? 0 : 1);
        }
    }
    WG_COMMIT();
}

__global__ void __cluster_dims__(2, 1, 1) __launch_bounds__(NTHREADS, 1)
fused_kernel(const __grid_constant__ Params p) {
    extern __shared__ __align__(1024) uint8_t smem_raw[];
    const uint32_t sb = smem_u32(smem_raw);
    const int tid = threadIdx.x, warp = tid >> 5, lane = tid & 31;
    const int b = blockIdx.x;
    const int rank = b & 1;
    const int j = (b >> 1) & 7;
    const int i = ((b >> 4) << 1) | rank;
    const int cb = j >> 1;
    const bool convCTA = j & 1;
    const int cidx = 4 * i + cb;

    if (warp == 8 && lane < 4) {
        mbar_init(sb + SM_BARS + (B_XFULL + lane) * 8, 1);
        asm volatile("fence.proxy.async.shared::cta;" ::: "memory");
        mbar_expect_tx(sb + SM_BARS + (B_XFULL + lane) * 8, 32768);
    }
    if (tid == 288) {
        for (int s = 0; s < 5; s++) { mbar_init(sb + SM_BARS + (B_FULL + s) * 8, 1); mbar_init(sb + SM_BARS + (B_EMPTY + s) * 8, 16); }
        mbar_init(sb + SM_BARS + B_CONV * 8, 1);
        mbar_init(sb + SM_BARS + B_YT * 8, 1);
        mbar_init(sb + SM_BARS + B_XR * 8, 1);
        mbar_init(sb + SM_BARS + B_G1DONE * 8, 8);
        mbar_init(sb + SM_BARS + B_XFREE * 8, 8);
        mbar_init(sb + SM_BARS + B_YST * 8, 8);
        for (int s = 0; s < 4; s++) mbar_init(sb + SM_BARS + (B_HD + s) * 8, 4);
        for (int s = 0; s < 2; s++) mbar_init(sb + SM_BARS + (B_HRDY + s) * 8, 1);
        asm volatile("fence.mbarrier_init.release.cluster;" ::: "memory");
        asm volatile("fence.proxy.async.shared::cta;" ::: "memory");
    }
    __syncwarp();
    asm volatile("barrier.cluster.arrive.relaxed.aligned;\n" ::: "memory");
    if (warp == 8) {
        const int rg = lane >> 3, sl = lane & 7;
        tma2d(sb + SM_X + sl * 16384 + rg * 4096, &p.tm_x, 64 * ((sl + 2 * cb + 2) & 7), 128 * i + 32 * rg, sb + SM_BARS + (B_XFULL + rg) * 8);
        __syncwarp();
    }
    asm volatile("barrier.cluster.wait.aligned;\n" ::: "memory");
    PROFW(1, 0);

    if (warp < 8) {
        asm volatile("setmaxnreg.inc.sync.aligned.u32 200;");
        const int wgi = warp >> 2, warp4 = warp & 3;
        const int g = lane >> 2, c = lane & 3;
        const uint32_t e_cl = mapa(sb + SM_BARS + B_EMPTY * 8, lane & 1);
        {
            const uint32_t xa = sb + SM_X + (lane >> 3) * 16384 + warp * 16 * 128;
            uint4 xr[16][2];
            float v[32];
            mbar_wait(sb + SM_BARS + (B_XFULL + (warp >> 1)) * 8, 0);
            PROFW(16, 0); PROFW(18, 7);
            #pragma unroll
            for (int r = 0; r < 16; r++) {
                const uint32_t a = xa + r * 128 + (((lane & 7) ^ (r & 7)) << 4);
                xr[r][0] = lds128(a); xr[r][1] = lds128(a + 65536);
            }
            #pragma unroll
            for (int r = 0; r < 16; r++) {
                const uint32_t* u = (const uint32_t*)&xr[r][0];
                float s = 0.f, q = 0.f;
                #pragma unroll
                for (int e = 0; e < 8; e++) { const float lo = bf_lo(u[e]), hi = bf_hi(u[e]); s += lo; q = fmaf(lo, lo, q); s += hi; q = fmaf(hi, hi, q); }
                v[r] = s; v[16 + r] = q;
            }
            xreduce<16>(v, lane); xreduce<8>(v, lane); xreduce<4>(v, lane); xreduce<2>(v, lane); xreduce<1>(v, lane);
            const float other = __shfl_xor_sync(0xffffffffu, v[0], 16);
            const float mean = (lane < 16 ? v[0] : other) * (1.0f / DM);
            const float msq = (lane < 16 ? other : v[0]) * (1.0f / DM);
            const float var_b = bf_round(fmaxf(msq - mean * mean, 0.f));
            const float sd = bf_round(sqrtf(bf_round(var_b + 1e-5f)));
            const uint32_t mb = pack_bf(mean, mean);
            if (lane < 16) { sts32(sb + SM_STATS + (warp * 16 + lane) * 8, mb); sts32(sb + SM_STATS + (warp * 16 + lane) * 8 + 4, __float_as_uint(1.0f / sd)); }
            #pragma unroll
            for (int r = 0; r < 16; r++) {
                const uint32_t m = __shfl_sync(0xffffffffu, mb, r);
                const uint32_t a = xa + r * 128 + (((lane & 7) ^ (r & 7)) << 4);
                #pragma unroll
                for (int hh = 0; hh < 2; hh++) {
                    uint4 t = xr[r][hh];
                    t.x = bsub2(t.x, m); t.y = bsub2(t.y, m); t.z = bsub2(t.z, m); t.w = bsub2(t.w, m);
                    sts128(a + hh * 65536, t);
                }
            }
            asm volatile("fence.proxy.async.shared::cta;" ::: "memory");
            named_bar(1 + wgi, 128);
            PROFW(17, 0); PROFW(19, 7);
        }
        int st = 0; uint32_t fph = 0;
        const int rb64 = 2 * i + wgi;
        gemm1_pass<4>(sb, wgi, warp4, lane, st, fph, e_cl, rb64, 4 * j, convCTA);
        gemm1_pass<3>(sb, wgi, warp4, lane, st, fph, e_cl, rb64, 32 + 3 * j, convCTA);

        if (convCTA) {
            const int m_lane = g + 2 * c + 16 * warp4;
            const int cp = (c + warp4) & 3, ish = (c + warp4) >> 2;
            const uint32_t rdst = sb + SM_RING + wgi * 32768 + warp4 * 8192 + ish * 512 + (g * 4 + cp) * 16;
            const uint32_t rsrc = sb + SM_RING + wgi * 32768 + warp4 * 2048 + lane * 16;
            const uint2 dd = ldg_nc64(p.ssm_D + 8 * cidx + 4 * wgi);
            const uint32_t hk0 = sb + SM_CVH + wgi * 16384 + (m_lane - 8) * 4;
            uint32_t a0[4][2][4], a1[4][2][4];
            mbar_wait(sb + SM_BARS + B_CONV * 8, 0);
            conv_load_a<0, 4>(a0, hk0, m_lane);
            if (wgi == 1) named_bar(3, 256);
            #pragma unroll 1
            for (int ch = 0; ch < 4; ch++) {
                const int gch = 8 * cidx + 4 * wgi + ch;
                const uint32_t dw = (ch & 2) ? dd.y : dd.x;
                const uint32_t d2 = __byte_perm(dw, dw, (ch & 1) ? 0x3232 : 0x1010);
                const uint32_t cbase = sb + SM_CVR + (4 * wgi + ch) * RB_CH;
                const uint64_t db = make_desc(cbase + RB_Z * 16, RB_R1, 128, 0);
                const uint32_t hk_lane = hk0 + ch * 4096;
                float acc[4][16];
                PROFW(32 + ch * 2, 4);
                conv_mma<0, 4>(acc, a0, db);
                conv_load_a<4, 4>(a1, hk_lane, m_lane);
                conv_mma<4, 4>(acc, a1, db);
                wg_wait<1>();
                conv_load_a<8, 4>(a0, hk_lane, m_lane);
                conv_mma<8, 4>(acc, a0, db);
                wg_wait<1>();
                conv_load_a<12, 4>(a1, hk_lane, m_lane);
                conv_mma<12, 4>(acc, a1, db);
                if (wgi == 0 && ch == 0) asm volatile("bar.arrive 3, 256;" ::: "memory");
                wg_wait<1>();
                conv_load_a<0, 4>(a0, hk0 + (ch < 3 ? ch + 1 : 3) * 4096, m_lane);
                wg_wait<0>();
                PROFW(33 + ch * 2, 4);
                if (ch == 0) mbar_wait(sb + SM_BARS + B_G1DONE * 8, 0);
                else named_bar(1 + wgi, 128);
                #pragma unroll
                for (int ii = 0; ii < 16; ii++) {
                    if (ii < 15 || ish == 0)
                        sts128(rdst + ii * 512, make_uint4(__float_as_uint(acc[ii >> 2][4 * (ii & 3)]), __float_as_uint(acc[ii >> 2][4 * (ii & 3) + 1]),
                                                           __float_as_uint(acc[ii >> 2][4 * (ii & 3) + 2]), __float_as_uint(acc[ii >> 2][4 * (ii & 3) + 3])));
                }
                named_bar(1 + wgi, 128);
                const uint32_t kvaddr = cbase + ((7 - g) & 1) * RB_R1 + (RB_Z + 32 * warp4 + 2 * c) * 16 + ((7 - g) >> 1) * 4;
                uint32_t* ydst = (uint32_t*)(g_yT + (size_t)gch * SEQ + 512 * warp4 + 32 * c + 2 * g);
                uint4 t[4][4]; uint32_t k0[4], k1[4];
                #pragma unroll
                for (int ii = 0; ii < 4; ii++) {
                    #pragma unroll
                    for (int ww = 0; ww < 4; ww++) t[ii][ww] = lds128(rsrc + ww * 8192 + ii * 512);
                    k0[ii] = lds32(kvaddr + ii * 128); k1[ii] = lds32(kvaddr + ii * 128 + 16);
                }
                #pragma unroll
                for (int ii = 0; ii < 4; ii++) {
                    float sx = __uint_as_float(t[ii][0].x), sy = __uint_as_float(t[ii][0].y), sz = __uint_as_float(t[ii][0].z), sw = __uint_as_float(t[ii][0].w);
                    #pragma unroll
                    for (int ww = 1; ww < 4; ww++) {
                        if (!(ii == 0 && warp4 == 0 && c < ww)) {
                            sx += __uint_as_float(t[ii][ww].x); sy += __uint_as_float(t[ii][ww].y); sz += __uint_as_float(t[ii][ww].z); sw += __uint_as_float(t[ii][ww].w);
                        }
                    }
                    ydst[ii * 64] = badd2(pack_bf(sz, sx), bmul2(__byte_perm(k0[ii], k0[ii], 0x1032), d2));
                    ydst[ii * 64 + 8] = badd2(pack_bf(sw, sy), bmul2(__byte_perm(k1[ii], k1[ii], 0x1032), d2));
                }
            }
            PROFW(44, 4);
            asm volatile("fence.proxy.async.global;" ::: "memory");
            __syncwarp();
            if (lane == 0) mbar_arrive(sb + SM_BARS + B_YST * 8);
        } else {
            float acc[64];
            const uint64_t descB0 = make_desc(sb, 4096, 1024, 1);
            const uint64_t descA0 = make_desc(sb + 16384 + wgi * 4096, 128, 256, 0);
            int sg = 3, p0 = 0; uint32_t ph = 6;
            PROFW(20, 0);
            #pragma unroll 1
            for (int u = 0; u < 28; u++) {
                if (warp == 0 && !(u & 1)) PROF2(2, 16 + (u >> 1));
                mbar_wait(sb + SM_BARS + (B_FULL + sg) * 8, (ph >> sg) & 1);
                ph ^= 1u << sg;
                if (warp == 0 && !(u & 1)) PROF2(1, 16 + (u >> 1));
                const uint32_t o0 = stage_off_rt(sg) >> 4;
                const uint64_t da0 = desc_add(descA0, o0), db0 = desc_add(descB0, o0);
                WG_FENCE();
                #pragma unroll
                for (int kk = 0; kk < 4; kk++) wgmma_ss_n128_tb(acc, da0 + ((kk >> 1) * 512 + (kk & 1) * 128), db0 + ((kk >> 1) * 512 + (kk & 1) * 128), (u | kk) ? 1 : 0);
                WG_COMMIT();
                wg_wait<1>();
                if (warp == 0 && !(u & 1)) PROF2(3, 16 + (u >> 1));
                if (lane < 2 && u > 0 && u + 4 < 28) mbar_arrive_cluster(e_cl + p0 * 8, 1);
                p0 = sg;
                sg = next_st2(sg);
            }
            wg_wait<0>();
            PROFW(27, 0);
            mbar_wait(sb + SM_BARS + B_XR * 8, 0);
            mbar_wait(sb + SM_BARS + B_YT * 8, 0);
            PROFW(28, 0);
            const int r0 = wgi * 64 + warp4 * 16 + g;
            const float2 st0 = lds64f(sb + SM_STATS + r0 * 8), st1 = lds64f(sb + SM_STATS + (r0 + 8) * 8);
            const uint32_t m0 = __float_as_uint(st0.x), m1 = __float_as_uint(st1.x);
            const uint32_t xrow0 = sb + SM_XE + r0 * 128 + c * 4;
            const int mi = lane >> 3, lr = lane & 7;
            const uint32_t yaddr = sb + SM_YT + wgi * 16384 + ((mi >> 1) * 8 + lr) * 128 + (((2 * warp4 + (mi & 1)) ^ lr) << 4);
            uint32_t y[8][4], xv[16][2];
            #pragma unroll
            for (int t2 = 0; t2 < 8; t2++)
                asm volatile("ldmatrix.sync.aligned.m8n8.x4.trans.shared.b16 {%0,%1,%2,%3}, [%4];"
                    : "=r"(y[t2][0]), "=r"(y[t2][1]), "=r"(y[t2][2]), "=r"(y[t2][3]) : "r"(yaddr + t2 * 2048) : "memory");
            #pragma unroll
            for (int t = 0; t < 16; t++) {
                const uint32_t off = (t >> 3) * 16384 + (((t & 7) ^ g) << 4);
                xv[t][0] = lds32(xrow0 + off); xv[t][1] = lds32(xrow0 + 1024 + off);
            }
            #pragma unroll
            for (int t = 0; t < 16; t++) {
                const uint32_t off = (t >> 3) * 16384 + (((t & 7) ^ g) << 4);
                const uint32_t d0 = bsub2(xv[t][0], m0), d1 = bsub2(xv[t][1], m1);
                const uint32_t n0 = pack_bf(bf_lo(d0) * st0.y, bf_hi(d0) * st0.y), n1 = pack_bf(bf_lo(d1) * st1.y, bf_hi(d1) * st1.y);
                const uint32_t o0 = badd2(badd2(xv[t][0], bmul2(n0, y[t >> 1][2 * (t & 1)])), pack_bf(acc[4 * t], acc[4 * t + 1]));
                const uint32_t o1 = badd2(badd2(xv[t][1], bmul2(n1, y[t >> 1][2 * (t & 1) + 1])), pack_bf(acc[4 * t + 2], acc[4 * t + 3]));
                sts32(xrow0 + off, o0); sts32(xrow0 + 1024 + off, o1);
            }
            asm volatile("fence.proxy.async.shared::cta;" ::: "memory");
            named_bar(1 + wgi, 128);
            if ((tid & 127) == 0) {
                tma2d_store(&p.tm_out, 128 * cb, 128 * i + 64 * wgi, sb + SM_XE + wgi * 8192);
                tma2d_store(&p.tm_out, 128 * cb + 64, 128 * i + 64 * wgi, sb + SM_XE + 16384 + wgi * 8192);
                asm volatile("cp.async.bulk.commit_group;" ::: "memory");
                asm volatile("cp.async.bulk.wait_group.read 0;" ::: "memory");
                PROFW(29, 0);
            }
        }
    } else {
        asm volatile("setmaxnreg.dec.sync.aligned.u32 104;");
        if (warp == 8) {
            if (lane == 0) {
                int st = 0; uint32_t eph = 7;
                #pragma unroll 1
                for (int it = 0; it < 16; it++) {
                    const int pass = it >> 3, sl = it & 7;
                    const int nb = pass ? 3 : 4;
                    const CUtensorMap* tm = pass ? (rank ? &p.tm_uB : &p.tm_gB) : (rank ? &p.tm_uA : &p.tm_gA);
                    mbar_wait(sb + SM_BARS + (B_EMPTY + st) * 8, (eph >> st) & 1);
                    eph ^= 1u << st;
                    if (it == 1) mbar_wait(sb + SM_BARS + (B_XFULL + 2) * 8, 0);
                    PROF2(0, it);
                    mbar_expect_tx(sb + SM_BARS + (B_FULL + st) * 8, nb * 8192);
                    tma3d_mc(sb + SM_RING + st * STAGE_BYTES + rank * nb * 4096, tm, 0, ((sl + 2 * cb + 2) & 7) * 64, 7 * j + 4 * pass, sb + SM_BARS + (B_FULL + st) * 8);
                    st = (st == 2) ? 0 : st + 1;
                }
            }
            __syncwarp();
            if (!convCTA && lane < 2) {
                int st = 3; uint32_t eph = 1;
                const uint8_t* hsrc = (const uint8_t*)g_h + (size_t)i * 56 * 8192;
                const uint32_t doff = lane ? 16384 : rank * 8192;
                int pr = (i >> 1) * 2;
                #pragma unroll 1
                for (int u = 0; u < 28; u++) {
                    const int f0 = blk_f0(2 * pr + rank, 0);
                    const uint32_t so = sb + stage_off_rt(st) + doff, bar = sb + SM_BARS + (B_FULL + st) * 8;
                    mbar_wait(sb + SM_BARS + (B_EMPTY + st) * 8, (eph >> st) & 1);
                    eph ^= 1u << st;
                    if ((u & 1) == 0) PROF2(0, 16 + (u >> 1));
                    if (lane == 0) {
                        mbar_expect_tx(bar, 32768);
                        tma3d_mc(so, &p.tm_w2, 0, f0, 2 * cb, bar);
                    } else {
                        if ((u & 15) == 0) mbar_wait(sb + SM_BARS + (B_HRDY + (u >> 4)) * 8, 0);
                        bulk_g2s(so, hsrc + pr * 16384, 16384, bar);
                    }
                    st = next_st2(st);
                    pr++;
                    if (u < 15) pr &= 15; else if (u == 15) pr = 16 + (i >> 1); else if (pr == 28) pr = 16;
                }
                PROF(48);
            }
        } else if (warp < 11) {
            mbar_wait(sb + SM_BARS + (B_XFULL + 3) * 8, 0);
            #pragma unroll 1
            for (int rnd = 0; rnd < 2; rnd++) {
                const int tt = (tid - 288) + 64 * rnd;
                uint32_t sk[4][2];
                uint4 skw[2];
                skw[0] = ldg_nc128(p.shift_k + 16 * tt); skw[1] = ldg_nc128(p.shift_k + 16 * tt + 8);
                const __nv_bfloat16* kp = p.k + (size_t)(16 * b) * DM + 4 * tt;
                const __nv_bfloat16* vp = p.v + (size_t)(16 * b) * DM + 4 * tt;
                uint2 kr[19];
                uint2 kv[16];
                #pragma unroll
                for (int r = 0; r < 3; r++) kr[r] = (b > 0) ? ldg_nc64(kp + (r - 3) * DM) : make_uint2(0, 0);
                #pragma unroll
                for (int r = 0; r < 16; r++) { kr[3 + r] = ldg_nc64(kp + r * DM); if (r < 10) kv[r] = ldg_nc64(vp + r * DM); }
                {
                    const uint4 w0 = skw[0], w1 = skw[1];
                    sk[0][0] = __byte_perm(w0.x, w0.z, 0x5410); sk[1][0] = __byte_perm(w0.x, w0.z, 0x7632);
                    sk[2][0] = __byte_perm(w0.y, w0.w, 0x5410); sk[3][0] = __byte_perm(w0.y, w0.w, 0x7632);
                    sk[0][1] = __byte_perm(w1.x, w1.z, 0x5410); sk[1][1] = __byte_perm(w1.x, w1.z, 0x7632);
                    sk[2][1] = __byte_perm(w1.y, w1.w, 0x5410); sk[3][1] = __byte_perm(w1.y, w1.w, 0x7632);
                }
                #pragma unroll
                for (int s = 0; s < 16; s++) {
                    uint32_t a = bmul2(kr[s].x, sk[3][0]);
                    a = badd2(a, bmul2(kr[s + 1].x, sk[2][0]));
                    a = badd2(a, bmul2(kr[s + 2].x, sk[1][0]));
                    a = badd2(a, bmul2(kr[s + 3].x, sk[0][0]));
                    kv[s].x = bmul2(a, kv[s].x);
                    a = bmul2(kr[s].y, sk[3][1]);
                    a = badd2(a, bmul2(kr[s + 1].y, sk[2][1]));
                    a = badd2(a, bmul2(kr[s + 2].y, sk[1][1]));
                    a = badd2(a, bmul2(kr[s + 3].y, sk[0][1]));
                    kv[s].y = bmul2(a, kv[s].y);
                    if (s < 6) kv[10 + s] = ldg_nc64(vp + (10 + s) * DM);
                }
                PROFW(57 + 2 * rnd, 9);
                #pragma unroll
                for (int cc = 0; cc < 4; cc++) {
                    const uint32_t sel = (cc & 1) ? 0x7632 : 0x5410;
                    #define KVW(r) ((cc & 2) ? kv[r].y : kv[r].x)
                    uint8_t* dst = g_rb + (size_t)(4 * tt + cc) * RB_CH + (RB_Z + b) * 16;
                    *(uint4*)dst = make_uint4(__byte_perm(KVW(15), KVW(14), sel), __byte_perm(KVW(11), KVW(10), sel),
                                              __byte_perm(KVW(7), KVW(6), sel), __byte_perm(KVW(3), KVW(2), sel));
                    *(uint4*)(dst + RB_R1) = make_uint4(__byte_perm(KVW(13), KVW(12), sel), __byte_perm(KVW(9), KVW(8), sel),
                                                        __byte_perm(KVW(5), KVW(4), sel), __byte_perm(KVW(1), KVW(0), sel));
                    if (b < RB_Z) {
                        uint8_t* z = g_rb + (size_t)(4 * tt + cc) * RB_CH + b * 16;
                        *(uint4*)z = make_uint4(0, 0, 0, 0);
                        *(uint4*)(z + RB_R1) = make_uint4(0, 0, 0, 0);
                    }
                    #undef KVW
                }
                PROFW(58 + 2 * rnd, 9);
            }
            asm volatile("fence.proxy.async.global;" ::: "memory");
            __syncwarp();
            if (lane == 0) {
                flag_add(&g_cnt_kv[0]);
                PROFW(50, 9);
                const int wgi = warp - 9;
                mbar_wait(sb + SM_BARS + (B_HD + wgi * 2) * 8, 0);
                flag_add(&g_flag_h[(i * 2 + 0) * 8]);
                mbar_wait(sb + SM_BARS + (B_HD + wgi * 2 + 1) * 8, 0);
                flag_add(&g_flag_h[(i * 2 + 1) * 8]);
                if (wgi == 1 && convCTA) {
                    mbar_wait(sb + SM_BARS + B_YST * 8, 0);
                    flag_add(&g_cnt_y[(cidx >> 4) * 32]);
                    PROF(46);
                }
            }
        } else {
            if (lane == 0) {
                const unsigned ep = g_launch[b] + 1;
                g_launch[b] = ep;
                sts32(sb + SM_EPOCH, ep);
                tmap_prefetch(rank ? &p.tm_uA : &p.tm_gA);
                mbar_wait(sb + SM_BARS + (B_XFULL + 1) * 8, 0);
                l2_prefetch(p.wg + (size_t)b * (FF * DM / NCTA), FF * DM / NCTA * 2);
                l2_prefetch(p.wu + (size_t)b * (FF * DM / NCTA), FF * DM / NCTA * 2);
                tmap_prefetch(rank ? &p.tm_uB : &p.tm_gB);
                tmap_prefetch(&p.tm_w2); tmap_prefetch(&p.tm_yT); tmap_prefetch(&p.tm_out); tmap_prefetch(&p.tm_xe);
                mbar_wait(sb + SM_BARS + (B_FULL + 2) * 8, 0);
                l2_prefetch(p.ssm_k + (size_t)(4 * b) * SEQ, 4 * SEQ * 2);
                l2_prefetch(p.wd + (size_t)b * (FF * DM / NCTA), FF * DM / NCTA * 2);
                mbar_wait(sb + SM_BARS + (B_HD + 0) * 8, 0);
                if (convCTA) {
                    flag_wait(&g_cnt_kv[0], ep * 256);
                    asm volatile("fence.proxy.async.global;" ::: "memory");
                    PROF(53);
                    mbar_wait(sb + SM_BARS + B_XFREE * 8, 0);
                    PROF(54);
                    mbar_expect_tx(sb + SM_BARS + B_CONV * 8, 8 * RB_CH + 32768);
                    bulk_g2s(sb + SM_CVR, g_rb + (size_t)(8 * cidx) * RB_CH, 8 * RB_CH, sb + SM_BARS + B_CONV * 8);
                    bulk_g2s(sb + SM_CVH, p.ssm_k + (size_t)(8 * cidx) * SEQ, 32768, sb + SM_BARS + B_CONV * 8);
                } else {
                    flag_wait(&g_flag_h[(i * 2 + 0) * 8], ep * 16);
                    asm volatile("fence.proxy.async.global;" ::: "memory");
                    mbar_arrive(sb + SM_BARS + B_HRDY * 8);
                    mbar_wait(sb + SM_BARS + B_G1DONE * 8, 0);
                    mbar_expect_tx(sb + SM_BARS + B_XR * 8, 32768);
                    for (int q = 0; q < 4; q++)
                        tma2d(sb + SM_XE + q * 8192, &p.tm_xe, 128 * cb + 64 * (q >> 1), 128 * i + 64 * (q & 1), sb + SM_BARS + B_XR * 8);
                    flag_wait(&g_flag_h[(i * 2 + 1) * 8], ep * 16);
                    asm volatile("fence.proxy.async.global;" ::: "memory");
                    mbar_arrive(sb + SM_BARS + (B_HRDY + 1) * 8);
                    __nanosleep(3000);
                    flag_wait(&g_cnt_y[cb * 32], ep * 16);
                    PROF(49);
                    asm volatile("fence.proxy.async.global;" ::: "memory");
                    mbar_expect_tx(sb + SM_BARS + B_YT * 8, 32768);
                    tma2d(sb + SM_YT, &p.tm_yT, 128 * i, 128 * cb, sb + SM_BARS + B_YT * 8);
                    tma2d(sb + SM_YT + 16384, &p.tm_yT, 128 * i + 64, 128 * cb, sb + SM_BARS + B_YT * 8);
                }
            }
        }
    }
}

typedef CUresult (*EncodeFn)(CUtensorMap*, CUtensorMapDataType, cuuint32_t, void*, const cuuint64_t*, const cuuint64_t*,
                             const cuuint32_t*, const cuuint32_t*, CUtensorMapInterleave, CUtensorMapSwizzle,
                             CUtensorMapL2promotion, CUtensorMapFloatOOBfill);

void encode(EncodeFn fn, CUtensorMap* tm, const void* base, int rank, const cuuint64_t* dims, const cuuint64_t* strides,
            const cuuint32_t* box, CUtensorMapSwizzle swz) {
    cuuint32_t es[5] = {1, 1, 1, 1, 1};
    fn(tm, CU_TENSOR_MAP_DATA_TYPE_BFLOAT16, rank, (void*)base, dims, strides, box, es, CU_TENSOR_MAP_INTERLEAVE_NONE, swz,
       CU_TENSOR_MAP_L2_PROMOTION_L2_128B, CU_TENSOR_MAP_FLOAT_OOB_FILL_NONE);
}

}

extern "C" void kernel_launch(void* const* d_in, const int* in_sizes, int n_in, void* d_out, int out_size) {
    (void)in_sizes; (void)n_in; (void)out_size;
    static EncodeFn enc = nullptr;
    static void* yT_ptr = nullptr;
    if (!enc) {
        void* fn = nullptr; cudaDriverEntryPointQueryResult qr;
        cudaGetDriverEntryPoint("cuTensorMapEncodeTiled", &fn, cudaEnableDefault, &qr);
        enc = (EncodeFn)fn;
        cudaGetSymbolAddress(&yT_ptr, g_yT);
        cudaFuncSetAttribute(fused_kernel, cudaFuncAttributeMaxDynamicSharedMemorySize, SM_TOTAL);
    }
    Params p;
    p.q = (const __nv_bfloat16*)d_in[0]; p.k = (const __nv_bfloat16*)d_in[1]; p.v = (const __nv_bfloat16*)d_in[2];
    p.shift_k = (const __nv_bfloat16*)d_in[3]; p.ssm_k = (const __nv_bfloat16*)d_in[4]; p.ssm_D = (const __nv_bfloat16*)d_in[5];
    p.wg = (const __nv_bfloat16*)d_in[7]; p.wu = (const __nv_bfloat16*)d_in[8]; p.wd = (const __nv_bfloat16*)d_in[9];
    {
        cuuint64_t dims[2] = {DM, SEQ}; cuuint64_t str[1] = {DM * 2};
        cuuint32_t box[2] = {64, 32};
        encode(enc, &p.tm_x, p.q, 2, dims, str, box, CU_TENSOR_MAP_SWIZZLE_128B);
        cuuint32_t box2[2] = {64, 64};
        encode(enc, &p.tm_out, d_out, 2, dims, str, box2, CU_TENSOR_MAP_SWIZZLE_128B);
        encode(enc, &p.tm_xe, p.q, 2, dims, str, box2, CU_TENSOR_MAP_SWIZZLE_128B);
    }
    {
        cuuint64_t dims[3] = {32, DM, FF / 32}; cuuint64_t str[2] = {FF * 2, 64};
        cuuint32_t boxA[3] = {32, 64, 4}, boxB[3] = {32, 64, 3};
        encode(enc, &p.tm_gA, p.wg, 3, dims, str, boxA, CU_TENSOR_MAP_SWIZZLE_64B);
        encode(enc, &p.tm_gB, p.wg, 3, dims, str, boxB, CU_TENSOR_MAP_SWIZZLE_64B);
        encode(enc, &p.tm_uA, p.wu, 3, dims, str, boxA, CU_TENSOR_MAP_SWIZZLE_64B);
        encode(enc, &p.tm_uB, p.wu, 3, dims, str, boxB, CU_TENSOR_MAP_SWIZZLE_64B);
    }
    {
        cuuint64_t dims[3] = {64, FF, DM / 64}; cuuint64_t str[2] = {DM * 2, 128};
        cuuint32_t box[3] = {64, 32, 2};
        encode(enc, &p.tm_w2, p.wd, 3, dims, str, box, CU_TENSOR_MAP_SWIZZLE_128B);
    }
    {
        cuuint64_t dims[2] = {SEQ, DM}; cuuint64_t str[1] = {SEQ * 2};
        cuuint32_t box[2] = {64, 128};
        encode(enc, &p.tm_yT, yT_ptr, 2, dims, str, box, CU_TENSOR_MAP_SWIZZLE_128B);
    }
    fused_kernel<<<NCTA, NTHREADS, SM_TOTAL>>>(p);
}
```

```cpp
#include <cuda_runtime.h>
#include <cuda_bf16.h>
#include <cuda.h>
#include <stdint.h>

namespace {

constexpr int SEQ = 2048, DM = 512, FF = 1792;
constexpr int NCTA = 128;
constexpr int NTHREADS = 384;
constexpr int STAGE_BYTES = 32768;

constexpr uint32_t SM_X = 0;
constexpr uint32_t SM_RING = 131072;
constexpr uint32_t SM_MISC = SM_RING + 3 * STAGE_BYTES;
constexpr uint32_t SM_BARS = SM_MISC;
constexpr uint32_t SM_EPOCH = SM_MISC + 248;
constexpr uint32_t SM_STATS = SM_MISC + 256;
constexpr uint32_t SM_TOTAL = SM_STATS + 1024;
static_assert(SM_TOTAL <= 232448, "smem");
constexpr int RB_Z = 25;
constexpr int RB_R1 = (128 + RB_Z) * 16;
constexpr int RB_CH = 2 * RB_R1;
constexpr uint32_t SM_CVR = 0;
constexpr uint32_t SM_CVH = 8 * RB_CH;
static_assert(SM_CVH + 8 * 4096 <= 5 * 16384, "conv operands");
constexpr uint32_t SM_YT = 4 * 16384;
constexpr uint32_t SM_XE = 6 * 16384;

constexpr int B_FULL = 0, B_EMPTY = 5, B_XFULL = 10, B_CONV = 14, B_YT = 15, B_XR = 16, B_G1DONE = 17, B_HD = 18, B_HRDY = 22,
              B_XFREE = 24, B_YST = 25, B_COUNT = 26;
static_assert(B_COUNT * 8 <= 248, "barrier space");

__device__ __align__(128) uint32_t g_h[16 * 56 * 2048];
__device__ __align__(128) uint8_t g_rb[DM * RB_CH];
__device__ __align__(128) __nv_bfloat16 g_yT[DM * SEQ];
__device__ unsigned g_launch[NCTA];
__device__ unsigned g_cnt_kv[32];
__device__ unsigned g_cnt_y[4 * 32];
__device__ unsigned g_flag_h[16 * 2 * 8];

#define PROF(idx)
#define PROF2(a, idx)
#define PROFW(idx, w)

struct Params {
    CUtensorMap tm_x, tm_gA, tm_gB, tm_uA, tm_uB, tm_w2, tm_yT, tm_out, tm_xe;
    const __nv_bfloat16 *q, *k, *v, *shift_k, *ssm_k, *ssm_D, *wg, *wu, *wd;
};

__device__ __forceinline__ void wgmma_rs_n32(float (&d)[16], uint32_t a0, uint32_t a1, uint32_t a2, uint32_t a3, uint64_t db, int sc) {
  asm volatile("{\n.reg .pred p;\nsetp.ne.b32 p, %21, 0;\n"
    "wgmma.mma_async.sync.aligned.m64n32k16.f32.bf16.bf16 {%0,%1,%2,%3,%4,%5,%6,%7,%8,%9,%10,%11,%12,%13,%14,%15}, {%16,%17,%18,%19}, %20, p, 1, 1, 0;\n}\n"
    : "+f"(d[0]),"+f"(d[1]),"+f"(d[2]),"+f"(d[3]),"+f"(d[4]),"+f"(d[5]),"+f"(d[6]),"+f"(d[7]),"+f"(d[8]),"+f"(d[9]),"+f"(d[10]),"+f"(d[11]),"+f"(d[12]),"+f"(d[13]),"+f"(d[14]),"+f"(d[15])
    : "r"(a0),"r"(a1),"r"(a2),"r"(a3),"l"(db),"r"(sc));
}
__device__ __forceinline__ void wgmma_rs_n128_tb(float (&d)[64], uint32_t a0, uint32_t a1, uint32_t a2, uint32_t a3, uint64_t db, int sc) {
  asm volatile("{\n.reg .pred p;\nsetp.ne.b32 p, %69, 0;\n"
    "wgmma.mma_async.sync.aligned.m64n128k16.f32.bf16.bf16 {%0,%1,%2,%3,%4,%5,%6,%7,%8,%9,%10,%11,%12,%13,%14,%15,%16,%17,%18,%19,%20,%21,%22,%23,%24,%25,%26,%27,%28,%29,%30,%31,%32,%33,%34,%35,%36,%37,%38,%39,%40,%41,%42,%43,%44,%45,%46,%47,%48,%49,%50,%51,%52,%53,%54,%55,%56,%57,%58,%59,%60,%61,%62,%63}, {%64,%65,%66,%67}, %68, p, 1, 1, 1;\n}\n"
    : "+f"(d[0]),"+f"(d[1]),"+f"(d[2]),"+f"(d[3]),"+f"(d[4]),"+f"(d[5]),"+f"(d[6]),"+f"(d[7]),"+f"(d[8]),"+f"(d[9]),"+f"(d[10]),"+f"(d[11]),"+f"(d[12]),"+f"(d[13]),"+f"(d[14]),"+f"(d[15]),"+f"(d[16]),"+f"(d[17]),"+f"(d[18]),"+f"(d[19]),"+f"(d[20]),"+f"(d[21]),"+f"(d[22]),"+f"(d[23]),"+f"(d[24]),"+f"(d[25]),"+f"(d[26]),"+f"(d[27]),"+f"(d[28]),"+f"(d[29]),"+f"(d[30]),"+f"(d[31]),"+f"(d[32]),"+f"(d[33]),"+f"(d[34]),"+f"(d[35]),"+f"(d[36]),"+f"(d[37]),"+f"(d[38]),"+f"(d[39]),"+f"(d[40]),"+f"(d[41]),"+f"(d[42]),"+f"(d[43]),"+f"(d[44]),"+f"(d[45]),"+f"(d[46]),"+f"(d[47]),"+f"(d[48]),"+f"(d[49]),"+f"(d[50]),"+f"(d[51]),"+f"(d[52]),"+f"(d[53]),"+f"(d[54]),"+f"(d[55]),"+f"(d[56]),"+f"(d[57]),"+f"(d[58]),"+f"(d[59]),"+f"(d[60]),"+f"(d[61]),"+f"(d[62]),"+f"(d[63])
    : "r"(a0),"r"(a1),"r"(a2),"r"(a3),"l"(db),"r"(sc));
}
__device__ __forceinline__ void wgmma_ss_n256_tb(float (&d)[128], uint64_t da, uint64_t db, int sc) {
  asm volatile("{\n.reg .pred p;\nsetp.ne.b32 p, %130, 0;\n"
    "wgmma.mma_async.sync.aligned.m64n256k16.f32.bf16.bf16 {%0,%1,%2,%3,%4,%5,%6,%7,%8,%9,%10,%11,%12,%13,%14,%15,%16,%17,%18,%19,%20,%21,%22,%23,%24,%25,%26,%27,%28,%29,%30,%31,%32,%33,%34,%35,%36,%37,%38,%39,%40,%41,%42,%43,%44,%45,%46,%47,%48,%49,%50,%51,%52,%53,%54,%55,%56,%57,%58,%59,%60,%61,%62,%63,%64,%65,%66,%67,%68,%69,%70,%71,%72,%73,%74,%75,%76,%77,%78,%79,%80,%81,%82,%83,%84,%85,%86,%87,%88,%89,%90,%91,%92,%93,%94,%95,%96,%97,%98,%99,%100,%101,%102,%103,%104,%105,%106,%107,%108,%109,%110,%111,%112,%113,%114,%115,%116,%117,%118,%119,%120,%121,%122,%123,%124,%125,%126,%127}, %128, %129, p, 1, 1, 0, 1;\n}\n"
    : "+f"(d[0]),"+f"(d[1]),"+f"(d[2]),"+f"(d[3]),"+f"(d[4]),"+f"(d[5]),"+f"(d[6]),"+f"(d[7]),"+f"(d[8]),"+f"(d[9]),"+f"(d[10]),"+f"(d[11]),"+f"(d[12]),"+f"(d[13]),"+f"(d[14]),"+f"(d[15]),"+f"(d[16]),"+f"(d[17]),"+f"(d[18]),"+f"(d[19]),"+f"(d[20]),"+f"(d[21]),"+f"(d[22]),"+f"(d[23]),"+f"(d[24]),"+f"(d[25]),"+f"(d[26]),"+f"(d[27]),"+f"(d[28]),"+f"(d[29]),"+f"(d[30]),"+f"(d[31]),"+f"(d[32]),"+f"(d[33]),"+f"(d[34]),"+f"(d[35]),"+f"(d[36]),"+f"(d[37]),"+f"(d[38]),"+f"(d[39]),"+f"(d[40]),"+f"(d[41]),"+f"(d[42]),"+f"(d[43]),"+f"(d[44]),"+f"(d[45]),"+f"(d[46]),"+f"(d[47]),"+f"(d[48]),"+f"(d[49]),"+f"(d[50]),"+f"(d[51]),"+f"(d[52]),"+f"(d[53]),"+f"(d[54]),"+f"(d[55]),"+f"(d[56]),"+f"(d[57]),"+f"(d[58]),"+f"(d[59]),"+f"(d[60]),"+f"(d[61]),"+f"(d[62]),"+f"(d[63]),"+f"(d[64]),"+f"(d[65]),"+f"(d[66]),"+f"(d[67]),"+f"(d[68]),"+f"(d[69]),"+f"(d[70]),"+f"(d[71]),"+f"(d[72]),"+f"(d[73]),"+f"(d[74]),"+f"(d[75]),"+f"(d[76]),"+f"(d[77]),"+f"(d[78]),"+f"(d[79]),"+f"(d[80]),"+f"(d[81]),"+f"(d[82]),"+f"(d[83]),"+f"(d[84]),"+f"(d[85]),"+f"(d[86]),"+f"(d[87]),"+f"(d[88]),"+f"(d[89]),"+f"(d[90]),"+f"(d[91]),"+f"(d[92]),"+f"(d[93]),"+f"(d[94]),"+f"(d[95]),"+f"(d[96]),"+f"(d[97]),"+f"(d[98]),"+f"(d[99]),"+f"(d[100]),"+f"(d[101]),"+f"(d[102]),"+f"(d[103]),"+f"(d[104]),"+f"(d[105]),"+f"(d[106]),"+f"(d[107]),"+f"(d[108]),"+f"(d[109]),"+f"(d[110]),"+f"(d[111]),"+f"(d[112]),"+f"(d[113]),"+f"(d[114]),"+f"(d[115]),"+f"(d[116]),"+f"(d[117]),"+f"(d[118]),"+f"(d[119]),"+f"(d[120]),"+f"(d[121]),"+f"(d[122]),"+f"(d[123]),"+f"(d[124]),"+f"(d[125]),"+f"(d[126]),"+f"(d[127])
    : "l"(da),"l"(db),"r"(sc));
}
__device__ __forceinline__ void wgmma_ss_n192_tb(float (&d)[96], uint64_t da, uint64_t db, int sc) {
  asm volatile("{\n.reg .pred p;\nsetp.ne.b32 p, %98, 0;\n"
    "wgmma.mma_async.sync.aligned.m64n192k16.f32.bf16.bf16 {%0,%1,%2,%3,%4,%5,%6,%7,%8,%9,%10,%11,%12,%13,%14,%15,%16,%17,%18,%19,%20,%21,%22,%23,%24,%25,%26,%27,%28,%29,%30,%31,%32,%33,%34,%35,%36,%37,%38,%39,%40,%41,%42,%43,%44,%45,%46,%47,%48,%49,%50,%51,%52,%53,%54,%55,%56,%57,%58,%59,%60,%61,%62,%63,%64,%65,%66,%67,%68,%69,%70,%71,%72,%73,%74,%75,%76,%77,%78,%79,%80,%81,%82,%83,%84,%85,%86,%87,%88,%89,%90,%91,%92,%93,%94,%95}, %96, %97, p, 1, 1, 0, 1;\n}\n"
    : "+f"(d[0]),"+f"(d[1]),"+f"(d[2]),"+f"(d[3]),"+f"(d[4]),"+f"(d[5]),"+f"(d[6]),"+f"(d[7]),"+f"(d[8]),"+f"(d[9]),"+f"(d[10]),"+f"(d[11]),"+f"(d[12]),"+f"(d[13]),"+f"(d[14]),"+f"(d[15]),"+f"(d[16]),"+f"(d[17]),"+f"(d[18]),"+f"(d[19]),"+f"(d[20]),"+f"(d[21]),"+f"(d[22]),"+f"(d[23]),"+f"(d[24]),"+f"(d[25]),"+f"(d[26]),"+f"(d[27]),"+f"(d[28]),"+f"(d[29]),"+f"(d[30]),"+f"(d[31]),"+f"(d[32]),"+f"(d[33]),"+f"(d[34]),"+f"(d[35]),"+f"(d[36]),"+f"(d[37]),"+f"(d[38]),"+f"(d[39]),"+f"(d[40]),"+f"(d[41]),"+f"(d[42]),"+f"(d[43]),"+f"(d[44]),"+f"(d[45]),"+f"(d[46]),"+f"(d[47]),"+f"(d[48]),"+f"(d[49]),"+f"(d[50]),"+f"(d[51]),"+f"(d[52]),"+f"(d[53]),"+f"(d[54]),"+f"(d[55]),"+f"(d[56]),"+f"(d[57]),"+f"(d[58]),"+f"(d[59]),"+f"(d[60]),"+f"(d[61]),"+f"(d[62]),"+f"(d[63]),"+f"(d[64]),"+f"(d[65]),"+f"(d[66]),"+f"(d[67]),"+f"(d[68]),"+f"(d[69]),"+f"(d[70]),"+f"(d[71]),"+f"(d[72]),"+f"(d[73]),"+f"(d[74]),"+f"(d[75]),"+f"(d[76]),"+f"(d[77]),"+f"(d[78]),"+f"(d[79]),"+f"(d[80]),"+f"(d[81]),"+f"(d[82]),"+f"(d[83]),"+f"(d[84]),"+f"(d[85]),"+f"(d[86]),"+f"(d[87]),"+f"(d[88]),"+f"(d[89]),"+f"(d[90]),"+f"(d[91]),"+f"(d[92]),"+f"(d[93]),"+f"(d[94]),"+f"(d[95])
    : "l"(da),"l"(db),"r"(sc));
}

__device__ __forceinline__ uint32_t smem_u32(const void* p) { return (uint32_t)__cvta_generic_to_shared(p); }
__device__ __forceinline__ void mbar_init(uint32_t bar, uint32_t cnt) { asm volatile("mbarrier.init.shared::cta.b64 [%0], %1;" :: "r"(bar), "r"(cnt)); }
__device__ __forceinline__ void mbar_expect_tx(uint32_t bar, uint32_t bytes) { asm volatile("mbarrier.arrive.expect_tx.shared::cta.b64 _, [%0], %1;" :: "r"(bar), "r"(bytes) : "memory"); }
__device__ __forceinline__ void mbar_arrive(uint32_t bar) { asm volatile("mbarrier.arrive.shared::cta.b64 _, [%0];" :: "r"(bar) : "memory"); }
__device__ __forceinline__ void mbar_arrive_cluster(uint32_t cbar, uint32_t cnt) { asm volatile("mbarrier.arrive.shared::cluster.b64 _, [%0], %1;" :: "r"(cbar), "r"(cnt) : "memory"); }
__device__ __forceinline__ uint32_t mapa(uint32_t a, uint32_t rank) { uint32_t r; asm volatile("mapa.shared::cluster.u32 %0, %1, %2;" : "=r"(r) : "r"(a), "r"(rank)); return r; }
__device__ __forceinline__ void mbar_wait(uint32_t bar, uint32_t parity) {
    uint32_t ok; uint32_t n = 0;
    do {
        asm volatile("{\n.reg .pred p;\nmbarrier.try_wait.parity.shared::cta.b64 p, [%1], %2;\nselp.u32 %0, 1, 0, p;\n}" : "=r"(ok) : "r"(bar), "r"(parity) : "memory");
    } while (!ok && ++n < (1u << 17));
}
__device__ __forceinline__ void pace_wait(uint32_t a, uint32_t target) {
    uint32_t v, n = 0;
    do {
        asm volatile("ld.volatile.shared.u32 %0, [%1];" : "=r"(v) : "r"(a) : "memory");
        if (v < target) __nanosleep(150);
    } while (v < target && ++n < (1u << 14));
}
__device__ __forceinline__ void flag_wait(const unsigned* p, unsigned target) {
    unsigned v; uint32_t n = 0;
    while (true) {
        asm volatile("ld.acquire.gpu.global.u32 %0, [%1];" : "=r"(v) : "l"(p) : "memory");
        if ((int)(v - target) >= 0 || ++n >= (1u << 17)) break;
        __nanosleep(100);
    }
}
__device__ __forceinline__ void flag_add(unsigned* p) {
    asm volatile("fence.acq_rel.gpu;\nred.relaxed.gpu.global.add.u32 [%0], 1;" :: "l"(p) : "memory");
}
__device__ __forceinline__ uint64_t make_desc(uint32_t addr, uint32_t lbo, uint32_t sbo, uint32_t swz) {
    return (uint64_t)((addr & 0x3FFFF) >> 4) | ((uint64_t)((lbo & 0x3FFFF) >> 4) << 16) | ((uint64_t)((sbo & 0x3FFFF) >> 4) << 32) | ((uint64_t)swz << 62);
}
__device__ __forceinline__ uint64_t desc_add(uint64_t d, uint32_t off16) {
    return (d & 0xFFFFFFFF00000000ull) | (uint64_t)((uint32_t)d + off16);
}
__device__ __forceinline__ void tma2d(uint32_t dst, const CUtensorMap* tm, int c0, int c1, uint32_t bar) {
    asm volatile("cp.async.bulk.tensor.2d.shared::cluster.global.mbarrier::complete_tx::bytes [%0], [%1, {%3, %4}], [%2];"
        :: "r"(dst), "l"((uint64_t)tm), "r"(bar), "r"(c0), "r"(c1) : "memory");
}
__device__ __forceinline__ void tma3d_mc(uint32_t dst, const CUtensorMap* tm, int c0, int c1, int c2, uint32_t bar) {
    asm volatile("cp.async.bulk.tensor.3d.shared::cluster.global.mbarrier::complete_tx::bytes.multicast::cluster [%0], [%1, {%3, %4, %5}], [%2], %6;"
        :: "r"(dst), "l"((uint64_t)tm), "r"(bar), "r"(c0), "r"(c1), "r"(c2), "h"((uint16_t)3) : "memory");
}
__device__ __forceinline__ void bulk_g2s(uint32_t dst, const void* src, uint32_t bytes, uint32_t bar) {
    asm volatile("cp.async.bulk.shared::cluster.global.mbarrier::complete_tx::bytes [%0], [%1], %2, [%3];"
        :: "r"(dst), "l"(src), "r"(bytes), "r"(bar) : "memory");
}
__device__ __forceinline__ void bulk_s2g(void* dst, uint32_t src, uint32_t bytes) {
    asm volatile("cp.async.bulk.global.shared::cta.bulk_group [%0], [%1], %2;" :: "l"(dst), "r"(src), "r"(bytes) : "memory");
}
__device__ __forceinline__ void tma2d_store(const CUtensorMap* tm, int c0, int c1, uint32_t src) {
    asm volatile("cp.async.bulk.tensor.2d.global.shared::cta.bulk_group [%0, {%2, %3}], [%1];"
        :: "l"((uint64_t)tm), "r"(src), "r"(c0), "r"(c1) : "memory");
}
__device__ __forceinline__ void l2_prefetch(const void* p, uint32_t bytes) {
    asm volatile("cp.async.bulk.prefetch.L2.global [%0], %1;" :: "l"(p), "r"(bytes) : "memory");
}
__device__ __forceinline__ void tmap_prefetch(const CUtensorMap* tm) { asm volatile("prefetch.tensormap [%0];" :: "l"((uint64_t)tm) : "memory"); }
__device__ __forceinline__ uint32_t lds32(uint32_t a) { uint32_t v; asm volatile("ld.shared.u32 %0, [%1];" : "=r"(v) : "r"(a)); return v; }
__device__ __forceinline__ uint2 lds64(uint32_t a) { uint2 v; asm volatile("ld.shared.v2.u32 {%0,%1}, [%2];" : "=r"(v.x), "=r"(v.y) : "r"(a)); return v; }
__device__ __forceinline__ uint4 lds128(uint32_t a) { uint4 v; asm volatile("ld.shared.v4.u32 {%0,%1,%2,%3}, [%4];" : "=r"(v.x), "=r"(v.y), "=r"(v.z), "=r"(v.w) : "r"(a)); return v; }
__device__ __forceinline__ float2 lds64f(uint32_t a) { float2 v; asm volatile("ld.shared.v2.f32 {%0,%1}, [%2];" : "=f"(v.x), "=f"(v.y) : "r"(a)); return v; }
__device__ __forceinline__ void sts32(uint32_t a, uint32_t v) { asm volatile("st.shared.u32 [%0], %1;" :: "r"(a), "r"(v) : "memory"); }
__device__ __forceinline__ void sts128(uint32_t a, uint4 v) { asm volatile("st.shared.v4.u32 [%0], {%1,%2,%3,%4};" :: "r"(a), "r"(v.x), "r"(v.y), "r"(v.z), "r"(v.w) : "memory"); }
__device__ __forceinline__ uint4 ldg_cg128(const void* p) { uint4 v; asm volatile("ld.global.cg.v4.u32 {%0,%1,%2,%3}, [%4];" : "=r"(v.x), "=r"(v.y), "=r"(v.z), "=r"(v.w) : "l"(p)); return v; }
__device__ __forceinline__ uint4 ldg_nc128(const void* p) { uint4 v; asm volatile("ld.global.nc.L1::no_allocate.v4.u32 {%0,%1,%2,%3}, [%4];" : "=r"(v.x), "=r"(v.y), "=r"(v.z), "=r"(v.w) : "l"(p)); return v; }
__device__ __forceinline__ uint2 ldg_nc64(const void* p) { uint2 v; asm volatile("ld.global.nc.L1::no_allocate.v2.u32 {%0,%1}, [%2];" : "=r"(v.x), "=r"(v.y) : "l"(p)); return v; }
#define WG_FENCE() asm volatile("wgmma.fence.sync.aligned;\n" ::: "memory")
#define WG_COMMIT() asm volatile("wgmma.commit_group.sync.aligned;\n" ::: "memory")
template<int N> __device__ __forceinline__ void wg_wait() { asm volatile("wgmma.wait_group.sync.aligned %0;\n" :: "n"(N) : "memory"); }
__device__ __forceinline__ bool elect_one() {
    uint32_t pr;
    asm volatile("{\n.reg .pred p;\nelect.sync _|p, 0xffffffff;\nselp.u32 %0, 1, 0, p;\n}" : "=r"(pr));
    return pr != 0;
}
__device__ __forceinline__ void named_bar(int id, int n) { asm volatile("bar.sync %0, %1;" :: "r"(id), "r"(n) : "memory"); }

__device__ __forceinline__ float bf_lo(uint32_t u) { return __uint_as_float(u << 16); }
__device__ __forceinline__ float bf_hi(uint32_t u) { return __uint_as_float(u & 0xFFFF0000u); }
__device__ __forceinline__ uint32_t pack_bf(float lo, float hi) { uint32_t r; asm("cvt.rn.bf16x2.f32 %0, %1, %2;" : "=r"(r) : "f"(hi), "f"(lo)); return r; }
__device__ __forceinline__ float bf_round(float x) { return __bfloat162float(__float2bfloat16_rn(x)); }
__device__ __forceinline__ uint32_t bmul2(uint32_t a, uint32_t b) { uint32_t r; asm("mul.rn.bf16x2 %0, %1, %2;" : "=r"(r) : "r"(a), "r"(b)); return r; }
__device__ __forceinline__ uint32_t badd2(uint32_t a, uint32_t b) { uint32_t r; asm("add.rn.bf16x2 %0, %1, %2;" : "=r"(r) : "r"(a), "r"(b)); return r; }
__device__ __forceinline__ uint32_t bsub2(uint32_t a, uint32_t b) { uint32_t r; asm("sub.rn.bf16x2 %0, %1, %2;" : "=r"(r) : "r"(a), "r"(b)); return r; }
__device__ __forceinline__ void mma16816(float (&d)[4], uint32_t a0, uint32_t a1, uint32_t a2, uint32_t a3, uint2 b) {
    asm volatile("mma.sync.aligned.m16n8k16.row.col.f32.bf16.bf16.f32 {%0,%1,%2,%3}, {%4,%5,%6,%7}, {%8,%9}, {%0,%1,%2,%3};\n"
        : "+f"(d[0]), "+f"(d[1]), "+f"(d[2]), "+f"(d[3]) : "r"(a0), "r"(a1), "r"(a2), "r"(a3), "r"(b.x), "r"(b.y));
}

template<int HS> __device__ __forceinline__ void xreduce(float (&v)[32], int lane) {
    const int up = lane & HS;
    #pragma unroll
    for (int e = 0; e < HS; e++) {
        float keep, send;
        asm("{\n.reg .pred p;\nsetp.ne.b32 p, %4, 0;\nselp.f32 %0, %3, %2, p;\nselp.f32 %1, %2, %3, p;\n}"
            : "=f"(keep), "=f"(send) : "f"(v[e]), "f"(v[e + HS]), "r"(up));
        v[e] = keep + __shfl_xor_sync(0xffffffffu, send, HS);
    }
}

__device__ __forceinline__ int blk_f0(int bi, int j) {
    if (bi < 32) return 224 * ((j + (bi >> 2)) & 7) + 32 * (bi & 3);
    int b2 = bi - 32; int q3 = (b2 * 11) >> 5;
    return 224 * ((j + q3) & 7) + 128 + 32 * (b2 - 3 * q3);
}
__device__ __forceinline__ int next_st2(int s) { return (0x14023 >> (4 * s)) & 7; }
__device__ __forceinline__ uint32_t stage_off_rt(int s) { return s < 3 ? SM_RING + s * STAGE_BYTES : (uint32_t)(s - 3) * STAGE_BYTES; }

template<int NB>
__device__ __forceinline__ void gemm1_pass(uint32_t sb, int wgi, int warp4, int lane, int& st, uint32_t& fph, uint32_t e_cl,
                                           int rb64, int ks0, bool convCTA) {
    constexpr bool passA = (NB == 4);
    float acc[NB * 32];
    const uint64_t descA0 = make_desc(sb + SM_X + wgi * 8192, 16, 1024, 1);
    const uint64_t descB0 = make_desc(sb + SM_RING, 4096, 512, 2);
    int prev = 0;
    #pragma unroll 1
    for (int sl = 0; sl < 8; sl++) {
        if (warp4 == 0 && wgi == 0) PROF2(2, sl + (passA ? 0 : 8));
        mbar_wait(sb + SM_BARS + (B_FULL + st) * 8, (fph >> st) & 1);
        fph ^= 1u << st;
        if (sl == 0 && warp4 == 0) PROF(2 + wgi * 8 + (passA ? 0 : 3));
        if (warp4 == 0 && wgi == 0) PROF2(1, sl + (passA ? 0 : 8));
        const uint64_t da = desc_add(descA0, sl * 1024), db = desc_add(descB0, st * 2048);
        WG_FENCE();
        #pragma unroll
        for (int kk = 0; kk < 4; kk++) {
            int sc = (sl | kk) ? 1 : 0;
            if constexpr (NB == 4) wgmma_ss_n256_tb(acc, da + kk * 2, db + kk * 64, sc); else wgmma_ss_n192_tb(acc, da + kk * 2, db + kk * 64, sc);
        }
        WG_COMMIT();
        wg_wait<1>();
        if (warp4 == 0 && wgi == 0) PROF2(3, sl + (passA ? 0 : 8));
        if (lane < 2 && sl && (passA || !convCTA || sl < 6)) mbar_arrive_cluster(e_cl + prev * 8, 1);
        if (!passA) {
            if (convCTA) { if (sl == 5 && lane == 0) mbar_arrive(sb + SM_BARS + B_XFREE * 8); }
            else if ((sl == 2 || sl == 4) && lane < 2) mbar_arrive_cluster(e_cl + (2 + (sl >> 1)) * 8, 1);
        }
        prev = st;
        st = (st == 2) ? 0 : st + 1;
    }
    wg_wait<0>();
    if (lane < 2 && (passA || !convCTA)) mbar_arrive_cluster(e_cl + prev * 8, 1);
    if (!passA && lane == 0) mbar_arrive(sb + SM_BARS + B_G1DONE * 8);
    if (warp4 == 0) PROF(3 + wgi * 8 + (passA ? 0 : 3));
    const int g = lane >> 2;
    const int r0 = wgi * 64 + warp4 * 16 + g;
    const float s0 = __uint_as_float(lds32(sb + SM_STATS + r0 * 8 + 4)), s1 = __uint_as_float(lds32(sb + SM_STATS + (r0 + 8) * 8 + 4));
    uint32_t* dst = g_h + (size_t)((rb64 >> 1) * 56 + ks0) * 2048 + wgi * 1024 + warp4 * 128 + lane;
    #pragma unroll
    for (int kk = 0; kk < NB * 2; kk++) {
        uint32_t h[4];
        #pragma unroll
        for (int tt = 0; tt < 2; tt++) {
            const int t = 2 * kk + tt;
            const float* ag = &acc[4 * t];
            const float* au = &acc[NB * 16 + 4 * t];
            h[2 * tt] = bmul2(pack_bf(ag[0] * s0, ag[1] * s0), pack_bf(au[0] * s0, au[1] * s0));
            h[2 * tt + 1] = bmul2(pack_bf(ag[2] * s1, ag[3] * s1), pack_bf(au[2] * s1, au[3] * s1));
        }
        uint32_t* d2 = dst + (kk >> 1) * 2048 + (kk & 1) * 512;
        d2[0] = h[0]; d2[64] = h[1]; d2[32] = h[2]; d2[96] = h[3];
    }
    asm volatile("fence.proxy.async.global;" ::: "memory");
    __syncwarp();
    if (lane == 0) mbar_arrive(sb + SM_BARS + (B_HD + wgi * 2 + (passA ? 0 : 1)) * 8);
    if (warp4 == 0) PROF(4 + wgi * 8 + (passA ? 0 : 3));
}

template<int P0, int NP>
__device__ __forceinline__ void conv_load_a(uint32_t (&a)[NP][2][4], uint32_t hk_lane, int m_lane) {
    #pragma unroll
    for (int pp = 0; pp < NP; pp++) {
        #pragma unroll
        for (int q = 0; q < 2; q++) {
            const int off = (8 * q + 64 * (P0 + pp)) * 4;
            uint32_t w0, w1, w2;
            if (P0 + pp == 0 && q == 0) {
                w0 = (m_lane + 0 < 8) ? 0u : lds32(hk_lane + off);
                w1 = (m_lane + 1 < 8) ? 0u : lds32(hk_lane + off + 4);
                w2 = (m_lane + 2 < 8) ? 0u : lds32(hk_lane + off + 8);
            } else {
                w0 = lds32(hk_lane + off); w1 = lds32(hk_lane + off + 4); w2 = lds32(hk_lane + off + 8);
            }
            a[pp][q][0] = w1;
            a[pp][q][1] = __byte_perm(w0, w1, 0x5432);
            a[pp][q][2] = w2;
            a[pp][q][3] = __byte_perm(w1, w2, 0x5432);
        }
    }
}
template<int P0, int NP>
__device__ __forceinline__ void conv_mma(float (&acc)[4][16], uint32_t (&a)[NP][2][4], uint64_t db) {
    WG_FENCE();
    #pragma unroll
    for (int pp = 0; pp < NP; pp++) {
        #pragma unroll
        for (int q = 0; q < 2; q++) {
            const int P = P0 + pp;
            #pragma unroll
            for (int bq = P / 4; bq < 4; bq++)
                wgmma_rs_n32(acc[bq], a[pp][q][0], a[pp][q][1], a[pp][q][2], a[pp][q][3],
                             db + (uint64_t)(int64_t)(32 * bq - 8 * P - q), (P == 0 && q == 0) ? 0 : 1);
        }
    }
    WG_COMMIT();
}

__global__ void __cluster_dims__(2, 1, 1) __launch_bounds__(NTHREADS, 1)
fused_kernel(const __grid_constant__ Params p) {
    extern __shared__ __align__(1024) uint8_t smem_raw[];
    const uint32_t sb = smem_u32(smem_raw);
    const int tid = threadIdx.x, warp = tid >> 5, lane = tid & 31;
    const int b = blockIdx.x;
    const int rank = b & 1;
    const int j = (b >> 1) & 7;
    const int i = ((b >> 4) << 1) | rank;
    const int cb = j >> 1;
    const bool convCTA = j & 1;
    const int cidx = 4 * i + cb;

    if (warp == 8 && lane < 4) {
        mbar_init(sb + SM_BARS + (B_XFULL + lane) * 8, 1);
        asm volatile("fence.proxy.async.shared::cta;" ::: "memory");
        mbar_expect_tx(sb + SM_BARS + (B_XFULL + lane) * 8, 32768);
    }
    if (tid == 288) {
        for (int s = 0; s < 5; s++) { mbar_init(sb + SM_BARS + (B_FULL + s) * 8, 1); mbar_init(sb + SM_BARS + (B_EMPTY + s) * 8, 16); }
        mbar_init(sb + SM_BARS + B_CONV * 8, 1);
        mbar_init(sb + SM_BARS + B_YT * 8, 1);
        mbar_init(sb + SM_BARS + B_XR * 8, 1);
        mbar_init(sb + SM_BARS + B_G1DONE * 8, 8);
        mbar_init(sb + SM_BARS + B_XFREE * 8, 8);
        mbar_init(sb + SM_BARS + B_YST * 8, 8);
        for (int s = 0; s < 4; s++) mbar_init(sb + SM_BARS + (B_HD + s) * 8, 4);
        for (int s = 0; s < 2; s++) mbar_init(sb + SM_BARS + (B_HRDY + s) * 8, 1);
        asm volatile("fence.mbarrier_init.release.cluster;" ::: "memory");
        asm volatile("fence.proxy.async.shared::cta;" ::: "memory");
    }
    __syncwarp();
    asm volatile("barrier.cluster.arrive.relaxed.aligned;\n" ::: "memory");
    if (warp == 8) {
        const int rg = lane >> 3, sl = lane & 7;
        tma2d(sb + SM_X + sl * 16384 + rg * 4096, &p.tm_x, 64 * ((sl + 2 * cb + 2) & 7), 128 * i + 32 * rg, sb + SM_BARS + (B_XFULL + rg) * 8);
        __syncwarp();
    }
    asm volatile("barrier.cluster.wait.aligned;\n" ::: "memory");
    PROFW(1, 0);

    if (warp < 8) {
        asm volatile("setmaxnreg.inc.sync.aligned.u32 200;");
        const int wgi = warp >> 2, warp4 = warp & 3;
        const int g = lane >> 2, c = lane & 3;
        const uint32_t e_cl = mapa(sb + SM_BARS + B_EMPTY * 8, lane & 1);
        {
            const uint32_t xa = sb + SM_X + (lane >> 3) * 16384 + warp * 16 * 128;
            uint4 xr[16][2];
            float v[32];
            mbar_wait(sb + SM_BARS + (B_XFULL + (warp >> 1)) * 8, 0);
            PROFW(16, 0); PROFW(18, 7);
            #pragma unroll
            for (int r = 0; r < 16; r++) {
                const uint32_t a = xa + r * 128 + (((lane & 7) ^ (r & 7)) << 4);
                xr[r][0] = lds128(a); xr[r][1] = lds128(a + 65536);
            }
            #pragma unroll
            for (int r = 0; r < 16; r++) {
                const uint32_t* u = (const uint32_t*)&xr[r][0];
                float s = 0.f, q = 0.f;
                #pragma unroll
                for (int e = 0; e < 8; e++) { const float lo = bf_lo(u[e]), hi = bf_hi(u[e]); s += lo; q = fmaf(lo, lo, q); s += hi; q = fmaf(hi, hi, q); }
                v[r] = s; v[16 + r] = q;
            }
            xreduce<16>(v, lane); xreduce<8>(v, lane); xreduce<4>(v, lane); xreduce<2>(v, lane); xreduce<1>(v, lane);
            const float other = __shfl_xor_sync(0xffffffffu, v[0], 16);
            const float mean = (lane < 16 ? v[0] : other) * (1.0f / DM);
            const float msq = (lane < 16 ? other : v[0]) * (1.0f / DM);
            const float var_b = bf_round(fmaxf(msq - mean * mean, 0.f));
            const float sd = bf_round(sqrtf(bf_round(var_b + 1e-5f)));
            const uint32_t mb = pack_bf(mean, mean);
            if (lane < 16) { sts32(sb + SM_STATS + (warp * 16 + lane) * 8, mb); sts32(sb + SM_STATS + (warp * 16 + lane) * 8 + 4, __float_as_uint(1.0f / sd)); }
            #pragma unroll
            for (int r = 0; r < 16; r++) {
                const uint32_t m = __shfl_sync(0xffffffffu, mb, r);
                const uint32_t a = xa + r * 128 + (((lane & 7) ^ (r & 7)) << 4);
                #pragma unroll
                for (int hh = 0; hh < 2; hh++) {
                    uint4 t = xr[r][hh];
                    t.x = bsub2(t.x, m); t.y = bsub2(t.y, m); t.z = bsub2(t.z, m); t.w = bsub2(t.w, m);
                    sts128(a + hh * 65536, t);
                }
            }
            asm volatile("fence.proxy.async.shared::cta;" ::: "memory");
            named_bar(1 + wgi, 128);
            PROFW(17, 0); PROFW(19, 7);
        }
        int st = 0; uint32_t fph = 0;
        const int rb64 = 2 * i + wgi;
        gemm1_pass<4>(sb, wgi, warp4, lane, st, fph, e_cl, rb64, 4 * j, convCTA);
        gemm1_pass<3>(sb, wgi, warp4, lane, st, fph, e_cl, rb64, 32 + 3 * j, convCTA);

        if (convCTA) {
            const int m_lane = g + 2 * c + 16 * warp4;
            const int cp = (c + warp4) & 3, ish = (c + warp4) >> 2;
            const uint32_t rdst = sb + SM_RING + wgi * 32768 + warp4 * 8192 + ish * 512 + (g * 4 + cp) * 16;
            const uint32_t rsrc = sb + SM_RING + wgi * 32768 + warp4 * 2048 + lane * 16;
            const uint2 dd = ldg_nc64(p.ssm_D + 8 * cidx + 4 * wgi);
            const uint32_t hk0 = sb + SM_CVH + wgi * 16384 + (m_lane - 8) * 4;
            uint32_t a0[4][2][4], a1[4][2][4];
            mbar_wait(sb + SM_BARS + B_CONV * 8, 0);
            conv_load_a<0, 4>(a0, hk0, m_lane);
            if (wgi == 1) named_bar(3, 256);
            #pragma unroll 1
            for (int ch = 0; ch < 4; ch++) {
                const int gch = 8 * cidx + 4 * wgi + ch;
                const uint32_t dw = (ch & 2) ? dd.y : dd.x;
                const uint32_t d2 = __byte_perm(dw, dw, (ch & 1) ? 0x3232 : 0x1010);
                const uint32_t cbase = sb + SM_CVR + (4 * wgi + ch) * RB_CH;
                const uint64_t db = make_desc(cbase + RB_Z * 16, RB_R1, 128, 0);
                const uint32_t hk_lane = hk0 + ch * 4096;
                float acc[4][16];
                PROFW(32 + ch * 2, 4);
                conv_mma<0, 4>(acc, a0, db);
                conv_load_a<4, 4>(a1, hk_lane, m_lane);
                conv_mma<4, 4>(acc, a1, db);
                wg_wait<1>();
                conv_load_a<8, 4>(a0, hk_lane, m_lane);
                conv_mma<8, 4>(acc, a0, db);
                wg_wait<1>();
                conv_load_a<12, 4>(a1, hk_lane, m_lane);
                conv_mma<12, 4>(acc, a1, db);
                if (wgi == 0 && ch == 0) asm volatile("bar.arrive 3, 256;" ::: "memory");
                wg_wait<1>();
                conv_load_a<0, 4>(a0, hk0 + (ch < 3 ? ch + 1 : 3) * 4096, m_lane);
                wg_wait<0>();
                PROFW(33 + ch * 2, 4);
                if (ch == 0) mbar_wait(sb + SM_BARS + B_G1DONE * 8, 0);
                else named_bar(1 + wgi, 128);
                #pragma unroll
                for (int ii = 0; ii < 16; ii++) {
                    if (ii < 15 || ish == 0)
                        sts128(rdst + ii * 512, make_uint4(__float_as_uint(acc[ii >> 2][4 * (ii & 3)]), __float_as_uint(acc[ii >> 2][4 * (ii & 3) + 1]),
                                                           __float_as_uint(acc[ii >> 2][4 * (ii & 3) + 2]), __float_as_uint(acc[ii >> 2][4 * (ii & 3) + 3])));
                }
                named_bar(1 + wgi, 128);
                const uint32_t kvaddr = cbase + ((7 - g) & 1) * RB_R1 + (RB_Z + 32 * warp4 + 2 * c) * 16 + ((7 - g) >> 1) * 4;
                uint32_t* ydst = (uint32_t*)(g_yT + (size_t)gch * SEQ + 512 * warp4 + 32 * c + 2 * g);
                uint4 t[4][4]; uint32_t k0[4], k1[4];
                #pragma unroll
                for (int ii = 0; ii < 4; ii++) {
                    #pragma unroll
                    for (int ww = 0; ww < 4; ww++) t[ii][ww] = lds128(rsrc + ww * 8192 + ii * 512);
                    k0[ii] = lds32(kvaddr + ii * 128); k1[ii] = lds32(kvaddr + ii * 128 + 16);
                }
                #pragma unroll
                for (int ii = 0; ii < 4; ii++) {
                    float sx = __uint_as_float(t[ii][0].x), sy = __uint_as_float(t[ii][0].y), sz = __uint_as_float(t[ii][0].z), sw = __uint_as_float(t[ii][0].w);
                    #pragma unroll
                    for (int ww = 1; ww < 4; ww++) {
                        if (!(ii == 0 && warp4 == 0 && c < ww)) {
                            sx += __uint_as_float(t[ii][ww].x); sy += __uint_as_float(t[ii][ww].y); sz += __uint_as_float(t[ii][ww].z); sw += __uint_as_float(t[ii][ww].w);
                        }
                    }
                    ydst[ii * 64] = badd2(pack_bf(sz, sx), bmul2(__byte_perm(k0[ii], k0[ii], 0x1032), d2));
                    ydst[ii * 64 + 8] = badd2(pack_bf(sw, sy), bmul2(__byte_perm(k1[ii], k1[ii], 0x1032), d2));
                }
            }
            PROFW(44, 4);
            asm volatile("fence.proxy.async.global;" ::: "memory");
            __syncwarp();
            if (lane == 0) mbar_arrive(sb + SM_BARS + B_YST * 8);
        } else {
            float acc[64];
            const uint64_t descB0 = make_desc(sb, 4096, 1024, 1);
            const uint64_t descA0 = make_desc(sb + 16384 + wgi * 4096, 128, 256, 0);
            int sg = 3, p0 = 0; uint32_t ph = 6;
            PROFW(20, 0);
            #pragma unroll 1
            for (int u = 0; u < 28; u++) {
                if (warp == 0 && !(u & 1)) PROF2(2, 16 + (u >> 1));
                mbar_wait(sb + SM_BARS + (B_FULL + sg) * 8, (ph >> sg) & 1);
                ph ^= 1u << sg;
                if (warp == 0 && !(u & 1)) PROF2(1, 16 + (u >> 1));
                const uint32_t o0 = stage_off_rt(sg) >> 4;
                const uint64_t da0 = desc_add(descA0, o0), db0 = desc_add(descB0, o0);
                WG_FENCE();
                #pragma unroll
                for (int kk = 0; kk < 4; kk++) wgmma_ss_n128_tb(acc, da0 + ((kk >> 1) * 512 + (kk & 1) * 128), db0 + ((kk >> 1) * 512 + (kk & 1) * 128), (u | kk) ? 1 : 0);
                WG_COMMIT();
                wg_wait<1>();
                if (warp == 0 && !(u & 1)) PROF2(3, 16 + (u >> 1));
                if (lane < 2 && u > 0 && u + 4 < 28) mbar_arrive_cluster(e_cl + p0 * 8, 1);
                p0 = sg;
                sg = next_st2(sg);
            }
            wg_wait<0>();
            PROFW(27, 0);
            mbar_wait(sb + SM_BARS + B_XR * 8, 0);
            mbar_wait(sb + SM_BARS + B_YT * 8, 0);
            PROFW(28, 0);
            const int r0 = wgi * 64 + warp4 * 16 + g;
            const float2 st0 = lds64f(sb + SM_STATS + r0 * 8), st1 = lds64f(sb + SM_STATS + (r0 + 8) * 8);
            const uint32_t m0 = __float_as_uint(st0.x), m1 = __float_as_uint(st1.x);
            const uint32_t xrow0 = sb + SM_XE + r0 * 128 + c * 4;
            const int mi = lane >> 3, lr = lane & 7;
            const uint32_t yaddr = sb + SM_YT + wgi * 16384 + ((mi >> 1) * 8 + lr) * 128 + (((2 * warp4 + (mi & 1)) ^ lr) << 4);
            uint32_t y[8][4], xv[16][2];
            #pragma unroll
            for (int t2 = 0; t2 < 8; t2++)
                asm volatile("ldmatrix.sync.aligned.m8n8.x4.trans.shared.b16 {%0,%1,%2,%3}, [%4];"
                    : "=r"(y[t2][0]), "=r"(y[t2][1]), "=r"(y[t2][2]), "=r"(y[t2][3]) : "r"(yaddr + t2 * 2048) : "memory");
            #pragma unroll
            for (int t = 0; t < 16; t++) {
                const uint32_t off = (t >> 3) * 16384 + (((t & 7) ^ g) << 4);
                xv[t][0] = lds32(xrow0 + off); xv[t][1] = lds32(xrow0 + 1024 + off);
            }
            #pragma unroll
            for (int t = 0; t < 16; t++) {
                const uint32_t off = (t >> 3) * 16384 + (((t & 7) ^ g) << 4);
                const uint32_t d0 = bsub2(xv[t][0], m0), d1 = bsub2(xv[t][1], m1);
                const uint32_t n0 = pack_bf(bf_lo(d0) * st0.y, bf_hi(d0) * st0.y), n1 = pack_bf(bf_lo(d1) * st1.y, bf_hi(d1) * st1.y);
                const uint32_t o0 = badd2(badd2(xv[t][0], bmul2(n0, y[t >> 1][2 * (t & 1)])), pack_bf(acc[4 * t], acc[4 * t + 1]));
                const uint32_t o1 = badd2(badd2(xv[t][1], bmul2(n1, y[t >> 1][2 * (t & 1) + 1])), pack_bf(acc[4 * t + 2], acc[4 * t + 3]));
                sts32(xrow0 + off, o0); sts32(xrow0 + 1024 + off, o1);
            }
            asm volatile("fence.proxy.async.shared::cta;" ::: "memory");
            named_bar(1 + wgi, 128);
            if ((tid & 127) == 0) {
                tma2d_store(&p.tm_out, 128 * cb, 128 * i + 64 * wgi, sb + SM_XE + wgi * 8192);
                tma2d_store(&p.tm_out, 128 * cb + 64, 128 * i + 64 * wgi, sb + SM_XE + 16384 + wgi * 8192);
                asm volatile("cp.async.bulk.commit_group;" ::: "memory");
                asm volatile("cp.async.bulk.wait_group.read 0;" ::: "memory");
                PROFW(29, 0);
            }
        }
    } else {
        asm volatile("setmaxnreg.dec.sync.aligned.u32 104;");
        if (warp == 8) {
            int st = 0; uint32_t eph = 7;
            #pragma unroll 1
            for (int it = 0; it < 16; it++) {
                const int pass = it >> 3, sl = it & 7;
                const int nb = pass ? 3 : 4;
                const CUtensorMap* tm = pass ? (rank ? &p.tm_uB : &p.tm_gB) : (rank ? &p.tm_uA : &p.tm_gA);
                mbar_wait(sb + SM_BARS + (B_EMPTY + st) * 8, (eph >> st) & 1);
                eph ^= 1u << st;
                if (it == 1) mbar_wait(sb + SM_BARS + (B_XFULL + 2) * 8, 0);
                PROF2(0, it);
                if (elect_one()) {
                    mbar_expect_tx(sb + SM_BARS + (B_FULL + st) * 8, nb * 8192);
                    tma3d_mc(sb + SM_RING + st * STAGE_BYTES + rank * nb * 4096, tm, 0, ((sl + 2 * cb + 2) & 7) * 64, 7 * j + 4 * pass, sb + SM_BARS + (B_FULL + st) * 8);
                }
                st = (st == 2) ? 0 : st + 1;
            }
            if (!convCTA) {
                st = 3;
                int f0 = 32 * rank, t3 = rank;
                #pragma unroll 1
                for (int u = 0; u < 28; u++) {
                    const uint32_t bar = sb + SM_BARS + (B_FULL + st) * 8;
                    mbar_wait(sb + SM_BARS + (B_EMPTY + st) * 8, (eph >> st) & 1);
                    eph ^= 1u << st;
                    if ((u & 1) == 0) PROF2(0, 16 + (u >> 1));
                    if (elect_one()) {
                        mbar_expect_tx(bar, 32768);
                        tma3d_mc(sb + stage_off_rt(st) + rank * 8192, &p.tm_w2, 0, f0, 2 * cb, bar);
                    }
                    st = next_st2(st);
                    if (u < 15) f0 += (u & 1) ? 160 : 64;
                    else if (u == 15) f0 = 128 + 32 * rank;
                    else { f0 += (t3 == 0) ? 64 : 192; t3 = (t3 == 0) ? 2 : t3 - 1; }
                }
                PROF(48);
            }
        } else if (warp < 11) {
            mbar_wait(sb + SM_BARS + (B_XFULL + 3) * 8, 0);
            #pragma unroll 1
            for (int rnd = 0; rnd < 2; rnd++) {
                const int tt = (tid - 288) + 64 * rnd;
                uint32_t sk[4][2];
                uint4 skw[2];
                skw[0] = ldg_nc128(p.shift_k + 16 * tt); skw[1] = ldg_nc128(p.shift_k + 16 * tt + 8);
                const __nv_bfloat16* kp = p.k + (size_t)(16 * b) * DM + 4 * tt;
                const __nv_bfloat16* vp = p.v + (size_t)(16 * b) * DM + 4 * tt;
                uint2 kr[19];
                uint2 kv[16];
                #pragma unroll
                for (int r = 0; r < 3; r++) kr[r] = (b > 0) ? ldg_nc64(kp + (r - 3) * DM) : make_uint2(0, 0);
                #pragma unroll
                for (int r = 0; r < 16; r++) { kr[3 + r] = ldg_nc64(kp + r * DM); if (r < 10) kv[r] = ldg_nc64(vp + r * DM); }
                {
                    const uint4 w0 = skw[0], w1 = skw[1];
                    sk[0][0] = __byte_perm(w0.x, w0.z, 0x5410); sk[1][0] = __byte_perm(w0.x, w0.z, 0x7632);
                    sk[2][0] = __byte_perm(w0.y, w0.w, 0x5410); sk[3][0] = __byte_perm(w0.y, w0.w, 0x7632);
                    sk[0][1] = __byte_perm(w1.x, w1.z, 0x5410); sk[1][1] = __byte_perm(w1.x, w1.z, 0x7632);
                    sk[2][1] = __byte_perm(w1.y, w1.w, 0x5410); sk[3][1] = __byte_perm(w1.y, w1.w, 0x7632);
                }
                #pragma unroll
                for (int s = 0; s < 16; s++) {
                    uint32_t a = bmul2(kr[s].x, sk[3][0]);
                    a = badd2(a, bmul2(kr[s + 1].x, sk[2][0]));
                    a = badd2(a, bmul2(kr[s + 2].x, sk[1][0]));
                    a = badd2(a, bmul2(kr[s + 3].x, sk[0][0]));
                    kv[s].x = bmul2(a, kv[s].x);
                    a = bmul2(kr[s].y, sk[3][1]);
                    a = badd2(a, bmul2(kr[s + 1].y, sk[2][1]));
                    a = badd2(a, bmul2(kr[s + 2].y, sk[1][1]));
                    a = badd2(a, bmul2(kr[s + 3].y, sk[0][1]));
                    kv[s].y = bmul2(a, kv[s].y);
                    if (s < 6) kv[10 + s] = ldg_nc64(vp + (10 + s) * DM);
                }
                PROFW(57 + 2 * rnd, 9);
                #pragma unroll
                for (int cc = 0; cc < 4; cc++) {
                    const uint32_t sel = (cc & 1) ? 0x7632 : 0x5410;
                    #define KVW(r) ((cc & 2) ? kv[r].y : kv[r].x)
                    uint8_t* dst = g_rb + (size_t)(4 * tt + cc) * RB_CH + (RB_Z + b) * 16;
                    *(uint4*)dst = make_uint4(__byte_perm(KVW(15), KVW(14), sel), __byte_perm(KVW(11), KVW(10), sel),
                                              __byte_perm(KVW(7), KVW(6), sel), __byte_perm(KVW(3), KVW(2), sel));
                    *(uint4*)(dst + RB_R1) = make_uint4(__byte_perm(KVW(13), KVW(12), sel), __byte_perm(KVW(9), KVW(8), sel),
                                                        __byte_perm(KVW(5), KVW(4), sel), __byte_perm(KVW(1), KVW(0), sel));
                    if (b < RB_Z) {
                        uint8_t* z = g_rb + (size_t)(4 * tt + cc) * RB_CH + b * 16;
                        *(uint4*)z = make_uint4(0, 0, 0, 0);
                        *(uint4*)(z + RB_R1) = make_uint4(0, 0, 0, 0);
                    }
                    #undef KVW
                }
                PROFW(58 + 2 * rnd, 9);
            }
            asm volatile("fence.proxy.async.global;" ::: "memory");
            __syncwarp();
            if (lane == 0) {
                flag_add(&g_cnt_kv[0]);
                PROFW(50, 9);
                const int wgi = warp - 9;
                mbar_wait(sb + SM_BARS + (B_HD + wgi * 2) * 8, 0);
                flag_add(&g_flag_h[(i * 2 + 0) * 8]);
                mbar_wait(sb + SM_BARS + (B_HD + wgi * 2 + 1) * 8, 0);
                flag_add(&g_flag_h[(i * 2 + 1) * 8]);
                if (wgi == 1 && convCTA) {
                    mbar_wait(sb + SM_BARS + B_YST * 8, 0);
                    flag_add(&g_cnt_y[(cidx >> 4) * 32]);
                    PROF(46);
                }
                if (wgi == 1 && !convCTA) {
                    const unsigned ep = lds32(sb + SM_EPOCH);
                    mbar_wait(sb + SM_BARS + B_G1DONE * 8, 0);
                    mbar_expect_tx(sb + SM_BARS + B_XR * 8, 32768);
                    for (int q = 0; q < 4; q++)
                        tma2d(sb + SM_XE + q * 8192, &p.tm_xe, 128 * cb + 64 * (q >> 1), 128 * i + 64 * (q & 1), sb + SM_BARS + B_XR * 8);
                    flag_wait(&g_flag_h[(i * 2 + 1) * 8], ep * 16);
                    mbar_arrive(sb + SM_BARS + (B_HRDY + 1) * 8);
                    __nanosleep(3000);
                    flag_wait(&g_cnt_y[cb * 32], ep * 16);
                    PROF(49);
                    asm volatile("fence.proxy.async.global;" ::: "memory");
                    mbar_expect_tx(sb + SM_BARS + B_YT * 8, 32768);
                    tma2d(sb + SM_YT, &p.tm_yT, 128 * i, 128 * cb, sb + SM_BARS + B_YT * 8);
                    tma2d(sb + SM_YT + 16384, &p.tm_yT, 128 * i + 64, 128 * cb, sb + SM_BARS + B_YT * 8);
                }
            }
        } else {
            if (lane == 0) {
                const unsigned ep = g_launch[b] + 1;
                g_launch[b] = ep;
                sts32(sb + SM_EPOCH, ep);
                tmap_prefetch(rank ? &p.tm_uA : &p.tm_gA);
                mbar_wait(sb + SM_BARS + (B_XFULL + 1) * 8, 0);
                l2_prefetch(p.wg + (size_t)b * (FF * DM / NCTA), FF * DM / NCTA * 2);
                l2_prefetch(p.wu + (size_t)b * (FF * DM / NCTA), FF * DM / NCTA * 2);
                tmap_prefetch(rank ? &p.tm_uB : &p.tm_gB);
                tmap_prefetch(&p.tm_w2); tmap_prefetch(&p.tm_yT); tmap_prefetch(&p.tm_out); tmap_prefetch(&p.tm_xe);
                mbar_wait(sb + SM_BARS + (B_FULL + 2) * 8, 0);
                l2_prefetch(p.ssm_k + (size_t)(4 * b) * SEQ, 4 * SEQ * 2);
                l2_prefetch(p.wd + (size_t)b * (FF * DM / NCTA), FF * DM / NCTA * 2);
                mbar_wait(sb + SM_BARS + (B_HD + 0) * 8, 0);
                if (convCTA) {
                    flag_wait(&g_cnt_kv[0], ep * 256);
                    asm volatile("fence.proxy.async.global;" ::: "memory");
                    PROF(53);
                    mbar_wait(sb + SM_BARS + B_XFREE * 8, 0);
                    PROF(54);
                    mbar_expect_tx(sb + SM_BARS + B_CONV * 8, 8 * RB_CH + 32768);
                    bulk_g2s(sb + SM_CVR, g_rb + (size_t)(8 * cidx) * RB_CH, 8 * RB_CH, sb + SM_BARS + B_CONV * 8);
                    bulk_g2s(sb + SM_CVH, p.ssm_k + (size_t)(8 * cidx) * SEQ, 32768, sb + SM_BARS + B_CONV * 8);
                } else {
                    flag_wait(&g_flag_h[(i * 2 + 0) * 8], ep * 16);
                }
            }
            __syncwarp();
            if (!convCTA) {
                asm volatile("fence.proxy.async.global;" ::: "memory");
                int st = 3; uint32_t eph = 1;
                const uint8_t* hsrc = (const uint8_t*)g_h + (size_t)i * 56 * 8192;
                #pragma unroll 1
                for (int u = 0; u < 28; u++) {
                    mbar_wait(sb + SM_BARS + (B_EMPTY + st) * 8, (eph >> st) & 1);
                    eph ^= 1u << st;
                    if (u == 16) {
                        mbar_wait(sb + SM_BARS + (B_HRDY + 1) * 8, 0);
                        asm volatile("fence.proxy.async.global;" ::: "memory");
                    }
                    if (elect_one()) bulk_g2s(sb + stage_off_rt(st) + 16384, hsrc + u * 16384, 16384, sb + SM_BARS + (B_FULL + st) * 8);
                    st = next_st2(st);
                }
            }
        }
    }
}

typedef CUresult (*EncodeFn)(CUtensorMap*, CUtensorMapDataType, cuuint32_t, void*, const cuuint64_t*, const cuuint64_t*,
                             const cuuint32_t*, const cuuint32_t*, CUtensorMapInterleave, CUtensorMapSwizzle,
                             CUtensorMapL2promotion, CUtensorMapFloatOOBfill);

void encode(EncodeFn fn, CUtensorMap* tm, const void* base, int rank, const cuuint64_t* dims, const cuuint64_t* strides,
            const cuuint32_t* box, CUtensorMapSwizzle swz) {
    cuuint32_t es[5] = {1, 1, 1, 1, 1};
    fn(tm, CU_TENSOR_MAP_DATA_TYPE_BFLOAT16, rank, (void*)base, dims, strides, box, es, CU_TENSOR_MAP_INTERLEAVE_NONE, swz,
       CU_TENSOR_MAP_L2_PROMOTION_L2_128B, CU_TENSOR_MAP_FLOAT_OOB_FILL_NONE);
}

}

extern "C" void kernel_launch(void* const* d_in, const int* in_sizes, int n_in, void* d_out, int out_size) {
    (void)in_sizes; (void)n_in; (void)out_size;
    static EncodeFn enc = nullptr;
    static void* yT_ptr = nullptr;
    if (!enc) {
        void* fn = nullptr; cudaDriverEntryPointQueryResult qr;
        cudaGetDriverEntryPoint("cuTensorMapEncodeTiled", &fn, cudaEnableDefault, &qr);
        enc = (EncodeFn)fn;
        cudaGetSymbolAddress(&yT_ptr, g_yT);
        cudaFuncSetAttribute(fused_kernel, cudaFuncAttributeMaxDynamicSharedMemorySize, SM_TOTAL);
    }
    Params p;
    p.q = (const __nv_bfloat16*)d_in[0]; p.k = (const __nv_bfloat16*)d_in[1]; p.v = (const __nv_bfloat16*)d_in[2];
    p.shift_k = (const __nv_bfloat16*)d_in[3]; p.ssm_k = (const __nv_bfloat16*)d_in[4]; p.ssm_D = (const __nv_bfloat16*)d_in[5];
    p.wg = (const __nv_bfloat16*)d_in[7]; p.wu = (const __nv_bfloat16*)d_in[8]; p.wd = (const __nv_bfloat16*)d_in[9];
    {
        cuuint64_t dims[2] = {DM, SEQ}; cuuint64_t str[1] = {DM * 2};
        cuuint32_t box[2] = {64, 32};
        encode(enc, &p.tm_x, p.q, 2, dims, str, box, CU_TENSOR_MAP_SWIZZLE_128B);
        cuuint32_t box2[2] = {64, 64};
        encode(enc, &p.tm_out, d_out, 2, dims, str, box2, CU_TENSOR_MAP_SWIZZLE_128B);
        encode(enc, &p.tm_xe, p.q, 2, dims, str, box2, CU_TENSOR_MAP_SWIZZLE_128B);
    }
    {
        cuuint64_t dims[3] = {32, DM, FF / 32}; cuuint64_t str[2] = {FF * 2, 64};
        cuuint32_t boxA[3] = {32, 64, 4}, boxB[3] = {32, 64, 3};
        encode(enc, &p.tm_gA, p.wg, 3, dims, str, boxA, CU_TENSOR_MAP_SWIZZLE_64B);
        encode(enc, &p.tm_gB, p.wg, 3, dims, str, boxB, CU_TENSOR_MAP_SWIZZLE_64B);
        encode(enc, &p.tm_uA, p.wu, 3, dims, str, boxA, CU_TENSOR_MAP_SWIZZLE_64B);
        encode(enc, &p.tm_uB, p.wu, 3, dims, str, boxB, CU_TENSOR_MAP_SWIZZLE_64B);
    }
    {
        cuuint64_t dims[3] = {64, FF, DM / 64}; cuuint64_t str[2] = {DM * 2, 128};
        cuuint32_t box[3] = {64, 32, 2};
        encode(enc, &p.tm_w2, p.wd, 3, dims, str, box, CU_TENSOR_MAP_SWIZZLE_128B);
    }
    {
        cuuint64_t dims[2] = {SEQ, DM}; cuuint64_t str[1] = {SEQ * 2};
        cuuint32_t box[2] = {64, 128};
        encode(enc, &p.tm_yT, yT_ptr, 2, dims, str, box, CU_TENSOR_MAP_SWIZZLE_128B);
    }
    fused_kernel<<<NCTA, NTHREADS, SM_TOTAL>>>(p);
}
```

```cpp
#include <cuda_runtime.h>
#include <cuda_bf16.h>
#include <cuda.h>
#include <stdint.h>

namespace {

constexpr int SEQ = 2048, DM = 512, FF = 1792;
constexpr int NCTA = 128;
constexpr int NTHREADS = 384;
constexpr int STAGE_BYTES = 32768;

constexpr uint32_t SM_X = 0;
constexpr uint32_t SM_RING = 131072;
constexpr uint32_t SM_MISC = SM_RING + 3 * STAGE_BYTES;
constexpr uint32_t SM_BARS = SM_MISC;
constexpr uint32_t SM_EPOCH = SM_MISC + 248;
constexpr uint32_t SM_STATS = SM_MISC + 256;
constexpr uint32_t SM_TOTAL = SM_STATS + 1024;
static_assert(SM_TOTAL <= 232448, "smem");
constexpr int RB_Z = 25;
constexpr int RB_R1 = (128 + RB_Z) * 16;
constexpr int RB_CH = 2 * RB_R1;
constexpr uint32_t SM_CVR = 0;
constexpr uint32_t SM_CVH = 8 * RB_CH;
static_assert(SM_CVH + 8 * 4096 <= 5 * 16384, "conv operands");
constexpr uint32_t SM_YT = 4 * 16384;
constexpr uint32_t SM_XE = 6 * 16384;

constexpr int B_FULL = 0, B_EMPTY = 5, B_XFULL = 10, B_CONV = 14, B_YT = 15, B_XR = 16, B_G1DONE = 17, B_HD = 18, B_HRDY = 22,
              B_XFREE = 24, B_YST = 25, B_COUNT = 26;
static_assert(B_COUNT * 8 <= 248, "barrier space");

__device__ __align__(128) uint32_t g_h[16 * 56 * 2048];
__device__ __align__(128) uint8_t g_rb[DM * RB_CH];
__device__ __align__(128) __nv_bfloat16 g_yT[DM * SEQ];
__device__ unsigned g_launch[NCTA];
__device__ unsigned g_cnt_kv[32];
__device__ unsigned g_cnt_y[4 * 32];
__device__ unsigned g_flag_h[16 * 2 * 8];

#define PROF(idx)
#define PROF2(a, idx)
#define PROFW(idx, w)

struct Params {
    CUtensorMap tm_x, tm_gA, tm_gB, tm_uA, tm_uB, tm_w2, tm_yT, tm_out, tm_xe;
    const __nv_bfloat16 *q, *k, *v, *shift_k, *ssm_k, *ssm_D, *wg, *wu, *wd;
};

__device__ __forceinline__ void wgmma_rs_n32(float (&d)[16], uint32_t a0, uint32_t a1, uint32_t a2, uint32_t a3, uint64_t db, int sc) {
  asm volatile("{\n.reg .pred p;\nsetp.ne.b32 p, %21, 0;\n"
    "wgmma.mma_async.sync.aligned.m64n32k16.f32.bf16.bf16 {%0,%1,%2,%3,%4,%5,%6,%7,%8,%9,%10,%11,%12,%13,%14,%15}, {%16,%17,%18,%19}, %20, p, 1, 1, 0;\n}\n"
    : "+f"(d[0]),"+f"(d[1]),"+f"(d[2]),"+f"(d[3]),"+f"(d[4]),"+f"(d[5]),"+f"(d[6]),"+f"(d[7]),"+f"(d[8]),"+f"(d[9]),"+f"(d[10]),"+f"(d[11]),"+f"(d[12]),"+f"(d[13]),"+f"(d[14]),"+f"(d[15])
    : "r"(a0),"r"(a1),"r"(a2),"r"(a3),"l"(db),"r"(sc));
}
__device__ __forceinline__ void wgmma_rs_n128_tb(float (&d)[64], uint32_t a0, uint32_t a1, uint32_t a2, uint32_t a3, uint64_t db, int sc) {
  asm volatile("{\n.reg .pred p;\nsetp.ne.b32 p, %69, 0;\n"
    "wgmma.mma_async.sync.aligned.m64n128k16.f32.bf16.bf16 {%0,%1,%2,%3,%4,%5,%6,%7,%8,%9,%10,%11,%12,%13,%14,%15,%16,%17,%18,%19,%20,%21,%22,%23,%24,%25,%26,%27,%28,%29,%30,%31,%32,%33,%34,%35,%36,%37,%38,%39,%40,%41,%42,%43,%44,%45,%46,%47,%48,%49,%50,%51,%52,%53,%54,%55,%56,%57,%58,%59,%60,%61,%62,%63}, {%64,%65,%66,%67}, %68, p, 1, 1, 1;\n}\n"
    : "+f"(d[0]),"+f"(d[1]),"+f"(d[2]),"+f"(d[3]),"+f"(d[4]),"+f"(d[5]),"+f"(d[6]),"+f"(d[7]),"+f"(d[8]),"+f"(d[9]),"+f"(d[10]),"+f"(d[11]),"+f"(d[12]),"+f"(d[13]),"+f"(d[14]),"+f"(d[15]),"+f"(d[16]),"+f"(d[17]),"+f"(d[18]),"+f"(d[19]),"+f"(d[20]),"+f"(d[21]),"+f"(d[22]),"+f"(d[23]),"+f"(d[24]),"+f"(d[25]),"+f"(d[26]),"+f"(d[27]),"+f"(d[28]),"+f"(d[29]),"+f"(d[30]),"+f"(d[31]),"+f"(d[32]),"+f"(d[33]),"+f"(d[34]),"+f"(d[35]),"+f"(d[36]),"+f"(d[37]),"+f"(d[38]),"+f"(d[39]),"+f"(d[40]),"+f"(d[41]),"+f"(d[42]),"+f"(d[43]),"+f"(d[44]),"+f"(d[45]),"+f"(d[46]),"+f"(d[47]),"+f"(d[48]),"+f"(d[49]),"+f"(d[50]),"+f"(d[51]),"+f"(d[52]),"+f"(d[53]),"+f"(d[54]),"+f"(d[55]),"+f"(d[56]),"+f"(d[57]),"+f"(d[58]),"+f"(d[59]),"+f"(d[60]),"+f"(d[61]),"+f"(d[62]),"+f"(d[63])
    : "r"(a0),"r"(a1),"r"(a2),"r"(a3),"l"(db),"r"(sc));
}
__device__ __forceinline__ void wgmma_ss_n256_tb(float (&d)[128], uint64_t da, uint64_t db, int sc) {
  asm volatile("{\n.reg .pred p;\nsetp.ne.b32 p, %130, 0;\n"
    "wgmma.mma_async.sync.aligned.m64n256k16.f32.bf16.bf16 {%0,%1,%2,%3,%4,%5,%6,%7,%8,%9,%10,%11,%12,%13,%14,%15,%16,%17,%18,%19,%20,%21,%22,%23,%24,%25,%26,%27,%28,%29,%30,%31,%32,%33,%34,%35,%36,%37,%38,%39,%40,%41,%42,%43,%44,%45,%46,%47,%48,%49,%50,%51,%52,%53,%54,%55,%56,%57,%58,%59,%60,%61,%62,%63,%64,%65,%66,%67,%68,%69,%70,%71,%72,%73,%74,%75,%76,%77,%78,%79,%80,%81,%82,%83,%84,%85,%86,%87,%88,%89,%90,%91,%92,%93,%94,%95,%96,%97,%98,%99,%100,%101,%102,%103,%104,%105,%106,%107,%108,%109,%110,%111,%112,%113,%114,%115,%116,%117,%118,%119,%120,%121,%122,%123,%124,%125,%126,%127}, %128, %129, p, 1, 1, 0, 1;\n}\n"
    : "+f"(d[0]),"+f"(d[1]),"+f"(d[2]),"+f"(d[3]),"+f"(d[4]),"+f"(d[5]),"+f"(d[6]),"+f"(d[7]),"+f"(d[8]),"+f"(d[9]),"+f"(d[10]),"+f"(d[11]),"+f"(d[12]),"+f"(d[13]),"+f"(d[14]),"+f"(d[15]),"+f"(d[16]),"+f"(d[17]),"+f"(d[18]),"+f"(d[19]),"+f"(d[20]),"+f"(d[21]),"+f"(d[22]),"+f"(d[23]),"+f"(d[24]),"+f"(d[25]),"+f"(d[26]),"+f"(d[27]),"+f"(d[28]),"+f"(d[29]),"+f"(d[30]),"+f"(d[31]),"+f"(d[32]),"+f"(d[33]),"+f"(d[34]),"+f"(d[35]),"+f"(d[36]),"+f"(d[37]),"+f"(d[38]),"+f"(d[39]),"+f"(d[40]),"+f"(d[41]),"+f"(d[42]),"+f"(d[43]),"+f"(d[44]),"+f"(d[45]),"+f"(d[46]),"+f"(d[47]),"+f"(d[48]),"+f"(d[49]),"+f"(d[50]),"+f"(d[51]),"+f"(d[52]),"+f"(d[53]),"+f"(d[54]),"+f"(d[55]),"+f"(d[56]),"+f"(d[57]),"+f"(d[58]),"+f"(d[59]),"+f"(d[60]),"+f"(d[61]),"+f"(d[62]),"+f"(d[63]),"+f"(d[64]),"+f"(d[65]),"+f"(d[66]),"+f"(d[67]),"+f"(d[68]),"+f"(d[69]),"+f"(d[70]),"+f"(d[71]),"+f"(d[72]),"+f"(d[73]),"+f"(d[74]),"+f"(d[75]),"+f"(d[76]),"+f"(d[77]),"+f"(d[78]),"+f"(d[79]),"+f"(d[80]),"+f"(d[81]),"+f"(d[82]),"+f"(d[83]),"+f"(d[84]),"+f"(d[85]),"+f"(d[86]),"+f"(d[87]),"+f"(d[88]),"+f"(d[89]),"+f"(d[90]),"+f"(d[91]),"+f"(d[92]),"+f"(d[93]),"+f"(d[94]),"+f"(d[95]),"+f"(d[96]),"+f"(d[97]),"+f"(d[98]),"+f"(d[99]),"+f"(d[100]),"+f"(d[101]),"+f"(d[102]),"+f"(d[103]),"+f"(d[104]),"+f"(d[105]),"+f"(d[106]),"+f"(d[107]),"+f"(d[108]),"+f"(d[109]),"+f"(d[110]),"+f"(d[111]),"+f"(d[112]),"+f"(d[113]),"+f"(d[114]),"+f"(d[115]),"+f"(d[116]),"+f"(d[117]),"+f"(d[118]),"+f"(d[119]),"+f"(d[120]),"+f"(d[121]),"+f"(d[122]),"+f"(d[123]),"+f"(d[124]),"+f"(d[125]),"+f"(d[126]),"+f"(d[127])
    : "l"(da),"l"(db),"r"(sc));
}
__device__ __forceinline__ void wgmma_ss_n192_tb(float (&d)[96], uint64_t da, uint64_t db, int sc) {
  asm volatile("{\n.reg .pred p;\nsetp.ne.b32 p, %98, 0;\n"
    "wgmma.mma_async.sync.aligned.m64n192k16.f32.bf16.bf16 {%0,%1,%2,%3,%4,%5,%6,%7,%8,%9,%10,%11,%12,%13,%14,%15,%16,%17,%18,%19,%20,%21,%22,%23,%24,%25,%26,%27,%28,%29,%30,%31,%32,%33,%34,%35,%36,%37,%38,%39,%40,%41,%42,%43,%44,%45,%46,%47,%48,%49,%50,%51,%52,%53,%54,%55,%56,%57,%58,%59,%60,%61,%62,%63,%64,%65,%66,%67,%68,%69,%70,%71,%72,%73,%74,%75,%76,%77,%78,%79,%80,%81,%82,%83,%84,%85,%86,%87,%88,%89,%90,%91,%92,%93,%94,%95}, %96, %97, p, 1, 1, 0, 1;\n}\n"
    : "+f"(d[0]),"+f"(d[1]),"+f"(d[2]),"+f"(d[3]),"+f"(d[4]),"+f"(d[5]),"+f"(d[6]),"+f"(d[7]),"+f"(d[8]),"+f"(d[9]),"+f"(d[10]),"+f"(d[11]),"+f"(d[12]),"+f"(d[13]),"+f"(d[14]),"+f"(d[15]),"+f"(d[16]),"+f"(d[17]),"+f"(d[18]),"+f"(d[19]),"+f"(d[20]),"+f"(d[21]),"+f"(d[22]),"+f"(d[23]),"+f"(d[24]),"+f"(d[25]),"+f"(d[26]),"+f"(d[27]),"+f"(d[28]),"+f"(d[29]),"+f"(d[30]),"+f"(d[31]),"+f"(d[32]),"+f"(d[33]),"+f"(d[34]),"+f"(d[35]),"+f"(d[36]),"+f"(d[37]),"+f"(d[38]),"+f"(d[39]),"+f"(d[40]),"+f"(d[41]),"+f"(d[42]),"+f"(d[43]),"+f"(d[44]),"+f"(d[45]),"+f"(d[46]),"+f"(d[47]),"+f"(d[48]),"+f"(d[49]),"+f"(d[50]),"+f"(d[51]),"+f"(d[52]),"+f"(d[53]),"+f"(d[54]),"+f"(d[55]),"+f"(d[56]),"+f"(d[57]),"+f"(d[58]),"+f"(d[59]),"+f"(d[60]),"+f"(d[61]),"+f"(d[62]),"+f"(d[63]),"+f"(d[64]),"+f"(d[65]),"+f"(d[66]),"+f"(d[67]),"+f"(d[68]),"+f"(d[69]),"+f"(d[70]),"+f"(d[71]),"+f"(d[72]),"+f"(d[73]),"+f"(d[74]),"+f"(d[75]),"+f"(d[76]),"+f"(d[77]),"+f"(d[78]),"+f"(d[79]),"+f"(d[80]),"+f"(d[81]),"+f"(d[82]),"+f"(d[83]),"+f"(d[84]),"+f"(d[85]),"+f"(d[86]),"+f"(d[87]),"+f"(d[88]),"+f"(d[89]),"+f"(d[90]),"+f"(d[91]),"+f"(d[92]),"+f"(d[93]),"+f"(d[94]),"+f"(d[95])
    : "l"(da),"l"(db),"r"(sc));
}

__device__ __forceinline__ uint32_t smem_u32(const void* p) { return (uint32_t)__cvta_generic_to_shared(p); }
__device__ __forceinline__ void mbar_init(uint32_t bar, uint32_t cnt) { asm volatile("mbarrier.init.shared::cta.b64 [%0], %1;" :: "r"(bar), "r"(cnt)); }
__device__ __forceinline__ void mbar_expect_tx(uint32_t bar, uint32_t bytes) { asm volatile("mbarrier.arrive.expect_tx.shared::cta.b64 _, [%0], %1;" :: "r"(bar), "r"(bytes) : "memory"); }
__device__ __forceinline__ void mbar_arrive(uint32_t bar) { asm volatile("mbarrier.arrive.shared::cta.b64 _, [%0];" :: "r"(bar) : "memory"); }
__device__ __forceinline__ void mbar_arrive_cluster(uint32_t cbar, uint32_t cnt) { asm volatile("mbarrier.arrive.shared::cluster.b64 _, [%0], %1;" :: "r"(cbar), "r"(cnt) : "memory"); }
__device__ __forceinline__ uint32_t mapa(uint32_t a, uint32_t rank) { uint32_t r; asm volatile("mapa.shared::cluster.u32 %0, %1, %2;" : "=r"(r) : "r"(a), "r"(rank)); return r; }
__device__ __forceinline__ void mbar_wait(uint32_t bar, uint32_t parity) {
    uint32_t ok; uint32_t n = 0;
    do {
        asm volatile("{\n.reg .pred p;\nmbarrier.try_wait.parity.shared::cta.b64 p, [%1], %2;\nselp.u32 %0, 1, 0, p;\n}" : "=r"(ok) : "r"(bar), "r"(parity) : "memory");
    } while (!ok && ++n < (1u << 17));
}
__device__ __forceinline__ void pace_wait(uint32_t a, uint32_t target) {
    uint32_t v, n = 0;
    do {
        asm volatile("ld.volatile.shared.u32 %0, [%1];" : "=r"(v) : "r"(a) : "memory");
        if (v < target) __nanosleep(150);
    } while (v < target && ++n < (1u << 14));
}
__device__ __forceinline__ void flag_wait(const unsigned* p, unsigned target) {
    unsigned v; uint32_t n = 0;
    while (true) {
        asm volatile("ld.acquire.gpu.global.u32 %0, [%1];" : "=r"(v) : "l"(p) : "memory");
        if ((int)(v - target) >= 0 || ++n >= (1u << 17)) break;
        __nanosleep(100);
    }
}
__device__ __forceinline__ void flag_add(unsigned* p) {
    asm volatile("fence.acq_rel.gpu;\nred.relaxed.gpu.global.add.u32 [%0], 1;" :: "l"(p) : "memory");
}
__device__ __forceinline__ uint64_t make_desc(uint32_t addr, uint32_t lbo, uint32_t sbo, uint32_t swz) {
    return (uint64_t)((addr & 0x3FFFF) >> 4) | ((uint64_t)((lbo & 0x3FFFF) >> 4) << 16) | ((uint64_t)((sbo & 0x3FFFF) >> 4) << 32) | ((uint64_t)swz << 62);
}
__device__ __forceinline__ uint64_t desc_add(uint64_t d, uint32_t off16) {
    return (d & 0xFFFFFFFF00000000ull) | (uint64_t)((uint32_t)d + off16);
}
__device__ __forceinline__ void tma2d(uint32_t dst, const CUtensorMap* tm, int c0, int c1, uint32_t bar) {
    asm volatile("cp.async.bulk.tensor.2d.shared::cluster.global.mbarrier::complete_tx::bytes [%0], [%1, {%3, %4}], [%2];"
        :: "r"(dst), "l"((uint64_t)tm), "r"(bar), "r"(c0), "r"(c1) : "memory");
}
__device__ __forceinline__ void tma3d_mc(uint32_t dst, const CUtensorMap* tm, int c0, int c1, int c2, uint32_t bar) {
    asm volatile("cp.async.bulk.tensor.3d.shared::cluster.global.mbarrier::complete_tx::bytes.multicast::cluster [%0], [%1, {%3, %4, %5}], [%2], %6;"
        :: "r"(dst), "l"((uint64_t)tm), "r"(bar), "r"(c0), "r"(c1), "r"(c2), "h"((uint16_t)3) : "memory");
}
__device__ __forceinline__ void bulk_g2s(uint32_t dst, const void* src, uint32_t bytes, uint32_t bar) {
    asm volatile("cp.async.bulk.shared::cluster.global.mbarrier::complete_tx::bytes [%0], [%1], %2, [%3];"
        :: "r"(dst), "l"(src), "r"(bytes), "r"(bar) : "memory");
}
__device__ __forceinline__ void bulk_s2g(void* dst, uint32_t src, uint32_t bytes) {
    asm volatile("cp.async.bulk.global.shared::cta.bulk_group [%0], [%1], %2;" :: "l"(dst), "r"(src), "r"(bytes) : "memory");
}
__device__ __forceinline__ void tma2d_store(const CUtensorMap* tm, int c0, int c1, uint32_t src) {
    asm volatile("cp.async.bulk.tensor.2d.global.shared::cta.bulk_group [%0, {%2, %3}], [%1];"
        :: "l"((uint64_t)tm), "r"(src), "r"(c0), "r"(c1) : "memory");
}
__device__ __forceinline__ void l2_prefetch(const void* p, uint32_t bytes) {
    asm volatile("cp.async.bulk.prefetch.L2.global [%0], %1;" :: "l"(p), "r"(bytes) : "memory");
}
__device__ __forceinline__ void tmap_prefetch(const CUtensorMap* tm) { asm volatile("prefetch.tensormap [%0];" :: "l"((uint64_t)tm) : "memory"); }
__device__ __forceinline__ uint32_t lds32(uint32_t a) { uint32_t v; asm volatile("ld.shared.u32 %0, [%1];" : "=r"(v) : "r"(a)); return v; }
__device__ __forceinline__ uint2 lds64(uint32_t a) { uint2 v; asm volatile("ld.shared.v2.u32 {%0,%1}, [%2];" : "=r"(v.x), "=r"(v.y) : "r"(a)); return v; }
__device__ __forceinline__ uint4 lds128(uint32_t a) { uint4 v; asm volatile("ld.shared.v4.u32 {%0,%1,%2,%3}, [%4];" : "=r"(v.x), "=r"(v.y), "=r"(v.z), "=r"(v.w) : "r"(a)); return v; }
__device__ __forceinline__ float2 lds64f(uint32_t a) { float2 v; asm volatile("ld.shared.v2.f32 {%0,%1}, [%2];" : "=f"(v.x), "=f"(v.y) : "r"(a)); return v; }
__device__ __forceinline__ void sts32(uint32_t a, uint32_t v) { asm volatile("st.shared.u32 [%0], %1;" :: "r"(a), "r"(v) : "memory"); }
__device__ __forceinline__ void sts128(uint32_t a, uint4 v) { asm volatile("st.shared.v4.u32 [%0], {%1,%2,%3,%4};" :: "r"(a), "r"(v.x), "r"(v.y), "r"(v.z), "r"(v.w) : "memory"); }
__device__ __forceinline__ uint4 ldg_cg128(const void* p) { uint4 v; asm volatile("ld.global.cg.v4.u32 {%0,%1,%2,%3}, [%4];" : "=r"(v.x), "=r"(v.y), "=r"(v.z), "=r"(v.w) : "l"(p)); return v; }
__device__ __forceinline__ uint4 ldg_nc128(const void* p) { uint4 v; asm volatile("ld.global.nc.L1::no_allocate.v4.u32 {%0,%1,%2,%3}, [%4];" : "=r"(v.x), "=r"(v.y), "=r"(v.z), "=r"(v.w) : "l"(p)); return v; }
__device__ __forceinline__ uint2 ldg_nc64(const void* p) { uint2 v; asm volatile("ld.global.nc.L1::no_allocate.v2.u32 {%0,%1}, [%2];" : "=r"(v.x), "=r"(v.y) : "l"(p)); return v; }
#define WG_FENCE() asm volatile("wgmma.fence.sync.aligned;\n" ::: "memory")
#define WG_COMMIT() asm volatile("wgmma.commit_group.sync.aligned;\n" ::: "memory")
template<int N> __device__ __forceinline__ void wg_wait() { asm volatile("wgmma.wait_group.sync.aligned %0;\n" :: "n"(N) : "memory"); }
__device__ __forceinline__ bool elect_one() {
    uint32_t pr;
    asm volatile("{\n.reg .pred p;\nelect.sync _|p, 0xffffffff;\nselp.u32 %0, 1, 0, p;\n}" : "=r"(pr));
    return pr != 0;
}
__device__ __forceinline__ void named_bar(int id, int n) { asm volatile("bar.sync %0, %1;" :: "r"(id), "r"(n) : "memory"); }

__device__ __forceinline__ float bf_lo(uint32_t u) { return __uint_as_float(u << 16); }
__device__ __forceinline__ float bf_hi(uint32_t u) { return __uint_as_float(u & 0xFFFF0000u); }
__device__ __forceinline__ uint32_t pack_bf(float lo, float hi) { uint32_t r; asm("cvt.rn.bf16x2.f32 %0, %1, %2;" : "=r"(r) : "f"(hi), "f"(lo)); return r; }
__device__ __forceinline__ float bf_round(float x) { return __bfloat162float(__float2bfloat16_rn(x)); }
__device__ __forceinline__ uint32_t bmul2(uint32_t a, uint32_t b) { uint32_t r; asm("mul.rn.bf16x2 %0, %1, %2;" : "=r"(r) : "r"(a), "r"(b)); return r; }
__device__ __forceinline__ uint32_t badd2(uint32_t a, uint32_t b) { uint32_t r; asm("add.rn.bf16x2 %0, %1, %2;" : "=r"(r) : "r"(a), "r"(b)); return r; }
__device__ __forceinline__ uint32_t bsub2(uint32_t a, uint32_t b) { uint32_t r; asm("sub.rn.bf16x2 %0, %1, %2;" : "=r"(r) : "r"(a), "r"(b)); return r; }
__device__ __forceinline__ void mma16816(float (&d)[4], uint32_t a0, uint32_t a1, uint32_t a2, uint32_t a3, uint2 b) {
    asm volatile("mma.sync.aligned.m16n8k16.row.col.f32.bf16.bf16.f32 {%0,%1,%2,%3}, {%4,%5,%6,%7}, {%8,%9}, {%0,%1,%2,%3};\n"
        : "+f"(d[0]), "+f"(d[1]), "+f"(d[2]), "+f"(d[3]) : "r"(a0), "r"(a1), "r"(a2), "r"(a3), "r"(b.x), "r"(b.y));
}

template<int HS> __device__ __forceinline__ void xreduce(float (&v)[32], int lane) {
    const int up = lane & HS;
    #pragma unroll
    for (int e = 0; e < HS; e++) {
        float keep, send;
        asm("{\n.reg .pred p;\nsetp.ne.b32 p, %4, 0;\nselp.f32 %0, %3, %2, p;\nselp.f32 %1, %2, %3, p;\n}"
            : "=f"(keep), "=f"(send) : "f"(v[e]), "f"(v[e + HS]), "r"(up));
        v[e] = keep + __shfl_xor_sync(0xffffffffu, send, HS);
    }
}

__device__ __forceinline__ int blk_f0(int bi, int j) {
    if (bi < 32) return 224 * ((j + (bi >> 2)) & 7) + 32 * (bi & 3);
    int b2 = bi - 32; int q3 = (b2 * 11) >> 5;
    return 224 * ((j + q3) & 7) + 128 + 32 * (b2 - 3 * q3);
}
__device__ __forceinline__ int next_st2(int s) { return (0x14023 >> (4 * s)) & 7; }
__device__ __forceinline__ uint32_t stage_off_rt(int s) { return s < 3 ? SM_RING + s * STAGE_BYTES : (uint32_t)(s - 3) * STAGE_BYTES; }

template<int NB>
__device__ __forceinline__ void gemm1_pass(uint32_t sb, int wgi, int warp4, int lane, int& st, uint32_t& fph, uint32_t e_cl,
                                           int rb64, int ks0, bool convCTA) {
    constexpr bool passA = (NB == 4);
    float acc[NB * 32];
    const uint64_t descA0 = make_desc(sb + SM_X + wgi * 8192, 16, 1024, 1);
    const uint64_t descB0 = make_desc(sb + SM_RING, 4096, 512, 2);
    int prev = 0;
    #pragma unroll 1
    for (int sl = 0; sl < 8; sl++) {
        if (warp4 == 0 && wgi == 0) PROF2(2, sl + (passA ? 0 : 8));
        mbar_wait(sb + SM_BARS + (B_FULL + st) * 8, (fph >> st) & 1);
        fph ^= 1u << st;
        if (sl == 0 && warp4 == 0) PROF(2 + wgi * 8 + (passA ? 0 : 3));
        if (warp4 == 0 && wgi == 0) PROF2(1, sl + (passA ? 0 : 8));
        const uint64_t da = desc_add(descA0, sl * 1024), db = desc_add(descB0, st * 2048);
        WG_FENCE();
        #pragma unroll
        for (int kk = 0; kk < 4; kk++) {
            int sc = (sl | kk) ? 1 : 0;
            if constexpr (NB == 4) wgmma_ss_n256_tb(acc, da + kk * 2, db + kk * 64, sc); else wgmma_ss_n192_tb(acc, da + kk * 2, db + kk * 64, sc);
        }
        WG_COMMIT();
        wg_wait<1>();
        if (warp4 == 0 && wgi == 0) PROF2(3, sl + (passA ? 0 : 8));
        if (lane < 2 && sl && (passA || !convCTA || sl < 6)) mbar_arrive_cluster(e_cl + prev * 8, 1);
        if (!passA) {
            if (convCTA) { if (sl == 5 && lane == 0) mbar_arrive(sb + SM_BARS + B_XFREE * 8); }
            else if ((sl == 2 || sl == 4) && lane < 2) mbar_arrive_cluster(e_cl + (2 + (sl >> 1)) * 8, 1);
        }
        prev = st;
        st = (st == 2) ? 0 : st + 1;
    }
    wg_wait<0>();
    if (lane < 2 && (passA || !convCTA)) mbar_arrive_cluster(e_cl + prev * 8, 1);
    if (!passA && lane == 0) mbar_arrive(sb + SM_BARS + B_G1DONE * 8);
    if (warp4 == 0) PROF(3 + wgi * 8 + (passA ? 0 : 3));
    const int g = lane >> 2;
    const int r0 = wgi * 64 + warp4 * 16 + g;
    const float s0 = __uint_as_float(lds32(sb + SM_STATS + r0 * 8 + 4)), s1 = __uint_as_float(lds32(sb + SM_STATS + (r0 + 8) * 8 + 4));
    uint32_t* dst = g_h + (size_t)((rb64 >> 1) * 56 + ks0) * 2048 + wgi * 1024 + warp4 * 128 + lane;
    #pragma unroll
    for (int kk = 0; kk < NB * 2; kk++) {
        uint32_t h[4];
        #pragma unroll
        for (int tt = 0; tt < 2; tt++) {
            const int t = 2 * kk + tt;
            const float* ag = &acc[4 * t];
            const float* au = &acc[NB * 16 + 4 * t];
            h[2 * tt] = bmul2(pack_bf(ag[0] * s0, ag[1] * s0), pack_bf(au[0] * s0, au[1] * s0));
            h[2 * tt + 1] = bmul2(pack_bf(ag[2] * s1, ag[3] * s1), pack_bf(au[2] * s1, au[3] * s1));
        }
        uint32_t* d2 = dst + (kk >> 1) * 2048 + (kk & 1) * 512;
        d2[0] = h[0]; d2[64] = h[1]; d2[32] = h[2]; d2[96] = h[3];
    }
    asm volatile("fence.proxy.async.global;" ::: "memory");
    __syncwarp();
    if (lane == 0) mbar_arrive(sb + SM_BARS + (B_HD + wgi * 2 + (passA ? 0 : 1)) * 8);
    if (warp4 == 0) PROF(4 + wgi * 8 + (passA ? 0 : 3));
}

template<int P0, int NP>
__device__ __forceinline__ void conv_load_a(uint32_t (&a)[NP][2][4], uint32_t hk_lane, int m_lane) {
    #pragma unroll
    for (int pp = 0; pp < NP; pp++) {
        #pragma unroll
        for (int q = 0; q < 2; q++) {
            const int off = (8 * q + 64 * (P0 + pp)) * 4;
            uint32_t w0, w1, w2;
            if (P0 + pp == 0 && q == 0) {
                w0 = (m_lane + 0 < 8) ? 0u : lds32(hk_lane + off);
                w1 = (m_lane + 1 < 8) ? 0u : lds32(hk_lane + off + 4);
                w2 = (m_lane + 2 < 8) ? 0u : lds32(hk_lane + off + 8);
            } else {
                w0 = lds32(hk_lane + off); w1 = lds32(hk_lane + off + 4); w2 = lds32(hk_lane + off + 8);
            }
            a[pp][q][0] = w1;
            a[pp][q][1] = __byte_perm(w0, w1, 0x5432);
            a[pp][q][2] = w2;
            a[pp][q][3] = __byte_perm(w1, w2, 0x5432);
        }
    }
}
template<int P0, int NP>
__device__ __forceinline__ void conv_mma(float (&acc)[4][16], uint32_t (&a)[NP][2][4], uint64_t db) {
    WG_FENCE();
    #pragma unroll
    for (int pp = 0; pp < NP; pp++) {
        #pragma unroll
        for (int q = 0; q < 2; q++) {
            const int P = P0 + pp;
            #pragma unroll
            for (int bq = P / 4; bq < 4; bq++)
                wgmma_rs_n32(acc[bq], a[pp][q][0], a[pp][q][1], a[pp][q][2], a[pp][q][3],
                             db + (uint64_t)(int64_t)(32 * bq - 8 * P - q), (P == 0 && q == 0) ? 0 : 1);
        }
    }
    WG_COMMIT();
}

__global__ void __cluster_dims__(2, 1, 1) __launch_bounds__(NTHREADS, 1)
fused_kernel(const __grid_constant__ Params p) {
    extern __shared__ __align__(1024) uint8_t smem_raw[];
    const uint32_t sb = smem_u32(smem_raw);
    const int tid = threadIdx.x, warp = tid >> 5, lane = tid & 31;
    const int b = blockIdx.x;
    const int rank = b & 1;
    const int j = (b >> 1) & 7;
    const int i = ((b >> 4) << 1) | rank;
    const int cb = j >> 1;
    const bool convCTA = j & 1;
    const int cidx = 4 * i + cb;

    if (warp == 8 && lane < 4) {
        mbar_init(sb + SM_BARS + (B_XFULL + lane) * 8, 1);
        asm volatile("fence.proxy.async.shared::cta;" ::: "memory");
        mbar_expect_tx(sb + SM_BARS + (B_XFULL + lane) * 8, 32768);
    }
    if (tid == 288) {
        for (int s = 0; s < 5; s++) { mbar_init(sb + SM_BARS + (B_FULL + s) * 8, 1); mbar_init(sb + SM_BARS + (B_EMPTY + s) * 8, 16); }
        mbar_init(sb + SM_BARS + B_CONV * 8, 1);
        mbar_init(sb + SM_BARS + B_YT * 8, 1);
        mbar_init(sb + SM_BARS + B_XR * 8, 1);
        mbar_init(sb + SM_BARS + B_G1DONE * 8, 8);
        mbar_init(sb + SM_BARS + B_XFREE * 8, 8);
        mbar_init(sb + SM_BARS + B_YST * 8, 8);
        for (int s = 0; s < 4; s++) mbar_init(sb + SM_BARS + (B_HD + s) * 8, 4);
        for (int s = 0; s < 2; s++) mbar_init(sb + SM_BARS + (B_HRDY + s) * 8, 1);
        asm volatile("fence.mbarrier_init.release.cluster;" ::: "memory");
        asm volatile("fence.proxy.async.shared::cta;" ::: "memory");
    }
    __syncwarp();
    asm volatile("barrier.cluster.arrive.relaxed.aligned;\n" ::: "memory");
    if (warp == 8) {
        const int rg = lane >> 3, sl = lane & 7;
        tma2d(sb + SM_X + sl * 16384 + rg * 4096, &p.tm_x, 64 * ((sl + 2 * cb + 2) & 7), 128 * i + 32 * rg, sb + SM_BARS + (B_XFULL + rg) * 8);
        __syncwarp();
    }
    asm volatile("barrier.cluster.wait.aligned;\n" ::: "memory");
    PROFW(1, 0);

    if (warp < 8) {
        asm volatile("setmaxnreg.inc.sync.aligned.u32 200;");
        const int wgi = warp >> 2, warp4 = warp & 3;
        const int g = lane >> 2, c = lane & 3;
        const uint32_t e_cl = mapa(sb + SM_BARS + B_EMPTY * 8, lane & 1);
        {
            const uint32_t xa = sb + SM_X + (lane >> 3) * 16384 + warp * 16 * 128;
            uint4 xr[16][2];
            float v[32];
            mbar_wait(sb + SM_BARS + (B_XFULL + (warp >> 1)) * 8, 0);
            PROFW(16, 0); PROFW(18, 7);
            #pragma unroll
            for (int r = 0; r < 16; r++) {
                const uint32_t a = xa + r * 128 + (((lane & 7) ^ (r & 7)) << 4);
                xr[r][0] = lds128(a); xr[r][1] = lds128(a + 65536);
            }
            #pragma unroll
            for (int r = 0; r < 16; r++) {
                const uint32_t* u = (const uint32_t*)&xr[r][0];
                float s = 0.f, q = 0.f;
                #pragma unroll
                for (int e = 0; e < 8; e++) { const float lo = bf_lo(u[e]), hi = bf_hi(u[e]); s += lo; q = fmaf(lo, lo, q); s += hi; q = fmaf(hi, hi, q); }
                v[r] = s; v[16 + r] = q;
            }
            xreduce<16>(v, lane); xreduce<8>(v, lane); xreduce<4>(v, lane); xreduce<2>(v, lane); xreduce<1>(v, lane);
            const float other = __shfl_xor_sync(0xffffffffu, v[0], 16);
            const float mean = (lane < 16 ? v[0] : other) * (1.0f / DM);
            const float msq = (lane < 16 ? other : v[0]) * (1.0f / DM);
            const float var_b = bf_round(fmaxf(msq - mean * mean, 0.f));
            const float sd = bf_round(sqrtf(bf_round(var_b + 1e-5f)));
            const uint32_t mb = pack_bf(mean, mean);
            if (lane < 16) { sts32(sb + SM_STATS + (warp * 16 + lane) * 8, mb); sts32(sb + SM_STATS + (warp * 16 + lane) * 8 + 4, __float_as_uint(1.0f / sd)); }
            #pragma unroll
            for (int r = 0; r < 16; r++) {
                const uint32_t m = __shfl_sync(0xffffffffu, mb, r);
                const uint32_t a = xa + r * 128 + (((lane & 7) ^ (r & 7)) << 4);
                #pragma unroll
                for (int hh = 0; hh < 2; hh++) {
                    uint4 t = xr[r][hh];
                    t.x = bsub2(t.x, m); t.y = bsub2(t.y, m); t.z = bsub2(t.z, m); t.w = bsub2(t.w, m);
                    sts128(a + hh * 65536, t);
                }
            }
            asm volatile("fence.proxy.async.shared::cta;" ::: "memory");
            named_bar(1 + wgi, 128);
            PROFW(17, 0); PROFW(19, 7);
        }
        int st = 0; uint32_t fph = 0;
        const int rb64 = 2 * i + wgi;
        gemm1_pass<4>(sb, wgi, warp4, lane, st, fph, e_cl, rb64, 4 * j, convCTA);
        gemm1_pass<3>(sb, wgi, warp4, lane, st, fph, e_cl, rb64, 32 + 3 * j, convCTA);

        if (convCTA) {
            const int m_lane = g + 2 * c + 16 * warp4;
            const int cp = (c + warp4) & 3, ish = (c + warp4) >> 2;
            const uint32_t rdst = sb + SM_RING + wgi * 32768 + warp4 * 8192 + ish * 512 + (g * 4 + cp) * 16;
            const uint32_t rsrc = sb + SM_RING + wgi * 32768 + warp4 * 2048 + lane * 16;
            const uint2 dd = ldg_nc64(p.ssm_D + 8 * cidx + 4 * wgi);
            const uint32_t hk0 = sb + SM_CVH + wgi * 16384 + (m_lane - 8) * 4;
            uint32_t a0[4][2][4], a1[4][2][4], a2[4][2][4];
            mbar_wait(sb + SM_BARS + B_CONV * 8, 0);
            conv_load_a<0, 4>(a0, hk0, m_lane);
            conv_load_a<4, 4>(a1, hk0, m_lane);
            if (wgi == 1) asm volatile("bar.arrive 4, 256;" ::: "memory");
            #pragma unroll 1
            for (int ch = 0; ch < 4; ch++) {
                const int gch = 8 * cidx + 4 * wgi + ch;
                const uint32_t dw = (ch & 2) ? dd.y : dd.x;
                const uint32_t d2 = __byte_perm(dw, dw, (ch & 1) ? 0x3232 : 0x1010);
                const uint32_t cbase = sb + SM_CVR + (4 * wgi + ch) * RB_CH;
                const uint64_t db = make_desc(cbase + RB_Z * 16, RB_R1, 128, 0);
                const uint32_t hk_lane = hk0 + ch * 4096;
                const uint32_t hk_next = hk0 + (ch < 3 ? ch + 1 : 3) * 4096;
                float acc[4][16];
                conv_load_a<8, 4>(a2, hk_lane, m_lane);
                named_bar(4 + wgi, 256);
                PROFW(32 + ch * 2, 4);
                conv_mma<0, 4>(acc, a0, db);
                conv_mma<4, 4>(acc, a1, db);
                conv_mma<8, 4>(acc, a2, db);
                wg_wait<2>();
                conv_load_a<12, 4>(a0, hk_lane, m_lane);
                conv_mma<12, 4>(acc, a0, db);
                if (wgi == 0 || ch < 3) asm volatile("bar.arrive %0, 256;" :: "r"(5 - wgi) : "memory");
                wg_wait<2>();
                conv_load_a<4, 4>(a1, hk_next, m_lane);
                wg_wait<0>();
                conv_load_a<0, 4>(a0, hk_next, m_lane);
                PROFW(33 + ch * 2, 4);
                if (ch == 0) mbar_wait(sb + SM_BARS + B_G1DONE * 8, 0);
                else named_bar(1 + wgi, 128);
                #pragma unroll
                for (int ii = 0; ii < 16; ii++) {
                    if (ii < 15 || ish == 0)
                        sts128(rdst + ii * 512, make_uint4(__float_as_uint(acc[ii >> 2][4 * (ii & 3)]), __float_as_uint(acc[ii >> 2][4 * (ii & 3) + 1]),
                                                           __float_as_uint(acc[ii >> 2][4 * (ii & 3) + 2]), __float_as_uint(acc[ii >> 2][4 * (ii & 3) + 3])));
                }
                named_bar(1 + wgi, 128);
                const uint32_t kvaddr = cbase + ((7 - g) & 1) * RB_R1 + (RB_Z + 32 * warp4 + 2 * c) * 16 + ((7 - g) >> 1) * 4;
                uint32_t* ydst = (uint32_t*)(g_yT + (size_t)gch * SEQ + 512 * warp4 + 32 * c + 2 * g);
                uint4 t[4][4]; uint32_t k0[4], k1[4];
                #pragma unroll
                for (int ii = 0; ii < 4; ii++) {
                    #pragma unroll
                    for (int ww = 0; ww < 4; ww++) t[ii][ww] = lds128(rsrc + ww * 8192 + ii * 512);
                    k0[ii] = lds32(kvaddr + ii * 128); k1[ii] = lds32(kvaddr + ii * 128 + 16);
                }
                #pragma unroll
                for (int ii = 0; ii < 4; ii++) {
                    float sx = __uint_as_float(t[ii][0].x), sy = __uint_as_float(t[ii][0].y), sz = __uint_as_float(t[ii][0].z), sw = __uint_as_float(t[ii][0].w);
                    #pragma unroll
                    for (int ww = 1; ww < 4; ww++) {
                        if (!(ii == 0 && warp4 == 0 && c < ww)) {
                            sx += __uint_as_float(t[ii][ww].x); sy += __uint_as_float(t[ii][ww].y); sz += __uint_as_float(t[ii][ww].z); sw += __uint_as_float(t[ii][ww].w);
                        }
                    }
                    ydst[ii * 64] = badd2(pack_bf(sz, sx), bmul2(__byte_perm(k0[ii], k0[ii], 0x1032), d2));
                    ydst[ii * 64 + 8] = badd2(pack_bf(sw, sy), bmul2(__byte_perm(k1[ii], k1[ii], 0x1032), d2));
                }
            }
            PROFW(44, 4);
            asm volatile("fence.proxy.async.global;" ::: "memory");
            __syncwarp();
            if (lane == 0) mbar_arrive(sb + SM_BARS + B_YST * 8);
        } else {
            float acc[64];
            const uint64_t descB0 = make_desc(sb, 4096, 1024, 1);
            const uint64_t descA0 = make_desc(sb + 16384 + wgi * 4096, 128, 256, 0);
            int sg = 3, p0 = 0; uint32_t ph = 6;
            PROFW(20, 0);
            #pragma unroll 1
            for (int u = 0; u < 28; u++) {
                if (warp == 0 && !(u & 1)) PROF2(2, 16 + (u >> 1));
                mbar_wait(sb + SM_BARS + (B_FULL + sg) * 8, (ph >> sg) & 1);
                ph ^= 1u << sg;
                if (warp == 0 && !(u & 1)) PROF2(1, 16 + (u >> 1));
                const uint32_t o0 = stage_off_rt(sg) >> 4;
                const uint64_t da0 = desc_add(descA0, o0), db0 = desc_add(descB0, o0);
                WG_FENCE();
                #pragma unroll
                for (int kk = 0; kk < 4; kk++) wgmma_ss_n128_tb(acc, da0 + ((kk >> 1) * 512 + (kk & 1) * 128), db0 + ((kk >> 1) * 512 + (kk & 1) * 128), (u | kk) ? 1 : 0);
                WG_COMMIT();
                wg_wait<1>();
                if (warp == 0 && !(u & 1)) PROF2(3, 16 + (u >> 1));
                if (lane < 2 && u > 0 && u + 4 < 28) mbar_arrive_cluster(e_cl + p0 * 8, 1);
                p0 = sg;
                sg = next_st2(sg);
            }
            wg_wait<0>();
            PROFW(27, 0);
            mbar_wait(sb + SM_BARS + B_XR * 8, 0);
            const int r0 = wgi * 64 + warp4 * 16 + g;
            const float2 st0 = lds64f(sb + SM_STATS + r0 * 8), st1 = lds64f(sb + SM_STATS + (r0 + 8) * 8);
            const uint32_t m0 = __float_as_uint(st0.x), m1 = __float_as_uint(st1.x);
            const uint32_t xrow0 = sb + SM_XE + r0 * 128 + c * 4;
            const int mi = lane >> 3, lr = lane & 7;
            const uint32_t yaddr = sb + SM_YT + wgi * 16384 + ((mi >> 1) * 8 + lr) * 128 + (((2 * warp4 + (mi & 1)) ^ lr) << 4);
            uint32_t y[8][4], xv[16][2], nv[16][2], bv[16][2];
            #pragma unroll
            for (int t = 0; t < 16; t++) {
                const uint32_t off = (t >> 3) * 16384 + (((t & 7) ^ g) << 4);
                xv[t][0] = lds32(xrow0 + off); xv[t][1] = lds32(xrow0 + 1024 + off);
            }
            #pragma unroll
            for (int t = 0; t < 16; t++) {
                const uint32_t d0 = bsub2(xv[t][0], m0), d1 = bsub2(xv[t][1], m1);
                nv[t][0] = pack_bf(bf_lo(d0) * st0.y, bf_hi(d0) * st0.y); nv[t][1] = pack_bf(bf_lo(d1) * st1.y, bf_hi(d1) * st1.y);
                bv[t][0] = pack_bf(acc[4 * t], acc[4 * t + 1]); bv[t][1] = pack_bf(acc[4 * t + 2], acc[4 * t + 3]);
            }
            mbar_wait(sb + SM_BARS + B_YT * 8, 0);
            PROFW(28, 0);
            #pragma unroll
            for (int t2 = 0; t2 < 8; t2++)
                asm volatile("ldmatrix.sync.aligned.m8n8.x4.trans.shared.b16 {%0,%1,%2,%3}, [%4];"
                    : "=r"(y[t2][0]), "=r"(y[t2][1]), "=r"(y[t2][2]), "=r"(y[t2][3]) : "r"(yaddr + t2 * 2048) : "memory");
            #pragma unroll
            for (int t = 0; t < 16; t++) {
                const uint32_t off = (t >> 3) * 16384 + (((t & 7) ^ g) << 4);
                sts32(xrow0 + off, badd2(badd2(xv[t][0], bmul2(nv[t][0], y[t >> 1][2 * (t & 1)])), bv[t][0]));
                sts32(xrow0 + 1024 + off, badd2(badd2(xv[t][1], bmul2(nv[t][1], y[t >> 1][2 * (t & 1) + 1])), bv[t][1]));
            }
            asm volatile("fence.proxy.async.shared::cta;" ::: "memory");
            named_bar(1 + wgi, 128);
            if ((tid & 127) == 0) {
                tma2d_store(&p.tm_out, 128 * cb, 128 * i + 64 * wgi, sb + SM_XE + wgi * 8192);
                tma2d_store(&p.tm_out, 128 * cb + 64, 128 * i + 64 * wgi, sb + SM_XE + 16384 + wgi * 8192);
                asm volatile("cp.async.bulk.commit_group;" ::: "memory");
                asm volatile("cp.async.bulk.wait_group.read 0;" ::: "memory");
                PROFW(29, 0);
            }
        }
    } else {
        asm volatile("setmaxnreg.dec.sync.aligned.u32 104;");
        if (warp == 8) {
            int st = 0; uint32_t eph = 7;
            #pragma unroll 1
            for (int it = 0; it < 16; it++) {
                const int pass = it >> 3, sl = it & 7;
                const int nb = pass ? 3 : 4;
                const CUtensorMap* tm = pass ? (rank ? &p.tm_uB : &p.tm_gB) : (rank ? &p.tm_uA : &p.tm_gA);
                mbar_wait(sb + SM_BARS + (B_EMPTY + st) * 8, (eph >> st) & 1);
                eph ^= 1u << st;
                if (it == 1) mbar_wait(sb + SM_BARS + (B_XFULL + 2) * 8, 0);
                PROF2(0, it);
                if (elect_one()) {
                    mbar_expect_tx(sb + SM_BARS + (B_FULL + st) * 8, nb * 8192);
                    tma3d_mc(sb + SM_RING + st * STAGE_BYTES + rank * nb * 4096, tm, 0, ((sl + 2 * cb + 2) & 7) * 64, 7 * j + 4 * pass, sb + SM_BARS + (B_FULL + st) * 8);
                }
                st = (st == 2) ? 0 : st + 1;
            }
            if (!convCTA) {
                st = 3;
                int f0 = 32 * rank, t3 = rank;
                #pragma unroll 1
                for (int u = 0; u < 28; u++) {
                    const uint32_t bar = sb + SM_BARS + (B_FULL + st) * 8;
                    mbar_wait(sb + SM_BARS + (B_EMPTY + st) * 8, (eph >> st) & 1);
                    eph ^= 1u << st;
                    if ((u & 1) == 0) PROF2(0, 16 + (u >> 1));
                    if (elect_one()) {
                        mbar_expect_tx(bar, 32768);
                        tma3d_mc(sb + stage_off_rt(st) + rank * 8192, &p.tm_w2, 0, f0, 2 * cb, bar);
                    }
                    st = next_st2(st);
                    if (u < 15) f0 += (u & 1) ? 160 : 64;
                    else if (u == 15) f0 = 128 + 32 * rank;
                    else { f0 += (t3 == 0) ? 64 : 192; t3 = (t3 == 0) ? 2 : t3 - 1; }
                }
                PROF(48);
            }
        } else if (warp < 11) {
            mbar_wait(sb + SM_BARS + (B_XFULL + 3) * 8, 0);
            #pragma unroll 1
            for (int rnd = 0; rnd < 2; rnd++) {
                const int tt = (tid - 288) + 64 * rnd;
                uint32_t sk[4][2];
                uint4 skw[2];
                skw[0] = ldg_nc128(p.shift_k + 16 * tt); skw[1] = ldg_nc128(p.shift_k + 16 * tt + 8);
                const __nv_bfloat16* kp = p.k + (size_t)(16 * b) * DM + 4 * tt;
                const __nv_bfloat16* vp = p.v + (size_t)(16 * b) * DM + 4 * tt;
                uint2 kr[19];
                uint2 kv[16];
                #pragma unroll
                for (int r = 0; r < 3; r++) kr[r] = (b > 0) ? ldg_nc64(kp + (r - 3) * DM) : make_uint2(0, 0);
                #pragma unroll
                for (int r = 0; r < 16; r++) { kr[3 + r] = ldg_nc64(kp + r * DM); if (r < 10) kv[r] = ldg_nc64(vp + r * DM); }
                {
                    const uint4 w0 = skw[0], w1 = skw[1];
                    sk[0][0] = __byte_perm(w0.x, w0.z, 0x5410); sk[1][0] = __byte_perm(w0.x, w0.z, 0x7632);
                    sk[2][0] = __byte_perm(w0.y, w0.w, 0x5410); sk[3][0] = __byte_perm(w0.y, w0.w, 0x7632);
                    sk[0][1] = __byte_perm(w1.x, w1.z, 0x5410); sk[1][1] = __byte_perm(w1.x, w1.z, 0x7632);
                    sk[2][1] = __byte_perm(w1.y, w1.w, 0x5410); sk[3][1] = __byte_perm(w1.y, w1.w, 0x7632);
                }
                #pragma unroll
                for (int s = 0; s < 16; s++) {
                    uint32_t a = bmul2(kr[s].x, sk[3][0]);
                    a = badd2(a, bmul2(kr[s + 1].x, sk[2][0]));
                    a = badd2(a, bmul2(kr[s + 2].x, sk[1][0]));
                    a = badd2(a, bmul2(kr[s + 3].x, sk[0][0]));
                    kv[s].x = bmul2(a, kv[s].x);
                    a = bmul2(kr[s].y, sk[3][1]);
                    a = badd2(a, bmul2(kr[s + 1].y, sk[2][1]));
                    a = badd2(a, bmul2(kr[s + 2].y, sk[1][1]));
                    a = badd2(a, bmul2(kr[s + 3].y, sk[0][1]));
                    kv[s].y = bmul2(a, kv[s].y);
                    if (s < 6) kv[10 + s] = ldg_nc64(vp + (10 + s) * DM);
                }
                PROFW(57 + 2 * rnd, 9);
                #pragma unroll
                for (int cc = 0; cc < 4; cc++) {
                    const uint32_t sel = (cc & 1) ? 0x7632 : 0x5410;
                    #define KVW(r) ((cc & 2) ? kv[r].y : kv[r].x)
                    uint8_t* dst = g_rb + (size_t)(4 * tt + cc) * RB_CH + (RB_Z + b) * 16;
                    *(uint4*)dst = make_uint4(__byte_perm(KVW(15), KVW(14), sel), __byte_perm(KVW(11), KVW(10), sel),
                                              __byte_perm(KVW(7), KVW(6), sel), __byte_perm(KVW(3), KVW(2), sel));
                    *(uint4*)(dst + RB_R1) = make_uint4(__byte_perm(KVW(13), KVW(12), sel), __byte_perm(KVW(9), KVW(8), sel),
                                                        __byte_perm(KVW(5), KVW(4), sel), __byte_perm(KVW(1), KVW(0), sel));
                    if (b < RB_Z) {
                        uint8_t* z = g_rb + (size_t)(4 * tt + cc) * RB_CH + b * 16;
                        *(uint4*)z = make_uint4(0, 0, 0, 0);
                        *(uint4*)(z + RB_R1) = make_uint4(0, 0, 0, 0);
                    }
                    #undef KVW
                }
                PROFW(58 + 2 * rnd, 9);
            }
            asm volatile("fence.proxy.async.global;" ::: "memory");
            __syncwarp();
            if (lane == 0) {
                flag_add(&g_cnt_kv[0]);
                PROFW(50, 9);
                const int wgi = warp - 9;
                mbar_wait(sb + SM_BARS + (B_HD + wgi * 2) * 8, 0);
                flag_add(&g_flag_h[(i * 2 + 0) * 8]);
                mbar_wait(sb + SM_BARS + (B_HD + wgi * 2 + 1) * 8, 0);
                flag_add(&g_flag_h[(i * 2 + 1) * 8]);
                if (wgi == 1 && convCTA) {
                    mbar_wait(sb + SM_BARS + B_YST * 8, 0);
                    flag_add(&g_cnt_y[(cidx >> 4) * 32]);
                    PROF(46);
                }
                if (wgi == 1 && !convCTA) {
                    const unsigned ep = lds32(sb + SM_EPOCH);
                    mbar_wait(sb + SM_BARS + B_G1DONE * 8, 0);
                    mbar_expect_tx(sb + SM_BARS + B_XR * 8, 32768);
                    for (int q = 0; q < 4; q++)
                        tma2d(sb + SM_XE + q * 8192, &p.tm_xe, 128 * cb + 64 * (q >> 1), 128 * i + 64 * (q & 1), sb + SM_BARS + B_XR * 8);
                    flag_wait(&g_flag_h[(i * 2 + 1) * 8], ep * 16);
                    mbar_arrive(sb + SM_BARS + (B_HRDY + 1) * 8);
                    __nanosleep(3000);
                    flag_wait(&g_cnt_y[cb * 32], ep * 16);
                    PROF(49);
                    asm volatile("fence.proxy.async.global;" ::: "memory");
                    mbar_expect_tx(sb + SM_BARS + B_YT * 8, 32768);
                    tma2d(sb + SM_YT, &p.tm_yT, 128 * i, 128 * cb, sb + SM_BARS + B_YT * 8);
                    tma2d(sb + SM_YT + 16384, &p.tm_yT, 128 * i + 64, 128 * cb, sb + SM_BARS + B_YT * 8);
                }
            }
        } else {
            if (lane == 0) {
                const unsigned ep = g_launch[b] + 1;
                g_launch[b] = ep;
                sts32(sb + SM_EPOCH, ep);
                tmap_prefetch(rank ? &p.tm_uA : &p.tm_gA);
                mbar_wait(sb + SM_BARS + (B_XFULL + 1) * 8, 0);
                l2_prefetch(p.wg + (size_t)b * (FF * DM / NCTA), FF * DM / NCTA * 2);
                l2_prefetch(p.wu + (size_t)b * (FF * DM / NCTA), FF * DM / NCTA * 2);
                tmap_prefetch(rank ? &p.tm_uB : &p.tm_gB);
                tmap_prefetch(&p.tm_w2); tmap_prefetch(&p.tm_yT); tmap_prefetch(&p.tm_out); tmap_prefetch(&p.tm_xe);
                mbar_wait(sb + SM_BARS + (B_FULL + 2) * 8, 0);
                l2_prefetch(p.ssm_k + (size_t)(4 * b) * SEQ, 4 * SEQ * 2);
                l2_prefetch(p.wd + (size_t)b * (FF * DM / NCTA), FF * DM / NCTA * 2);
                mbar_wait(sb + SM_BARS + (B_HD + 0) * 8, 0);
                if (convCTA) {
                    flag_wait(&g_cnt_kv[0], ep * 256);
                    asm volatile("fence.proxy.async.global;" ::: "memory");
                    PROF(53);
                    mbar_wait(sb + SM_BARS + B_XFREE * 8, 0);
                    PROF(54);
                    mbar_expect_tx(sb + SM_BARS + B_CONV * 8, 8 * RB_CH + 32768);
                    bulk_g2s(sb + SM_CVR, g_rb + (size_t)(8 * cidx) * RB_CH, 8 * RB_CH, sb + SM_BARS + B_CONV * 8);
                    bulk_g2s(sb + SM_CVH, p.ssm_k + (size_t)(8 * cidx) * SEQ, 32768, sb + SM_BARS + B_CONV * 8);
                } else {
                    flag_wait(&g_flag_h[(i * 2 + 0) * 8], ep * 16);
                }
            }
            __syncwarp();
            if (!convCTA) {
                asm volatile("fence.proxy.async.global;" ::: "memory");
                int st = 3; uint32_t eph = 1;
                const uint8_t* hsrc = (const uint8_t*)g_h + (size_t)i * 56 * 8192;
                #pragma unroll 1
                for (int u = 0; u < 28; u++) {
                    mbar_wait(sb + SM_BARS + (B_EMPTY + st) * 8, (eph >> st) & 1);
                    eph ^= 1u << st;
                    if (u == 16) {
                        mbar_wait(sb + SM_BARS + (B_HRDY + 1) * 8, 0);
                        asm volatile("fence.proxy.async.global;" ::: "memory");
                    }
                    if (elect_one()) bulk_g2s(sb + stage_off_rt(st) + 16384, hsrc + u * 16384, 16384, sb + SM_BARS + (B_FULL + st) * 8);
                    st = next_st2(st);
                }
            }
        }
    }
}

typedef CUresult (*EncodeFn)(CUtensorMap*, CUtensorMapDataType, cuuint32_t, void*, const cuuint64_t*, const cuuint64_t*,
                             const cuuint32_t*, const cuuint32_t*, CUtensorMapInterleave, CUtensorMapSwizzle,
                             CUtensorMapL2promotion, CUtensorMapFloatOOBfill);

void encode(EncodeFn fn, CUtensorMap* tm, const void* base, int rank, const cuuint64_t* dims, const cuuint64_t* strides,
            const cuuint32_t* box, CUtensorMapSwizzle swz) {
    cuuint32_t es[5] = {1, 1, 1, 1, 1};
    fn(tm, CU_TENSOR_MAP_DATA_TYPE_BFLOAT16, rank, (void*)base, dims, strides, box, es, CU_TENSOR_MAP_INTERLEAVE_NONE, swz,
       CU_TENSOR_MAP_L2_PROMOTION_L2_128B, CU_TENSOR_MAP_FLOAT_OOB_FILL_NONE);
}

}

extern "C" void kernel_launch(void* const* d_in, const int* in_sizes, int n_in, void* d_out, int out_size) {
    (void)in_sizes; (void)n_in; (void)out_size;
    static EncodeFn enc = nullptr;
    static void* yT_ptr = nullptr;
    if (!enc) {
        void* fn = nullptr; cudaDriverEntryPointQueryResult qr;
        cudaGetDriverEntryPoint("cuTensorMapEncodeTiled", &fn, cudaEnableDefault, &qr);
        enc = (EncodeFn)fn;
        cudaGetSymbolAddress(&yT_ptr, g_yT);
        cudaFuncSetAttribute(fused_kernel, cudaFuncAttributeMaxDynamicSharedMemorySize, SM_TOTAL);
    }
    Params p;
    p.q = (const __nv_bfloat16*)d_in[0]; p.k = (const __nv_bfloat16*)d_in[1]; p.v = (const __nv_bfloat16*)d_in[2];
    p.shift_k = (const __nv_bfloat16*)d_in[3]; p.ssm_k = (const __nv_bfloat16*)d_in[4]; p.ssm_D = (const __nv_bfloat16*)d_in[5];
    p.wg = (const __nv_bfloat16*)d_in[7]; p.wu = (const __nv_bfloat16*)d_in[8]; p.wd = (const __nv_bfloat16*)d_in[9];
    {
        cuuint64_t dims[2] = {DM, SEQ}; cuuint64_t str[1] = {DM * 2};
        cuuint32_t box[2] = {64, 32};
        encode(enc, &p.tm_x, p.q, 2, dims, str, box, CU_TENSOR_MAP_SWIZZLE_128B);
        cuuint32_t box2[2] = {64, 64};
        encode(enc, &p.tm_out, d_out, 2, dims, str, box2, CU_TENSOR_MAP_SWIZZLE_128B);
        encode(enc, &p.tm_xe, p.q, 2, dims, str, box2, CU_TENSOR_MAP_SWIZZLE_128B);
    }
    {
        cuuint64_t dims[3] = {32, DM, FF / 32}; cuuint64_t str[2] = {FF * 2, 64};
        cuuint32_t boxA[3] = {32, 64, 4}, boxB[3] = {32, 64, 3};
        encode(enc, &p.tm_gA, p.wg, 3, dims, str, boxA, CU_TENSOR_MAP_SWIZZLE_64B);
        encode(enc, &p.tm_gB, p.wg, 3, dims, str, boxB, CU_TENSOR_MAP_SWIZZLE_64B);
        encode(enc, &p.tm_uA, p.wu, 3, dims, str, boxA, CU_TENSOR_MAP_SWIZZLE_64B);
        encode(enc, &p.tm_uB, p.wu, 3, dims, str, boxB, CU_TENSOR_MAP_SWIZZLE_64B);
    }
    {
        cuuint64_t dims[3] = {64, FF, DM / 64}; cuuint64_t str[2] = {DM * 2, 128};
        cuuint32_t box[3] = {64, 32, 2};
        encode(enc, &p.tm_w2, p.wd, 3, dims, str, box, CU_TENSOR_MAP_SWIZZLE_128B);
    }
    {
        cuuint64_t dims[2] = {SEQ, DM}; cuuint64_t str[1] = {SEQ * 2};
        cuuint32_t box[2] = {64, 128};
        encode(enc, &p.tm_yT, yT_ptr, 2, dims, str, box, CU_TENSOR_MAP_SWIZZLE_128B);
    }
    fused_kernel<<<NCTA, NTHREADS, SM_TOTAL>>>(p);
}
```

```cpp
#include <cuda_runtime.h>
#include <cuda_bf16.h>
#include <cuda.h>
#include <stdint.h>

namespace {

constexpr int SEQ = 2048, DM = 512, FF = 1792;
constexpr int NCTA = 128;
constexpr int NTHREADS = 384;
constexpr int STAGE_BYTES = 32768;

constexpr uint32_t SM_X = 0;
constexpr uint32_t SM_RING = 131072;
constexpr uint32_t SM_MISC = SM_RING + 3 * STAGE_BYTES;
constexpr uint32_t SM_BARS = SM_MISC;
constexpr uint32_t SM_EPOCH = SM_MISC + 248;
constexpr uint32_t SM_STATS = SM_MISC + 256;
constexpr uint32_t SM_TOTAL = SM_STATS + 1024;
static_assert(SM_TOTAL <= 232448, "smem");
constexpr uint32_t SM_CVX = 0;
constexpr uint32_t SM_CVH = 32768;
constexpr uint32_t SM_YT = 4 * 16384;
constexpr uint32_t SM_XE = 6 * 16384;

constexpr int B_FULL = 0, B_EMPTY = 5, B_XFULL = 10, B_CONV = 14, B_YT = 15, B_XR = 16, B_G1DONE = 17, B_HD = 18, B_HRDY = 22,
              B_XFREE = 24, B_YST = 25, B_COUNT = 26;
static_assert(B_COUNT * 8 <= 248, "barrier space");

__device__ __align__(128) uint32_t g_h[16 * 56 * 2048];
__device__ __align__(128) __nv_bfloat16 g_kvT[DM * SEQ];
__device__ __align__(128) __nv_bfloat16 g_yT[DM * SEQ];
__device__ unsigned g_launch[NCTA];
__device__ unsigned g_cnt_kv[32];
__device__ unsigned g_cnt_y[4 * 32];
__device__ unsigned g_flag_h[16 * 2 * 8];

#define PROF(idx)
#define PROF2(a, idx)
#define PROFW(idx, w)

struct Params {
    CUtensorMap tm_x, tm_gA, tm_gB, tm_uA, tm_uB, tm_w2, tm_yT, tm_out, tm_xe;
    const __nv_bfloat16 *q, *k, *v, *shift_k, *ssm_k, *ssm_D, *wg, *wu, *wd;
};

__device__ __forceinline__ void wgmma_rs_n32(float (&d)[16], uint32_t a0, uint32_t a1, uint32_t a2, uint32_t a3, uint64_t db, int sc) {
  asm volatile("{\n.reg .pred p;\nsetp.ne.b32 p, %21, 0;\n"
    "wgmma.mma_async.sync.aligned.m64n32k16.f32.bf16.bf16 {%0,%1,%2,%3,%4,%5,%6,%7,%8,%9,%10,%11,%12,%13,%14,%15}, {%16,%17,%18,%19}, %20, p, 1, 1, 0;\n}\n"
    : "+f"(d[0]),"+f"(d[1]),"+f"(d[2]),"+f"(d[3]),"+f"(d[4]),"+f"(d[5]),"+f"(d[6]),"+f"(d[7]),"+f"(d[8]),"+f"(d[9]),"+f"(d[10]),"+f"(d[11]),"+f"(d[12]),"+f"(d[13]),"+f"(d[14]),"+f"(d[15])
    : "r"(a0),"r"(a1),"r"(a2),"r"(a3),"l"(db),"r"(sc));
}
__device__ __forceinline__ void wgmma_rs_n128_tb(float (&d)[64], uint32_t a0, uint32_t a1, uint32_t a2, uint32_t a3, uint64_t db, int sc) {
  asm volatile("{\n.reg .pred p;\nsetp.ne.b32 p, %69, 0;\n"
    "wgmma.mma_async.sync.aligned.m64n128k16.f32.bf16.bf16 {%0,%1,%2,%3,%4,%5,%6,%7,%8,%9,%10,%11,%12,%13,%14,%15,%16,%17,%18,%19,%20,%21,%22,%23,%24,%25,%26,%27,%28,%29,%30,%31,%32,%33,%34,%35,%36,%37,%38,%39,%40,%41,%42,%43,%44,%45,%46,%47,%48,%49,%50,%51,%52,%53,%54,%55,%56,%57,%58,%59,%60,%61,%62,%63}, {%64,%65,%66,%67}, %68, p, 1, 1, 1;\n}\n"
    : "+f"(d[0]),"+f"(d[1]),"+f"(d[2]),"+f"(d[3]),"+f"(d[4]),"+f"(d[5]),"+f"(d[6]),"+f"(d[7]),"+f"(d[8]),"+f"(d[9]),"+f"(d[10]),"+f"(d[11]),"+f"(d[12]),"+f"(d[13]),"+f"(d[14]),"+f"(d[15]),"+f"(d[16]),"+f"(d[17]),"+f"(d[18]),"+f"(d[19]),"+f"(d[20]),"+f"(d[21]),"+f"(d[22]),"+f"(d[23]),"+f"(d[24]),"+f"(d[25]),"+f"(d[26]),"+f"(d[27]),"+f"(d[28]),"+f"(d[29]),"+f"(d[30]),"+f"(d[31]),"+f"(d[32]),"+f"(d[33]),"+f"(d[34]),"+f"(d[35]),"+f"(d[36]),"+f"(d[37]),"+f"(d[38]),"+f"(d[39]),"+f"(d[40]),"+f"(d[41]),"+f"(d[42]),"+f"(d[43]),"+f"(d[44]),"+f"(d[45]),"+f"(d[46]),"+f"(d[47]),"+f"(d[48]),"+f"(d[49]),"+f"(d[50]),"+f"(d[51]),"+f"(d[52]),"+f"(d[53]),"+f"(d[54]),"+f"(d[55]),"+f"(d[56]),"+f"(d[57]),"+f"(d[58]),"+f"(d[59]),"+f"(d[60]),"+f"(d[61]),"+f"(d[62]),"+f"(d[63])
    : "r"(a0),"r"(a1),"r"(a2),"r"(a3),"l"(db),"r"(sc));
}
__device__ __forceinline__ void wgmma_ss_n256_tb(float (&d)[128], uint64_t da, uint64_t db, int sc) {
  asm volatile("{\n.reg .pred p;\nsetp.ne.b32 p, %130, 0;\n"
    "wgmma.mma_async.sync.aligned.m64n256k16.f32.bf16.bf16 {%0,%1,%2,%3,%4,%5,%6,%7,%8,%9,%10,%11,%12,%13,%14,%15,%16,%17,%18,%19,%20,%21,%22,%23,%24,%25,%26,%27,%28,%29,%30,%31,%32,%33,%34,%35,%36,%37,%38,%39,%40,%41,%42,%43,%44,%45,%46,%47,%48,%49,%50,%51,%52,%53,%54,%55,%56,%57,%58,%59,%60,%61,%62,%63,%64,%65,%66,%67,%68,%69,%70,%71,%72,%73,%74,%75,%76,%77,%78,%79,%80,%81,%82,%83,%84,%85,%86,%87,%88,%89,%90,%91,%92,%93,%94,%95,%96,%97,%98,%99,%100,%101,%102,%103,%104,%105,%106,%107,%108,%109,%110,%111,%112,%113,%114,%115,%116,%117,%118,%119,%120,%121,%122,%123,%124,%125,%126,%127}, %128, %129, p, 1, 1, 0, 1;\n}\n"
    : "+f"(d[0]),"+f"(d[1]),"+f"(d[2]),"+f"(d[3]),"+f"(d[4]),"+f"(d[5]),"+f"(d[6]),"+f"(d[7]),"+f"(d[8]),"+f"(d[9]),"+f"(d[10]),"+f"(d[11]),"+f"(d[12]),"+f"(d[13]),"+f"(d[14]),"+f"(d[15]),"+f"(d[16]),"+f"(d[17]),"+f"(d[18]),"+f"(d[19]),"+f"(d[20]),"+f"(d[21]),"+f"(d[22]),"+f"(d[23]),"+f"(d[24]),"+f"(d[25]),"+f"(d[26]),"+f"(d[27]),"+f"(d[28]),"+f"(d[29]),"+f"(d[30]),"+f"(d[31]),"+f"(d[32]),"+f"(d[33]),"+f"(d[34]),"+f"(d[35]),"+f"(d[36]),"+f"(d[37]),"+f"(d[38]),"+f"(d[39]),"+f"(d[40]),"+f"(d[41]),"+f"(d[42]),"+f"(d[43]),"+f"(d[44]),"+f"(d[45]),"+f"(d[46]),"+f"(d[47]),"+f"(d[48]),"+f"(d[49]),"+f"(d[50]),"+f"(d[51]),"+f"(d[52]),"+f"(d[53]),"+f"(d[54]),"+f"(d[55]),"+f"(d[56]),"+f"(d[57]),"+f"(d[58]),"+f"(d[59]),"+f"(d[60]),"+f"(d[61]),"+f"(d[62]),"+f"(d[63]),"+f"(d[64]),"+f"(d[65]),"+f"(d[66]),"+f"(d[67]),"+f"(d[68]),"+f"(d[69]),"+f"(d[70]),"+f"(d[71]),"+f"(d[72]),"+f"(d[73]),"+f"(d[74]),"+f"(d[75]),"+f"(d[76]),"+f"(d[77]),"+f"(d[78]),"+f"(d[79]),"+f"(d[80]),"+f"(d[81]),"+f"(d[82]),"+f"(d[83]),"+f"(d[84]),"+f"(d[85]),"+f"(d[86]),"+f"(d[87]),"+f"(d[88]),"+f"(d[89]),"+f"(d[90]),"+f"(d[91]),"+f"(d[92]),"+f"(d[93]),"+f"(d[94]),"+f"(d[95]),"+f"(d[96]),"+f"(d[97]),"+f"(d[98]),"+f"(d[99]),"+f"(d[100]),"+f"(d[101]),"+f"(d[102]),"+f"(d[103]),"+f"(d[104]),"+f"(d[105]),"+f"(d[106]),"+f"(d[107]),"+f"(d[108]),"+f"(d[109]),"+f"(d[110]),"+f"(d[111]),"+f"(d[112]),"+f"(d[113]),"+f"(d[114]),"+f"(d[115]),"+f"(d[116]),"+f"(d[117]),"+f"(d[118]),"+f"(d[119]),"+f"(d[120]),"+f"(d[121]),"+f"(d[122]),"+f"(d[123]),"+f"(d[124]),"+f"(d[125]),"+f"(d[126]),"+f"(d[127])
    : "l"(da),"l"(db),"r"(sc));
}
__device__ __forceinline__ void wgmma_ss_n192_tb(float (&d)[96], uint64_t da, uint64_t db, int sc) {
  asm volatile("{\n.reg .pred p;\nsetp.ne.b32 p, %98, 0;\n"
    "wgmma.mma_async.sync.aligned.m64n192k16.f32.bf16.bf16 {%0,%1,%2,%3,%4,%5,%6,%7,%8,%9,%10,%11,%12,%13,%14,%15,%16,%17,%18,%19,%20,%21,%22,%23,%24,%25,%26,%27,%28,%29,%30,%31,%32,%33,%34,%35,%36,%37,%38,%39,%40,%41,%42,%43,%44,%45,%46,%47,%48,%49,%50,%51,%52,%53,%54,%55,%56,%57,%58,%59,%60,%61,%62,%63,%64,%65,%66,%67,%68,%69,%70,%71,%72,%73,%74,%75,%76,%77,%78,%79,%80,%81,%82,%83,%84,%85,%86,%87,%88,%89,%90,%91,%92,%93,%94,%95}, %96, %97, p, 1, 1, 0, 1;\n}\n"
    : "+f"(d[0]),"+f"(d[1]),"+f"(d[2]),"+f"(d[3]),"+f"(d[4]),"+f"(d[5]),"+f"(d[6]),"+f"(d[7]),"+f"(d[8]),"+f"(d[9]),"+f"(d[10]),"+f"(d[11]),"+f"(d[12]),"+f"(d[13]),"+f"(d[14]),"+f"(d[15]),"+f"(d[16]),"+f"(d[17]),"+f"(d[18]),"+f"(d[19]),"+f"(d[20]),"+f"(d[21]),"+f"(d[22]),"+f"(d[23]),"+f"(d[24]),"+f"(d[25]),"+f"(d[26]),"+f"(d[27]),"+f"(d[28]),"+f"(d[29]),"+f"(d[30]),"+f"(d[31]),"+f"(d[32]),"+f"(d[33]),"+f"(d[34]),"+f"(d[35]),"+f"(d[36]),"+f"(d[37]),"+f"(d[38]),"+f"(d[39]),"+f"(d[40]),"+f"(d[41]),"+f"(d[42]),"+f"(d[43]),"+f"(d[44]),"+f"(d[45]),"+f"(d[46]),"+f"(d[47]),"+f"(d[48]),"+f"(d[49]),"+f"(d[50]),"+f"(d[51]),"+f"(d[52]),"+f"(d[53]),"+f"(d[54]),"+f"(d[55]),"+f"(d[56]),"+f"(d[57]),"+f"(d[58]),"+f"(d[59]),"+f"(d[60]),"+f"(d[61]),"+f"(d[62]),"+f"(d[63]),"+f"(d[64]),"+f"(d[65]),"+f"(d[66]),"+f"(d[67]),"+f"(d[68]),"+f"(d[69]),"+f"(d[70]),"+f"(d[71]),"+f"(d[72]),"+f"(d[73]),"+f"(d[74]),"+f"(d[75]),"+f"(d[76]),"+f"(d[77]),"+f"(d[78]),"+f"(d[79]),"+f"(d[80]),"+f"(d[81]),"+f"(d[82]),"+f"(d[83]),"+f"(d[84]),"+f"(d[85]),"+f"(d[86]),"+f"(d[87]),"+f"(d[88]),"+f"(d[89]),"+f"(d[90]),"+f"(d[91]),"+f"(d[92]),"+f"(d[93]),"+f"(d[94]),"+f"(d[95])
    : "l"(da),"l"(db),"r"(sc));
}

__device__ __forceinline__ uint32_t smem_u32(const void* p) { return (uint32_t)__cvta_generic_to_shared(p); }
__device__ __forceinline__ void mbar_init(uint32_t bar, uint32_t cnt) { asm volatile("mbarrier.init.shared::cta.b64 [%0], %1;" :: "r"(bar), "r"(cnt)); }
__device__ __forceinline__ void mbar_expect_tx(uint32_t bar, uint32_t bytes) { asm volatile("mbarrier.arrive.expect_tx.shared::cta.b64 _, [%0], %1;" :: "r"(bar), "r"(bytes) : "memory"); }
__device__ __forceinline__ void mbar_arrive(uint32_t bar) { asm volatile("mbarrier.arrive.shared::cta.b64 _, [%0];" :: "r"(bar) : "memory"); }
__device__ __forceinline__ void mbar_arrive_cluster(uint32_t cbar, uint32_t cnt) { asm volatile("mbarrier.arrive.shared::cluster.b64 _, [%0], %1;" :: "r"(cbar), "r"(cnt) : "memory"); }
__device__ __forceinline__ uint32_t mapa(uint32_t a, uint32_t rank) { uint32_t r; asm volatile("mapa.shared::cluster.u32 %0, %1, %2;" : "=r"(r) : "r"(a), "r"(rank)); return r; }
__device__ __forceinline__ void mbar_wait(uint32_t bar, uint32_t parity) {
    uint32_t ok; uint32_t n = 0;
    do {
        asm volatile("{\n.reg .pred p;\nmbarrier.try_wait.parity.shared::cta.b64 p, [%1], %2;\nselp.u32 %0, 1, 0, p;\n}" : "=r"(ok) : "r"(bar), "r"(parity) : "memory");
    } while (!ok && ++n < (1u << 17));
}
__device__ __forceinline__ void pace_wait(uint32_t a, uint32_t target) {
    uint32_t v, n = 0;
    do {
        asm volatile("ld.volatile.shared.u32 %0, [%1];" : "=r"(v) : "r"(a) : "memory");
        if (v < target) __nanosleep(150);
    } while (v < target && ++n < (1u << 14));
}
__device__ __forceinline__ void flag_wait(const unsigned* p, unsigned target) {
    unsigned v; uint32_t n = 0;
    while (true) {
        asm volatile("ld.acquire.gpu.global.u32 %0, [%1];" : "=r"(v) : "l"(p) : "memory");
        if ((int)(v - target) >= 0 || ++n >= (1u << 17)) break;
        __nanosleep(100);
    }
}
__device__ __forceinline__ void flag_add(unsigned* p) {
    asm volatile("fence.acq_rel.gpu;\nred.relaxed.gpu.global.add.u32 [%0], 1;" :: "l"(p) : "memory");
}
__device__ __forceinline__ uint64_t make_desc(uint32_t addr, uint32_t lbo, uint32_t sbo, uint32_t swz) {
    return (uint64_t)((addr & 0x3FFFF) >> 4) | ((uint64_t)((lbo & 0x3FFFF) >> 4) << 16) | ((uint64_t)((sbo & 0x3FFFF) >> 4) << 32) | ((uint64_t)swz << 62);
}
__device__ __forceinline__ uint64_t desc_add(uint64_t d, uint32_t off16) {
    return (d & 0xFFFFFFFF00000000ull) | (uint64_t)((uint32_t)d + off16);
}
__device__ __forceinline__ void tma2d(uint32_t dst, const CUtensorMap* tm, int c0, int c1, uint32_t bar) {
    asm volatile("cp.async.bulk.tensor.2d.shared::cluster.global.mbarrier::complete_tx::bytes [%0], [%1, {%3, %4}], [%2];"
        :: "r"(dst), "l"((uint64_t)tm), "r"(bar), "r"(c0), "r"(c1) : "memory");
}
__device__ __forceinline__ void tma3d_mc(uint32_t dst, const CUtensorMap* tm, int c0, int c1, int c2, uint32_t bar) {
    asm volatile("cp.async.bulk.tensor.3d.shared::cluster.global.mbarrier::complete_tx::bytes.multicast::cluster [%0], [%1, {%3, %4, %5}], [%2], %6;"
        :: "r"(dst), "l"((uint64_t)tm), "r"(bar), "r"(c0), "r"(c1), "r"(c2), "h"((uint16_t)3) : "memory");
}
__device__ __forceinline__ void bulk_g2s(uint32_t dst, const void* src, uint32_t bytes, uint32_t bar) {
    asm volatile("cp.async.bulk.shared::cluster.global.mbarrier::complete_tx::bytes [%0], [%1], %2, [%3];"
        :: "r"(dst), "l"(src), "r"(bytes), "r"(bar) : "memory");
}
__device__ __forceinline__ void bulk_s2g(void* dst, uint32_t src, uint32_t bytes) {
    asm volatile("cp.async.bulk.global.shared::cta.bulk_group [%0], [%1], %2;" :: "l"(dst), "r"(src), "r"(bytes) : "memory");
}
__device__ __forceinline__ void tma2d_store(const CUtensorMap* tm, int c0, int c1, uint32_t src) {
    asm volatile("cp.async.bulk.tensor.2d.global.shared::cta.bulk_group [%0, {%2, %3}], [%1];"
        :: "l"((uint64_t)tm), "r"(src), "r"(c0), "r"(c1) : "memory");
}
__device__ __forceinline__ void l2_prefetch(const void* p, uint32_t bytes) {
    asm volatile("cp.async.bulk.prefetch.L2.global [%0], %1;" :: "l"(p), "r"(bytes) : "memory");
}
__device__ __forceinline__ void tmap_prefetch(const CUtensorMap* tm) { asm volatile("prefetch.tensormap [%0];" :: "l"((uint64_t)tm) : "memory"); }
__device__ __forceinline__ uint32_t lds32(uint32_t a) { uint32_t v; asm volatile("ld.shared.u32 %0, [%1];" : "=r"(v) : "r"(a)); return v; }
__device__ __forceinline__ uint2 lds64(uint32_t a) { uint2 v; asm volatile("ld.shared.v2.u32 {%0,%1}, [%2];" : "=r"(v.x), "=r"(v.y) : "r"(a)); return v; }
__device__ __forceinline__ uint4 lds128(uint32_t a) { uint4 v; asm volatile("ld.shared.v4.u32 {%0,%1,%2,%3}, [%4];" : "=r"(v.x), "=r"(v.y), "=r"(v.z), "=r"(v.w) : "r"(a)); return v; }
__device__ __forceinline__ float2 lds64f(uint32_t a) { float2 v; asm volatile("ld.shared.v2.f32 {%0,%1}, [%2];" : "=f"(v.x), "=f"(v.y) : "r"(a)); return v; }
__device__ __forceinline__ void sts32(uint32_t a, uint32_t v) { asm volatile("st.shared.u32 [%0], %1;" :: "r"(a), "r"(v) : "memory"); }
__device__ __forceinline__ void sts128(uint32_t a, uint4 v) { asm volatile("st.shared.v4.u32 [%0], {%1,%2,%3,%4};" :: "r"(a), "r"(v.x), "r"(v.y), "r"(v.z), "r"(v.w) : "memory"); }
__device__ __forceinline__ uint4 ldg_cg128(const void* p) { uint4 v; asm volatile("ld.global.cg.v4.u32 {%0,%1,%2,%3}, [%4];" : "=r"(v.x), "=r"(v.y), "=r"(v.z), "=r"(v.w) : "l"(p)); return v; }
__device__ __forceinline__ uint4 ldg_nc128(const void* p) { uint4 v; asm volatile("ld.global.nc.L1::no_allocate.v4.u32 {%0,%1,%2,%3}, [%4];" : "=r"(v.x), "=r"(v.y), "=r"(v.z), "=r"(v.w) : "l"(p)); return v; }
__device__ __forceinline__ uint2 ldg_nc64(const void* p) { uint2 v; asm volatile("ld.global.nc.L1::no_allocate.v2.u32 {%0,%1}, [%2];" : "=r"(v.x), "=r"(v.y) : "l"(p)); return v; }
#define WG_FENCE() asm volatile("wgmma.fence.sync.aligned;\n" ::: "memory")
#define WG_COMMIT() asm volatile("wgmma.commit_group.sync.aligned;\n" ::: "memory")
template<int N> __device__ __forceinline__ void wg_wait() { asm volatile("wgmma.wait_group.sync.aligned %0;\n" :: "n"(N) : "memory"); }
__device__ __forceinline__ bool elect_one() {
    uint32_t pr;
    asm volatile("{\n.reg .pred p;\nelect.sync _|p, 0xffffffff;\nselp.u32 %0, 1, 0, p;\n}" : "=r"(pr));
    return pr != 0;
}
__device__ __forceinline__ void named_bar(int id, int n) { asm volatile("bar.sync %0, %1;" :: "r"(id), "r"(n) : "memory"); }

__device__ __forceinline__ float bf_lo(uint32_t u) { return __uint_as_float(u << 16); }
__device__ __forceinline__ float bf_hi(uint32_t u) { return __uint_as_float(u & 0xFFFF0000u); }
__device__ __forceinline__ uint32_t pack_bf(float lo, float hi) { uint32_t r; asm("cvt.rn.bf16x2.f32 %0, %1, %2;" : "=r"(r) : "f"(hi), "f"(lo)); return r; }
__device__ __forceinline__ float bf_round(float x) { return __bfloat162float(__float2bfloat16_rn(x)); }
__device__ __forceinline__ uint32_t bmul2(uint32_t a, uint32_t b) { uint32_t r; asm("mul.rn.bf16x2 %0, %1, %2;" : "=r"(r) : "r"(a), "r"(b)); return r; }
__device__ __forceinline__ uint32_t badd2(uint32_t a, uint32_t b) { uint32_t r; asm("add.rn.bf16x2 %0, %1, %2;" : "=r"(r) : "r"(a), "r"(b)); return r; }
__device__ __forceinline__ uint32_t bsub2(uint32_t a, uint32_t b) { uint32_t r; asm("sub.rn.bf16x2 %0, %1, %2;" : "=r"(r) : "r"(a), "r"(b)); return r; }
__device__ __forceinline__ void mma16816(float (&d)[4], uint32_t a0, uint32_t a1, uint32_t a2, uint32_t a3, uint2 b) {
    asm volatile("mma.sync.aligned.m16n8k16.row.col.f32.bf16.bf16.f32 {%0,%1,%2,%3}, {%4,%5,%6,%7}, {%8,%9}, {%0,%1,%2,%3};\n"
        : "+f"(d[0]), "+f"(d[1]), "+f"(d[2]), "+f"(d[3]) : "r"(a0), "r"(a1), "r"(a2), "r"(a3), "r"(b.x), "r"(b.y));
}

template<int HS> __device__ __forceinline__ void xreduce(float (&v)[32], int lane) {
    const int up = lane & HS;
    #pragma unroll
    for (int e = 0; e < HS; e++) {
        float keep, send;
        asm("{\n.reg .pred p;\nsetp.ne.b32 p, %4, 0;\nselp.f32 %0, %3, %2, p;\nselp.f32 %1, %2, %3, p;\n}"
            : "=f"(keep), "=f"(send) : "f"(v[e]), "f"(v[e + HS]), "r"(up));
        v[e] = keep + __shfl_xor_sync(0xffffffffu, send, HS);
    }
}

__device__ __forceinline__ int blk_f0(int bi, int j) {
    if (bi < 32) return 224 * ((j + (bi >> 2)) & 7) + 32 * (bi & 3);
    int b2 = bi - 32; int q3 = (b2 * 11) >> 5;
    return 224 * ((j + q3) & 7) + 128 + 32 * (b2 - 3 * q3);
}
__device__ __forceinline__ int next_st2(int s) { return (0x14023 >> (4 * s)) & 7; }
__device__ __forceinline__ uint32_t stage_off_rt(int s) { return s < 3 ? SM_RING + s * STAGE_BYTES : (uint32_t)(s - 3) * STAGE_BYTES; }

template<int NB>
__device__ __forceinline__ void gemm1_pass(uint32_t sb, int wgi, int warp4, int lane, int& st, uint32_t& fph, uint32_t e_cl,
                                           int rb64, int ks0, bool convCTA) {
    constexpr bool passA = (NB == 4);
    float acc[NB * 32];
    const uint64_t descA0 = make_desc(sb + SM_X + wgi * 8192, 16, 1024, 1);
    const uint64_t descB0 = make_desc(sb + SM_RING, 4096, 512, 2);
    int prev = 0;
    #pragma unroll 1
    for (int sl = 0; sl < 8; sl++) {
        if (warp4 == 0 && wgi == 0) PROF2(2, sl + (passA ? 0 : 8));
        mbar_wait(sb + SM_BARS + (B_FULL + st) * 8, (fph >> st) & 1);
        fph ^= 1u << st;
        if (sl == 0 && warp4 == 0) PROF(2 + wgi * 8 + (passA ? 0 : 3));
        if (warp4 == 0 && wgi == 0) PROF2(1, sl + (passA ? 0 : 8));
        const uint64_t da = desc_add(descA0, sl * 1024), db = desc_add(descB0, st * 2048);
        WG_FENCE();
        #pragma unroll
        for (int kk = 0; kk < 4; kk++) {
            int sc = (sl | kk) ? 1 : 0;
            if constexpr (NB == 4) wgmma_ss_n256_tb(acc, da + kk * 2, db + kk * 64, sc); else wgmma_ss_n192_tb(acc, da + kk * 2, db + kk * 64, sc);
        }
        WG_COMMIT();
        wg_wait<1>();
        if (warp4 == 0 && wgi == 0) PROF2(3, sl + (passA ? 0 : 8));
        if (lane < 2 && sl && (passA || !convCTA || sl < 6)) mbar_arrive_cluster(e_cl + prev * 8, 1);
        if (!passA) {
            if (convCTA) { if (sl == 4 && lane == 0) mbar_arrive(sb + SM_BARS + B_XFREE * 8); }
            else if ((sl == 2 || sl == 4) && lane < 2) mbar_arrive_cluster(e_cl + (2 + (sl >> 1)) * 8, 1);
        }
        prev = st;
        st = (st == 2) ? 0 : st + 1;
    }
    wg_wait<0>();
    if (lane < 2 && (passA || !convCTA)) mbar_arrive_cluster(e_cl + prev * 8, 1);
    if (!passA && lane == 0) mbar_arrive(sb + SM_BARS + B_G1DONE * 8);
    if (warp4 == 0) PROF(3 + wgi * 8 + (passA ? 0 : 3));
    const int g = lane >> 2;
    const int r0 = wgi * 64 + warp4 * 16 + g;
    const float s0 = __uint_as_float(lds32(sb + SM_STATS + r0 * 8 + 4)), s1 = __uint_as_float(lds32(sb + SM_STATS + (r0 + 8) * 8 + 4));
    uint32_t* dst = g_h + (size_t)((rb64 >> 1) * 56 + ks0) * 2048 + wgi * 1024 + warp4 * 128 + lane;
    #pragma unroll
    for (int kk = 0; kk < NB * 2; kk++) {
        uint32_t h[4];
        #pragma unroll
        for (int tt = 0; tt < 2; tt++) {
            const int t = 2 * kk + tt;
            const float* ag = &acc[4 * t];
            const float* au = &acc[NB * 16 + 4 * t];
            h[2 * tt] = bmul2(pack_bf(ag[0] * s0, ag[1] * s0), pack_bf(au[0] * s0, au[1] * s0));
            h[2 * tt + 1] = bmul2(pack_bf(ag[2] * s1, ag[3] * s1), pack_bf(au[2] * s1, au[3] * s1));
        }
        uint32_t* d2 = dst + (kk >> 1) * 2048 + (kk & 1) * 512;
        d2[0] = h[0]; d2[64] = h[1]; d2[32] = h[2]; d2[96] = h[3];
    }
    asm volatile("fence.proxy.async.global;" ::: "memory");
    __syncwarp();
    if (lane == 0) mbar_arrive(sb + SM_BARS + (B_HD + wgi * 2 + (passA ? 0 : 1)) * 8);
    if (warp4 == 0) PROF(4 + wgi * 8 + (passA ? 0 : 3));
}

__global__ void __cluster_dims__(2, 1, 1) __launch_bounds__(NTHREADS, 1)
fused_kernel(const __grid_constant__ Params p) {
    extern __shared__ __align__(1024) uint8_t smem_raw[];
    const uint32_t sb = smem_u32(smem_raw);
    const int tid = threadIdx.x, warp = tid >> 5, lane = tid & 31;
    const int b = blockIdx.x;
    const int rank = b & 1;
    const int j = (b >> 1) & 7;
    const int i = ((b >> 4) << 1) | rank;
    const int cb = j >> 1;
    const bool convCTA = j & 1;
    const int cidx = 4 * i + cb;

    if (warp == 8 && lane < 4) {
        mbar_init(sb + SM_BARS + (B_XFULL + lane) * 8, 1);
        asm volatile("fence.proxy.async.shared::cta;" ::: "memory");
        mbar_expect_tx(sb + SM_BARS + (B_XFULL + lane) * 8, 32768);
    }
    if (tid == 288) {
        for (int s = 0; s < 5; s++) { mbar_init(sb + SM_BARS + (B_FULL + s) * 8, 1); mbar_init(sb + SM_BARS + (B_EMPTY + s) * 8, 16); }
        mbar_init(sb + SM_BARS + B_CONV * 8, 1);
        mbar_init(sb + SM_BARS + B_YT * 8, 1);
        mbar_init(sb + SM_BARS + B_XR * 8, 1);
        mbar_init(sb + SM_BARS + B_G1DONE * 8, 8);
        mbar_init(sb + SM_BARS + B_XFREE * 8, 8);
        mbar_init(sb + SM_BARS + B_YST * 8, 8);
        for (int s = 0; s < 4; s++) mbar_init(sb + SM_BARS + (B_HD + s) * 8, 4);
        for (int s = 0; s < 2; s++) mbar_init(sb + SM_BARS + (B_HRDY + s) * 8, 1);
        asm volatile("fence.mbarrier_init.release.cluster;" ::: "memory");
        asm volatile("fence.proxy.async.shared::cta;" ::: "memory");
    }
    __syncwarp();
    asm volatile("barrier.cluster.arrive.relaxed.aligned;\n" ::: "memory");
    if (warp == 8) {
        const int rg = lane >> 3, sl = lane & 7;
        tma2d(sb + SM_X + sl * 16384 + rg * 4096, &p.tm_x, 64 * ((sl + 2 * cb + 2) & 7), 128 * i + 32 * rg, sb + SM_BARS + (B_XFULL + rg) * 8);
        __syncwarp();
    }
    asm volatile("barrier.cluster.wait.aligned;\n" ::: "memory");
    PROFW(1, 0);

    if (warp < 8) {
        asm volatile("setmaxnreg.inc.sync.aligned.u32 200;");
        const int wgi = warp >> 2, warp4 = warp & 3;
        const int g = lane >> 2, c = lane & 3;
        const uint32_t e_cl = mapa(sb + SM_BARS + B_EMPTY * 8, lane & 1);
        {
            const uint32_t xa = sb + SM_X + (lane >> 3) * 16384 + warp * 16 * 128;
            uint4 xr[16][2];
            float v[32];
            mbar_wait(sb + SM_BARS + (B_XFULL + (warp >> 1)) * 8, 0);
            PROFW(16, 0); PROFW(18, 7);
            #pragma unroll
            for (int r = 0; r < 16; r++) {
                const uint32_t a = xa + r * 128 + (((lane & 7) ^ (r & 7)) << 4);
                xr[r][0] = lds128(a); xr[r][1] = lds128(a + 65536);
            }
            #pragma unroll
            for (int r = 0; r < 16; r++) {
                const uint32_t* u = (const uint32_t*)&xr[r][0];
                float s = 0.f, q = 0.f;
                #pragma unroll
                for (int e = 0; e < 8; e++) { const float lo = bf_lo(u[e]), hi = bf_hi(u[e]); s += lo; q = fmaf(lo, lo, q); s += hi; q = fmaf(hi, hi, q); }
                v[r] = s; v[16 + r] = q;
            }
            xreduce<16>(v, lane); xreduce<8>(v, lane); xreduce<4>(v, lane); xreduce<2>(v, lane); xreduce<1>(v, lane);
            const float other = __shfl_xor_sync(0xffffffffu, v[0], 16);
            const float mean = (lane < 16 ? v[0] : other) * (1.0f / DM);
            const float msq = (lane < 16 ? other : v[0]) * (1.0f / DM);
            const float var_b = bf_round(fmaxf(msq - mean * mean, 0.f));
            const float sd = bf_round(sqrtf(bf_round(var_b + 1e-5f)));
            const uint32_t mb = pack_bf(mean, mean);
            if (lane < 16) { sts32(sb + SM_STATS + (warp * 16 + lane) * 8, mb); sts32(sb + SM_STATS + (warp * 16 + lane) * 8 + 4, __float_as_uint(1.0f / sd)); }
            #pragma unroll
            for (int r = 0; r < 16; r++) {
                const uint32_t m = __shfl_sync(0xffffffffu, mb, r);
                const uint32_t a = xa + r * 128 + (((lane & 7) ^ (r & 7)) << 4);
                #pragma unroll
                for (int hh = 0; hh < 2; hh++) {
                    uint4 t = xr[r][hh];
                    t.x = bsub2(t.x, m); t.y = bsub2(t.y, m); t.z = bsub2(t.z, m); t.w = bsub2(t.w, m);
                    sts128(a + hh * 65536, t);
                }
            }
            asm volatile("fence.proxy.async.shared::cta;" ::: "memory");
            named_bar(1 + wgi, 128);
            PROFW(17, 0); PROFW(19, 7);
        }
        int st = 0; uint32_t fph = 0;
        const int rb64 = 2 * i + wgi;
        gemm1_pass<4>(sb, wgi, warp4, lane, st, fph, e_cl, rb64, 4 * j, convCTA);
        gemm1_pass<3>(sb, wgi, warp4, lane, st, fph, e_cl, rb64, 32 + 3 * j, convCTA);

        if (convCTA) {
            const int gch = 8 * cidx + warp;
            const uint32_t xb = sb + SM_CVX + warp * 4096;
            const uint32_t hb = sb + SM_CVH + warp * 4096;
            const uint32_t dw = ((const unsigned short*)p.ssm_D)[gch];
            const uint32_t d2 = dw | (dw << 16);
            mbar_wait(sb + SM_BARS + B_CONV * 8, 0);
            PROFW(32, 4);
            float acc[16][4];
            #pragma unroll
            for (int jj = 0; jj < 16; jj++) { acc[jj][0] = 0.f; acc[jj][1] = 0.f; acc[jj][2] = 0.f; acc[jj][3] = 0.f; }
            uint2 bh[8], bl0[8], bl1[8];
            uint32_t xl = xb + g * 32 + c * 8;
            uint32_t hl = hb + (g + 2 * c - 8) * 4;
            #pragma unroll
            for (int d = 0; d < 8; d++) { bl0[d] = lds64(xl + d * 256); bh[d] = lds64(xl + (8 + d) * 256); }
            uint32_t w[6];
            w[0] = 0; w[1] = 0; w[2] = 0;
            if (g + 2 * c >= 8) w[0] = lds32(hl);
            if (g + 2 * c >= 7) w[1] = lds32(hl + 4);
            if (g + 2 * c >= 6) w[2] = lds32(hl + 8);
            w[3] = lds32(hl + 2048); w[4] = lds32(hl + 2052); w[5] = lds32(hl + 2056);
            auto conv_m0 = [&](int m0, uint2 (&bl)[8], uint2 (&bn)[8]) {
                xl -= 32;
                #pragma unroll
                for (int k = 0; k < 8; k++) {
                    const uint32_t a0 = w[1], a1 = __byte_perm(w[0], w[1], 0x5432), a2 = w[2], a3 = __byte_perm(w[1], w[2], 0x5432);
                    const uint32_t c0 = w[4], c1 = __byte_perm(w[3], w[4], 0x5432), c2 = w[5], c3 = __byte_perm(w[4], w[5], 0x5432);
                    const uint32_t nx = (k < 7) ? hl + (k + 1) * 256 : hl + 32;
                    w[0] = lds32(nx); w[1] = lds32(nx + 4); w[2] = lds32(nx + 8);
                    w[3] = lds32(nx + 2048); w[4] = lds32(nx + 2052); w[5] = lds32(nx + 2056);
                    if (k > 0) bn[k] = lds64(xl + k * 256);
                    else { bn[0] = make_uint2(0, 0); if (g > m0) bn[0] = lds64(xl); }
                    #pragma unroll
                    for (int jj = k; jj < 16; jj++) mma16816(acc[jj], a0, a1, a2, a3, (jj - k < 8) ? bl[(jj - k) & 7] : bh[(jj - k) & 7]);
                    bh[7 - k] = lds64(xl + (15 - k) * 256);
                    #pragma unroll
                    for (int jj = k + 8; jj < 16; jj++) mma16816(acc[jj], c0, c1, c2, c3, bl[jj - k - 8]);
                }
                hl += 32;
            };
            #pragma unroll 1
            for (int m0 = 0; m0 < 8; m0 += 2) {
                conv_m0(m0, bl0, bl1);
                conv_m0(m0 + 1, bl1, bl0);
                PROFW(34 + (m0 >> 1), 4);
            }
            PROFW(33, 4);
            const uint32_t kvl = xb + c * 64 + (7 - g) * 4;
            uint32_t* ydst = (uint32_t*)(g_yT + (size_t)gch * SEQ + 32 * c + 2 * g);
            uint32_t kk0[16], kk1[16];
            #pragma unroll
            for (int jj = 0; jj < 16; jj++) { kk0[jj] = lds32(kvl + jj * 256); kk1[jj] = lds32(kvl + jj * 256 + 32); }
            #pragma unroll
            for (int jj = 0; jj < 16; jj++) {
                ydst[jj * 64] = badd2(pack_bf(acc[jj][2], acc[jj][0]), bmul2(__byte_perm(kk0[jj], kk0[jj], 0x1032), d2));
                ydst[jj * 64 + 8] = badd2(pack_bf(acc[jj][3], acc[jj][1]), bmul2(__byte_perm(kk1[jj], kk1[jj], 0x1032), d2));
            }
            asm volatile("fence.proxy.async.global;" ::: "memory");
            __syncwarp();
            PROFW(44, 4);
            if (lane == 0) mbar_arrive(sb + SM_BARS + B_YST * 8);
        } else {
            float acc[64];
            const uint64_t descB0 = make_desc(sb, 4096, 1024, 1);
            const uint64_t descA0 = make_desc(sb + 16384 + wgi * 4096, 128, 256, 0);
            int sg = 3, p0 = 0; uint32_t ph = 6;
            PROFW(20, 0);
            #pragma unroll 1
            for (int u = 0; u < 28; u++) {
                if (warp == 0 && !(u & 1)) PROF2(2, 16 + (u >> 1));
                mbar_wait(sb + SM_BARS + (B_FULL + sg) * 8, (ph >> sg) & 1);
                ph ^= 1u << sg;
                if (warp == 0 && !(u & 1)) PROF2(1, 16 + (u >> 1));
                const uint32_t o0 = stage_off_rt(sg) >> 4;
                const uint64_t da0 = desc_add(descA0, o0), db0 = desc_add(descB0, o0);
                WG_FENCE();
                #pragma unroll
                for (int kk = 0; kk < 4; kk++) wgmma_ss_n128_tb(acc, da0 + ((kk >> 1) * 512 + (kk & 1) * 128), db0 + ((kk >> 1) * 512 + (kk & 1) * 128), (u | kk) ? 1 : 0);
                WG_COMMIT();
                wg_wait<1>();
                if (warp == 0 && !(u & 1)) PROF2(3, 16 + (u >> 1));
                if (lane < 2 && u > 0 && u + 4 < 28) mbar_arrive_cluster(e_cl + p0 * 8, 1);
                p0 = sg;
                sg = next_st2(sg);
            }
            wg_wait<0>();
            PROFW(27, 0);
            mbar_wait(sb + SM_BARS + B_XR * 8, 0);
            const int r0 = wgi * 64 + warp4 * 16 + g;
            const float2 st0 = lds64f(sb + SM_STATS + r0 * 8), st1 = lds64f(sb + SM_STATS + (r0 + 8) * 8);
            const uint32_t m0 = __float_as_uint(st0.x), m1 = __float_as_uint(st1.x);
            const uint32_t xrow0 = sb + SM_XE + r0 * 128 + c * 4;
            const int mi = lane >> 3, lr = lane & 7;
            const uint32_t yaddr = sb + SM_YT + wgi * 16384 + ((mi >> 1) * 8 + lr) * 128 + (((2 * warp4 + (mi & 1)) ^ lr) << 4);
            uint32_t y[8][4], xv[16][2], nv[16][2], bv[16][2];
            #pragma unroll
            for (int t = 0; t < 16; t++) {
                const uint32_t off = (t >> 3) * 16384 + (((t & 7) ^ g) << 4);
                xv[t][0] = lds32(xrow0 + off); xv[t][1] = lds32(xrow0 + 1024 + off);
            }
            #pragma unroll
            for (int t = 0; t < 16; t++) {
                const uint32_t d0 = bsub2(xv[t][0], m0), d1 = bsub2(xv[t][1], m1);
                nv[t][0] = pack_bf(bf_lo(d0) * st0.y, bf_hi(d0) * st0.y); nv[t][1] = pack_bf(bf_lo(d1) * st1.y, bf_hi(d1) * st1.y);
                bv[t][0] = pack_bf(acc[4 * t], acc[4 * t + 1]); bv[t][1] = pack_bf(acc[4 * t + 2], acc[4 * t + 3]);
            }
            mbar_wait(sb + SM_BARS + B_YT * 8, 0);
            PROFW(28, 0);
            #pragma unroll
            for (int t2 = 0; t2 < 8; t2++)
                asm volatile("ldmatrix.sync.aligned.m8n8.x4.trans.shared.b16 {%0,%1,%2,%3}, [%4];"
                    : "=r"(y[t2][0]), "=r"(y[t2][1]), "=r"(y[t2][2]), "=r"(y[t2][3]) : "r"(yaddr + t2 * 2048) : "memory");
            #pragma unroll
            for (int t = 0; t < 16; t++) {
                const uint32_t off = (t >> 3) * 16384 + (((t & 7) ^ g) << 4);
                sts32(xrow0 + off, badd2(badd2(xv[t][0], bmul2(nv[t][0], y[t >> 1][2 * (t & 1)])), bv[t][0]));
                sts32(xrow0 + 1024 + off, badd2(badd2(xv[t][1], bmul2(nv[t][1], y[t >> 1][2 * (t & 1) + 1])), bv[t][1]));
            }
            asm volatile("fence.proxy.async.shared::cta;" ::: "memory");
            named_bar(1 + wgi, 128);
            if ((tid & 127) == 0) {
                tma2d_store(&p.tm_out, 128 * cb, 128 * i + 64 * wgi, sb + SM_XE + wgi * 8192);
                tma2d_store(&p.tm_out, 128 * cb + 64, 128 * i + 64 * wgi, sb + SM_XE + 16384 + wgi * 8192);
                asm volatile("cp.async.bulk.commit_group;" ::: "memory");
                asm volatile("cp.async.bulk.wait_group.read 0;" ::: "memory");
                PROFW(29, 0);
            }
        }
    } else {
        asm volatile("setmaxnreg.dec.sync.aligned.u32 104;");
        if (warp == 8) {
            int st = 0; uint32_t eph = 7;
            #pragma unroll 1
            for (int it = 0; it < 16; it++) {
                const int pass = it >> 3, sl = it & 7;
                const int nb = pass ? 3 : 4;
                const CUtensorMap* tm = pass ? (rank ? &p.tm_uB : &p.tm_gB) : (rank ? &p.tm_uA : &p.tm_gA);
                mbar_wait(sb + SM_BARS + (B_EMPTY + st) * 8, (eph >> st) & 1);
                eph ^= 1u << st;
                if (it == 1) mbar_wait(sb + SM_BARS + (B_XFULL + 2) * 8, 0);
                PROF2(0, it);
                if (elect_one()) {
                    mbar_expect_tx(sb + SM_BARS + (B_FULL + st) * 8, nb * 8192);
                    tma3d_mc(sb + SM_RING + st * STAGE_BYTES + rank * nb * 4096, tm, 0, ((sl + 2 * cb + 2) & 7) * 64, 7 * j + 4 * pass, sb + SM_BARS + (B_FULL + st) * 8);
                }
                st = (st == 2) ? 0 : st + 1;
            }
            if (!convCTA) {
                st = 3;
                int f0 = 32 * rank, t3 = rank;
                #pragma unroll 1
                for (int u = 0; u < 28; u++) {
                    const uint32_t bar = sb + SM_BARS + (B_FULL + st) * 8;
                    mbar_wait(sb + SM_BARS + (B_EMPTY + st) * 8, (eph >> st) & 1);
                    eph ^= 1u << st;
                    if ((u & 1) == 0) PROF2(0, 16 + (u >> 1));
                    if (elect_one()) {
                        mbar_expect_tx(bar, 32768);
                        tma3d_mc(sb + stage_off_rt(st) + rank * 8192, &p.tm_w2, 0, f0, 2 * cb, bar);
                    }
                    st = next_st2(st);
                    if (u < 15) f0 += (u & 1) ? 160 : 64;
                    else if (u == 15) f0 = 128 + 32 * rank;
                    else { f0 += (t3 == 0) ? 64 : 192; t3 = (t3 == 0) ? 2 : t3 - 1; }
                }
                PROF(48);
            }
        } else if (warp < 11) {
            mbar_wait(sb + SM_BARS + (B_XFULL + 3) * 8, 0);
            #pragma unroll 1
            for (int rnd = 0; rnd < 2; rnd++) {
                const int tt = (tid - 288) + 64 * rnd;
                uint32_t sk[4][2];
                uint4 skw[2];
                skw[0] = ldg_nc128(p.shift_k + 16 * tt); skw[1] = ldg_nc128(p.shift_k + 16 * tt + 8);
                const __nv_bfloat16* kp = p.k + (size_t)(16 * b) * DM + 4 * tt;
                const __nv_bfloat16* vp = p.v + (size_t)(16 * b) * DM + 4 * tt;
                uint2 kr[19];
                uint2 kv[16];
                #pragma unroll
                for (int r = 0; r < 3; r++) kr[r] = (b > 0) ? ldg_nc64(kp + (r - 3) * DM) : make_uint2(0, 0);
                #pragma unroll
                for (int r = 0; r < 16; r++) { kr[3 + r] = ldg_nc64(kp + r * DM); if (r < 10) kv[r] = ldg_nc64(vp + r * DM); }
                {
                    const uint4 w0 = skw[0], w1 = skw[1];
                    sk[0][0] = __byte_perm(w0.x, w0.z, 0x5410); sk[1][0] = __byte_perm(w0.x, w0.z, 0x7632);
                    sk[2][0] = __byte_perm(w0.y, w0.w, 0x5410); sk[3][0] = __byte_perm(w0.y, w0.w, 0x7632);
                    sk[0][1] = __byte_perm(w1.x, w1.z, 0x5410); sk[1][1] = __byte_perm(w1.x, w1.z, 0x7632);
                    sk[2][1] = __byte_perm(w1.y, w1.w, 0x5410); sk[3][1] = __byte_perm(w1.y, w1.w, 0x7632);
                }
                #pragma unroll
                for (int s = 0; s < 16; s++) {
                    uint32_t a = bmul2(kr[s].x, sk[3][0]);
                    a = badd2(a, bmul2(kr[s + 1].x, sk[2][0]));
                    a = badd2(a, bmul2(kr[s + 2].x, sk[1][0]));
                    a = badd2(a, bmul2(kr[s + 3].x, sk[0][0]));
                    kv[s].x = bmul2(a, kv[s].x);
                    a = bmul2(kr[s].y, sk[3][1]);
                    a = badd2(a, bmul2(kr[s + 1].y, sk[2][1]));
                    a = badd2(a, bmul2(kr[s + 2].y, sk[1][1]));
                    a = badd2(a, bmul2(kr[s + 3].y, sk[0][1]));
                    kv[s].y = bmul2(a, kv[s].y);
                    if (s < 6) kv[10 + s] = ldg_nc64(vp + (10 + s) * DM);
                }
                PROFW(57 + 2 * rnd, 9);
                #pragma unroll
                for (int cc = 0; cc < 4; cc++) {
                    const uint32_t sel = (cc & 1) ? 0x7632 : 0x5410;
                    #define KVW(r) ((cc & 2) ? kv[r].y : kv[r].x)
                    uint4* dst = (uint4*)(g_kvT + (size_t)(4 * tt + cc) * SEQ + 16 * b);
                    dst[0] = make_uint4(__byte_perm(KVW(15), KVW(14), sel), __byte_perm(KVW(13), KVW(12), sel),
                                        __byte_perm(KVW(11), KVW(10), sel), __byte_perm(KVW(9), KVW(8), sel));
                    dst[1] = make_uint4(__byte_perm(KVW(7), KVW(6), sel), __byte_perm(KVW(5), KVW(4), sel),
                                        __byte_perm(KVW(3), KVW(2), sel), __byte_perm(KVW(1), KVW(0), sel));
                    #undef KVW
                }
                PROFW(58 + 2 * rnd, 9);
            }
            asm volatile("fence.proxy.async.global;" ::: "memory");
            __syncwarp();
            if (lane == 0) {
                flag_add(&g_cnt_kv[0]);
                PROFW(50, 9);
                const int wgi = warp - 9;
                mbar_wait(sb + SM_BARS + (B_HD + wgi * 2) * 8, 0);
                flag_add(&g_flag_h[(i * 2 + 0) * 8]);
                mbar_wait(sb + SM_BARS + (B_HD + wgi * 2 + 1) * 8, 0);
                flag_add(&g_flag_h[(i * 2 + 1) * 8]);
                if (wgi == 1 && convCTA) {
                    mbar_wait(sb + SM_BARS + B_YST * 8, 0);
                    flag_add(&g_cnt_y[(cidx >> 4) * 32]);
                    PROF(46);
                }
                if (wgi == 1 && !convCTA) {
                    const unsigned ep = lds32(sb + SM_EPOCH);
                    mbar_wait(sb + SM_BARS + B_G1DONE * 8, 0);
                    mbar_expect_tx(sb + SM_BARS + B_XR * 8, 32768);
                    for (int q = 0; q < 4; q++)
                        tma2d(sb + SM_XE + q * 8192, &p.tm_xe, 128 * cb + 64 * (q >> 1), 128 * i + 64 * (q & 1), sb + SM_BARS + B_XR * 8);
                    flag_wait(&g_flag_h[(i * 2 + 1) * 8], ep * 16);
                    mbar_arrive(sb + SM_BARS + (B_HRDY + 1) * 8);
                    __nanosleep(3000);
                    flag_wait(&g_cnt_y[cb * 32], ep * 16);
                    PROF(49);
                    asm volatile("fence.proxy.async.global;" ::: "memory");
                    mbar_expect_tx(sb + SM_BARS + B_YT * 8, 32768);
                    tma2d(sb + SM_YT, &p.tm_yT, 128 * i, 128 * cb, sb + SM_BARS + B_YT * 8);
                    tma2d(sb + SM_YT + 16384, &p.tm_yT, 128 * i + 64, 128 * cb, sb + SM_BARS + B_YT * 8);
                }
            }
        } else {
            if (lane == 0) {
                const unsigned ep = g_launch[b] + 1;
                g_launch[b] = ep;
                sts32(sb + SM_EPOCH, ep);
                tmap_prefetch(rank ? &p.tm_uA : &p.tm_gA);
                mbar_wait(sb + SM_BARS + (B_XFULL + 1) * 8, 0);
                l2_prefetch(p.wg + (size_t)b * (FF * DM / NCTA), FF * DM / NCTA * 2);
                l2_prefetch(p.wu + (size_t)b * (FF * DM / NCTA), FF * DM / NCTA * 2);
                tmap_prefetch(rank ? &p.tm_uB : &p.tm_gB);
                tmap_prefetch(&p.tm_w2); tmap_prefetch(&p.tm_yT); tmap_prefetch(&p.tm_out); tmap_prefetch(&p.tm_xe);
                mbar_wait(sb + SM_BARS + (B_FULL + 2) * 8, 0);
                l2_prefetch(p.ssm_k + (size_t)(4 * b) * SEQ, 4 * SEQ * 2);
                l2_prefetch(p.wd + (size_t)b * (FF * DM / NCTA), FF * DM / NCTA * 2);
                mbar_wait(sb + SM_BARS + (B_HD + 0) * 8, 0);
                if (convCTA) {
                    flag_wait(&g_cnt_kv[0], ep * 256);
                    asm volatile("fence.proxy.async.global;" ::: "memory");
                    PROF(53);
                    mbar_wait(sb + SM_BARS + B_XFREE * 8, 0);
                    PROF(54);
                    mbar_expect_tx(sb + SM_BARS + B_CONV * 8, 65536);
                    bulk_g2s(sb + SM_CVX, g_kvT + (size_t)(8 * cidx) * SEQ, 32768, sb + SM_BARS + B_CONV * 8);
                    bulk_g2s(sb + SM_CVH, p.ssm_k + (size_t)(8 * cidx) * SEQ, 32768, sb + SM_BARS + B_CONV * 8);
                } else {
                    flag_wait(&g_flag_h[(i * 2 + 0) * 8], ep * 16);
                }
            }
            __syncwarp();
            if (!convCTA) {
                asm volatile("fence.proxy.async.global;" ::: "memory");
                int st = 3; uint32_t eph = 1;
                const uint8_t* hsrc = (const uint8_t*)g_h + (size_t)i * 56 * 8192;
                #pragma unroll 1
                for (int u = 0; u < 28; u++) {
                    mbar_wait(sb + SM_BARS + (B_EMPTY + st) * 8, (eph >> st) & 1);
                    eph ^= 1u << st;
                    if (u == 16) {
                        mbar_wait(sb + SM_BARS + (B_HRDY + 1) * 8, 0);
                        asm volatile("fence.proxy.async.global;" ::: "memory");
                    }
                    if (elect_one()) bulk_g2s(sb + stage_off_rt(st) + 16384, hsrc + u * 16384, 16384, sb + SM_BARS + (B_FULL + st) * 8);
                    st = next_st2(st);
                }
            }
        }
    }
}

typedef CUresult (*EncodeFn)(CUtensorMap*, CUtensorMapDataType, cuuint32_t, void*, const cuuint64_t*, const cuuint64_t*,
                             const cuuint32_t*, const cuuint32_t*, CUtensorMapInterleave, CUtensorMapSwizzle,
                             CUtensorMapL2promotion, CUtensorMapFloatOOBfill);

void encode(EncodeFn fn, CUtensorMap* tm, const void* base, int rank, const cuuint64_t* dims, const cuuint64_t* strides,
            const cuuint32_t* box, CUtensorMapSwizzle swz) {
    cuuint32_t es[5] = {1, 1, 1, 1, 1};
    fn(tm, CU_TENSOR_MAP_DATA_TYPE_BFLOAT16, rank, (void*)base, dims, strides, box, es, CU_TENSOR_MAP_INTERLEAVE_NONE, swz,
       CU_TENSOR_MAP_L2_PROMOTION_L2_128B, CU_TENSOR_MAP_FLOAT_OOB_FILL_NONE);
}

}

extern "C" void kernel_launch(void* const* d_in, const int* in_sizes, int n_in, void* d_out, int out_size) {
    (void)in_sizes; (void)n_in; (void)out_size;
    static EncodeFn enc = nullptr;
    static void* yT_ptr = nullptr;
    if (!enc) {
        void* fn = nullptr; cudaDriverEntryPointQueryResult qr;
        cudaGetDriverEntryPoint("cuTensorMapEncodeTiled", &fn, cudaEnableDefault, &qr);
        enc = (EncodeFn)fn;
        cudaGetSymbolAddress(&yT_ptr, g_yT);
        cudaFuncSetAttribute(fused_kernel, cudaFuncAttributeMaxDynamicSharedMemorySize, SM_TOTAL);
    }
    Params p;
    p.q = (const __nv_bfloat16*)d_in[0]; p.k = (const __nv_bfloat16*)d_in[1]; p.v = (const __nv_bfloat16*)d_in[2];
    p.shift_k = (const __nv_bfloat16*)d_in[3]; p.ssm_k = (const __nv_bfloat16*)d_in[4]; p.ssm_D = (const __nv_bfloat16*)d_in[5];
    p.wg = (const __nv_bfloat16*)d_in[7]; p.wu = (const __nv_bfloat16*)d_in[8]; p.wd = (const __nv_bfloat16*)d_in[9];
    {
        cuuint64_t dims[2] = {DM, SEQ}; cuuint64_t str[1] = {DM * 2};
        cuuint32_t box[2] = {64, 32};
        encode(enc, &p.tm_x, p.q, 2, dims, str, box, CU_TENSOR_MAP_SWIZZLE_128B);
        cuuint32_t box2[2] = {64, 64};
        encode(enc, &p.tm_out, d_out, 2, dims, str, box2, CU_TENSOR_MAP_SWIZZLE_128B);
        encode(enc, &p.tm_xe, p.q, 2, dims, str, box2, CU_TENSOR_MAP_SWIZZLE_128B);
    }
    {
        cuuint64_t dims[3] = {32, DM, FF / 32}; cuuint64_t str[2] = {FF * 2, 64};
        cuuint32_t boxA[3] = {32, 64, 4}, boxB[3] = {32, 64, 3};
        encode(enc, &p.tm_gA, p.wg, 3, dims, str, boxA, CU_TENSOR_MAP_SWIZZLE_64B);
        encode(enc, &p.tm_gB, p.wg, 3, dims, str, boxB, CU_TENSOR_MAP_SWIZZLE_64B);
        encode(enc, &p.tm_uA, p.wu, 3, dims, str, boxA, CU_TENSOR_MAP_SWIZZLE_64B);
        encode(enc, &p.tm_uB, p.wu, 3, dims, str, boxB, CU_TENSOR_MAP_SWIZZLE_64B);
    }
    {
        cuuint64_t dims[3] = {64, FF, DM / 64}; cuuint64_t str[2] = {DM * 2, 128};
        cuuint32_t box[3] = {64, 32, 2};
        encode(enc, &p.tm_w2, p.wd, 3, dims, str, box, CU_TENSOR_MAP_SWIZZLE_128B);
    }
    {
        cuuint64_t dims[2] = {SEQ, DM}; cuuint64_t str[1] = {SEQ * 2};
        cuuint32_t box[2] = {64, 128};
        encode(enc, &p.tm_yT, yT_ptr, 2, dims, str, box, CU_TENSOR_MAP_SWIZZLE_128B);
    }
    fused_kernel<<<NCTA, NTHREADS, SM_TOTAL>>>(p);
}
```

```cpp
#include <cuda_runtime.h>
#include <cuda_bf16.h>
#include <cuda.h>
#include <stdint.h>

namespace {

constexpr int SEQ = 2048, DM = 512, FF = 1792;
constexpr int NCTA = 128;
constexpr int NTHREADS = 384;
constexpr int STAGE_BYTES = 32768;

constexpr uint32_t SM_X = 0;
constexpr uint32_t SM_RING = 131072;
constexpr uint32_t SM_MISC = SM_RING + 3 * STAGE_BYTES;
constexpr uint32_t SM_BARS = SM_MISC;
constexpr uint32_t SM_EPOCH = SM_MISC + 248;
constexpr uint32_t SM_STATS = SM_MISC + 256;
constexpr uint32_t SM_TOTAL = SM_STATS + 1024;
static_assert(SM_TOTAL <= 232448, "smem");
constexpr uint32_t SM_CVX = 0;
constexpr uint32_t SM_CVH = 32768;
constexpr uint32_t SM_YT = 4 * 16384;
constexpr uint32_t SM_XE = 6 * 16384;

constexpr int B_FULL = 0, B_EMPTY = 5, B_XFULL = 10, B_CONV = 14, B_YT = 15, B_XR = 16, B_G1DONE = 17, B_HD = 18, B_HRDY = 22,
              B_XFREE = 24, B_YST = 25, B_COUNT = 26;
static_assert(B_COUNT * 8 <= 248, "barrier space");

__device__ __align__(128) uint32_t g_h[16 * 56 * 2048];
__device__ __align__(128) __nv_bfloat16 g_kvT[DM * SEQ];
__device__ __align__(128) __nv_bfloat16 g_yT[DM * SEQ];
__device__ unsigned g_launch[NCTA];
__device__ unsigned g_cnt_kv[32];
__device__ unsigned g_cnt_y[4 * 32];
__device__ unsigned g_flag_h[16 * 2 * 8];

#define PROF(idx)
#define PROF2(a, idx)
#define PROFW(idx, w)

struct Params {
    CUtensorMap tm_x, tm_gA, tm_gB, tm_uA, tm_uB, tm_w2, tm_yT, tm_out, tm_xe;
    const __nv_bfloat16 *q, *k, *v, *shift_k, *ssm_k, *ssm_D, *wg, *wu, *wd;
};

__device__ __forceinline__ void wgmma_rs_n32(float (&d)[16], uint32_t a0, uint32_t a1, uint32_t a2, uint32_t a3, uint64_t db, int sc) {
  asm volatile("{\n.reg .pred p;\nsetp.ne.b32 p, %21, 0;\n"
    "wgmma.mma_async.sync.aligned.m64n32k16.f32.bf16.bf16 {%0,%1,%2,%3,%4,%5,%6,%7,%8,%9,%10,%11,%12,%13,%14,%15}, {%16,%17,%18,%19}, %20, p, 1, 1, 0;\n}\n"
    : "+f"(d[0]),"+f"(d[1]),"+f"(d[2]),"+f"(d[3]),"+f"(d[4]),"+f"(d[5]),"+f"(d[6]),"+f"(d[7]),"+f"(d[8]),"+f"(d[9]),"+f"(d[10]),"+f"(d[11]),"+f"(d[12]),"+f"(d[13]),"+f"(d[14]),"+f"(d[15])
    : "r"(a0),"r"(a1),"r"(a2),"r"(a3),"l"(db),"r"(sc));
}
__device__ __forceinline__ void wgmma_rs_n128_tb(float (&d)[64], uint32_t a0, uint32_t a1, uint32_t a2, uint32_t a3, uint64_t db, int sc) {
  asm volatile("{\n.reg .pred p;\nsetp.ne.b32 p, %69, 0;\n"
    "wgmma.mma_async.sync.aligned.m64n128k16.f32.bf16.bf16 {%0,%1,%2,%3,%4,%5,%6,%7,%8,%9,%10,%11,%12,%13,%14,%15,%16,%17,%18,%19,%20,%21,%22,%23,%24,%25,%26,%27,%28,%29,%30,%31,%32,%33,%34,%35,%36,%37,%38,%39,%40,%41,%42,%43,%44,%45,%46,%47,%48,%49,%50,%51,%52,%53,%54,%55,%56,%57,%58,%59,%60,%61,%62,%63}, {%64,%65,%66,%67}, %68, p, 1, 1, 1;\n}\n"
    : "+f"(d[0]),"+f"(d[1]),"+f"(d[2]),"+f"(d[3]),"+f"(d[4]),"+f"(d[5]),"+f"(d[6]),"+f"(d[7]),"+f"(d[8]),"+f"(d[9]),"+f"(d[10]),"+f"(d[11]),"+f"(d[12]),"+f"(d[13]),"+f"(d[14]),"+f"(d[15]),"+f"(d[16]),"+f"(d[17]),"+f"(d[18]),"+f"(d[19]),"+f"(d[20]),"+f"(d[21]),"+f"(d[22]),"+f"(d[23]),"+f"(d[24]),"+f"(d[25]),"+f"(d[26]),"+f"(d[27]),"+f"(d[28]),"+f"(d[29]),"+f"(d[30]),"+f"(d[31]),"+f"(d[32]),"+f"(d[33]),"+f"(d[34]),"+f"(d[35]),"+f"(d[36]),"+f"(d[37]),"+f"(d[38]),"+f"(d[39]),"+f"(d[40]),"+f"(d[41]),"+f"(d[42]),"+f"(d[43]),"+f"(d[44]),"+f"(d[45]),"+f"(d[46]),"+f"(d[47]),"+f"(d[48]),"+f"(d[49]),"+f"(d[50]),"+f"(d[51]),"+f"(d[52]),"+f"(d[53]),"+f"(d[54]),"+f"(d[55]),"+f"(d[56]),"+f"(d[57]),"+f"(d[58]),"+f"(d[59]),"+f"(d[60]),"+f"(d[61]),"+f"(d[62]),"+f"(d[63])
    : "r"(a0),"r"(a1),"r"(a2),"r"(a3),"l"(db),"r"(sc));
}
__device__ __forceinline__ void wgmma_ss_n256_tb(float (&d)[128], uint64_t da, uint64_t db, int sc) {
  asm volatile("{\n.reg .pred p;\nsetp.ne.b32 p, %130, 0;\n"
    "wgmma.mma_async.sync.aligned.m64n256k16.f32.bf16.bf16 {%0,%1,%2,%3,%4,%5,%6,%7,%8,%9,%10,%11,%12,%13,%14,%15,%16,%17,%18,%19,%20,%21,%22,%23,%24,%25,%26,%27,%28,%29,%30,%31,%32,%33,%34,%35,%36,%37,%38,%39,%40,%41,%42,%43,%44,%45,%46,%47,%48,%49,%50,%51,%52,%53,%54,%55,%56,%57,%58,%59,%60,%61,%62,%63,%64,%65,%66,%67,%68,%69,%70,%71,%72,%73,%74,%75,%76,%77,%78,%79,%80,%81,%82,%83,%84,%85,%86,%87,%88,%89,%90,%91,%92,%93,%94,%95,%96,%97,%98,%99,%100,%101,%102,%103,%104,%105,%106,%107,%108,%109,%110,%111,%112,%113,%114,%115,%116,%117,%118,%119,%120,%121,%122,%123,%124,%125,%126,%127}, %128, %129, p, 1, 1, 0, 1;\n}\n"
    : "+f"(d[0]),"+f"(d[1]),"+f"(d[2]),"+f"(d[3]),"+f"(d[4]),"+f"(d[5]),"+f"(d[6]),"+f"(d[7]),"+f"(d[8]),"+f"(d[9]),"+f"(d[10]),"+f"(d[11]),"+f"(d[12]),"+f"(d[13]),"+f"(d[14]),"+f"(d[15]),"+f"(d[16]),"+f"(d[17]),"+f"(d[18]),"+f"(d[19]),"+f"(d[20]),"+f"(d[21]),"+f"(d[22]),"+f"(d[23]),"+f"(d[24]),"+f"(d[25]),"+f"(d[26]),"+f"(d[27]),"+f"(d[28]),"+f"(d[29]),"+f"(d[30]),"+f"(d[31]),"+f"(d[32]),"+f"(d[33]),"+f"(d[34]),"+f"(d[35]),"+f"(d[36]),"+f"(d[37]),"+f"(d[38]),"+f"(d[39]),"+f"(d[40]),"+f"(d[41]),"+f"(d[42]),"+f"(d[43]),"+f"(d[44]),"+f"(d[45]),"+f"(d[46]),"+f"(d[47]),"+f"(d[48]),"+f"(d[49]),"+f"(d[50]),"+f"(d[51]),"+f"(d[52]),"+f"(d[53]),"+f"(d[54]),"+f"(d[55]),"+f"(d[56]),"+f"(d[57]),"+f"(d[58]),"+f"(d[59]),"+f"(d[60]),"+f"(d[61]),"+f"(d[62]),"+f"(d[63]),"+f"(d[64]),"+f"(d[65]),"+f"(d[66]),"+f"(d[67]),"+f"(d[68]),"+f"(d[69]),"+f"(d[70]),"+f"(d[71]),"+f"(d[72]),"+f"(d[73]),"+f"(d[74]),"+f"(d[75]),"+f"(d[76]),"+f"(d[77]),"+f"(d[78]),"+f"(d[79]),"+f"(d[80]),"+f"(d[81]),"+f"(d[82]),"+f"(d[83]),"+f"(d[84]),"+f"(d[85]),"+f"(d[86]),"+f"(d[87]),"+f"(d[88]),"+f"(d[89]),"+f"(d[90]),"+f"(d[91]),"+f"(d[92]),"+f"(d[93]),"+f"(d[94]),"+f"(d[95]),"+f"(d[96]),"+f"(d[97]),"+f"(d[98]),"+f"(d[99]),"+f"(d[100]),"+f"(d[101]),"+f"(d[102]),"+f"(d[103]),"+f"(d[104]),"+f"(d[105]),"+f"(d[106]),"+f"(d[107]),"+f"(d[108]),"+f"(d[109]),"+f"(d[110]),"+f"(d[111]),"+f"(d[112]),"+f"(d[113]),"+f"(d[114]),"+f"(d[115]),"+f"(d[116]),"+f"(d[117]),"+f"(d[118]),"+f"(d[119]),"+f"(d[120]),"+f"(d[121]),"+f"(d[122]),"+f"(d[123]),"+f"(d[124]),"+f"(d[125]),"+f"(d[126]),"+f"(d[127])
    : "l"(da),"l"(db),"r"(sc));
}
__device__ __forceinline__ void wgmma_ss_n192_tb(float (&d)[96], uint64_t da, uint64_t db, int sc) {
  asm volatile("{\n.reg .pred p;\nsetp.ne.b32 p, %98, 0;\n"
    "wgmma.mma_async.sync.aligned.m64n192k16.f32.bf16.bf16 {%0,%1,%2,%3,%4,%5,%6,%7,%8,%9,%10,%11,%12,%13,%14,%15,%16,%17,%18,%19,%20,%21,%22,%23,%24,%25,%26,%27,%28,%29,%30,%31,%32,%33,%34,%35,%36,%37,%38,%39,%40,%41,%42,%43,%44,%45,%46,%47,%48,%49,%50,%51,%52,%53,%54,%55,%56,%57,%58,%59,%60,%61,%62,%63,%64,%65,%66,%67,%68,%69,%70,%71,%72,%73,%74,%75,%76,%77,%78,%79,%80,%81,%82,%83,%84,%85,%86,%87,%88,%89,%90,%91,%92,%93,%94,%95}, %96, %97, p, 1, 1, 0, 1;\n}\n"
    : "+f"(d[0]),"+f"(d[1]),"+f"(d[2]),"+f"(d[3]),"+f"(d[4]),"+f"(d[5]),"+f"(d[6]),"+f"(d[7]),"+f"(d[8]),"+f"(d[9]),"+f"(d[10]),"+f"(d[11]),"+f"(d[12]),"+f"(d[13]),"+f"(d[14]),"+f"(d[15]),"+f"(d[16]),"+f"(d[17]),"+f"(d[18]),"+f"(d[19]),"+f"(d[20]),"+f"(d[21]),"+f"(d[22]),"+f"(d[23]),"+f"(d[24]),"+f"(d[25]),"+f"(d[26]),"+f"(d[27]),"+f"(d[28]),"+f"(d[29]),"+f"(d[30]),"+f"(d[31]),"+f"(d[32]),"+f"(d[33]),"+f"(d[34]),"+f"(d[35]),"+f"(d[36]),"+f"(d[37]),"+f"(d[38]),"+f"(d[39]),"+f"(d[40]),"+f"(d[41]),"+f"(d[42]),"+f"(d[43]),"+f"(d[44]),"+f"(d[45]),"+f"(d[46]),"+f"(d[47]),"+f"(d[48]),"+f"(d[49]),"+f"(d[50]),"+f"(d[51]),"+f"(d[52]),"+f"(d[53]),"+f"(d[54]),"+f"(d[55]),"+f"(d[56]),"+f"(d[57]),"+f"(d[58]),"+f"(d[59]),"+f"(d[60]),"+f"(d[61]),"+f"(d[62]),"+f"(d[63]),"+f"(d[64]),"+f"(d[65]),"+f"(d[66]),"+f"(d[67]),"+f"(d[68]),"+f"(d[69]),"+f"(d[70]),"+f"(d[71]),"+f"(d[72]),"+f"(d[73]),"+f"(d[74]),"+f"(d[75]),"+f"(d[76]),"+f"(d[77]),"+f"(d[78]),"+f"(d[79]),"+f"(d[80]),"+f"(d[81]),"+f"(d[82]),"+f"(d[83]),"+f"(d[84]),"+f"(d[85]),"+f"(d[86]),"+f"(d[87]),"+f"(d[88]),"+f"(d[89]),"+f"(d[90]),"+f"(d[91]),"+f"(d[92]),"+f"(d[93]),"+f"(d[94]),"+f"(d[95])
    : "l"(da),"l"(db),"r"(sc));
}

__device__ __forceinline__ uint32_t smem_u32(const void* p) { return (uint32_t)__cvta_generic_to_shared(p); }
__device__ __forceinline__ void mbar_init(uint32_t bar, uint32_t cnt) { asm volatile("mbarrier.init.shared::cta.b64 [%0], %1;" :: "r"(bar), "r"(cnt)); }
__device__ __forceinline__ void mbar_expect_tx(uint32_t bar, uint32_t bytes) { asm volatile("mbarrier.arrive.expect_tx.shared::cta.b64 _, [%0], %1;" :: "r"(bar), "r"(bytes) : "memory"); }
__device__ __forceinline__ void mbar_arrive(uint32_t bar) { asm volatile("mbarrier.arrive.shared::cta.b64 _, [%0];" :: "r"(bar) : "memory"); }
__device__ __forceinline__ void mbar_arrive_cluster(uint32_t cbar, uint32_t cnt) { asm volatile("mbarrier.arrive.shared::cluster.b64 _, [%0], %1;" :: "r"(cbar), "r"(cnt) : "memory"); }
__device__ __forceinline__ uint32_t mapa(uint32_t a, uint32_t rank) { uint32_t r; asm volatile("mapa.shared::cluster.u32 %0, %1, %2;" : "=r"(r) : "r"(a), "r"(rank)); return r; }
__device__ __forceinline__ void mbar_wait(uint32_t bar, uint32_t parity) {
    uint32_t ok; uint32_t n = 0;
    do {
        asm volatile("{\n.reg .pred p;\nmbarrier.try_wait.parity.shared::cta.b64 p, [%1], %2;\nselp.u32 %0, 1, 0, p;\n}" : "=r"(ok) : "r"(bar), "r"(parity) : "memory");
    } while (!ok && ++n < (1u << 17));
}
__device__ __forceinline__ void pace_wait(uint32_t a, uint32_t target) {
    uint32_t v, n = 0;
    do {
        asm volatile("ld.volatile.shared.u32 %0, [%1];" : "=r"(v) : "r"(a) : "memory");
        if (v < target) __nanosleep(150);
    } while (v < target && ++n < (1u << 14));
}
__device__ __forceinline__ void flag_wait(const unsigned* p, unsigned target) {
    unsigned v; uint32_t n = 0;
    while (true) {
        asm volatile("ld.acquire.gpu.global.u32 %0, [%1];" : "=r"(v) : "l"(p) : "memory");
        if ((int)(v - target) >= 0 || ++n >= (1u << 17)) break;
        __nanosleep(100);
    }
}
__device__ __forceinline__ void flag_add(unsigned* p) {
    asm volatile("fence.acq_rel.gpu;\nred.relaxed.gpu.global.add.u32 [%0], 1;" :: "l"(p) : "memory");
}
__device__ __forceinline__ uint64_t make_desc(uint32_t addr, uint32_t lbo, uint32_t sbo, uint32_t swz) {
    return (uint64_t)((addr & 0x3FFFF) >> 4) | ((uint64_t)((lbo & 0x3FFFF) >> 4) << 16) | ((uint64_t)((sbo & 0x3FFFF) >> 4) << 32) | ((uint64_t)swz << 62);
}
__device__ __forceinline__ uint64_t desc_add(uint64_t d, uint32_t off16) {
    return (d & 0xFFFFFFFF00000000ull) | (uint64_t)((uint32_t)d + off16);
}
__device__ __forceinline__ void tma2d(uint32_t dst, const CUtensorMap* tm, int c0, int c1, uint32_t bar) {
    asm volatile("cp.async.bulk.tensor.2d.shared::cluster.global.mbarrier::complete_tx::bytes [%0], [%1, {%3, %4}], [%2];"
        :: "r"(dst), "l"((uint64_t)tm), "r"(bar), "r"(c0), "r"(c1) : "memory");
}
__device__ __forceinline__ void tma3d_mc(uint32_t dst, const CUtensorMap* tm, int c0, int c1, int c2, uint32_t bar) {
    asm volatile("cp.async.bulk.tensor.3d.shared::cluster.global.mbarrier::complete_tx::bytes.multicast::cluster [%0], [%1, {%3, %4, %5}], [%2], %6;"
        :: "r"(dst), "l"((uint64_t)tm), "r"(bar), "r"(c0), "r"(c1), "r"(c2), "h"((uint16_t)3) : "memory");
}
__device__ __forceinline__ void bulk_g2s(uint32_t dst, const void* src, uint32_t bytes, uint32_t bar) {
    asm volatile("cp.async.bulk.shared::cluster.global.mbarrier::complete_tx::bytes [%0], [%1], %2, [%3];"
        :: "r"(dst), "l"(src), "r"(bytes), "r"(bar) : "memory");
}
__device__ __forceinline__ void bulk_s2g(void* dst, uint32_t src, uint32_t bytes) {
    asm volatile("cp.async.bulk.global.shared::cta.bulk_group [%0], [%1], %2;" :: "l"(dst), "r"(src), "r"(bytes) : "memory");
}
__device__ __forceinline__ void tma2d_store(const CUtensorMap* tm, int c0, int c1, uint32_t src) {
    asm volatile("cp.async.bulk.tensor.2d.global.shared::cta.bulk_group [%0, {%2, %3}], [%1];"
        :: "l"((uint64_t)tm), "r"(src), "r"(c0), "r"(c1) : "memory");
}
__device__ __forceinline__ void l2_prefetch(const void* p, uint32_t bytes) {
    asm volatile("cp.async.bulk.prefetch.L2.global [%0], %1;" :: "l"(p), "r"(bytes) : "memory");
}
__device__ __forceinline__ void tmap_prefetch(const CUtensorMap* tm) { asm volatile("prefetch.tensormap [%0];" :: "l"((uint64_t)tm) : "memory"); }
__device__ __forceinline__ uint32_t lds32(uint32_t a) { uint32_t v; asm volatile("ld.shared.u32 %0, [%1];" : "=r"(v) : "r"(a)); return v; }
__device__ __forceinline__ uint2 lds64(uint32_t a) { uint2 v; asm volatile("ld.shared.v2.u32 {%0,%1}, [%2];" : "=r"(v.x), "=r"(v.y) : "r"(a)); return v; }
__device__ __forceinline__ uint4 lds128(uint32_t a) { uint4 v; asm volatile("ld.shared.v4.u32 {%0,%1,%2,%3}, [%4];" : "=r"(v.x), "=r"(v.y), "=r"(v.z), "=r"(v.w) : "r"(a)); return v; }
__device__ __forceinline__ float2 lds64f(uint32_t a) { float2 v; asm volatile("ld.shared.v2.f32 {%0,%1}, [%2];" : "=f"(v.x), "=f"(v.y) : "r"(a)); return v; }
__device__ __forceinline__ void sts32(uint32_t a, uint32_t v) { asm volatile("st.shared.u32 [%0], %1;" :: "r"(a), "r"(v) : "memory"); }
__device__ __forceinline__ void sts128(uint32_t a, uint4 v) { asm volatile("st.shared.v4.u32 [%0], {%1,%2,%3,%4};" :: "r"(a), "r"(v.x), "r"(v.y), "r"(v.z), "r"(v.w) : "memory"); }
__device__ __forceinline__ uint4 ldg_cg128(const void* p) { uint4 v; asm volatile("ld.global.cg.v4.u32 {%0,%1,%2,%3}, [%4];" : "=r"(v.x), "=r"(v.y), "=r"(v.z), "=r"(v.w) : "l"(p)); return v; }
__device__ __forceinline__ uint4 ldg_nc128(const void* p) { uint4 v; asm volatile("ld.global.nc.L1::no_allocate.v4.u32 {%0,%1,%2,%3}, [%4];" : "=r"(v.x), "=r"(v.y), "=r"(v.z), "=r"(v.w) : "l"(p)); return v; }
__device__ __forceinline__ uint2 ldg_nc64(const void* p) { uint2 v; asm volatile("ld.global.nc.L1::no_allocate.v2.u32 {%0,%1}, [%2];" : "=r"(v.x), "=r"(v.y) : "l"(p)); return v; }
#define WG_FENCE() asm volatile("wgmma.fence.sync.aligned;\n" ::: "memory")
#define WG_COMMIT() asm volatile("wgmma.commit_group.sync.aligned;\n" ::: "memory")
template<int N> __device__ __forceinline__ void wg_wait() { asm volatile("wgmma.wait_group.sync.aligned %0;\n" :: "n"(N) : "memory"); }
__device__ __forceinline__ bool elect_one() {
    uint32_t pr;
    asm volatile("{\n.reg .pred p;\nelect.sync _|p, 0xffffffff;\nselp.u32 %0, 1, 0, p;\n}" : "=r"(pr));
    return pr != 0;
}
__device__ __forceinline__ void named_bar(int id, int n) { asm volatile("bar.sync %0, %1;" :: "r"(id), "r"(n) : "memory"); }

__device__ __forceinline__ float bf_lo(uint32_t u) { return __uint_as_float(u << 16); }
__device__ __forceinline__ float bf_hi(uint32_t u) { return __uint_as_float(u & 0xFFFF0000u); }
__device__ __forceinline__ uint32_t pack_bf(float lo, float hi) { uint32_t r; asm("cvt.rn.bf16x2.f32 %0, %1, %2;" : "=r"(r) : "f"(hi), "f"(lo)); return r; }
__device__ __forceinline__ float bf_round(float x) { return __bfloat162float(__float2bfloat16_rn(x)); }
__device__ __forceinline__ uint32_t bmul2(uint32_t a, uint32_t b) { uint32_t r; asm("mul.rn.bf16x2 %0, %1, %2;" : "=r"(r) : "r"(a), "r"(b)); return r; }
__device__ __forceinline__ uint32_t badd2(uint32_t a, uint32_t b) { uint32_t r; asm("add.rn.bf16x2 %0, %1, %2;" : "=r"(r) : "r"(a), "r"(b)); return r; }
__device__ __forceinline__ uint32_t bsub2(uint32_t a, uint32_t b) { uint32_t r; asm("sub.rn.bf16x2 %0, %1, %2;" : "=r"(r) : "r"(a), "r"(b)); return r; }
__device__ __forceinline__ void mma16816(float (&d)[4], uint32_t a0, uint32_t a1, uint32_t a2, uint32_t a3, uint2 b) {
    asm volatile("mma.sync.aligned.m16n8k16.row.col.f32.bf16.bf16.f32 {%0,%1,%2,%3}, {%4,%5,%6,%7}, {%8,%9}, {%0,%1,%2,%3};\n"
        : "+f"(d[0]), "+f"(d[1]), "+f"(d[2]), "+f"(d[3]) : "r"(a0), "r"(a1), "r"(a2), "r"(a3), "r"(b.x), "r"(b.y));
}

template<int HS> __device__ __forceinline__ void xreduce(float (&v)[8], int lane) {
    const int up = lane & HS;
    #pragma unroll
    for (int e = 0; e < HS; e++) {
        float keep, send;
        asm("{\n.reg .pred p;\nsetp.ne.b32 p, %4, 0;\nselp.f32 %0, %3, %2, p;\nselp.f32 %1, %2, %3, p;\n}"
            : "=f"(keep), "=f"(send) : "f"(v[e]), "f"(v[e + HS]), "r"(up));
        v[e] = keep + __shfl_xor_sync(0xffffffffu, send, HS);
    }
}

__device__ __forceinline__ int blk_f0(int bi, int j) {
    if (bi < 32) return 224 * ((j + (bi >> 2)) & 7) + 32 * (bi & 3);
    int b2 = bi - 32; int q3 = (b2 * 11) >> 5;
    return 224 * ((j + q3) & 7) + 128 + 32 * (b2 - 3 * q3);
}
__device__ __forceinline__ int next_st2(int s) { return (0x14023 >> (4 * s)) & 7; }
__device__ __forceinline__ uint32_t stage_off_rt(int s) { return s < 3 ? SM_RING + s * STAGE_BYTES : (uint32_t)(s - 3) * STAGE_BYTES; }

template<int NB>
__device__ __forceinline__ void gemm1_pass(uint32_t sb, int wgi, int warp4, int lane, int& st, uint32_t& fph, uint32_t e_cl,
                                           int rb64, int ks0, bool convCTA) {
    constexpr bool passA = (NB == 4);
    float acc[NB * 32];
    const uint64_t descA0 = make_desc(sb + SM_X + wgi * 8192, 16, 1024, 1);
    const uint64_t descB0 = make_desc(sb + SM_RING, 4096, 512, 2);
    int prev = 0;
    #pragma unroll 1
    for (int sl = 0; sl < 8; sl++) {
        if (warp4 == 0 && wgi == 0) PROF2(2, sl + (passA ? 0 : 8));
        mbar_wait(sb + SM_BARS + (B_FULL + st) * 8, (fph >> st) & 1);
        fph ^= 1u << st;
        if (sl == 0 && warp4 == 0) PROF(2 + wgi * 8 + (passA ? 0 : 3));
        if (warp4 == 0 && wgi == 0) PROF2(1, sl + (passA ? 0 : 8));
        const uint64_t da = desc_add(descA0, sl * 1024), db = desc_add(descB0, st * 2048);
        WG_FENCE();
        #pragma unroll
        for (int kk = 0; kk < 4; kk++) {
            int sc = (sl | kk) ? 1 : 0;
            if constexpr (NB == 4) wgmma_ss_n256_tb(acc, da + kk * 2, db + kk * 64, sc); else wgmma_ss_n192_tb(acc, da + kk * 2, db + kk * 64, sc);
        }
        WG_COMMIT();
        wg_wait<1>();
        if (warp4 == 0 && wgi == 0) PROF2(3, sl + (passA ? 0 : 8));
        if (lane < 2 && sl && (passA || !convCTA || sl < 6)) mbar_arrive_cluster(e_cl + prev * 8, 1);
        if (!passA) {
            if (convCTA) { if (sl == 4 && lane == 0) mbar_arrive(sb + SM_BARS + B_XFREE * 8); }
            else if ((sl == 2 || sl == 4) && lane < 2) mbar_arrive_cluster(e_cl + (2 + (sl >> 1)) * 8, 1);
        }
        prev = st;
        st = (st == 2) ? 0 : st + 1;
    }
    wg_wait<0>();
    if (lane < 2 && (passA || !convCTA)) mbar_arrive_cluster(e_cl + prev * 8, 1);
    if (!passA && lane == 0) mbar_arrive(sb + SM_BARS + B_G1DONE * 8);
    if (warp4 == 0) PROF(3 + wgi * 8 + (passA ? 0 : 3));
    const int g = lane >> 2;
    const int r0 = wgi * 64 + warp4 * 16 + g;
    const float s0 = __uint_as_float(lds32(sb + SM_STATS + r0 * 8 + 4)), s1 = __uint_as_float(lds32(sb + SM_STATS + (r0 + 8) * 8 + 4));
    uint32_t* dst = g_h + (size_t)((rb64 >> 1) * 56 + ks0) * 2048 + wgi * 1024 + warp4 * 128 + lane;
    #pragma unroll
    for (int kk = 0; kk < NB * 2; kk++) {
        uint32_t h[4];
        #pragma unroll
        for (int tt = 0; tt < 2; tt++) {
            const int t = 2 * kk + tt;
            const float* ag = &acc[4 * t];
            const float* au = &acc[NB * 16 + 4 * t];
            h[2 * tt] = bmul2(pack_bf(ag[0] * s0, ag[1] * s0), pack_bf(au[0] * s0, au[1] * s0));
            h[2 * tt + 1] = bmul2(pack_bf(ag[2] * s1, ag[3] * s1), pack_bf(au[2] * s1, au[3] * s1));
        }
        uint32_t* d2 = dst + (kk >> 1) * 2048 + (kk & 1) * 512;
        d2[0] = h[0]; d2[64] = h[1]; d2[32] = h[2]; d2[96] = h[3];
    }
    __syncwarp();
    if (lane == 0) mbar_arrive(sb + SM_BARS + (B_HD + wgi * 2 + (passA ? 0 : 1)) * 8);
    if (warp4 == 0) PROF(4 + wgi * 8 + (passA ? 0 : 3));
}

__global__ void __cluster_dims__(2, 1, 1) __launch_bounds__(NTHREADS, 1)
fused_kernel(const __grid_constant__ Params p) {
    extern __shared__ __align__(1024) uint8_t smem_raw[];
    const uint32_t sb = smem_u32(smem_raw);
    const int tid = threadIdx.x, warp = tid >> 5, lane = tid & 31;
    const int b = blockIdx.x;
    const int rank = b & 1;
    const int j = (b >> 1) & 7;
    const int i = ((b >> 4) << 1) | rank;
    const int cb = j >> 1;
    const bool convCTA = j & 1;
    const int cidx = 4 * i + cb;

    if (warp == 8 && lane < 4) {
        mbar_init(sb + SM_BARS + (B_XFULL + lane) * 8, 1);
        asm volatile("fence.proxy.async.shared::cta;" ::: "memory");
        mbar_expect_tx(sb + SM_BARS + (B_XFULL + lane) * 8, 32768);
    }
    if (tid == 288) {
        for (int s = 0; s < 5; s++) { mbar_init(sb + SM_BARS + (B_FULL + s) * 8, 1); mbar_init(sb + SM_BARS + (B_EMPTY + s) * 8, 16); }
        mbar_init(sb + SM_BARS + B_CONV * 8, 1);
        mbar_init(sb + SM_BARS + B_YT * 8, 1);
        mbar_init(sb + SM_BARS + B_XR * 8, 1);
        mbar_init(sb + SM_BARS + B_G1DONE * 8, 8);
        mbar_init(sb + SM_BARS + B_XFREE * 8, 8);
        mbar_init(sb + SM_BARS + B_YST * 8, 8);
        for (int s = 0; s < 4; s++) mbar_init(sb + SM_BARS + (B_HD + s) * 8, 4);
        for (int s = 0; s < 2; s++) mbar_init(sb + SM_BARS + (B_HRDY + s) * 8, 1);
        asm volatile("fence.mbarrier_init.release.cluster;" ::: "memory");
        asm volatile("fence.proxy.async.shared::cta;" ::: "memory");
    }
    __syncwarp();
    asm volatile("barrier.cluster.arrive.relaxed.aligned;\n" ::: "memory");
    if (warp == 8) {
        const int rg = lane >> 3, sl = lane & 7;
        tma2d(sb + SM_X + sl * 16384 + rg * 4096, &p.tm_x, 64 * ((sl + 2 * cb + 2) & 7), 128 * i + 32 * rg, sb + SM_BARS + (B_XFULL + rg) * 8);
        __syncwarp();
    }
    asm volatile("barrier.cluster.wait.aligned;\n" ::: "memory");
    PROFW(1, 0);

    if (warp < 8) {
        asm volatile("setmaxnreg.inc.sync.aligned.u32 200;");
        const int wgi = warp >> 2, warp4 = warp & 3;
        const int g = lane >> 2, c = lane & 3;
        const uint32_t e_cl = mapa(sb + SM_BARS + B_EMPTY * 8, lane & 1);
        {
            #pragma unroll 1
            for (int rg = 0; rg < 4; rg++) {
                const int row0 = rg * 32 + warp * 4;
                const uint32_t xa = sb + SM_X + (lane >> 3) * 16384 + row0 * 128;
                uint4 xr[4][2];
                float v[8];
                mbar_wait(sb + SM_BARS + (B_XFULL + rg) * 8, 0);
                if (rg == 0) PROFW(16, 0);
                if (rg == 3) PROFW(18, 0);
                #pragma unroll
                for (int r = 0; r < 4; r++) {
                    const uint32_t a = xa + r * 128 + (((lane & 7) ^ ((row0 + r) & 7)) << 4);
                    xr[r][0] = lds128(a); xr[r][1] = lds128(a + 65536);
                }
                #pragma unroll
                for (int r = 0; r < 4; r++) {
                    const uint32_t* u = (const uint32_t*)&xr[r][0];
                    float s0 = 0.f, q0 = 0.f, s1 = 0.f, q1 = 0.f;
                    #pragma unroll
                    for (int e = 0; e < 8; e++) { const float lo = bf_lo(u[e]), hi = bf_hi(u[e]); s0 += lo; q0 = fmaf(lo, lo, q0); s1 += hi; q1 = fmaf(hi, hi, q1); }
                    v[r] = s0 + s1; v[4 + r] = q0 + q1;
                }
                xreduce<4>(v, lane); xreduce<2>(v, lane); xreduce<1>(v, lane);
                v[0] += __shfl_xor_sync(0xffffffffu, v[0], 8);
                v[0] += __shfl_xor_sync(0xffffffffu, v[0], 16);
                const float other = __shfl_xor_sync(0xffffffffu, v[0], 4);
                const float mean = ((lane & 4) ? other : v[0]) * (1.0f / DM);
                const float msq = ((lane & 4) ? v[0] : other) * (1.0f / DM);
                const uint32_t mb = pack_bf(mean, mean);
                #pragma unroll
                for (int r = 0; r < 4; r++) {
                    const uint32_t m = __shfl_sync(0xffffffffu, mb, r);
                    const uint32_t a = xa + r * 128 + (((lane & 7) ^ ((row0 + r) & 7)) << 4);
                    #pragma unroll
                    for (int hh = 0; hh < 2; hh++) {
                        uint4 t = xr[r][hh];
                        t.x = bsub2(t.x, m); t.y = bsub2(t.y, m); t.z = bsub2(t.z, m); t.w = bsub2(t.w, m);
                        sts128(a + hh * 65536, t);
                    }
                }
                if (lane < 4) {
                    const float var_b = bf_round(fmaxf(msq - mean * mean, 0.f));
                    const float sd = bf_round(sqrtf(bf_round(var_b + 1e-5f)));
                    sts32(sb + SM_STATS + (row0 + lane) * 8, mb);
                    sts32(sb + SM_STATS + (row0 + lane) * 8 + 4, __float_as_uint(1.0f / sd));
                }
            }
            asm volatile("fence.proxy.async.shared::cta;" ::: "memory");
            named_bar(3, 256);
            PROFW(17, 0);
        }
        int st = 0; uint32_t fph = 0;
        const int rb64 = 2 * i + wgi;
        gemm1_pass<4>(sb, wgi, warp4, lane, st, fph, e_cl, rb64, 4 * j, convCTA);
        gemm1_pass<3>(sb, wgi, warp4, lane, st, fph, e_cl, rb64, 32 + 3 * j, convCTA);

        if (convCTA) {
            const int gch = 8 * cidx + warp;
            const uint32_t xb = sb + SM_CVX + warp * 4096;
            const uint32_t hb = sb + SM_CVH + warp * 4096;
            const uint32_t dw = ((const unsigned short*)p.ssm_D)[gch];
            const uint32_t d2 = dw | (dw << 16);
            mbar_wait(sb + SM_BARS + B_CONV * 8, 0);
            PROFW(32, 4);
            float acc[16][4];
            #pragma unroll
            for (int jj = 0; jj < 16; jj++) { acc[jj][0] = 0.f; acc[jj][1] = 0.f; acc[jj][2] = 0.f; acc[jj][3] = 0.f; }
            uint2 bh[8], bl0[8], bl1[8];
            uint32_t xl = xb + g * 32 + c * 8;
            uint32_t hl = hb + (g + 2 * c - 8) * 4;
            #pragma unroll
            for (int d = 0; d < 8; d++) { bl0[d] = lds64(xl + d * 256); bh[d] = lds64(xl + (8 + d) * 256); }
            uint32_t w[6];
            w[0] = 0; w[1] = 0; w[2] = 0;
            if (g + 2 * c >= 8) w[0] = lds32(hl);
            if (g + 2 * c >= 7) w[1] = lds32(hl + 4);
            if (g + 2 * c >= 6) w[2] = lds32(hl + 8);
            w[3] = lds32(hl + 2048); w[4] = lds32(hl + 2052); w[5] = lds32(hl + 2056);
            auto conv_m0 = [&](int m0, uint2 (&bl)[8], uint2 (&bn)[8]) {
                xl -= 32;
                #pragma unroll
                for (int k = 0; k < 8; k++) {
                    const uint32_t a0 = w[1], a1 = __byte_perm(w[0], w[1], 0x5432), a2 = w[2], a3 = __byte_perm(w[1], w[2], 0x5432);
                    const uint32_t c0 = w[4], c1 = __byte_perm(w[3], w[4], 0x5432), c2 = w[5], c3 = __byte_perm(w[4], w[5], 0x5432);
                    const uint32_t nx = (k < 7) ? hl + (k + 1) * 256 : hl + 32;
                    w[0] = lds32(nx); w[1] = lds32(nx + 4); w[2] = lds32(nx + 8);
                    w[3] = lds32(nx + 2048); w[4] = lds32(nx + 2052); w[5] = lds32(nx + 2056);
                    if (k > 0) bn[k] = lds64(xl + k * 256);
                    else { bn[0] = make_uint2(0, 0); if (g > m0) bn[0] = lds64(xl); }
                    #pragma unroll
                    for (int jj = k; jj < 16; jj++) mma16816(acc[jj], a0, a1, a2, a3, (jj - k < 8) ? bl[(jj - k) & 7] : bh[(jj - k) & 7]);
                    bh[7 - k] = lds64(xl + (15 - k) * 256);
                    #pragma unroll
                    for (int jj = k + 8; jj < 16; jj++) mma16816(acc[jj], c0, c1, c2, c3, bl[jj - k - 8]);
                }
                hl += 32;
            };
            #pragma unroll 1
            for (int m0 = 0; m0 < 8; m0 += 2) {
                conv_m0(m0, bl0, bl1);
                conv_m0(m0 + 1, bl1, bl0);
                PROFW(34 + (m0 >> 1), 4);
            }
            PROFW(33, 4);
            const uint32_t kvl = xb + c * 64 + (7 - g) * 4;
            uint32_t* ydst = (uint32_t*)(g_yT + (size_t)gch * SEQ + 32 * c + 2 * g);
            uint32_t kk0[16], kk1[16];
            #pragma unroll
            for (int jj = 0; jj < 16; jj++) { kk0[jj] = lds32(kvl + jj * 256); kk1[jj] = lds32(kvl + jj * 256 + 32); }
            #pragma unroll
            for (int jj = 0; jj < 16; jj++) {
                ydst[jj * 64] = badd2(pack_bf(acc[jj][2], acc[jj][0]), bmul2(__byte_perm(kk0[jj], kk0[jj], 0x1032), d2));
                ydst[jj * 64 + 8] = badd2(pack_bf(acc[jj][3], acc[jj][1]), bmul2(__byte_perm(kk1[jj], kk1[jj], 0x1032), d2));
            }
            __syncwarp();
            PROFW(44, 4);
            if (lane == 0) mbar_arrive(sb + SM_BARS + B_YST * 8);
        } else {
            float acc[64];
            const uint64_t descB0 = make_desc(sb, 4096, 1024, 1);
            const uint64_t descA0 = make_desc(sb + 16384 + wgi * 4096, 128, 256, 0);
            int sg = 3, p0 = 0; uint32_t ph = 6;
            PROFW(20, 0);
            #pragma unroll 1
            for (int u = 0; u < 28; u++) {
                if (warp == 0 && !(u & 1)) PROF2(2, 16 + (u >> 1));
                mbar_wait(sb + SM_BARS + (B_FULL + sg) * 8, (ph >> sg) & 1);
                ph ^= 1u << sg;
                if (warp == 0 && !(u & 1)) PROF2(1, 16 + (u >> 1));
                const uint32_t o0 = stage_off_rt(sg) >> 4;
                const uint64_t da0 = desc_add(descA0, o0), db0 = desc_add(descB0, o0);
                WG_FENCE();
                #pragma unroll
                for (int kk = 0; kk < 4; kk++) wgmma_ss_n128_tb(acc, da0 + ((kk >> 1) * 512 + (kk & 1) * 128), db0 + ((kk >> 1) * 512 + (kk & 1) * 128), (u | kk) ? 1 : 0);
                WG_COMMIT();
                wg_wait<1>();
                if (warp == 0 && !(u & 1)) PROF2(3, 16 + (u >> 1));
                if (lane < 2 && u > 0 && u + 4 < 28) mbar_arrive_cluster(e_cl + p0 * 8, 1);
                p0 = sg;
                sg = next_st2(sg);
            }
            wg_wait<0>();
            PROFW(27, 0);
            mbar_wait(sb + SM_BARS + B_XR * 8, 0);
            const int r0 = wgi * 64 + warp4 * 16 + g;
            const float2 st0 = lds64f(sb + SM_STATS + r0 * 8), st1 = lds64f(sb + SM_STATS + (r0 + 8) * 8);
            const uint32_t m0 = __float_as_uint(st0.x), m1 = __float_as_uint(st1.x);
            const uint32_t xrow0 = sb + SM_XE + r0 * 128 + c * 4;
            const int mi = lane >> 3, lr = lane & 7;
            const uint32_t yaddr = sb + SM_YT + wgi * 16384 + ((mi >> 1) * 8 + lr) * 128 + (((2 * warp4 + (mi & 1)) ^ lr) << 4);
            uint32_t y[8][4], xv[16][2], nv[16][2], bv[16][2];
            #pragma unroll
            for (int t = 0; t < 16; t++) {
                const uint32_t off = (t >> 3) * 16384 + (((t & 7) ^ g) << 4);
                xv[t][0] = lds32(xrow0 + off); xv[t][1] = lds32(xrow0 + 1024 + off);
            }
            #pragma unroll
            for (int t = 0; t < 16; t++) {
                const uint32_t d0 = bsub2(xv[t][0], m0), d1 = bsub2(xv[t][1], m1);
                nv[t][0] = pack_bf(bf_lo(d0) * st0.y, bf_hi(d0) * st0.y); nv[t][1] = pack_bf(bf_lo(d1) * st1.y, bf_hi(d1) * st1.y);
                bv[t][0] = pack_bf(acc[4 * t], acc[4 * t + 1]); bv[t][1] = pack_bf(acc[4 * t + 2], acc[4 * t + 3]);
            }
            mbar_wait(sb + SM_BARS + B_YT * 8, 0);
            PROFW(28, 0);
            #pragma unroll
            for (int t2 = 0; t2 < 8; t2++)
                asm volatile("ldmatrix.sync.aligned.m8n8.x4.trans.shared.b16 {%0,%1,%2,%3}, [%4];"
                    : "=r"(y[t2][0]), "=r"(y[t2][1]), "=r"(y[t2][2]), "=r"(y[t2][3]) : "r"(yaddr + t2 * 2048) : "memory");
            #pragma unroll
            for (int t = 0; t < 16; t++) {
                const uint32_t off = (t >> 3) * 16384 + (((t & 7) ^ g) << 4);
                sts32(xrow0 + off, badd2(badd2(xv[t][0], bmul2(nv[t][0], y[t >> 1][2 * (t & 1)])), bv[t][0]));
                sts32(xrow0 + 1024 + off, badd2(badd2(xv[t][1], bmul2(nv[t][1], y[t >> 1][2 * (t & 1) + 1])), bv[t][1]));
            }
            asm volatile("fence.proxy.async.shared::cta;" ::: "memory");
            named_bar(1 + wgi, 128);
            if ((tid & 127) == 0) {
                tma2d_store(&p.tm_out, 128 * cb, 128 * i + 64 * wgi, sb + SM_XE + wgi * 8192);
                tma2d_store(&p.tm_out, 128 * cb + 64, 128 * i + 64 * wgi, sb + SM_XE + 16384 + wgi * 8192);
                asm volatile("cp.async.bulk.commit_group;" ::: "memory");
                asm volatile("cp.async.bulk.wait_group.read 0;" ::: "memory");
                PROFW(29, 0);
            }
        }
    } else {
        asm volatile("setmaxnreg.dec.sync.aligned.u32 104;");
        if (warp == 8) {
            int st = 0; uint32_t eph = 7;
            #pragma unroll 1
            for (int it = 0; it < 16; it++) {
                const int pass = it >> 3, sl = it & 7;
                const int nb = pass ? 3 : 4;
                const CUtensorMap* tm = pass ? (rank ? &p.tm_uB : &p.tm_gB) : (rank ? &p.tm_uA : &p.tm_gA);
                mbar_wait(sb + SM_BARS + (B_EMPTY + st) * 8, (eph >> st) & 1);
                eph ^= 1u << st;
                if (it == 1) mbar_wait(sb + SM_BARS + (B_XFULL + 2) * 8, 0);
                PROF2(0, it);
                if (elect_one()) {
                    mbar_expect_tx(sb + SM_BARS + (B_FULL + st) * 8, nb * 8192);
                    tma3d_mc(sb + SM_RING + st * STAGE_BYTES + rank * nb * 4096, tm, 0, ((sl + 2 * cb + 2) & 7) * 64, 7 * j + 4 * pass, sb + SM_BARS + (B_FULL + st) * 8);
                }
                st = (st == 2) ? 0 : st + 1;
            }
            if (!convCTA) {
                st = 3;
                int f0 = 32 * rank, t3 = rank;
                #pragma unroll 1
                for (int u = 0; u < 28; u++) {
                    const uint32_t bar = sb + SM_BARS + (B_FULL + st) * 8;
                    mbar_wait(sb + SM_BARS + (B_EMPTY + st) * 8, (eph >> st) & 1);
                    eph ^= 1u << st;
                    if ((u & 1) == 0) PROF2(0, 16 + (u >> 1));
                    if (elect_one()) {
                        mbar_expect_tx(bar, 32768);
                        tma3d_mc(sb + stage_off_rt(st) + rank * 8192, &p.tm_w2, 0, f0, 2 * cb, bar);
                    }
                    st = next_st2(st);
                    if (u < 15) f0 += (u & 1) ? 160 : 64;
                    else if (u == 15) f0 = 128 + 32 * rank;
                    else { f0 += (t3 == 0) ? 64 : 192; t3 = (t3 == 0) ? 2 : t3 - 1; }
                }
                PROF(48);
            }
        } else if (warp < 11) {
            mbar_wait(sb + SM_BARS + (B_XFULL + 3) * 8, 0);
            #pragma unroll 1
            for (int rnd = 0; rnd < 2; rnd++) {
                const int tt = (tid - 288) + 64 * rnd;
                uint32_t sk[4][2];
                uint4 skw[2];
                skw[0] = ldg_nc128(p.shift_k + 16 * tt); skw[1] = ldg_nc128(p.shift_k + 16 * tt + 8);
                const __nv_bfloat16* kp = p.k + (size_t)(16 * b) * DM + 4 * tt;
                const __nv_bfloat16* vp = p.v + (size_t)(16 * b) * DM + 4 * tt;
                uint2 kr[19];
                uint2 kv[16];
                #pragma unroll
                for (int r = 0; r < 3; r++) kr[r] = (b > 0) ? ldg_nc64(kp + (r - 3) * DM) : make_uint2(0, 0);
                #pragma unroll
                for (int r = 0; r < 16; r++) { kr[3 + r] = ldg_nc64(kp + r * DM); if (r < 10) kv[r] = ldg_nc64(vp + r * DM); }
                {
                    const uint4 w0 = skw[0], w1 = skw[1];
                    sk[0][0] = __byte_perm(w0.x, w0.z, 0x5410); sk[1][0] = __byte_perm(w0.x, w0.z, 0x7632);
                    sk[2][0] = __byte_perm(w0.y, w0.w, 0x5410); sk[3][0] = __byte_perm(w0.y, w0.w, 0x7632);
                    sk[0][1] = __byte_perm(w1.x, w1.z, 0x5410); sk[1][1] = __byte_perm(w1.x, w1.z, 0x7632);
                    sk[2][1] = __byte_perm(w1.y, w1.w, 0x5410); sk[3][1] = __byte_perm(w1.y, w1.w, 0x7632);
                }
                #pragma unroll
                for (int s = 0; s < 16; s++) {
                    uint32_t a = bmul2(kr[s].x, sk[3][0]);
                    a = badd2(a, bmul2(kr[s + 1].x, sk[2][0]));
                    a = badd2(a, bmul2(kr[s + 2].x, sk[1][0]));
                    a = badd2(a, bmul2(kr[s + 3].x, sk[0][0]));
                    kv[s].x = bmul2(a, kv[s].x);
                    a = bmul2(kr[s].y, sk[3][1]);
                    a = badd2(a, bmul2(kr[s + 1].y, sk[2][1]));
                    a = badd2(a, bmul2(kr[s + 2].y, sk[1][1]));
                    a = badd2(a, bmul2(kr[s + 3].y, sk[0][1]));
                    kv[s].y = bmul2(a, kv[s].y);
                    if (s < 6) kv[10 + s] = ldg_nc64(vp + (10 + s) * DM);
                }
                PROFW(57 + 2 * rnd, 9);
                #pragma unroll
                for (int cc = 0; cc < 4; cc++) {
                    const uint32_t sel = (cc & 1) ? 0x7632 : 0x5410;
                    #define KVW(r) ((cc & 2) ? kv[r].y : kv[r].x)
                    uint4* dst = (uint4*)(g_kvT + (size_t)(4 * tt + cc) * SEQ + 16 * b);
                    dst[0] = make_uint4(__byte_perm(KVW(15), KVW(14), sel), __byte_perm(KVW(13), KVW(12), sel),
                                        __byte_perm(KVW(11), KVW(10), sel), __byte_perm(KVW(9), KVW(8), sel));
                    dst[1] = make_uint4(__byte_perm(KVW(7), KVW(6), sel), __byte_perm(KVW(5), KVW(4), sel),
                                        __byte_perm(KVW(3), KVW(2), sel), __byte_perm(KVW(1), KVW(0), sel));
                    #undef KVW
                }
                PROFW(58 + 2 * rnd, 9);
            }
            asm volatile("fence.proxy.async.global;" ::: "memory");
            __syncwarp();
            if (lane == 0) {
                flag_add(&g_cnt_kv[0]);
                PROFW(50, 9);
                const int wgi = warp - 9;
                mbar_wait(sb + SM_BARS + (B_HD + wgi * 2) * 8, 0);
                flag_add(&g_flag_h[(i * 2 + 0) * 8]);
                mbar_wait(sb + SM_BARS + (B_HD + wgi * 2 + 1) * 8, 0);
                flag_add(&g_flag_h[(i * 2 + 1) * 8]);
                if (wgi == 1 && convCTA) {
                    mbar_wait(sb + SM_BARS + B_YST * 8, 0);
                    flag_add(&g_cnt_y[(cidx >> 4) * 32]);
                    PROF(46);
                }
                if (wgi == 1 && !convCTA) {
                    const unsigned ep = lds32(sb + SM_EPOCH);
                    mbar_wait(sb + SM_BARS + B_G1DONE * 8, 0);
                    mbar_expect_tx(sb + SM_BARS + B_XR * 8, 32768);
                    for (int q = 0; q < 4; q++)
                        tma2d(sb + SM_XE + q * 8192, &p.tm_xe, 128 * cb + 64 * (q >> 1), 128 * i + 64 * (q & 1), sb + SM_BARS + B_XR * 8);
                    flag_wait(&g_flag_h[(i * 2 + 1) * 8], ep * 16);
                    mbar_arrive(sb + SM_BARS + (B_HRDY + 1) * 8);
                    __nanosleep(3000);
                    flag_wait(&g_cnt_y[cb * 32], ep * 16);
                    PROF(49);
                    asm volatile("fence.proxy.async.global;" ::: "memory");
                    mbar_expect_tx(sb + SM_BARS + B_YT * 8, 32768);
                    tma2d(sb + SM_YT, &p.tm_yT, 128 * i, 128 * cb, sb + SM_BARS + B_YT * 8);
                    tma2d(sb + SM_YT + 16384, &p.tm_yT, 128 * i + 64, 128 * cb, sb + SM_BARS + B_YT * 8);
                }
            }
        } else {
            if (lane == 0) {
                const unsigned ep = g_launch[b] + 1;
                g_launch[b] = ep;
                sts32(sb + SM_EPOCH, ep);
                tmap_prefetch(rank ? &p.tm_uA : &p.tm_gA);
                mbar_wait(sb + SM_BARS + (B_XFULL + 1) * 8, 0);
                l2_prefetch(p.wg + (size_t)b * (FF * DM / NCTA), FF * DM / NCTA * 2);
                l2_prefetch(p.wu + (size_t)b * (FF * DM / NCTA), FF * DM / NCTA * 2);
                tmap_prefetch(rank ? &p.tm_uB : &p.tm_gB);
                tmap_prefetch(&p.tm_w2); tmap_prefetch(&p.tm_yT); tmap_prefetch(&p.tm_out); tmap_prefetch(&p.tm_xe);
                mbar_wait(sb + SM_BARS + (B_FULL + 2) * 8, 0);
                l2_prefetch(p.ssm_k + (size_t)(4 * b) * SEQ, 4 * SEQ * 2);
                l2_prefetch(p.wd + (size_t)b * (FF * DM / NCTA), FF * DM / NCTA * 2);
                mbar_wait(sb + SM_BARS + (B_HD + 0) * 8, 0);
                if (convCTA) {
                    flag_wait(&g_cnt_kv[0], ep * 256);
                    asm volatile("fence.proxy.async.global;" ::: "memory");
                    PROF(53);
                    mbar_wait(sb + SM_BARS + B_XFREE * 8, 0);
                    PROF(54);
                    mbar_expect_tx(sb + SM_BARS + B_CONV * 8, 65536);
                    bulk_g2s(sb + SM_CVX, g_kvT + (size_t)(8 * cidx) * SEQ, 32768, sb + SM_BARS + B_CONV * 8);
                    bulk_g2s(sb + SM_CVH, p.ssm_k + (size_t)(8 * cidx) * SEQ, 32768, sb + SM_BARS + B_CONV * 8);
                } else {
                    flag_wait(&g_flag_h[(i * 2 + 0) * 8], ep * 16);
                }
            }
            __syncwarp();
            if (!convCTA) {
                asm volatile("fence.proxy.async.global;" ::: "memory");
                int st = 3; uint32_t eph = 1;
                const uint8_t* hsrc = (const uint8_t*)g_h + (size_t)i * 56 * 8192;
                #pragma unroll 1
                for (int u = 0; u < 28; u++) {
                    mbar_wait(sb + SM_BARS + (B_EMPTY + st) * 8, (eph >> st) & 1);
                    eph ^= 1u << st;
                    if (u == 16) {
                        mbar_wait(sb + SM_BARS + (B_HRDY + 1) * 8, 0);
                        asm volatile("fence.proxy.async.global;" ::: "memory");
                    }
                    if (elect_one()) bulk_g2s(sb + stage_off_rt(st) + 16384, hsrc + u * 16384, 16384, sb + SM_BARS + (B_FULL + st) * 8);
                    st = next_st2(st);
                }
            }
        }
    }
}

typedef CUresult (*EncodeFn)(CUtensorMap*, CUtensorMapDataType, cuuint32_t, void*, const cuuint64_t*, const cuuint64_t*,
                             const cuuint32_t*, const cuuint32_t*, CUtensorMapInterleave, CUtensorMapSwizzle,
                             CUtensorMapL2promotion, CUtensorMapFloatOOBfill);

void encode(EncodeFn fn, CUtensorMap* tm, const void* base, int rank, const cuuint64_t* dims, const cuuint64_t* strides,
            const cuuint32_t* box, CUtensorMapSwizzle swz) {
    cuuint32_t es[5] = {1, 1, 1, 1, 1};
    fn(tm, CU_TENSOR_MAP_DATA_TYPE_BFLOAT16, rank, (void*)base, dims, strides, box, es, CU_TENSOR_MAP_INTERLEAVE_NONE, swz,
       CU_TENSOR_MAP_L2_PROMOTION_L2_128B, CU_TENSOR_MAP_FLOAT_OOB_FILL_NONE);
}

}

extern "C" void kernel_launch(void* const* d_in, const int* in_sizes, int n_in, void* d_out, int out_size) {
    (void)in_sizes; (void)n_in; (void)out_size;
    static EncodeFn enc = nullptr;
    static void* yT_ptr = nullptr;
    if (!enc) {
        void* fn = nullptr; cudaDriverEntryPointQueryResult qr;
        cudaGetDriverEntryPoint("cuTensorMapEncodeTiled", &fn, cudaEnableDefault, &qr);
        enc = (EncodeFn)fn;
        cudaGetSymbolAddress(&yT_ptr, g_yT);
        cudaFuncSetAttribute(fused_kernel, cudaFuncAttributeMaxDynamicSharedMemorySize, SM_TOTAL);
    }
    Params p;
    p.q = (const __nv_bfloat16*)d_in[0]; p.k = (const __nv_bfloat16*)d_in[1]; p.v = (const __nv_bfloat16*)d_in[2];
    p.shift_k = (const __nv_bfloat16*)d_in[3]; p.ssm_k = (const __nv_bfloat16*)d_in[4]; p.ssm_D = (const __nv_bfloat16*)d_in[5];
    p.wg = (const __nv_bfloat16*)d_in[7]; p.wu = (const __nv_bfloat16*)d_in[8]; p.wd = (const __nv_bfloat16*)d_in[9];
    {
        cuuint64_t dims[2] = {DM, SEQ}; cuuint64_t str[1] = {DM * 2};
        cuuint32_t box[2] = {64, 32};
        encode(enc, &p.tm_x, p.q, 2, dims, str, box, CU_TENSOR_MAP_SWIZZLE_128B);
        cuuint32_t box2[2] = {64, 64};
        encode(enc, &p.tm_out, d_out, 2, dims, str, box2, CU_TENSOR_MAP_SWIZZLE_128B);
        encode(enc, &p.tm_xe, p.q, 2, dims, str, box2, CU_TENSOR_MAP_SWIZZLE_128B);
    }
    {
        cuuint64_t dims[3] = {32, DM, FF / 32}; cuuint64_t str[2] = {FF * 2, 64};
        cuuint32_t boxA[3] = {32, 64, 4}, boxB[3] = {32, 64, 3};
        encode(enc, &p.tm_gA, p.wg, 3, dims, str, boxA, CU_TENSOR_MAP_SWIZZLE_64B);
        encode(enc, &p.tm_gB, p.wg, 3, dims, str, boxB, CU_TENSOR_MAP_SWIZZLE_64B);
        encode(enc, &p.tm_uA, p.wu, 3, dims, str, boxA, CU_TENSOR_MAP_SWIZZLE_64B);
        encode(enc, &p.tm_uB, p.wu, 3, dims, str, boxB, CU_TENSOR_MAP_SWIZZLE_64B);
    }
    {
        cuuint64_t dims[3] = {64, FF, DM / 64}; cuuint64_t str[2] = {DM * 2, 128};
        cuuint32_t box[3] = {64, 32, 2};
        encode(enc, &p.tm_w2, p.wd, 3, dims, str, box, CU_TENSOR_MAP_SWIZZLE_128B);
    }
    {
        cuuint64_t dims[2] = {SEQ, DM}; cuuint64_t str[1] = {SEQ * 2};
        cuuint32_t box[2] = {64, 128};
        encode(enc, &p.tm_yT, yT_ptr, 2, dims, str, box, CU_TENSOR_MAP_SWIZZLE_128B);
    }
    fused_kernel<<<NCTA, NTHREADS, SM_TOTAL>>>(p);
}
```

```cpp
#include <cuda_runtime.h>
#include <cuda_bf16.h>
#include <cuda.h>
#include <stdint.h>

namespace {

constexpr int SEQ = 2048, DM = 512, FF = 1792;
constexpr int NCTA = 128;
constexpr int NTHREADS = 384;
constexpr int STAGE_BYTES = 32768;

constexpr uint32_t SM_X = 0;
constexpr uint32_t SM_RING = 131072;
constexpr uint32_t SM_MISC = SM_RING + 3 * STAGE_BYTES;
constexpr uint32_t SM_BARS = SM_MISC;
constexpr uint32_t SM_EPOCH = SM_MISC + 248;
constexpr uint32_t SM_STATS = SM_MISC + 256;
constexpr uint32_t SM_TOTAL = SM_STATS + 1024;
static_assert(SM_TOTAL <= 232448, "smem");
constexpr uint32_t SM_CVX = 0;
constexpr uint32_t SM_CVH = 32768;
constexpr uint32_t SM_YT = 4 * 16384;
constexpr uint32_t SM_XE = 6 * 16384;

constexpr int B_FULL = 0, B_EMPTY = 5, B_XFULL = 10, B_CONV = 14, B_YT = 15, B_XR = 16, B_G1DONE = 17, B_HD = 18, B_HRDY = 22,
              B_XFREE = 24, B_YST = 25, B_COUNT = 26;
static_assert(B_COUNT * 8 <= 248, "barrier space");

__device__ __align__(128) uint32_t g_h[16 * 56 * 2048];
__device__ __align__(128) __nv_bfloat16 g_kvT[DM * SEQ];
__device__ __align__(128) __nv_bfloat16 g_yT[DM * SEQ];
__device__ unsigned g_launch[NCTA];
__device__ unsigned g_cnt_kv[32];
__device__ unsigned g_cnt_y[4 * 32];
__device__ unsigned g_flag_h[16 * 2 * 8];

#define PROF(idx)
#define PROF2(a, idx)
#define PROFW(idx, w)

struct Params {
    CUtensorMap tm_x, tm_gA, tm_gB, tm_uA, tm_uB, tm_w2, tm_yT, tm_out, tm_xe;
    const __nv_bfloat16 *q, *k, *v, *shift_k, *ssm_k, *ssm_D, *wg, *wu, *wd;
};

__device__ __forceinline__ void wgmma_rs_n32(float (&d)[16], uint32_t a0, uint32_t a1, uint32_t a2, uint32_t a3, uint64_t db, int sc) {
  asm volatile("{\n.reg .pred p;\nsetp.ne.b32 p, %21, 0;\n"
    "wgmma.mma_async.sync.aligned.m64n32k16.f32.bf16.bf16 {%0,%1,%2,%3,%4,%5,%6,%7,%8,%9,%10,%11,%12,%13,%14,%15}, {%16,%17,%18,%19}, %20, p, 1, 1, 0;\n}\n"
    : "+f"(d[0]),"+f"(d[1]),"+f"(d[2]),"+f"(d[3]),"+f"(d[4]),"+f"(d[5]),"+f"(d[6]),"+f"(d[7]),"+f"(d[8]),"+f"(d[9]),"+f"(d[10]),"+f"(d[11]),"+f"(d[12]),"+f"(d[13]),"+f"(d[14]),"+f"(d[15])
    : "r"(a0),"r"(a1),"r"(a2),"r"(a3),"l"(db),"r"(sc));
}
__device__ __forceinline__ void wgmma_rs_n128_tb(float (&d)[64], uint32_t a0, uint32_t a1, uint32_t a2, uint32_t a3, uint64_t db, int sc) {
  asm volatile("{\n.reg .pred p;\nsetp.ne.b32 p, %69, 0;\n"
    "wgmma.mma_async.sync.aligned.m64n128k16.f32.bf16.bf16 {%0,%1,%2,%3,%4,%5,%6,%7,%8,%9,%10,%11,%12,%13,%14,%15,%16,%17,%18,%19,%20,%21,%22,%23,%24,%25,%26,%27,%28,%29,%30,%31,%32,%33,%34,%35,%36,%37,%38,%39,%40,%41,%42,%43,%44,%45,%46,%47,%48,%49,%50,%51,%52,%53,%54,%55,%56,%57,%58,%59,%60,%61,%62,%63}, {%64,%65,%66,%67}, %68, p, 1, 1, 1;\n}\n"
    : "+f"(d[0]),"+f"(d[1]),"+f"(d[2]),"+f"(d[3]),"+f"(d[4]),"+f"(d[5]),"+f"(d[6]),"+f"(d[7]),"+f"(d[8]),"+f"(d[9]),"+f"(d[10]),"+f"(d[11]),"+f"(d[12]),"+f"(d[13]),"+f"(d[14]),"+f"(d[15]),"+f"(d[16]),"+f"(d[17]),"+f"(d[18]),"+f"(d[19]),"+f"(d[20]),"+f"(d[21]),"+f"(d[22]),"+f"(d[23]),"+f"(d[24]),"+f"(d[25]),"+f"(d[26]),"+f"(d[27]),"+f"(d[28]),"+f"(d[29]),"+f"(d[30]),"+f"(d[31]),"+f"(d[32]),"+f"(d[33]),"+f"(d[34]),"+f"(d[35]),"+f"(d[36]),"+f"(d[37]),"+f"(d[38]),"+f"(d[39]),"+f"(d[40]),"+f"(d[41]),"+f"(d[42]),"+f"(d[43]),"+f"(d[44]),"+f"(d[45]),"+f"(d[46]),"+f"(d[47]),"+f"(d[48]),"+f"(d[49]),"+f"(d[50]),"+f"(d[51]),"+f"(d[52]),"+f"(d[53]),"+f"(d[54]),"+f"(d[55]),"+f"(d[56]),"+f"(d[57]),"+f"(d[58]),"+f"(d[59]),"+f"(d[60]),"+f"(d[61]),"+f"(d[62]),"+f"(d[63])
    : "r"(a0),"r"(a1),"r"(a2),"r"(a3),"l"(db),"r"(sc));
}
__device__ __forceinline__ void wgmma_ss_n256_tb(float (&d)[128], uint64_t da, uint64_t db, int sc) {
  asm volatile("{\n.reg .pred p;\nsetp.ne.b32 p, %130, 0;\n"
    "wgmma.mma_async.sync.aligned.m64n256k16.f32.bf16.bf16 {%0,%1,%2,%3,%4,%5,%6,%7,%8,%9,%10,%11,%12,%13,%14,%15,%16,%17,%18,%19,%20,%21,%22,%23,%24,%25,%26,%27,%28,%29,%30,%31,%32,%33,%34,%35,%36,%37,%38,%39,%40,%41,%42,%43,%44,%45,%46,%47,%48,%49,%50,%51,%52,%53,%54,%55,%56,%57,%58,%59,%60,%61,%62,%63,%64,%65,%66,%67,%68,%69,%70,%71,%72,%73,%74,%75,%76,%77,%78,%79,%80,%81,%82,%83,%84,%85,%86,%87,%88,%89,%90,%91,%92,%93,%94,%95,%96,%97,%98,%99,%100,%101,%102,%103,%104,%105,%106,%107,%108,%109,%110,%111,%112,%113,%114,%115,%116,%117,%118,%119,%120,%121,%122,%123,%124,%125,%126,%127}, %128, %129, p, 1, 1, 0, 1;\n}\n"
    : "+f"(d[0]),"+f"(d[1]),"+f"(d[2]),"+f"(d[3]),"+f"(d[4]),"+f"(d[5]),"+f"(d[6]),"+f"(d[7]),"+f"(d[8]),"+f"(d[9]),"+f"(d[10]),"+f"(d[11]),"+f"(d[12]),"+f"(d[13]),"+f"(d[14]),"+f"(d[15]),"+f"(d[16]),"+f"(d[17]),"+f"(d[18]),"+f"(d[19]),"+f"(d[20]),"+f"(d[21]),"+f"(d[22]),"+f"(d[23]),"+f"(d[24]),"+f"(d[25]),"+f"(d[26]),"+f"(d[27]),"+f"(d[28]),"+f"(d[29]),"+f"(d[30]),"+f"(d[31]),"+f"(d[32]),"+f"(d[33]),"+f"(d[34]),"+f"(d[35]),"+f"(d[36]),"+f"(d[37]),"+f"(d[38]),"+f"(d[39]),"+f"(d[40]),"+f"(d[41]),"+f"(d[42]),"+f"(d[43]),"+f"(d[44]),"+f"(d[45]),"+f"(d[46]),"+f"(d[47]),"+f"(d[48]),"+f"(d[49]),"+f"(d[50]),"+f"(d[51]),"+f"(d[52]),"+f"(d[53]),"+f"(d[54]),"+f"(d[55]),"+f"(d[56]),"+f"(d[57]),"+f"(d[58]),"+f"(d[59]),"+f"(d[60]),"+f"(d[61]),"+f"(d[62]),"+f"(d[63]),"+f"(d[64]),"+f"(d[65]),"+f"(d[66]),"+f"(d[67]),"+f"(d[68]),"+f"(d[69]),"+f"(d[70]),"+f"(d[71]),"+f"(d[72]),"+f"(d[73]),"+f"(d[74]),"+f"(d[75]),"+f"(d[76]),"+f"(d[77]),"+f"(d[78]),"+f"(d[79]),"+f"(d[80]),"+f"(d[81]),"+f"(d[82]),"+f"(d[83]),"+f"(d[84]),"+f"(d[85]),"+f"(d[86]),"+f"(d[87]),"+f"(d[88]),"+f"(d[89]),"+f"(d[90]),"+f"(d[91]),"+f"(d[92]),"+f"(d[93]),"+f"(d[94]),"+f"(d[95]),"+f"(d[96]),"+f"(d[97]),"+f"(d[98]),"+f"(d[99]),"+f"(d[100]),"+f"(d[101]),"+f"(d[102]),"+f"(d[103]),"+f"(d[104]),"+f"(d[105]),"+f"(d[106]),"+f"(d[107]),"+f"(d[108]),"+f"(d[109]),"+f"(d[110]),"+f"(d[111]),"+f"(d[112]),"+f"(d[113]),"+f"(d[114]),"+f"(d[115]),"+f"(d[116]),"+f"(d[117]),"+f"(d[118]),"+f"(d[119]),"+f"(d[120]),"+f"(d[121]),"+f"(d[122]),"+f"(d[123]),"+f"(d[124]),"+f"(d[125]),"+f"(d[126]),"+f"(d[127])
    : "l"(da),"l"(db),"r"(sc));
}
__device__ __forceinline__ void wgmma_ss_n192_tb(float (&d)[96], uint64_t da, uint64_t db, int sc) {
  asm volatile("{\n.reg .pred p;\nsetp.ne.b32 p, %98, 0;\n"
    "wgmma.mma_async.sync.aligned.m64n192k16.f32.bf16.bf16 {%0,%1,%2,%3,%4,%5,%6,%7,%8,%9,%10,%11,%12,%13,%14,%15,%16,%17,%18,%19,%20,%21,%22,%23,%24,%25,%26,%27,%28,%29,%30,%31,%32,%33,%34,%35,%36,%37,%38,%39,%40,%41,%42,%43,%44,%45,%46,%47,%48,%49,%50,%51,%52,%53,%54,%55,%56,%57,%58,%59,%60,%61,%62,%63,%64,%65,%66,%67,%68,%69,%70,%71,%72,%73,%74,%75,%76,%77,%78,%79,%80,%81,%82,%83,%84,%85,%86,%87,%88,%89,%90,%91,%92,%93,%94,%95}, %96, %97, p, 1, 1, 0, 1;\n}\n"
    : "+f"(d[0]),"+f"(d[1]),"+f"(d[2]),"+f"(d[3]),"+f"(d[4]),"+f"(d[5]),"+f"(d[6]),"+f"(d[7]),"+f"(d[8]),"+f"(d[9]),"+f"(d[10]),"+f"(d[11]),"+f"(d[12]),"+f"(d[13]),"+f"(d[14]),"+f"(d[15]),"+f"(d[16]),"+f"(d[17]),"+f"(d[18]),"+f"(d[19]),"+f"(d[20]),"+f"(d[21]),"+f"(d[22]),"+f"(d[23]),"+f"(d[24]),"+f"(d[25]),"+f"(d[26]),"+f"(d[27]),"+f"(d[28]),"+f"(d[29]),"+f"(d[30]),"+f"(d[31]),"+f"(d[32]),"+f"(d[33]),"+f"(d[34]),"+f"(d[35]),"+f"(d[36]),"+f"(d[37]),"+f"(d[38]),"+f"(d[39]),"+f"(d[40]),"+f"(d[41]),"+f"(d[42]),"+f"(d[43]),"+f"(d[44]),"+f"(d[45]),"+f"(d[46]),"+f"(d[47]),"+f"(d[48]),"+f"(d[49]),"+f"(d[50]),"+f"(d[51]),"+f"(d[52]),"+f"(d[53]),"+f"(d[54]),"+f"(d[55]),"+f"(d[56]),"+f"(d[57]),"+f"(d[58]),"+f"(d[59]),"+f"(d[60]),"+f"(d[61]),"+f"(d[62]),"+f"(d[63]),"+f"(d[64]),"+f"(d[65]),"+f"(d[66]),"+f"(d[67]),"+f"(d[68]),"+f"(d[69]),"+f"(d[70]),"+f"(d[71]),"+f"(d[72]),"+f"(d[73]),"+f"(d[74]),"+f"(d[75]),"+f"(d[76]),"+f"(d[77]),"+f"(d[78]),"+f"(d[79]),"+f"(d[80]),"+f"(d[81]),"+f"(d[82]),"+f"(d[83]),"+f"(d[84]),"+f"(d[85]),"+f"(d[86]),"+f"(d[87]),"+f"(d[88]),"+f"(d[89]),"+f"(d[90]),"+f"(d[91]),"+f"(d[92]),"+f"(d[93]),"+f"(d[94]),"+f"(d[95])
    : "l"(da),"l"(db),"r"(sc));
}

__device__ __forceinline__ uint32_t smem_u32(const void* p) { return (uint32_t)__cvta_generic_to_shared(p); }
__device__ __forceinline__ void mbar_init(uint32_t bar, uint32_t cnt) { asm volatile("mbarrier.init.shared::cta.b64 [%0], %1;" :: "r"(bar), "r"(cnt)); }
__device__ __forceinline__ void mbar_expect_tx(uint32_t bar, uint32_t bytes) { asm volatile("mbarrier.arrive.expect_tx.shared::cta.b64 _, [%0], %1;" :: "r"(bar), "r"(bytes) : "memory"); }
__device__ __forceinline__ void mbar_arrive(uint32_t bar) { asm volatile("mbarrier.arrive.shared::cta.b64 _, [%0];" :: "r"(bar) : "memory"); }
__device__ __forceinline__ void mbar_arrive_cluster(uint32_t cbar, uint32_t cnt) { asm volatile("mbarrier.arrive.shared::cluster.b64 _, [%0], %1;" :: "r"(cbar), "r"(cnt) : "memory"); }
__device__ __forceinline__ uint32_t mapa(uint32_t a, uint32_t rank) { uint32_t r; asm volatile("mapa.shared::cluster.u32 %0, %1, %2;" : "=r"(r) : "r"(a), "r"(rank)); return r; }
__device__ __forceinline__ void mbar_wait(uint32_t bar, uint32_t parity) {
    uint32_t ok; uint32_t n = 0;
    do {
        asm volatile("{\n.reg .pred p;\nmbarrier.try_wait.parity.shared::cta.b64 p, [%1], %2;\nselp.u32 %0, 1, 0, p;\n}" : "=r"(ok) : "r"(bar), "r"(parity) : "memory");
    } while (!ok && ++n < (1u << 17));
}
__device__ __forceinline__ void pace_wait(uint32_t a, uint32_t target) {
    uint32_t v, n = 0;
    do {
        asm volatile("ld.volatile.shared.u32 %0, [%1];" : "=r"(v) : "r"(a) : "memory");
        if (v < target) __nanosleep(150);
    } while (v < target && ++n < (1u << 14));
}
__device__ __forceinline__ void flag_wait(const unsigned* p, unsigned target) {
    unsigned v; uint32_t n = 0;
    while (true) {
        asm volatile("ld.acquire.gpu.global.u32 %0, [%1];" : "=r"(v) : "l"(p) : "memory");
        if ((int)(v - target) >= 0 || ++n >= (1u << 17)) break;
        __nanosleep(100);
    }
}
__device__ __forceinline__ void flag_add(unsigned* p) {
    asm volatile("fence.acq_rel.gpu;\nred.relaxed.gpu.global.add.u32 [%0], 1;" :: "l"(p) : "memory");
}
__device__ __forceinline__ uint64_t make_desc(uint32_t addr, uint32_t lbo, uint32_t sbo, uint32_t swz) {
    return (uint64_t)((addr & 0x3FFFF) >> 4) | ((uint64_t)((lbo & 0x3FFFF) >> 4) << 16) | ((uint64_t)((sbo & 0x3FFFF) >> 4) << 32) | ((uint64_t)swz << 62);
}
__device__ __forceinline__ uint64_t desc_add(uint64_t d, uint32_t off16) {
    return (d & 0xFFFFFFFF00000000ull) | (uint64_t)((uint32_t)d + off16);
}
__device__ __forceinline__ void tma2d(uint32_t dst, const CUtensorMap* tm, int c0, int c1, uint32_t bar) {
    asm volatile("cp.async.bulk.tensor.2d.shared::cluster.global.mbarrier::complete_tx::bytes [%0], [%1, {%3, %4}], [%2];"
        :: "r"(dst), "l"((uint64_t)tm), "r"(bar), "r"(c0), "r"(c1) : "memory");
}
__device__ __forceinline__ void tma3d_mc(uint32_t dst, const CUtensorMap* tm, int c0, int c1, int c2, uint32_t bar) {
    asm volatile("cp.async.bulk.tensor.3d.shared::cluster.global.mbarrier::complete_tx::bytes.multicast::cluster [%0], [%1, {%3, %4, %5}], [%2], %6;"
        :: "r"(dst), "l"((uint64_t)tm), "r"(bar), "r"(c0), "r"(c1), "r"(c2), "h"((uint16_t)3) : "memory");
}
__device__ __forceinline__ void bulk_g2s(uint32_t dst, const void* src, uint32_t bytes, uint32_t bar) {
    asm volatile("cp.async.bulk.shared::cluster.global.mbarrier::complete_tx::bytes [%0], [%1], %2, [%3];"
        :: "r"(dst), "l"(src), "r"(bytes), "r"(bar) : "memory");
}
__device__ __forceinline__ void bulk_s2g(void* dst, uint32_t src, uint32_t bytes) {
    asm volatile("cp.async.bulk.global.shared::cta.bulk_group [%0], [%1], %2;" :: "l"(dst), "r"(src), "r"(bytes) : "memory");
}
__device__ __forceinline__ void tma2d_store(const CUtensorMap* tm, int c0, int c1, uint32_t src) {
    asm volatile("cp.async.bulk.tensor.2d.global.shared::cta.bulk_group [%0, {%2, %3}], [%1];"
        :: "l"((uint64_t)tm), "r"(src), "r"(c0), "r"(c1) : "memory");
}
__device__ __forceinline__ void l2_prefetch(const void* p, uint32_t bytes) {
    asm volatile("cp.async.bulk.prefetch.L2.global [%0], %1;" :: "l"(p), "r"(bytes) : "memory");
}
__device__ __forceinline__ void tmap_prefetch(const CUtensorMap* tm) { asm volatile("prefetch.tensormap [%0];" :: "l"((uint64_t)tm) : "memory"); }
__device__ __forceinline__ uint32_t lds32(uint32_t a) { uint32_t v; asm volatile("ld.shared.u32 %0, [%1];" : "=r"(v) : "r"(a)); return v; }
__device__ __forceinline__ uint2 lds64(uint32_t a) { uint2 v; asm volatile("ld.shared.v2.u32 {%0,%1}, [%2];" : "=r"(v.x), "=r"(v.y) : "r"(a)); return v; }
__device__ __forceinline__ uint4 lds128(uint32_t a) { uint4 v; asm volatile("ld.shared.v4.u32 {%0,%1,%2,%3}, [%4];" : "=r"(v.x), "=r"(v.y), "=r"(v.z), "=r"(v.w) : "r"(a)); return v; }
__device__ __forceinline__ float2 lds64f(uint32_t a) { float2 v; asm volatile("ld.shared.v2.f32 {%0,%1}, [%2];" : "=f"(v.x), "=f"(v.y) : "r"(a)); return v; }
__device__ __forceinline__ void sts32(uint32_t a, uint32_t v) { asm volatile("st.shared.u32 [%0], %1;" :: "r"(a), "r"(v) : "memory"); }
__device__ __forceinline__ void sts128(uint32_t a, uint4 v) { asm volatile("st.shared.v4.u32 [%0], {%1,%2,%3,%4};" :: "r"(a), "r"(v.x), "r"(v.y), "r"(v.z), "r"(v.w) : "memory"); }
__device__ __forceinline__ uint4 ldg_cg128(const void* p) { uint4 v; asm volatile("ld.global.cg.v4.u32 {%0,%1,%2,%3}, [%4];" : "=r"(v.x), "=r"(v.y), "=r"(v.z), "=r"(v.w) : "l"(p)); return v; }
__device__ __forceinline__ uint4 ldg_nc128(const void* p) { uint4 v; asm volatile("ld.global.nc.L1::no_allocate.v4.u32 {%0,%1,%2,%3}, [%4];" : "=r"(v.x), "=r"(v.y), "=r"(v.z), "=r"(v.w) : "l"(p)); return v; }
__device__ __forceinline__ uint2 ldg_nc64(const void* p) { uint2 v; asm volatile("ld.global.nc.L1::no_allocate.v2.u32 {%0,%1}, [%2];" : "=r"(v.x), "=r"(v.y) : "l"(p)); return v; }
#define WG_FENCE() asm volatile("wgmma.fence.sync.aligned;\n" ::: "memory")
#define WG_COMMIT() asm volatile("wgmma.commit_group.sync.aligned;\n" ::: "memory")
template<int N> __device__ __forceinline__ void wg_wait() { asm volatile("wgmma.wait_group.sync.aligned %0;\n" :: "n"(N) : "memory"); }
__device__ __forceinline__ bool elect_one() {
    uint32_t pr;
    asm volatile("{\n.reg .pred p;\nelect.sync _|p, 0xffffffff;\nselp.u32 %0, 1, 0, p;\n}" : "=r"(pr));
    return pr != 0;
}
__device__ __forceinline__ void named_bar(int id, int n) { asm volatile("bar.sync %0, %1;" :: "r"(id), "r"(n) : "memory"); }

__device__ __forceinline__ float bf_lo(uint32_t u) { return __uint_as_float(u << 16); }
__device__ __forceinline__ float bf_hi(uint32_t u) { return __uint_as_float(u & 0xFFFF0000u); }
__device__ __forceinline__ uint32_t pack_bf(float lo, float hi) { uint32_t r; asm("cvt.rn.bf16x2.f32 %0, %1, %2;" : "=r"(r) : "f"(hi), "f"(lo)); return r; }
__device__ __forceinline__ float bf_round(float x) { return __bfloat162float(__float2bfloat16_rn(x)); }
__device__ __forceinline__ uint32_t bmul2(uint32_t a, uint32_t b) { uint32_t r; asm("mul.rn.bf16x2 %0, %1, %2;" : "=r"(r) : "r"(a), "r"(b)); return r; }
__device__ __forceinline__ uint32_t badd2(uint32_t a, uint32_t b) { uint32_t r; asm("add.rn.bf16x2 %0, %1, %2;" : "=r"(r) : "r"(a), "r"(b)); return r; }
__device__ __forceinline__ uint32_t bsub2(uint32_t a, uint32_t b) { uint32_t r; asm("sub.rn.bf16x2 %0, %1, %2;" : "=r"(r) : "r"(a), "r"(b)); return r; }
__device__ __forceinline__ void mma16816(float (&d)[4], uint32_t a0, uint32_t a1, uint32_t a2, uint32_t a3, uint2 b) {
    asm volatile("mma.sync.aligned.m16n8k16.row.col.f32.bf16.bf16.f32 {%0,%1,%2,%3}, {%4,%5,%6,%7}, {%8,%9}, {%0,%1,%2,%3};\n"
        : "+f"(d[0]), "+f"(d[1]), "+f"(d[2]), "+f"(d[3]) : "r"(a0), "r"(a1), "r"(a2), "r"(a3), "r"(b.x), "r"(b.y));
}

template<int HS> __device__ __forceinline__ void xreduce(float (&v)[8], int lane) {
    const int up = lane & HS;
    #pragma unroll
    for (int e = 0; e < HS; e++) {
        float keep, send;
        asm("{\n.reg .pred p;\nsetp.ne.b32 p, %4, 0;\nselp.f32 %0, %3, %2, p;\nselp.f32 %1, %2, %3, p;\n}"
            : "=f"(keep), "=f"(send) : "f"(v[e]), "f"(v[e + HS]), "r"(up));
        v[e] = keep + __shfl_xor_sync(0xffffffffu, send, HS);
    }
}

__device__ __forceinline__ int blk_f0(int bi, int j) {
    if (bi < 32) return 224 * ((j + (bi >> 2)) & 7) + 32 * (bi & 3);
    int b2 = bi - 32; int q3 = (b2 * 11) >> 5;
    return 224 * ((j + q3) & 7) + 128 + 32 * (b2 - 3 * q3);
}
__device__ __forceinline__ int next_st2(int s) { return (0x14023 >> (4 * s)) & 7; }
__device__ __forceinline__ uint32_t stage_off_rt(int s) { return s < 3 ? SM_RING + s * STAGE_BYTES : (uint32_t)(s - 3) * STAGE_BYTES; }

template<int NB>
__device__ __forceinline__ void gemm1_pass(uint32_t sb, int wgi, int warp4, int lane, int& st, uint32_t& fph, uint32_t e_cl,
                                           int rb64, int ks0, bool convCTA) {
    constexpr bool passA = (NB == 4);
    float acc[NB * 32];
    const uint64_t descA0 = make_desc(sb + SM_X + wgi * 8192, 16, 1024, 1);
    const uint64_t descB0 = make_desc(sb + SM_RING, 4096, 512, 2);
    int prev = 0;
    #pragma unroll 1
    for (int sl = 0; sl < 8; sl++) {
        if (warp4 == 0 && wgi == 0) PROF2(2, sl + (passA ? 0 : 8));
        mbar_wait(sb + SM_BARS + (B_FULL + st) * 8, (fph >> st) & 1);
        fph ^= 1u << st;
        if (sl == 0 && warp4 == 0) PROF(2 + wgi * 8 + (passA ? 0 : 3));
        if (warp4 == 0 && wgi == 0) PROF2(1, sl + (passA ? 0 : 8));
        const uint64_t da = desc_add(descA0, sl * 1024), db = desc_add(descB0, st * 2048);
        WG_FENCE();
        #pragma unroll
        for (int kk = 0; kk < 4; kk++) {
            int sc = (sl | kk) ? 1 : 0;
            if constexpr (NB == 4) wgmma_ss_n256_tb(acc, da + kk * 2, db + kk * 64, sc); else wgmma_ss_n192_tb(acc, da + kk * 2, db + kk * 64, sc);
        }
        WG_COMMIT();
        wg_wait<1>();
        if (warp4 == 0 && wgi == 0) PROF2(3, sl + (passA ? 0 : 8));
        if (lane < 2 && sl && (passA || !convCTA || sl < 6)) mbar_arrive_cluster(e_cl + prev * 8, 1);
        if (!passA) {
            if (convCTA) { if (sl == 4 && lane == 0) mbar_arrive(sb + SM_BARS + B_XFREE * 8); }
            else if ((sl == 2 || sl == 4) && lane < 2) mbar_arrive_cluster(e_cl + (2 + (sl >> 1)) * 8, 1);
        }
        prev = st;
        st = (st == 2) ? 0 : st + 1;
    }
    wg_wait<0>();
    if (lane < 2 && (passA || !convCTA)) mbar_arrive_cluster(e_cl + prev * 8, 1);
    if (!passA && lane == 0) mbar_arrive(sb + SM_BARS + B_G1DONE * 8);
    if (warp4 == 0) PROF(3 + wgi * 8 + (passA ? 0 : 3));
    const int g = lane >> 2;
    const int r0 = wgi * 64 + warp4 * 16 + g;
    const float s0 = __uint_as_float(lds32(sb + SM_STATS + r0 * 8 + 4)), s1 = __uint_as_float(lds32(sb + SM_STATS + (r0 + 8) * 8 + 4));
    uint32_t* dst = g_h + (size_t)((rb64 >> 1) * 56 + ks0) * 2048 + wgi * 1024 + warp4 * 128 + lane;
    #pragma unroll
    for (int kk = 0; kk < NB * 2; kk++) {
        uint32_t h[4];
        #pragma unroll
        for (int tt = 0; tt < 2; tt++) {
            const int t = 2 * kk + tt;
            const float* ag = &acc[4 * t];
            const float* au = &acc[NB * 16 + 4 * t];
            h[2 * tt] = bmul2(pack_bf(ag[0] * s0, ag[1] * s0), pack_bf(au[0] * s0, au[1] * s0));
            h[2 * tt + 1] = bmul2(pack_bf(ag[2] * s1, ag[3] * s1), pack_bf(au[2] * s1, au[3] * s1));
        }
        uint32_t* d2 = dst + (kk >> 1) * 2048 + (kk & 1) * 512;
        d2[0] = h[0]; d2[64] = h[1]; d2[32] = h[2]; d2[96] = h[3];
    }
    __syncwarp();
    if (lane == 0) mbar_arrive(sb + SM_BARS + (B_HD + wgi * 2 + (passA ? 0 : 1)) * 8);
    if (warp4 == 0) PROF(4 + wgi * 8 + (passA ? 0 : 3));
}

__global__ void __cluster_dims__(2, 1, 1) __launch_bounds__(NTHREADS, 1)
fused_kernel(const __grid_constant__ Params p) {
    extern __shared__ __align__(1024) uint8_t smem_raw[];
    const uint32_t sb = smem_u32(smem_raw);
    const int tid = threadIdx.x, warp = tid >> 5, lane = tid & 31;
    const int b = blockIdx.x;
    const int rank = b & 1;
    const int j = (b >> 1) & 7;
    const int i = ((b >> 4) << 1) | rank;
    const int cb = j >> 1;
    const bool convCTA = j & 1;
    const int cidx = 4 * i + cb;

    if (warp == 8 && lane < 4) {
        mbar_init(sb + SM_BARS + (B_XFULL + lane) * 8, 1);
        asm volatile("fence.proxy.async.shared::cta;" ::: "memory");
        mbar_expect_tx(sb + SM_BARS + (B_XFULL + lane) * 8, 32768);
    }
    if (tid == 288) {
        for (int s = 0; s < 5; s++) { mbar_init(sb + SM_BARS + (B_FULL + s) * 8, 1); mbar_init(sb + SM_BARS + (B_EMPTY + s) * 8, 16); }
        mbar_init(sb + SM_BARS + B_CONV * 8, 1);
        mbar_init(sb + SM_BARS + B_YT * 8, 1);
        mbar_init(sb + SM_BARS + B_XR * 8, 1);
        mbar_init(sb + SM_BARS + B_G1DONE * 8, 8);
        mbar_init(sb + SM_BARS + B_XFREE * 8, 8);
        mbar_init(sb + SM_BARS + B_YST * 8, 8);
        for (int s = 0; s < 4; s++) mbar_init(sb + SM_BARS + (B_HD + s) * 8, 4);
        for (int s = 0; s < 2; s++) mbar_init(sb + SM_BARS + (B_HRDY + s) * 8, 1);
        asm volatile("fence.mbarrier_init.release.cluster;" ::: "memory");
        asm volatile("fence.proxy.async.shared::cta;" ::: "memory");
    }
    __syncwarp();
    asm volatile("barrier.cluster.arrive.relaxed.aligned;\n" ::: "memory");
    if (warp == 8) {
        const int rg = lane >> 3, sl = lane & 7;
        tma2d(sb + SM_X + sl * 16384 + rg * 4096, &p.tm_x, 64 * ((sl + 2 * cb + 2) & 7), 128 * i + 32 * rg, sb + SM_BARS + (B_XFULL + rg) * 8);
        __syncwarp();
    }
    asm volatile("barrier.cluster.wait.aligned;\n" ::: "memory");
    PROFW(1, 0);

    if (warp < 8) {
        asm volatile("setmaxnreg.inc.sync.aligned.u32 200;");
        const int wgi = warp >> 2, warp4 = warp & 3;
        const int g = lane >> 2, c = lane & 3;
        const uint32_t e_cl = mapa(sb + SM_BARS + B_EMPTY * 8, lane & 1);
        {
            const int lrow = warp * 4 + (lane >> 3);
            const uint32_t xa = sb + SM_X + lrow * 128 + (((lane & 7) ^ (lrow & 7)) << 4);
            #pragma unroll 1
            for (int rg = 0; rg < 4; rg++) {
                uint4 xr[8];
                mbar_wait(sb + SM_BARS + (B_XFULL + rg) * 8, 0);
                if (rg == 0) PROFW(16, 0);
                if (rg == 3) PROFW(18, 0);
                #pragma unroll
                for (int sl = 0; sl < 8; sl++) xr[sl] = lds128(xa + rg * 4096 + sl * 16384);
                float s0 = 0.f, q0 = 0.f, s1 = 0.f, q1 = 0.f, s2 = 0.f, q2 = 0.f, s3 = 0.f, q3 = 0.f;
                #pragma unroll
                for (int sl = 0; sl < 8; sl++) {
                    float lo = bf_lo(xr[sl].x), hi = bf_hi(xr[sl].x); s0 += lo; q0 = fmaf(lo, lo, q0); s1 += hi; q1 = fmaf(hi, hi, q1);
                    lo = bf_lo(xr[sl].y); hi = bf_hi(xr[sl].y); s2 += lo; q2 = fmaf(lo, lo, q2); s3 += hi; q3 = fmaf(hi, hi, q3);
                    lo = bf_lo(xr[sl].z); hi = bf_hi(xr[sl].z); s0 += lo; q0 = fmaf(lo, lo, q0); s1 += hi; q1 = fmaf(hi, hi, q1);
                    lo = bf_lo(xr[sl].w); hi = bf_hi(xr[sl].w); s2 += lo; q2 = fmaf(lo, lo, q2); s3 += hi; q3 = fmaf(hi, hi, q3);
                }
                float sm = (s0 + s1) + (s2 + s3), sq = (q0 + q1) + (q2 + q3);
                #pragma unroll
                for (int o = 1; o < 8; o <<= 1) { sm += __shfl_xor_sync(0xffffffffu, sm, o); sq += __shfl_xor_sync(0xffffffffu, sq, o); }
                const float mean = sm * (1.0f / DM);
                const uint32_t m = pack_bf(mean, mean);
                #pragma unroll
                for (int sl = 0; sl < 8; sl++) {
                    uint4 t = xr[sl];
                    t.x = bsub2(t.x, m); t.y = bsub2(t.y, m); t.z = bsub2(t.z, m); t.w = bsub2(t.w, m);
                    sts128(xa + rg * 4096 + sl * 16384, t);
                }
                if ((lane & 7) == 0) {
                    const float var_b = bf_round(fmaxf(sq * (1.0f / DM) - mean * mean, 0.f));
                    const float sd = bf_round(sqrtf(bf_round(var_b + 1e-5f)));
                    sts32(sb + SM_STATS + (rg * 32 + lrow) * 8, m);
                    sts32(sb + SM_STATS + (rg * 32 + lrow) * 8 + 4, __float_as_uint(1.0f / sd));
                }
            }
            asm volatile("fence.proxy.async.shared::cta;" ::: "memory");
            named_bar(3, 256);
            PROFW(17, 0);
        }
        int st = 0; uint32_t fph = 0;
        const int rb64 = 2 * i + wgi;
        gemm1_pass<4>(sb, wgi, warp4, lane, st, fph, e_cl, rb64, 4 * j, convCTA);
        gemm1_pass<3>(sb, wgi, warp4, lane, st, fph, e_cl, rb64, 32 + 3 * j, convCTA);

        if (convCTA) {
            const int gch = 8 * cidx + warp;
            const uint32_t xb = sb + SM_CVX + warp * 4096;
            const uint32_t hb = sb + SM_CVH + warp * 4096;
            const uint32_t dw = ((const unsigned short*)p.ssm_D)[gch];
            const uint32_t d2 = dw | (dw << 16);
            mbar_wait(sb + SM_BARS + B_CONV * 8, 0);
            PROFW(32, 4);
            float acc[16][4];
            #pragma unroll
            for (int jj = 0; jj < 16; jj++) { acc[jj][0] = 0.f; acc[jj][1] = 0.f; acc[jj][2] = 0.f; acc[jj][3] = 0.f; }
            uint2 bh[8], bl0[8], bl1[8];
            uint32_t xl = xb + g * 32 + c * 8;
            uint32_t hl = hb + (g + 2 * c - 8) * 4;
            #pragma unroll
            for (int d = 0; d < 8; d++) { bl0[d] = lds64(xl + d * 256); bh[d] = lds64(xl + (8 + d) * 256); }
            uint32_t w[6];
            w[0] = 0; w[1] = 0; w[2] = 0;
            if (g + 2 * c >= 8) w[0] = lds32(hl);
            if (g + 2 * c >= 7) w[1] = lds32(hl + 4);
            if (g + 2 * c >= 6) w[2] = lds32(hl + 8);
            w[3] = lds32(hl + 2048); w[4] = lds32(hl + 2052); w[5] = lds32(hl + 2056);
            auto conv_m0 = [&](int m0, uint2 (&bl)[8], uint2 (&bn)[8]) {
                xl -= 32;
                #pragma unroll
                for (int k = 0; k < 8; k++) {
                    const uint32_t a0 = w[1], a1 = __byte_perm(w[0], w[1], 0x5432), a2 = w[2], a3 = __byte_perm(w[1], w[2], 0x5432);
                    const uint32_t c0 = w[4], c1 = __byte_perm(w[3], w[4], 0x5432), c2 = w[5], c3 = __byte_perm(w[4], w[5], 0x5432);
                    const uint32_t nx = (k < 7) ? hl + (k + 1) * 256 : hl + 32;
                    w[0] = lds32(nx); w[1] = lds32(nx + 4); w[2] = lds32(nx + 8);
                    w[3] = lds32(nx + 2048); w[4] = lds32(nx + 2052); w[5] = lds32(nx + 2056);
                    if (k > 0) bn[k] = lds64(xl + k * 256);
                    else { bn[0] = make_uint2(0, 0); if (g > m0) bn[0] = lds64(xl); }
                    #pragma unroll
                    for (int jj = k; jj < 16; jj++) mma16816(acc[jj], a0, a1, a2, a3, (jj - k < 8) ? bl[(jj - k) & 7] : bh[(jj - k) & 7]);
                    bh[7 - k] = lds64(xl + (15 - k) * 256);
                    #pragma unroll
                    for (int jj = k + 8; jj < 16; jj++) mma16816(acc[jj], c0, c1, c2, c3, bl[jj - k - 8]);
                }
                hl += 32;
            };
            #pragma unroll 1
            for (int m0 = 0; m0 < 8; m0 += 2) {
                conv_m0(m0, bl0, bl1);
                conv_m0(m0 + 1, bl1, bl0);
                PROFW(34 + (m0 >> 1), 4);
            }
            PROFW(33, 4);
            const uint32_t kvl = xb + c * 64 + (7 - g) * 4;
            uint32_t* ydst = (uint32_t*)(g_yT + (size_t)gch * SEQ + 32 * c + 2 * g);
            uint32_t kk0[16], kk1[16];
            #pragma unroll
            for (int jj = 0; jj < 16; jj++) { kk0[jj] = lds32(kvl + jj * 256); kk1[jj] = lds32(kvl + jj * 256 + 32); }
            #pragma unroll
            for (int jj = 0; jj < 16; jj++) {
                ydst[jj * 64] = badd2(pack_bf(acc[jj][2], acc[jj][0]), bmul2(__byte_perm(kk0[jj], kk0[jj], 0x1032), d2));
                ydst[jj * 64 + 8] = badd2(pack_bf(acc[jj][3], acc[jj][1]), bmul2(__byte_perm(kk1[jj], kk1[jj], 0x1032), d2));
            }
            __syncwarp();
            PROFW(44, 4);
            if (lane == 0) mbar_arrive(sb + SM_BARS + B_YST * 8);
        } else {
            float acc[64];
            const uint64_t descB0 = make_desc(sb, 4096, 1024, 1);
            const uint64_t descA0 = make_desc(sb + 16384 + wgi * 4096, 128, 256, 0);
            int sg = 3, p0 = 0; uint32_t ph = 6;
            PROFW(20, 0);
            #pragma unroll 1
            for (int u = 0; u < 28; u++) {
                if (warp == 0 && !(u & 1)) PROF2(2, 16 + (u >> 1));
                mbar_wait(sb + SM_BARS + (B_FULL + sg) * 8, (ph >> sg) & 1);
                ph ^= 1u << sg;
                if (warp == 0 && !(u & 1)) PROF2(1, 16 + (u >> 1));
                const uint32_t o0 = stage_off_rt(sg) >> 4;
                const uint64_t da0 = desc_add(descA0, o0), db0 = desc_add(descB0, o0);
                WG_FENCE();
                #pragma unroll
                for (int kk = 0; kk < 4; kk++) wgmma_ss_n128_tb(acc, da0 + ((kk >> 1) * 512 + (kk & 1) * 128), db0 + ((kk >> 1) * 512 + (kk & 1) * 128), (u | kk) ? 1 : 0);
                WG_COMMIT();
                wg_wait<1>();
                if (warp == 0 && !(u & 1)) PROF2(3, 16 + (u >> 1));
                if (lane < 2 && u > 0 && u + 4 < 28) mbar_arrive_cluster(e_cl + p0 * 8, 1);
                p0 = sg;
                sg = next_st2(sg);
            }
            wg_wait<0>();
            PROFW(27, 0);
            mbar_wait(sb + SM_BARS + B_XR * 8, 0);
            const int r0 = wgi * 64 + warp4 * 16 + g;
            const float2 st0 = lds64f(sb + SM_STATS + r0 * 8), st1 = lds64f(sb + SM_STATS + (r0 + 8) * 8);
            const uint32_t m0 = __float_as_uint(st0.x), m1 = __float_as_uint(st1.x);
            const uint32_t xrow0 = sb + SM_XE + r0 * 128 + c * 4;
            const int mi = lane >> 3, lr = lane & 7;
            const uint32_t yaddr = sb + SM_YT + wgi * 16384 + ((mi >> 1) * 8 + lr) * 128 + (((2 * warp4 + (mi & 1)) ^ lr) << 4);
            uint32_t y[8][4], xv[16][2], nv[16][2], bv[16][2];
            #pragma unroll
            for (int t = 0; t < 16; t++) {
                const uint32_t off = (t >> 3) * 16384 + (((t & 7) ^ g) << 4);
                xv[t][0] = lds32(xrow0 + off); xv[t][1] = lds32(xrow0 + 1024 + off);
            }
            #pragma unroll
            for (int t = 0; t < 16; t++) {
                const uint32_t d0 = bsub2(xv[t][0], m0), d1 = bsub2(xv[t][1], m1);
                nv[t][0] = pack_bf(bf_lo(d0) * st0.y, bf_hi(d0) * st0.y); nv[t][1] = pack_bf(bf_lo(d1) * st1.y, bf_hi(d1) * st1.y);
                bv[t][0] = pack_bf(acc[4 * t], acc[4 * t + 1]); bv[t][1] = pack_bf(acc[4 * t + 2], acc[4 * t + 3]);
            }
            mbar_wait(sb + SM_BARS + B_YT * 8, 0);
            PROFW(28, 0);
            #pragma unroll
            for (int t2 = 0; t2 < 8; t2++)
                asm volatile("ldmatrix.sync.aligned.m8n8.x4.trans.shared.b16 {%0,%1,%2,%3}, [%4];"
                    : "=r"(y[t2][0]), "=r"(y[t2][1]), "=r"(y[t2][2]), "=r"(y[t2][3]) : "r"(yaddr + t2 * 2048) : "memory");
            #pragma unroll
            for (int t = 0; t < 16; t++) {
                const uint32_t off = (t >> 3) * 16384 + (((t & 7) ^ g) << 4);
                sts32(xrow0 + off, badd2(badd2(xv[t][0], bmul2(nv[t][0], y[t >> 1][2 * (t & 1)])), bv[t][0]));
                sts32(xrow0 + 1024 + off, badd2(badd2(xv[t][1], bmul2(nv[t][1], y[t >> 1][2 * (t & 1) + 1])), bv[t][1]));
            }
            asm volatile("fence.proxy.async.shared::cta;" ::: "memory");
            named_bar(1 + wgi, 128);
            if ((tid & 127) == 0) {
                tma2d_store(&p.tm_out, 128 * cb, 128 * i + 64 * wgi, sb + SM_XE + wgi * 8192);
                tma2d_store(&p.tm_out, 128 * cb + 64, 128 * i + 64 * wgi, sb + SM_XE + 16384 + wgi * 8192);
                asm volatile("cp.async.bulk.commit_group;" ::: "memory");
                asm volatile("cp.async.bulk.wait_group.read 0;" ::: "memory");
                PROFW(29, 0);
            }
        }
    } else {
        asm volatile("setmaxnreg.dec.sync.aligned.u32 104;");
        if (warp == 8) {
            int st = 0; uint32_t eph = 7;
            #pragma unroll 1
            for (int it = 0; it < 16; it++) {
                const int pass = it >> 3, sl = it & 7;
                const int nb = pass ? 3 : 4;
                const CUtensorMap* tm = pass ? (rank ? &p.tm_uB : &p.tm_gB) : (rank ? &p.tm_uA : &p.tm_gA);
                mbar_wait(sb + SM_BARS + (B_EMPTY + st) * 8, (eph >> st) & 1);
                eph ^= 1u << st;
                if (it == 1) mbar_wait(sb + SM_BARS + (B_XFULL + 2) * 8, 0);
                PROF2(0, it);
                if (elect_one()) {
                    mbar_expect_tx(sb + SM_BARS + (B_FULL + st) * 8, nb * 8192);
                    tma3d_mc(sb + SM_RING + st * STAGE_BYTES + rank * nb * 4096, tm, 0, ((sl + 2 * cb + 2) & 7) * 64, 7 * j + 4 * pass, sb + SM_BARS + (B_FULL + st) * 8);
                }
                st = (st == 2) ? 0 : st + 1;
            }
            if (!convCTA) {
                st = 3;
                int f0 = 32 * rank, t3 = rank;
                #pragma unroll 1
                for (int u = 0; u < 28; u++) {
                    const uint32_t bar = sb + SM_BARS + (B_FULL + st) * 8;
                    mbar_wait(sb + SM_BARS + (B_EMPTY + st) * 8, (eph >> st) & 1);
                    eph ^= 1u << st;
                    if ((u & 1) == 0) PROF2(0, 16 + (u >> 1));
                    if (elect_one()) {
                        mbar_expect_tx(bar, 32768);
                        tma3d_mc(sb + stage_off_rt(st) + rank * 8192, &p.tm_w2, 0, f0, 2 * cb, bar);
                    }
                    st = next_st2(st);
                    if (u < 15) f0 += (u & 1) ? 160 : 64;
                    else if (u == 15) f0 = 128 + 32 * rank;
                    else { f0 += (t3 == 0) ? 64 : 192; t3 = (t3 == 0) ? 2 : t3 - 1; }
                }
                PROF(48);
            }
        } else if (warp < 11) {
            mbar_wait(sb + SM_BARS + (B_XFULL + 3) * 8, 0);
            #pragma unroll 1
            for (int rnd = 0; rnd < 2; rnd++) {
                const int tt = (tid - 288) + 64 * rnd;
                uint32_t sk[4][2];
                uint4 skw[2];
                skw[0] = ldg_nc128(p.shift_k + 16 * tt); skw[1] = ldg_nc128(p.shift_k + 16 * tt + 8);
                const __nv_bfloat16* kp = p.k + (size_t)(16 * b) * DM + 4 * tt;
                const __nv_bfloat16* vp = p.v + (size_t)(16 * b) * DM + 4 * tt;
                uint2 kr[19];
                uint2 kv[16];
                #pragma unroll
                for (int r = 0; r < 3; r++) kr[r] = (b > 0) ? ldg_nc64(kp + (r - 3) * DM) : make_uint2(0, 0);
                #pragma unroll
                for (int r = 0; r < 16; r++) { kr[3 + r] = ldg_nc64(kp + r * DM); if (r < 10) kv[r] = ldg_nc64(vp + r * DM); }
                {
                    const uint4 w0 = skw[0], w1 = skw[1];
                    sk[0][0] = __byte_perm(w0.x, w0.z, 0x5410); sk[1][0] = __byte_perm(w0.x, w0.z, 0x7632);
                    sk[2][0] = __byte_perm(w0.y, w0.w, 0x5410); sk[3][0] = __byte_perm(w0.y, w0.w, 0x7632);
                    sk[0][1] = __byte_perm(w1.x, w1.z, 0x5410); sk[1][1] = __byte_perm(w1.x, w1.z, 0x7632);
                    sk[2][1] = __byte_perm(w1.y, w1.w, 0x5410); sk[3][1] = __byte_perm(w1.y, w1.w, 0x7632);
                }
                #pragma unroll
                for (int s = 0; s < 16; s++) {
                    uint32_t a = bmul2(kr[s].x, sk[3][0]);
                    a = badd2(a, bmul2(kr[s + 1].x, sk[2][0]));
                    a = badd2(a, bmul2(kr[s + 2].x, sk[1][0]));
                    a = badd2(a, bmul2(kr[s + 3].x, sk[0][0]));
                    kv[s].x = bmul2(a, kv[s].x);
                    a = bmul2(kr[s].y, sk[3][1]);
                    a = badd2(a, bmul2(kr[s + 1].y, sk[2][1]));
                    a = badd2(a, bmul2(kr[s + 2].y, sk[1][1]));
                    a = badd2(a, bmul2(kr[s + 3].y, sk[0][1]));
                    kv[s].y = bmul2(a, kv[s].y);
                    if (s < 6) kv[10 + s] = ldg_nc64(vp + (10 + s) * DM);
                }
                PROFW(57 + 2 * rnd, 9);
                #pragma unroll
                for (int cc = 0; cc < 4; cc++) {
                    const uint32_t sel = (cc & 1) ? 0x7632 : 0x5410;
                    #define KVW(r) ((cc & 2) ? kv[r].y : kv[r].x)
                    uint4* dst = (uint4*)(g_kvT + (size_t)(4 * tt + cc) * SEQ + 16 * b);
                    dst[0] = make_uint4(__byte_perm(KVW(15), KVW(14), sel), __byte_perm(KVW(13), KVW(12), sel),
                                        __byte_perm(KVW(11), KVW(10), sel), __byte_perm(KVW(9), KVW(8), sel));
                    dst[1] = make_uint4(__byte_perm(KVW(7), KVW(6), sel), __byte_perm(KVW(5), KVW(4), sel),
                                        __byte_perm(KVW(3), KVW(2), sel), __byte_perm(KVW(1), KVW(0), sel));
                    #undef KVW
                }
                PROFW(58 + 2 * rnd, 9);
            }
            asm volatile("fence.proxy.async.global;" ::: "memory");
            __syncwarp();
            if (lane == 0) {
                flag_add(&g_cnt_kv[0]);
                PROFW(50, 9);
                const int wgi = warp - 9;
                mbar_wait(sb + SM_BARS + (B_HD + wgi * 2) * 8, 0);
                flag_add(&g_flag_h[(i * 2 + 0) * 8]);
                mbar_wait(sb + SM_BARS + (B_HD + wgi * 2 + 1) * 8, 0);
                flag_add(&g_flag_h[(i * 2 + 1) * 8]);
                if (wgi == 1 && convCTA) {
                    mbar_wait(sb + SM_BARS + B_YST * 8, 0);
                    flag_add(&g_cnt_y[(cidx >> 4) * 32]);
                    PROF(46);
                }
                if (wgi == 1 && !convCTA) {
                    const unsigned ep = lds32(sb + SM_EPOCH);
                    mbar_wait(sb + SM_BARS + B_G1DONE * 8, 0);
                    mbar_expect_tx(sb + SM_BARS + B_XR * 8, 32768);
                    for (int q = 0; q < 4; q++)
                        tma2d(sb + SM_XE + q * 8192, &p.tm_xe, 128 * cb + 64 * (q >> 1), 128 * i + 64 * (q & 1), sb + SM_BARS + B_XR * 8);
                    flag_wait(&g_flag_h[(i * 2 + 1) * 8], ep * 16);
                    mbar_arrive(sb + SM_BARS + (B_HRDY + 1) * 8);
                    __nanosleep(3000);
                    flag_wait(&g_cnt_y[cb * 32], ep * 16);
                    PROF(49);
                    asm volatile("fence.proxy.async.global;" ::: "memory");
                    mbar_expect_tx(sb + SM_BARS + B_YT * 8, 32768);
                    tma2d(sb + SM_YT, &p.tm_yT, 128 * i, 128 * cb, sb + SM_BARS + B_YT * 8);
                    tma2d(sb + SM_YT + 16384, &p.tm_yT, 128 * i + 64, 128 * cb, sb + SM_BARS + B_YT * 8);
                }
            }
        } else {
            if (lane == 0) {
                const unsigned ep = g_launch[b] + 1;
                g_launch[b] = ep;
                sts32(sb + SM_EPOCH, ep);
                tmap_prefetch(rank ? &p.tm_uA : &p.tm_gA);
                mbar_wait(sb + SM_BARS + (B_XFULL + 1) * 8, 0);
                l2_prefetch(p.wg + (size_t)b * (FF * DM / NCTA), FF * DM / NCTA * 2);
                l2_prefetch(p.wu + (size_t)b * (FF * DM / NCTA), FF * DM / NCTA * 2);
                tmap_prefetch(rank ? &p.tm_uB : &p.tm_gB);
                tmap_prefetch(&p.tm_w2); tmap_prefetch(&p.tm_yT); tmap_prefetch(&p.tm_out); tmap_prefetch(&p.tm_xe);
                mbar_wait(sb + SM_BARS + (B_FULL + 2) * 8, 0);
                l2_prefetch(p.ssm_k + (size_t)(4 * b) * SEQ, 4 * SEQ * 2);
                l2_prefetch(p.wd + (size_t)b * (FF * DM / NCTA), FF * DM / NCTA * 2);
                mbar_wait(sb + SM_BARS + (B_HD + 0) * 8, 0);
                if (convCTA) {
                    flag_wait(&g_cnt_kv[0], ep * 256);
                    asm volatile("fence.proxy.async.global;" ::: "memory");
                    PROF(53);
                    mbar_wait(sb + SM_BARS + B_XFREE * 8, 0);
                    PROF(54);
                    mbar_expect_tx(sb + SM_BARS + B_CONV * 8, 65536);
                    bulk_g2s(sb + SM_CVX, g_kvT + (size_t)(8 * cidx) * SEQ, 32768, sb + SM_BARS + B_CONV * 8);
                    bulk_g2s(sb + SM_CVH, p.ssm_k + (size_t)(8 * cidx) * SEQ, 32768, sb + SM_BARS + B_CONV * 8);
                } else {
                    flag_wait(&g_flag_h[(i * 2 + 0) * 8], ep * 16);
                }
            }
            __syncwarp();
            if (!convCTA) {
                asm volatile("fence.proxy.async.global;" ::: "memory");
                int st = 3; uint32_t eph = 1;
                const uint8_t* hsrc = (const uint8_t*)g_h + (size_t)i * 56 * 8192;
                #pragma unroll 1
                for (int u = 0; u < 28; u++) {
                    mbar_wait(sb + SM_BARS + (B_EMPTY + st) * 8, (eph >> st) & 1);
                    eph ^= 1u << st;
                    if (u == 16) {
                        mbar_wait(sb + SM_BARS + (B_HRDY + 1) * 8, 0);
                        asm volatile("fence.proxy.async.global;" ::: "memory");
                    }
                    if (elect_one()) bulk_g2s(sb + stage_off_rt(st) + 16384, hsrc + u * 16384, 16384, sb + SM_BARS + (B_FULL + st) * 8);
                    st = next_st2(st);
                }
            }
        }
    }
}

typedef CUresult (*EncodeFn)(CUtensorMap*, CUtensorMapDataType, cuuint32_t, void*, const cuuint64_t*, const cuuint64_t*,
                             const cuuint32_t*, const cuuint32_t*, CUtensorMapInterleave, CUtensorMapSwizzle,
                             CUtensorMapL2promotion, CUtensorMapFloatOOBfill);

void encode(EncodeFn fn, CUtensorMap* tm, const void* base, int rank, const cuuint64_t* dims, const cuuint64_t* strides,
            const cuuint32_t* box, CUtensorMapSwizzle swz) {
    cuuint32_t es[5] = {1, 1, 1, 1, 1};
    fn(tm, CU_TENSOR_MAP_DATA_TYPE_BFLOAT16, rank, (void*)base, dims, strides, box, es, CU_TENSOR_MAP_INTERLEAVE_NONE, swz,
       CU_TENSOR_MAP_L2_PROMOTION_L2_128B, CU_TENSOR_MAP_FLOAT_OOB_FILL_NONE);
}

}

extern "C" void kernel_launch(void* const* d_in, const int* in_sizes, int n_in, void* d_out, int out_size) {
    (void)in_sizes; (void)n_in; (void)out_size;
    static EncodeFn enc = nullptr;
    static void* yT_ptr = nullptr;
    if (!enc) {
        void* fn = nullptr; cudaDriverEntryPointQueryResult qr;
        cudaGetDriverEntryPoint("cuTensorMapEncodeTiled", &fn, cudaEnableDefault, &qr);
        enc = (EncodeFn)fn;
        cudaGetSymbolAddress(&yT_ptr, g_yT);
        cudaFuncSetAttribute(fused_kernel, cudaFuncAttributeMaxDynamicSharedMemorySize, SM_TOTAL);
    }
    Params p;
    p.q = (const __nv_bfloat16*)d_in[0]; p.k = (const __nv_bfloat16*)d_in[1]; p.v = (const __nv_bfloat16*)d_in[2];
    p.shift_k = (const __nv_bfloat16*)d_in[3]; p.ssm_k = (const __nv_bfloat16*)d_in[4]; p.ssm_D = (const __nv_bfloat16*)d_in[5];
    p.wg = (const __nv_bfloat16*)d_in[7]; p.wu = (const __nv_bfloat16*)d_in[8]; p.wd = (const __nv_bfloat16*)d_in[9];
    {
        cuuint64_t dims[2] = {DM, SEQ}; cuuint64_t str[1] = {DM * 2};
        cuuint32_t box[2] = {64, 32};
        encode(enc, &p.tm_x, p.q, 2, dims, str, box, CU_TENSOR_MAP_SWIZZLE_128B);
        cuuint32_t box2[2] = {64, 64};
        encode(enc, &p.tm_out, d_out, 2, dims, str, box2, CU_TENSOR_MAP_SWIZZLE_128B);
        encode(enc, &p.tm_xe, p.q, 2, dims, str, box2, CU_TENSOR_MAP_SWIZZLE_128B);
    }
    {
        cuuint64_t dims[3] = {32, DM, FF / 32}; cuuint64_t str[2] = {FF * 2, 64};
        cuuint32_t boxA[3] = {32, 64, 4}, boxB[3] = {32, 64, 3};
        encode(enc, &p.tm_gA, p.wg, 3, dims, str, boxA, CU_TENSOR_MAP_SWIZZLE_64B);
        encode(enc, &p.tm_gB, p.wg, 3, dims, str, boxB, CU_TENSOR_MAP_SWIZZLE_64B);
        encode(enc, &p.tm_uA, p.wu, 3, dims, str, boxA, CU_TENSOR_MAP_SWIZZLE_64B);
        encode(enc, &p.tm_uB, p.wu, 3, dims, str, boxB, CU_TENSOR_MAP_SWIZZLE_64B);
    }
    {
        cuuint64_t dims[3] = {64, FF, DM / 64}; cuuint64_t str[2] = {DM * 2, 128};
        cuuint32_t box[3] = {64, 32, 2};
        encode(enc, &p.tm_w2, p.wd, 3, dims, str, box, CU_TENSOR_MAP_SWIZZLE_128B);
    }
    {
        cuuint64_t dims[2] = {SEQ, DM}; cuuint64_t str[1] = {SEQ * 2};
        cuuint32_t box[2] = {64, 128};
        encode(enc, &p.tm_yT, yT_ptr, 2, dims, str, box, CU_TENSOR_MAP_SWIZZLE_128B);
    }
    fused_kernel<<<NCTA, NTHREADS, SM_TOTAL>>>(p);
}
```

```cpp
#include <cuda_runtime.h>
#include <cuda_bf16.h>
#include <cuda.h>
#include <stdint.h>

namespace {

constexpr int SEQ = 2048, DM = 512, FF = 1792;
constexpr int NCTA = 128;
constexpr int NTHREADS = 384;
constexpr int STAGE_BYTES = 32768;

constexpr uint32_t SM_X = 0;
constexpr uint32_t SM_RING = 131072;
constexpr uint32_t SM_MISC = SM_RING + 3 * STAGE_BYTES;
constexpr uint32_t SM_BARS = SM_MISC;
constexpr uint32_t SM_EPOCH = SM_MISC + 248;
constexpr uint32_t SM_STATS = SM_MISC + 256;
constexpr uint32_t SM_TOTAL = SM_STATS + 1024;
static_assert(SM_TOTAL <= 232448, "smem");
constexpr uint32_t SM_CVX = 0;
constexpr uint32_t SM_CVH = 65536;
constexpr uint32_t SM_YT = 32768;
constexpr uint32_t SM_XE = 98304;

constexpr int B_FULL = 0, B_EMPTY = 5, B_XFULL = 10, B_CONV = 14, B_YT = 15, B_XR = 16, B_G1DONE = 17, B_HD = 18, B_HRDY = 22,
              B_XFREE = 24, B_YST = 25, B_KVLD = 26, B_COUNT = 27;
static_assert(B_COUNT * 8 <= 248, "barrier space");

__device__ __align__(128) uint32_t g_h[16 * 56 * 2048];
__device__ __align__(128) __nv_bfloat16 g_kvT[DM * SEQ];
__device__ __align__(128) __nv_bfloat16 g_yT[DM * SEQ];
__device__ unsigned g_launch[NCTA];
__device__ unsigned g_cnt_kv[32];
__device__ unsigned g_cnt_y[4 * 32];
__device__ unsigned g_flag_h[16 * 2 * 8];

#define PROF(idx)
#define PROF2(a, idx)
#define PROFW(idx, w)

struct Params {
    CUtensorMap tm_x, tm_gA, tm_gB, tm_uA, tm_uB, tm_w2, tm_yT, tm_out, tm_xe;
    const __nv_bfloat16 *q, *k, *v, *shift_k, *ssm_k, *ssm_D, *wg, *wu, *wd;
};

__device__ __forceinline__ void wgmma_rs_n32(float (&d)[16], uint32_t a0, uint32_t a1, uint32_t a2, uint32_t a3, uint64_t db, int sc) {
  asm volatile("{\n.reg .pred p;\nsetp.ne.b32 p, %21, 0;\n"
    "wgmma.mma_async.sync.aligned.m64n32k16.f32.bf16.bf16 {%0,%1,%2,%3,%4,%5,%6,%7,%8,%9,%10,%11,%12,%13,%14,%15}, {%16,%17,%18,%19}, %20, p, 1, 1, 0;\n}\n"
    : "+f"(d[0]),"+f"(d[1]),"+f"(d[2]),"+f"(d[3]),"+f"(d[4]),"+f"(d[5]),"+f"(d[6]),"+f"(d[7]),"+f"(d[8]),"+f"(d[9]),"+f"(d[10]),"+f"(d[11]),"+f"(d[12]),"+f"(d[13]),"+f"(d[14]),"+f"(d[15])
    : "r"(a0),"r"(a1),"r"(a2),"r"(a3),"l"(db),"r"(sc));
}
__device__ __forceinline__ void wgmma_rs_n128_tb(float (&d)[64], uint32_t a0, uint32_t a1, uint32_t a2, uint32_t a3, uint64_t db, int sc) {
  asm volatile("{\n.reg .pred p;\nsetp.ne.b32 p, %69, 0;\n"
    "wgmma.mma_async.sync.aligned.m64n128k16.f32.bf16.bf16 {%0,%1,%2,%3,%4,%5,%6,%7,%8,%9,%10,%11,%12,%13,%14,%15,%16,%17,%18,%19,%20,%21,%22,%23,%24,%25,%26,%27,%28,%29,%30,%31,%32,%33,%34,%35,%36,%37,%38,%39,%40,%41,%42,%43,%44,%45,%46,%47,%48,%49,%50,%51,%52,%53,%54,%55,%56,%57,%58,%59,%60,%61,%62,%63}, {%64,%65,%66,%67}, %68, p, 1, 1, 1;\n}\n"
    : "+f"(d[0]),"+f"(d[1]),"+f"(d[2]),"+f"(d[3]),"+f"(d[4]),"+f"(d[5]),"+f"(d[6]),"+f"(d[7]),"+f"(d[8]),"+f"(d[9]),"+f"(d[10]),"+f"(d[11]),"+f"(d[12]),"+f"(d[13]),"+f"(d[14]),"+f"(d[15]),"+f"(d[16]),"+f"(d[17]),"+f"(d[18]),"+f"(d[19]),"+f"(d[20]),"+f"(d[21]),"+f"(d[22]),"+f"(d[23]),"+f"(d[24]),"+f"(d[25]),"+f"(d[26]),"+f"(d[27]),"+f"(d[28]),"+f"(d[29]),"+f"(d[30]),"+f"(d[31]),"+f"(d[32]),"+f"(d[33]),"+f"(d[34]),"+f"(d[35]),"+f"(d[36]),"+f"(d[37]),"+f"(d[38]),"+f"(d[39]),"+f"(d[40]),"+f"(d[41]),"+f"(d[42]),"+f"(d[43]),"+f"(d[44]),"+f"(d[45]),"+f"(d[46]),"+f"(d[47]),"+f"(d[48]),"+f"(d[49]),"+f"(d[50]),"+f"(d[51]),"+f"(d[52]),"+f"(d[53]),"+f"(d[54]),"+f"(d[55]),"+f"(d[56]),"+f"(d[57]),"+f"(d[58]),"+f"(d[59]),"+f"(d[60]),"+f"(d[61]),"+f"(d[62]),"+f"(d[63])
    : "r"(a0),"r"(a1),"r"(a2),"r"(a3),"l"(db),"r"(sc));
}
__device__ __forceinline__ void wgmma_ss_n256_tb(float (&d)[128], uint64_t da, uint64_t db, int sc) {
  asm volatile("{\n.reg .pred p;\nsetp.ne.b32 p, %130, 0;\n"
    "wgmma.mma_async.sync.aligned.m64n256k16.f32.bf16.bf16 {%0,%1,%2,%3,%4,%5,%6,%7,%8,%9,%10,%11,%12,%13,%14,%15,%16,%17,%18,%19,%20,%21,%22,%23,%24,%25,%26,%27,%28,%29,%30,%31,%32,%33,%34,%35,%36,%37,%38,%39,%40,%41,%42,%43,%44,%45,%46,%47,%48,%49,%50,%51,%52,%53,%54,%55,%56,%57,%58,%59,%60,%61,%62,%63,%64,%65,%66,%67,%68,%69,%70,%71,%72,%73,%74,%75,%76,%77,%78,%79,%80,%81,%82,%83,%84,%85,%86,%87,%88,%89,%90,%91,%92,%93,%94,%95,%96,%97,%98,%99,%100,%101,%102,%103,%104,%105,%106,%107,%108,%109,%110,%111,%112,%113,%114,%115,%116,%117,%118,%119,%120,%121,%122,%123,%124,%125,%126,%127}, %128, %129, p, 1, 1, 0, 1;\n}\n"
    : "+f"(d[0]),"+f"(d[1]),"+f"(d[2]),"+f"(d[3]),"+f"(d[4]),"+f"(d[5]),"+f"(d[6]),"+f"(d[7]),"+f"(d[8]),"+f"(d[9]),"+f"(d[10]),"+f"(d[11]),"+f"(d[12]),"+f"(d[13]),"+f"(d[14]),"+f"(d[15]),"+f"(d[16]),"+f"(d[17]),"+f"(d[18]),"+f"(d[19]),"+f"(d[20]),"+f"(d[21]),"+f"(d[22]),"+f"(d[23]),"+f"(d[24]),"+f"(d[25]),"+f"(d[26]),"+f"(d[27]),"+f"(d[28]),"+f"(d[29]),"+f"(d[30]),"+f"(d[31]),"+f"(d[32]),"+f"(d[33]),"+f"(d[34]),"+f"(d[35]),"+f"(d[36]),"+f"(d[37]),"+f"(d[38]),"+f"(d[39]),"+f"(d[40]),"+f"(d[41]),"+f"(d[42]),"+f"(d[43]),"+f"(d[44]),"+f"(d[45]),"+f"(d[46]),"+f"(d[47]),"+f"(d[48]),"+f"(d[49]),"+f"(d[50]),"+f"(d[51]),"+f"(d[52]),"+f"(d[53]),"+f"(d[54]),"+f"(d[55]),"+f"(d[56]),"+f"(d[57]),"+f"(d[58]),"+f"(d[59]),"+f"(d[60]),"+f"(d[61]),"+f"(d[62]),"+f"(d[63]),"+f"(d[64]),"+f"(d[65]),"+f"(d[66]),"+f"(d[67]),"+f"(d[68]),"+f"(d[69]),"+f"(d[70]),"+f"(d[71]),"+f"(d[72]),"+f"(d[73]),"+f"(d[74]),"+f"(d[75]),"+f"(d[76]),"+f"(d[77]),"+f"(d[78]),"+f"(d[79]),"+f"(d[80]),"+f"(d[81]),"+f"(d[82]),"+f"(d[83]),"+f"(d[84]),"+f"(d[85]),"+f"(d[86]),"+f"(d[87]),"+f"(d[88]),"+f"(d[89]),"+f"(d[90]),"+f"(d[91]),"+f"(d[92]),"+f"(d[93]),"+f"(d[94]),"+f"(d[95]),"+f"(d[96]),"+f"(d[97]),"+f"(d[98]),"+f"(d[99]),"+f"(d[100]),"+f"(d[101]),"+f"(d[102]),"+f"(d[103]),"+f"(d[104]),"+f"(d[105]),"+f"(d[106]),"+f"(d[107]),"+f"(d[108]),"+f"(d[109]),"+f"(d[110]),"+f"(d[111]),"+f"(d[112]),"+f"(d[113]),"+f"(d[114]),"+f"(d[115]),"+f"(d[116]),"+f"(d[117]),"+f"(d[118]),"+f"(d[119]),"+f"(d[120]),"+f"(d[121]),"+f"(d[122]),"+f"(d[123]),"+f"(d[124]),"+f"(d[125]),"+f"(d[126]),"+f"(d[127])
    : "l"(da),"l"(db),"r"(sc));
}
__device__ __forceinline__ void wgmma_ss_n192_tb(float (&d)[96], uint64_t da, uint64_t db, int sc) {
  asm volatile("{\n.reg .pred p;\nsetp.ne.b32 p, %98, 0;\n"
    "wgmma.mma_async.sync.aligned.m64n192k16.f32.bf16.bf16 {%0,%1,%2,%3,%4,%5,%6,%7,%8,%9,%10,%11,%12,%13,%14,%15,%16,%17,%18,%19,%20,%21,%22,%23,%24,%25,%26,%27,%28,%29,%30,%31,%32,%33,%34,%35,%36,%37,%38,%39,%40,%41,%42,%43,%44,%45,%46,%47,%48,%49,%50,%51,%52,%53,%54,%55,%56,%57,%58,%59,%60,%61,%62,%63,%64,%65,%66,%67,%68,%69,%70,%71,%72,%73,%74,%75,%76,%77,%78,%79,%80,%81,%82,%83,%84,%85,%86,%87,%88,%89,%90,%91,%92,%93,%94,%95}, %96, %97, p, 1, 1, 0, 1;\n}\n"
    : "+f"(d[0]),"+f"(d[1]),"+f"(d[2]),"+f"(d[3]),"+f"(d[4]),"+f"(d[5]),"+f"(d[6]),"+f"(d[7]),"+f"(d[8]),"+f"(d[9]),"+f"(d[10]),"+f"(d[11]),"+f"(d[12]),"+f"(d[13]),"+f"(d[14]),"+f"(d[15]),"+f"(d[16]),"+f"(d[17]),"+f"(d[18]),"+f"(d[19]),"+f"(d[20]),"+f"(d[21]),"+f"(d[22]),"+f"(d[23]),"+f"(d[24]),"+f"(d[25]),"+f"(d[26]),"+f"(d[27]),"+f"(d[28]),"+f"(d[29]),"+f"(d[30]),"+f"(d[31]),"+f"(d[32]),"+f"(d[33]),"+f"(d[34]),"+f"(d[35]),"+f"(d[36]),"+f"(d[37]),"+f"(d[38]),"+f"(d[39]),"+f"(d[40]),"+f"(d[41]),"+f"(d[42]),"+f"(d[43]),"+f"(d[44]),"+f"(d[45]),"+f"(d[46]),"+f"(d[47]),"+f"(d[48]),"+f"(d[49]),"+f"(d[50]),"+f"(d[51]),"+f"(d[52]),"+f"(d[53]),"+f"(d[54]),"+f"(d[55]),"+f"(d[56]),"+f"(d[57]),"+f"(d[58]),"+f"(d[59]),"+f"(d[60]),"+f"(d[61]),"+f"(d[62]),"+f"(d[63]),"+f"(d[64]),"+f"(d[65]),"+f"(d[66]),"+f"(d[67]),"+f"(d[68]),"+f"(d[69]),"+f"(d[70]),"+f"(d[71]),"+f"(d[72]),"+f"(d[73]),"+f"(d[74]),"+f"(d[75]),"+f"(d[76]),"+f"(d[77]),"+f"(d[78]),"+f"(d[79]),"+f"(d[80]),"+f"(d[81]),"+f"(d[82]),"+f"(d[83]),"+f"(d[84]),"+f"(d[85]),"+f"(d[86]),"+f"(d[87]),"+f"(d[88]),"+f"(d[89]),"+f"(d[90]),"+f"(d[91]),"+f"(d[92]),"+f"(d[93]),"+f"(d[94]),"+f"(d[95])
    : "l"(da),"l"(db),"r"(sc));
}

__device__ __forceinline__ uint32_t smem_u32(const void* p) { return (uint32_t)__cvta_generic_to_shared(p); }
__device__ __forceinline__ void mbar_init(uint32_t bar, uint32_t cnt) { asm volatile("mbarrier.init.shared::cta.b64 [%0], %1;" :: "r"(bar), "r"(cnt)); }
__device__ __forceinline__ void mbar_expect_tx(uint32_t bar, uint32_t bytes) { asm volatile("mbarrier.arrive.expect_tx.shared::cta.b64 _, [%0], %1;" :: "r"(bar), "r"(bytes) : "memory"); }
__device__ __forceinline__ void mbar_arrive(uint32_t bar) { asm volatile("mbarrier.arrive.shared::cta.b64 _, [%0];" :: "r"(bar) : "memory"); }
__device__ __forceinline__ void mbar_arrive_cluster(uint32_t cbar, uint32_t cnt) { asm volatile("mbarrier.arrive.shared::cluster.b64 _, [%0], %1;" :: "r"(cbar), "r"(cnt) : "memory"); }
__device__ __forceinline__ uint32_t mapa(uint32_t a, uint32_t rank) { uint32_t r; asm volatile("mapa.shared::cluster.u32 %0, %1, %2;" : "=r"(r) : "r"(a), "r"(rank)); return r; }
__device__ __forceinline__ void mbar_wait(uint32_t bar, uint32_t parity) {
    uint32_t ok; uint32_t n = 0;
    do {
        asm volatile("{\n.reg .pred p;\nmbarrier.try_wait.parity.shared::cta.b64 p, [%1], %2;\nselp.u32 %0, 1, 0, p;\n}" : "=r"(ok) : "r"(bar), "r"(parity) : "memory");
    } while (!ok && ++n < (1u << 17));
}
__device__ __forceinline__ void pace_wait(uint32_t a, uint32_t target) {
    uint32_t v, n = 0;
    do {
        asm volatile("ld.volatile.shared.u32 %0, [%1];" : "=r"(v) : "r"(a) : "memory");
        if (v < target) __nanosleep(150);
    } while (v < target && ++n < (1u << 14));
}
__device__ __forceinline__ void flag_wait(const unsigned* p, unsigned target) {
    unsigned v; uint32_t n = 0;
    while (true) {
        asm volatile("ld.acquire.gpu.global.u32 %0, [%1];" : "=r"(v) : "l"(p) : "memory");
        if ((int)(v - target) >= 0 || ++n >= (1u << 17)) break;
        __nanosleep(100);
    }
}
__device__ __forceinline__ void flag_add(unsigned* p) {
    asm volatile("fence.acq_rel.gpu;\nred.relaxed.gpu.global.add.u32 [%0], 1;" :: "l"(p) : "memory");
}
__device__ __forceinline__ uint64_t make_desc(uint32_t addr, uint32_t lbo, uint32_t sbo, uint32_t swz) {
    return (uint64_t)((addr & 0x3FFFF) >> 4) | ((uint64_t)((lbo & 0x3FFFF) >> 4) << 16) | ((uint64_t)((sbo & 0x3FFFF) >> 4) << 32) | ((uint64_t)swz << 62);
}
__device__ __forceinline__ uint64_t desc_add(uint64_t d, uint32_t off16) {
    return (d & 0xFFFFFFFF00000000ull) | (uint64_t)((uint32_t)d + off16);
}
__device__ __forceinline__ void tma2d(uint32_t dst, const CUtensorMap* tm, int c0, int c1, uint32_t bar) {
    asm volatile("cp.async.bulk.tensor.2d.shared::cluster.global.mbarrier::complete_tx::bytes [%0], [%1, {%3, %4}], [%2];"
        :: "r"(dst), "l"((uint64_t)tm), "r"(bar), "r"(c0), "r"(c1) : "memory");
}
__device__ __forceinline__ void tma3d(uint32_t dst, const CUtensorMap* tm, int c0, int c1, int c2, uint32_t bar) {
    asm volatile("cp.async.bulk.tensor.3d.shared::cluster.global.mbarrier::complete_tx::bytes [%0], [%1, {%3, %4, %5}], [%2];"
        :: "r"(dst), "l"((uint64_t)tm), "r"(bar), "r"(c0), "r"(c1), "r"(c2) : "memory");
}
__device__ __forceinline__ void tma3d_mc(uint32_t dst, const CUtensorMap* tm, int c0, int c1, int c2, uint32_t bar) {
    asm volatile("cp.async.bulk.tensor.3d.shared::cluster.global.mbarrier::complete_tx::bytes.multicast::cluster [%0], [%1, {%3, %4, %5}], [%2], %6;"
        :: "r"(dst), "l"((uint64_t)tm), "r"(bar), "r"(c0), "r"(c1), "r"(c2), "h"((uint16_t)3) : "memory");
}
__device__ __forceinline__ void bulk_g2s(uint32_t dst, const void* src, uint32_t bytes, uint32_t bar) {
    asm volatile("cp.async.bulk.shared::cluster.global.mbarrier::complete_tx::bytes [%0], [%1], %2, [%3];"
        :: "r"(dst), "l"(src), "r"(bytes), "r"(bar) : "memory");
}
__device__ __forceinline__ void bulk_s2g(void* dst, uint32_t src, uint32_t bytes) {
    asm volatile("cp.async.bulk.global.shared::cta.bulk_group [%0], [%1], %2;" :: "l"(dst), "r"(src), "r"(bytes) : "memory");
}
__device__ __forceinline__ void tma2d_store(const CUtensorMap* tm, int c0, int c1, uint32_t src) {
    asm volatile("cp.async.bulk.tensor.2d.global.shared::cta.bulk_group [%0, {%2, %3}], [%1];"
        :: "l"((uint64_t)tm), "r"(src), "r"(c0), "r"(c1) : "memory");
}
__device__ __forceinline__ void l2_prefetch(const void* p, uint32_t bytes) {
    asm volatile("cp.async.bulk.prefetch.L2.global [%0], %1;" :: "l"(p), "r"(bytes) : "memory");
}
__device__ __forceinline__ void tmap_prefetch(const CUtensorMap* tm) { asm volatile("prefetch.tensormap [%0];" :: "l"((uint64_t)tm) : "memory"); }
__device__ __forceinline__ uint32_t lds32(uint32_t a) { uint32_t v; asm volatile("ld.shared.u32 %0, [%1];" : "=r"(v) : "r"(a)); return v; }
__device__ __forceinline__ uint2 lds64(uint32_t a) { uint2 v; asm volatile("ld.shared.v2.u32 {%0,%1}, [%2];" : "=r"(v.x), "=r"(v.y) : "r"(a)); return v; }
__device__ __forceinline__ uint4 lds128(uint32_t a) { uint4 v; asm volatile("ld.shared.v4.u32 {%0,%1,%2,%3}, [%4];" : "=r"(v.x), "=r"(v.y), "=r"(v.z), "=r"(v.w) : "r"(a)); return v; }
__device__ __forceinline__ float2 lds64f(uint32_t a) { float2 v; asm volatile("ld.shared.v2.f32 {%0,%1}, [%2];" : "=f"(v.x), "=f"(v.y) : "r"(a)); return v; }
__device__ __forceinline__ void sts32(uint32_t a, uint32_t v) { asm volatile("st.shared.u32 [%0], %1;" :: "r"(a), "r"(v) : "memory"); }
__device__ __forceinline__ void sts128(uint32_t a, uint4 v) { asm volatile("st.shared.v4.u32 [%0], {%1,%2,%3,%4};" :: "r"(a), "r"(v.x), "r"(v.y), "r"(v.z), "r"(v.w) : "memory"); }
__device__ __forceinline__ uint4 ldg_cg128(const void* p) { uint4 v; asm volatile("ld.global.cg.v4.u32 {%0,%1,%2,%3}, [%4];" : "=r"(v.x), "=r"(v.y), "=r"(v.z), "=r"(v.w) : "l"(p)); return v; }
__device__ __forceinline__ uint4 ldg_nc128(const void* p) { uint4 v; asm volatile("ld.global.nc.L1::no_allocate.v4.u32 {%0,%1,%2,%3}, [%4];" : "=r"(v.x), "=r"(v.y), "=r"(v.z), "=r"(v.w) : "l"(p)); return v; }
__device__ __forceinline__ uint2 ldg_nc64(const void* p) { uint2 v; asm volatile("ld.global.nc.L1::no_allocate.v2.u32 {%0,%1}, [%2];" : "=r"(v.x), "=r"(v.y) : "l"(p)); return v; }
#define WG_FENCE() asm volatile("wgmma.fence.sync.aligned;\n" ::: "memory")
#define WG_COMMIT() asm volatile("wgmma.commit_group.sync.aligned;\n" ::: "memory")
template<int N> __device__ __forceinline__ void wg_wait() { asm volatile("wgmma.wait_group.sync.aligned %0;\n" :: "n"(N) : "memory"); }
__device__ __forceinline__ bool elect_one() {
    uint32_t pr;
    asm volatile("{\n.reg .pred p;\nelect.sync _|p, 0xffffffff;\nselp.u32 %0, 1, 0, p;\n}" : "=r"(pr));
    return pr != 0;
}
__device__ __forceinline__ void named_bar(int id, int n) { asm volatile("bar.sync %0, %1;" :: "r"(id), "r"(n) : "memory"); }

__device__ __forceinline__ float bf_lo(uint32_t u) { return __uint_as_float(u << 16); }
__device__ __forceinline__ float bf_hi(uint32_t u) { return __uint_as_float(u & 0xFFFF0000u); }
__device__ __forceinline__ uint32_t pack_bf(float lo, float hi) { uint32_t r; asm("cvt.rn.bf16x2.f32 %0, %1, %2;" : "=r"(r) : "f"(hi), "f"(lo)); return r; }
__device__ __forceinline__ float bf_round(float x) { return __bfloat162float(__float2bfloat16_rn(x)); }
__device__ __forceinline__ uint32_t bmul2(uint32_t a, uint32_t b) { uint32_t r; asm("mul.rn.bf16x2 %0, %1, %2;" : "=r"(r) : "r"(a), "r"(b)); return r; }
__device__ __forceinline__ uint32_t badd2(uint32_t a, uint32_t b) { uint32_t r; asm("add.rn.bf16x2 %0, %1, %2;" : "=r"(r) : "r"(a), "r"(b)); return r; }
__device__ __forceinline__ uint32_t bsub2(uint32_t a, uint32_t b) { uint32_t r; asm("sub.rn.bf16x2 %0, %1, %2;" : "=r"(r) : "r"(a), "r"(b)); return r; }
__device__ __forceinline__ void mma16816(float (&d)[4], uint32_t a0, uint32_t a1, uint32_t a2, uint32_t a3, uint2 b) {
    asm volatile("mma.sync.aligned.m16n8k16.row.col.f32.bf16.bf16.f32 {%0,%1,%2,%3}, {%4,%5,%6,%7}, {%8,%9}, {%0,%1,%2,%3};\n"
        : "+f"(d[0]), "+f"(d[1]), "+f"(d[2]), "+f"(d[3]) : "r"(a0), "r"(a1), "r"(a2), "r"(a3), "r"(b.x), "r"(b.y));
}

template<int HS> __device__ __forceinline__ void xreduce(float (&v)[8], int lane) {
    const int up = lane & HS;
    #pragma unroll
    for (int e = 0; e < HS; e++) {
        float keep, send;
        asm("{\n.reg .pred p;\nsetp.ne.b32 p, %4, 0;\nselp.f32 %0, %3, %2, p;\nselp.f32 %1, %2, %3, p;\n}"
            : "=f"(keep), "=f"(send) : "f"(v[e]), "f"(v[e + HS]), "r"(up));
        v[e] = keep + __shfl_xor_sync(0xffffffffu, send, HS);
    }
}

__device__ __forceinline__ int blk_f0(int bi, int j) {
    if (bi < 32) return 224 * ((j + (bi >> 2)) & 7) + 32 * (bi & 3);
    int b2 = bi - 32; int q3 = (b2 * 11) >> 5;
    return 224 * ((j + q3) & 7) + 128 + 32 * (b2 - 3 * q3);
}
__device__ __forceinline__ int next_st2(int s) { return (0x14023 >> (4 * s)) & 7; }
__device__ __forceinline__ uint32_t stage_off_rt(int s) { return s < 3 ? SM_RING + s * STAGE_BYTES : (uint32_t)(s - 3) * 65536; }

template<int NB>
__device__ __forceinline__ void gemm1_pass(uint32_t sb, int wgi, int warp4, int lane, int& st, uint32_t& fph, uint32_t e_cl,
                                           int rb64, int ks0, bool convCTA) {
    constexpr bool passA = (NB == 4);
    float acc[NB * 32];
    const uint64_t descA0 = make_desc(sb + SM_X + wgi * 65536, 16, 1024, 1);
    const uint64_t descB0 = make_desc(sb + SM_RING, 4096, 512, 2);
    int prev = 0;
    #pragma unroll 1
    for (int sl = 0; sl < 8; sl++) {
        if (warp4 == 0 && wgi == 0) PROF2(2, sl + (passA ? 0 : 8));
        mbar_wait(sb + SM_BARS + (B_FULL + st) * 8, (fph >> st) & 1);
        fph ^= 1u << st;
        if (sl == 0 && warp4 == 0) PROF(2 + wgi * 8 + (passA ? 0 : 3));
        if (warp4 == 0 && wgi == 0) PROF2(1, sl + (passA ? 0 : 8));
        const uint64_t da = desc_add(descA0, sl * 512), db = desc_add(descB0, st * 2048);
        WG_FENCE();
        #pragma unroll
        for (int kk = 0; kk < 4; kk++) {
            int sc = (sl | kk) ? 1 : 0;
            if constexpr (NB == 4) wgmma_ss_n256_tb(acc, da + kk * 2, db + kk * 64, sc); else wgmma_ss_n192_tb(acc, da + kk * 2, db + kk * 64, sc);
        }
        WG_COMMIT();
        wg_wait<1>();
        if (warp4 == 0 && wgi == 0) PROF2(3, sl + (passA ? 0 : 8));
        if (lane < 2 && sl && (passA || !convCTA || sl < 6)) mbar_arrive_cluster(e_cl + prev * 8, 1);
        if (!passA) {
            if (sl == 4) {
                if (convCTA) { if (lane == 0) mbar_arrive(sb + SM_BARS + B_XFREE * 8); }
                else if (lane < 4) mbar_arrive_cluster(e_cl + (3 + (lane >> 1)) * 8, 1);
            }
        }
        prev = st;
        st = (st == 2) ? 0 : st + 1;
    }
    wg_wait<0>();
    if (lane < 2 && (passA || !convCTA)) mbar_arrive_cluster(e_cl + prev * 8, 1);
    if (!passA && lane == 0) mbar_arrive(sb + SM_BARS + B_G1DONE * 8);
    if (warp4 == 0) PROF(3 + wgi * 8 + (passA ? 0 : 3));
    const int g = lane >> 2;
    const int r0 = wgi * 64 + warp4 * 16 + g;
    const float s0 = __uint_as_float(lds32(sb + SM_STATS + r0 * 8 + 4)), s1 = __uint_as_float(lds32(sb + SM_STATS + (r0 + 8) * 8 + 4));
    uint32_t* dst = g_h + (size_t)((rb64 >> 1) * 56 + ks0) * 2048 + wgi * 1024 + warp4 * 128 + lane;
    #pragma unroll
    for (int kk = 0; kk < NB * 2; kk++) {
        uint32_t h[4];
        #pragma unroll
        for (int tt = 0; tt < 2; tt++) {
            const int t = 2 * kk + tt;
            const float* ag = &acc[4 * t];
            const float* au = &acc[NB * 16 + 4 * t];
            h[2 * tt] = bmul2(pack_bf(ag[0] * s0, ag[1] * s0), pack_bf(au[0] * s0, au[1] * s0));
            h[2 * tt + 1] = bmul2(pack_bf(ag[2] * s1, ag[3] * s1), pack_bf(au[2] * s1, au[3] * s1));
        }
        uint32_t* d2 = dst + (kk >> 1) * 2048 + (kk & 1) * 512;
        d2[0] = h[0]; d2[64] = h[1]; d2[32] = h[2]; d2[96] = h[3];
    }
    __syncwarp();
    if (lane == 0) mbar_arrive(sb + SM_BARS + (B_HD + wgi * 2 + (passA ? 0 : 1)) * 8);
    if (warp4 == 0) PROF(4 + wgi * 8 + (passA ? 0 : 3));
}

__global__ void __cluster_dims__(2, 1, 1) __launch_bounds__(NTHREADS, 1)
fused_kernel(const __grid_constant__ Params p) {
    extern __shared__ __align__(1024) uint8_t smem_raw[];
    const uint32_t sb = smem_u32(smem_raw);
    const int tid = threadIdx.x, warp = tid >> 5, lane = tid & 31;
    const int b = blockIdx.x;
    const int rank = b & 1;
    const int j = (b >> 1) & 7;
    const int i = ((b >> 4) << 1) | rank;
    const int cb = j >> 1;
    const bool convCTA = j & 1;
    const int cidx = 4 * i + cb;

    if (tid == 256) {
        mbar_init(sb + SM_BARS + B_XFULL * 8, 1);
        mbar_init(sb + SM_BARS + (B_XFULL + 1) * 8, 1);
        asm volatile("fence.proxy.async.shared::cta;" ::: "memory");
        mbar_expect_tx(sb + SM_BARS + B_XFULL * 8, 65536);
        tma3d(sb + SM_X, &p.tm_x, 0, 128 * i, 0, sb + SM_BARS + B_XFULL * 8);
        mbar_expect_tx(sb + SM_BARS + (B_XFULL + 1) * 8, 65536);
        tma3d(sb + SM_X + 65536, &p.tm_x, 0, 128 * i + 64, 0, sb + SM_BARS + (B_XFULL + 1) * 8);
    }
    if (tid == 288) {
        for (int s = 0; s < 5; s++) { mbar_init(sb + SM_BARS + (B_FULL + s) * 8, 1); mbar_init(sb + SM_BARS + (B_EMPTY + s) * 8, 16); }
        mbar_init(sb + SM_BARS + B_CONV * 8, 1);
        mbar_init(sb + SM_BARS + B_YT * 8, 1);
        mbar_init(sb + SM_BARS + B_XR * 8, 1);
        mbar_init(sb + SM_BARS + B_G1DONE * 8, 8);
        mbar_init(sb + SM_BARS + B_XFREE * 8, 8);
        mbar_init(sb + SM_BARS + B_YST * 8, 8);
        mbar_init(sb + SM_BARS + B_KVLD * 8, 2);
        for (int s = 0; s < 4; s++) mbar_init(sb + SM_BARS + (B_HD + s) * 8, 4);
        for (int s = 0; s < 2; s++) mbar_init(sb + SM_BARS + (B_HRDY + s) * 8, 1);
        asm volatile("fence.mbarrier_init.release.cluster;" ::: "memory");
        asm volatile("fence.proxy.async.shared::cta;" ::: "memory");
    }
    __syncwarp();
    asm volatile("barrier.cluster.arrive.relaxed.aligned;\n" ::: "memory");
    asm volatile("barrier.cluster.wait.aligned;\n" ::: "memory");
    PROFW(1, 0);

    if (warp < 8) {
        asm volatile("setmaxnreg.inc.sync.aligned.u32 200;");
        const int wgi = warp >> 2, warp4 = warp & 3;
        const int g = lane >> 2, c = lane & 3;
        const uint32_t e_cl = mapa(sb + SM_BARS + B_EMPTY * 8, lane & 1);
        {
            const int lrow = warp * 4 + (lane >> 3);
            const uint32_t xa = sb + SM_X + lrow * 128 + (((lane & 7) ^ (lrow & 7)) << 4);
            #pragma unroll 1
            for (int rg = 0; rg < 4; rg++) {
                uint4 xr[8];
                mbar_wait(sb + SM_BARS + (B_XFULL + (rg >> 1)) * 8, 0);
                if (rg == 0) PROFW(16, 0);
                if (rg == 2) PROFW(18, 0);
                const uint32_t xo = xa + (rg >> 1) * 65536 + (rg & 1) * 4096;
                #pragma unroll
                for (int sl = 0; sl < 8; sl++) xr[sl] = lds128(xo + sl * 8192);
                float s0 = 0.f, q0 = 0.f, s1 = 0.f, q1 = 0.f, s2 = 0.f, q2 = 0.f, s3 = 0.f, q3 = 0.f;
                #pragma unroll
                for (int sl = 0; sl < 8; sl++) {
                    float lo = bf_lo(xr[sl].x), hi = bf_hi(xr[sl].x); s0 += lo; q0 = fmaf(lo, lo, q0); s1 += hi; q1 = fmaf(hi, hi, q1);
                    lo = bf_lo(xr[sl].y); hi = bf_hi(xr[sl].y); s2 += lo; q2 = fmaf(lo, lo, q2); s3 += hi; q3 = fmaf(hi, hi, q3);
                    lo = bf_lo(xr[sl].z); hi = bf_hi(xr[sl].z); s0 += lo; q0 = fmaf(lo, lo, q0); s1 += hi; q1 = fmaf(hi, hi, q1);
                    lo = bf_lo(xr[sl].w); hi = bf_hi(xr[sl].w); s2 += lo; q2 = fmaf(lo, lo, q2); s3 += hi; q3 = fmaf(hi, hi, q3);
                }
                float sm = (s0 + s1) + (s2 + s3), sq = (q0 + q1) + (q2 + q3);
                #pragma unroll
                for (int o = 1; o < 8; o <<= 1) { sm += __shfl_xor_sync(0xffffffffu, sm, o); sq += __shfl_xor_sync(0xffffffffu, sq, o); }
                const float mean = sm * (1.0f / DM);
                const uint32_t m = pack_bf(mean, mean);
                #pragma unroll
                for (int sl = 0; sl < 8; sl++) {
                    uint4 t = xr[sl];
                    t.x = bsub2(t.x, m); t.y = bsub2(t.y, m); t.z = bsub2(t.z, m); t.w = bsub2(t.w, m);
                    sts128(xo + sl * 8192, t);
                }
                if ((lane & 7) == 0) {
                    const float var_b = bf_round(fmaxf(sq * (1.0f / DM) - mean * mean, 0.f));
                    const float sd = bf_round(sqrtf(bf_round(var_b + 1e-5f)));
                    sts32(sb + SM_STATS + (rg * 32 + lrow) * 8, m);
                    sts32(sb + SM_STATS + (rg * 32 + lrow) * 8 + 4, __float_as_uint(1.0f / sd));
                }
            }
            asm volatile("fence.proxy.async.shared::cta;" ::: "memory");
            named_bar(3, 256);
            PROFW(17, 0);
        }
        int st = 0; uint32_t fph = 0;
        const int rb64 = 2 * i + wgi;
        gemm1_pass<4>(sb, wgi, warp4, lane, st, fph, e_cl, rb64, 4 * j, convCTA);
        gemm1_pass<3>(sb, wgi, warp4, lane, st, fph, e_cl, rb64, 32 + 3 * j, convCTA);

        if (convCTA) {
            const int gch = 8 * cidx + warp;
            const uint32_t xb = sb + SM_CVX + warp * 4096;
            const uint32_t hb = sb + SM_CVH + warp * 4096;
            const uint32_t dw = ((const unsigned short*)p.ssm_D)[gch];
            const uint32_t d2 = dw | (dw << 16);
            mbar_wait(sb + SM_BARS + B_CONV * 8, 0);
            PROFW(32, 4);
            float acc[16][4];
            #pragma unroll
            for (int jj = 0; jj < 16; jj++) { acc[jj][0] = 0.f; acc[jj][1] = 0.f; acc[jj][2] = 0.f; acc[jj][3] = 0.f; }
            uint2 bh[8], bl0[8], bl1[8];
            uint32_t xl = xb + g * 32 + c * 8;
            uint32_t hl = hb + (g + 2 * c - 8) * 4;
            #pragma unroll
            for (int d = 0; d < 8; d++) { bl0[d] = lds64(xl + d * 256); bh[d] = lds64(xl + (8 + d) * 256); }
            uint32_t w[6];
            w[0] = 0; w[1] = 0; w[2] = 0;
            if (g + 2 * c >= 8) w[0] = lds32(hl);
            if (g + 2 * c >= 7) w[1] = lds32(hl + 4);
            if (g + 2 * c >= 6) w[2] = lds32(hl + 8);
            w[3] = lds32(hl + 2048); w[4] = lds32(hl + 2052); w[5] = lds32(hl + 2056);
            auto conv_m0 = [&](int m0, uint2 (&bl)[8], uint2 (&bn)[8]) {
                xl -= 32;
                #pragma unroll
                for (int k = 0; k < 8; k++) {
                    const uint32_t a0 = w[1], a1 = __byte_perm(w[0], w[1], 0x5432), a2 = w[2], a3 = __byte_perm(w[1], w[2], 0x5432);
                    const uint32_t c0 = w[4], c1 = __byte_perm(w[3], w[4], 0x5432), c2 = w[5], c3 = __byte_perm(w[4], w[5], 0x5432);
                    const uint32_t nx = (k < 7) ? hl + (k + 1) * 256 : hl + 32;
                    w[0] = lds32(nx); w[1] = lds32(nx + 4); w[2] = lds32(nx + 8);
                    w[3] = lds32(nx + 2048); w[4] = lds32(nx + 2052); w[5] = lds32(nx + 2056);
                    if (k > 0) bn[k] = lds64(xl + k * 256);
                    else { bn[0] = make_uint2(0, 0); if (g > m0) bn[0] = lds64(xl); }
                    #pragma unroll
                    for (int jj = k; jj < 16; jj++) mma16816(acc[jj], a0, a1, a2, a3, (jj - k < 8) ? bl[(jj - k) & 7] : bh[(jj - k) & 7]);
                    bh[7 - k] = lds64(xl + (15 - k) * 256);
                    #pragma unroll
                    for (int jj = k + 8; jj < 16; jj++) mma16816(acc[jj], c0, c1, c2, c3, bl[jj - k - 8]);
                }
                hl += 32;
            };
            #pragma unroll 1
            for (int m0 = 0; m0 < 8; m0 += 2) {
                conv_m0(m0, bl0, bl1);
                conv_m0(m0 + 1, bl1, bl0);
                PROFW(34 + (m0 >> 1), 4);
            }
            PROFW(33, 4);
            const uint32_t kvl = xb + c * 64 + (7 - g) * 4;
            uint32_t* ydst = (uint32_t*)(g_yT + (size_t)gch * SEQ + 32 * c + 2 * g);
            uint32_t kk0[16], kk1[16];
            #pragma unroll
            for (int jj = 0; jj < 16; jj++) { kk0[jj] = lds32(kvl + jj * 256); kk1[jj] = lds32(kvl + jj * 256 + 32); }
            #pragma unroll
            for (int jj = 0; jj < 16; jj++) {
                ydst[jj * 64] = badd2(pack_bf(acc[jj][2], acc[jj][0]), bmul2(__byte_perm(kk0[jj], kk0[jj], 0x1032), d2));
                ydst[jj * 64 + 8] = badd2(pack_bf(acc[jj][3], acc[jj][1]), bmul2(__byte_perm(kk1[jj], kk1[jj], 0x1032), d2));
            }
            __syncwarp();
            PROFW(44, 4);
            if (lane == 0) mbar_arrive(sb + SM_BARS + B_YST * 8);
        } else {
            float acc[64];
            const uint64_t descB0 = make_desc(sb, 4096, 1024, 1);
            const uint64_t descA0 = make_desc(sb + 16384 + wgi * 4096, 128, 256, 0);
            int sg = 3, p0 = 0; uint32_t ph = 6;
            PROFW(20, 0);
            #pragma unroll 1
            for (int u = 0; u < 28; u++) {
                if (warp == 0 && !(u & 1)) PROF2(2, 16 + (u >> 1));
                mbar_wait(sb + SM_BARS + (B_FULL + sg) * 8, (ph >> sg) & 1);
                ph ^= 1u << sg;
                if (warp == 0 && !(u & 1)) PROF2(1, 16 + (u >> 1));
                const uint32_t o0 = stage_off_rt(sg) >> 4;
                const uint64_t da0 = desc_add(descA0, o0), db0 = desc_add(descB0, o0);
                WG_FENCE();
                #pragma unroll
                for (int kk = 0; kk < 4; kk++) wgmma_ss_n128_tb(acc, da0 + ((kk >> 1) * 512 + (kk & 1) * 128), db0 + ((kk >> 1) * 512 + (kk & 1) * 128), (u | kk) ? 1 : 0);
                WG_COMMIT();
                wg_wait<1>();
                if (warp == 0 && !(u & 1)) PROF2(3, 16 + (u >> 1));
                if (lane < 2 && u > 0 && u + 4 < 28) mbar_arrive_cluster(e_cl + p0 * 8, 1);
                p0 = sg;
                sg = next_st2(sg);
            }
            wg_wait<0>();
            PROFW(27, 0);
            mbar_wait(sb + SM_BARS + B_XR * 8, 0);
            const int r0 = wgi * 64 + warp4 * 16 + g;
            const float2 st0 = lds64f(sb + SM_STATS + r0 * 8), st1 = lds64f(sb + SM_STATS + (r0 + 8) * 8);
            const uint32_t m0 = __float_as_uint(st0.x), m1 = __float_as_uint(st1.x);
            const uint32_t xrow0 = sb + SM_XE + r0 * 128 + c * 4;
            const int mi = lane >> 3, lr = lane & 7;
            const uint32_t yaddr = sb + SM_YT + wgi * 16384 + ((mi >> 1) * 8 + lr) * 128 + (((2 * warp4 + (mi & 1)) ^ lr) << 4);
            uint32_t y[8][4], xv[16][2], nv[16][2], bv[16][2];
            #pragma unroll
            for (int t = 0; t < 16; t++) {
                const uint32_t off = (t >> 3) * 16384 + (((t & 7) ^ g) << 4);
                xv[t][0] = lds32(xrow0 + off); xv[t][1] = lds32(xrow0 + 1024 + off);
            }
            #pragma unroll
            for (int t = 0; t < 16; t++) {
                const uint32_t d0 = bsub2(xv[t][0], m0), d1 = bsub2(xv[t][1], m1);
                nv[t][0] = pack_bf(bf_lo(d0) * st0.y, bf_hi(d0) * st0.y); nv[t][1] = pack_bf(bf_lo(d1) * st1.y, bf_hi(d1) * st1.y);
                bv[t][0] = pack_bf(acc[4 * t], acc[4 * t + 1]); bv[t][1] = pack_bf(acc[4 * t + 2], acc[4 * t + 3]);
            }
            mbar_wait(sb + SM_BARS + B_YT * 8, 0);
            PROFW(28, 0);
            #pragma unroll
            for (int t2 = 0; t2 < 8; t2++)
                asm volatile("ldmatrix.sync.aligned.m8n8.x4.trans.shared.b16 {%0,%1,%2,%3}, [%4];"
                    : "=r"(y[t2][0]), "=r"(y[t2][1]), "=r"(y[t2][2]), "=r"(y[t2][3]) : "r"(yaddr + t2 * 2048) : "memory");
            #pragma unroll
            for (int t = 0; t < 16; t++) {
                const uint32_t off = (t >> 3) * 16384 + (((t & 7) ^ g) << 4);
                sts32(xrow0 + off, badd2(badd2(xv[t][0], bmul2(nv[t][0], y[t >> 1][2 * (t & 1)])), bv[t][0]));
                sts32(xrow0 + 1024 + off, badd2(badd2(xv[t][1], bmul2(nv[t][1], y[t >> 1][2 * (t & 1) + 1])), bv[t][1]));
            }
            asm volatile("fence.proxy.async.shared::cta;" ::: "memory");
            named_bar(1 + wgi, 128);
            if ((tid & 127) == 0) {
                tma2d_store(&p.tm_out, 128 * cb, 128 * i + 64 * wgi, sb + SM_XE + wgi * 8192);
                tma2d_store(&p.tm_out, 128 * cb + 64, 128 * i + 64 * wgi, sb + SM_XE + 16384 + wgi * 8192);
                asm volatile("cp.async.bulk.commit_group;" ::: "memory");
                asm volatile("cp.async.bulk.wait_group.read 0;" ::: "memory");
                PROFW(29, 0);
            }
        }
    } else {
        asm volatile("setmaxnreg.dec.sync.aligned.u32 104;");
        if (warp == 8) {
            int st = 0; uint32_t eph = 7;
            #pragma unroll 1
            for (int it = 0; it < 16; it++) {
                const int pass = it >> 3, sl = it & 7;
                const int nb = pass ? 3 : 4;
                const CUtensorMap* tm = pass ? (rank ? &p.tm_uB : &p.tm_gB) : (rank ? &p.tm_uA : &p.tm_gA);
                mbar_wait(sb + SM_BARS + (B_EMPTY + st) * 8, (eph >> st) & 1);
                eph ^= 1u << st;
                if (it == 1) mbar_wait(sb + SM_BARS + B_XFULL * 8, 0);
                PROF2(0, it);
                if (elect_one()) {
                    mbar_expect_tx(sb + SM_BARS + (B_FULL + st) * 8, nb * 8192);
                    tma3d_mc(sb + SM_RING + st * STAGE_BYTES + rank * nb * 4096, tm, 0, sl * 64, 7 * j + 4 * pass, sb + SM_BARS + (B_FULL + st) * 8);
                }
                st = (st == 2) ? 0 : st + 1;
            }
            if (!convCTA) {
                st = 3;
                int f0 = 32 * rank, t3 = rank;
                #pragma unroll 1
                for (int u = 0; u < 28; u++) {
                    const uint32_t bar = sb + SM_BARS + (B_FULL + st) * 8;
                    mbar_wait(sb + SM_BARS + (B_EMPTY + st) * 8, (eph >> st) & 1);
                    eph ^= 1u << st;
                    if ((u & 1) == 0) PROF2(0, 16 + (u >> 1));
                    if (elect_one()) {
                        mbar_expect_tx(bar, 32768);
                        tma3d_mc(sb + stage_off_rt(st) + rank * 8192, &p.tm_w2, 0, f0, 2 * cb, bar);
                    }
                    st = next_st2(st);
                    if (u < 15) f0 += (u & 1) ? 160 : 64;
                    else if (u == 15) f0 = 128 + 32 * rank;
                    else { f0 += (t3 == 0) ? 64 : 192; t3 = (t3 == 0) ? 2 : t3 - 1; }
                }
                PROF(48);
            }
        } else if (warp < 11) {
            mbar_wait(sb + SM_BARS + (B_XFULL + 1) * 8, 0);
            #pragma unroll 1
            for (int rnd = 0; rnd < 2; rnd++) {
                const int tt = (tid - 288) + 64 * rnd;
                uint32_t sk[4][2];
                uint4 skw[2];
                skw[0] = ldg_nc128(p.shift_k + 16 * tt); skw[1] = ldg_nc128(p.shift_k + 16 * tt + 8);
                const __nv_bfloat16* kp = p.k + (size_t)(16 * b) * DM + 4 * tt;
                const __nv_bfloat16* vp = p.v + (size_t)(16 * b) * DM + 4 * tt;
                uint2 kr[19];
                uint2 kv[16];
                #pragma unroll
                for (int r = 0; r < 3; r++) kr[r] = (b > 0) ? ldg_nc64(kp + (r - 3) * DM) : make_uint2(0, 0);
                #pragma unroll
                for (int r = 0; r < 16; r++) { kr[3 + r] = ldg_nc64(kp + r * DM); kv[r] = ldg_nc64(vp + r * DM); }
                {
                    const uint4 w0 = skw[0], w1 = skw[1];
                    sk[0][0] = __byte_perm(w0.x, w0.z, 0x5410); sk[1][0] = __byte_perm(w0.x, w0.z, 0x7632);
                    sk[2][0] = __byte_perm(w0.y, w0.w, 0x5410); sk[3][0] = __byte_perm(w0.y, w0.w, 0x7632);
                    sk[0][1] = __byte_perm(w1.x, w1.z, 0x5410); sk[1][1] = __byte_perm(w1.x, w1.z, 0x7632);
                    sk[2][1] = __byte_perm(w1.y, w1.w, 0x5410); sk[3][1] = __byte_perm(w1.y, w1.w, 0x7632);
                }
                #pragma unroll
                for (int s = 0; s < 16; s++) {
                    uint32_t a = bmul2(kr[s].x, sk[3][0]);
                    a = badd2(a, bmul2(kr[s + 1].x, sk[2][0]));
                    a = badd2(a, bmul2(kr[s + 2].x, sk[1][0]));
                    a = badd2(a, bmul2(kr[s + 3].x, sk[0][0]));
                    kv[s].x = bmul2(a, kv[s].x);
                    a = bmul2(kr[s].y, sk[3][1]);
                    a = badd2(a, bmul2(kr[s + 1].y, sk[2][1]));
                    a = badd2(a, bmul2(kr[s + 2].y, sk[1][1]));
                    a = badd2(a, bmul2(kr[s + 3].y, sk[0][1]));
                    kv[s].y = bmul2(a, kv[s].y);
                }
                PROFW(57 + 2 * rnd, 9);
                if (rnd == 1 && lane == 0) mbar_arrive(sb + SM_BARS + B_KVLD * 8);
                #pragma unroll
                for (int cc = 0; cc < 4; cc++) {
                    const uint32_t sel = (cc & 1) ? 0x7632 : 0x5410;
                    #define KVW(r) ((cc & 2) ? kv[r].y : kv[r].x)
                    uint4* dst = (uint4*)(g_kvT + (size_t)(4 * tt + cc) * SEQ + 16 * b);
                    dst[0] = make_uint4(__byte_perm(KVW(15), KVW(14), sel), __byte_perm(KVW(13), KVW(12), sel),
                                        __byte_perm(KVW(11), KVW(10), sel), __byte_perm(KVW(9), KVW(8), sel));
                    dst[1] = make_uint4(__byte_perm(KVW(7), KVW(6), sel), __byte_perm(KVW(5), KVW(4), sel),
                                        __byte_perm(KVW(3), KVW(2), sel), __byte_perm(KVW(1), KVW(0), sel));
                    #undef KVW
                }
                PROFW(58 + 2 * rnd, 9);
            }
            asm volatile("fence.proxy.async.global;" ::: "memory");
            __syncwarp();
            if (lane == 0) {
                flag_add(&g_cnt_kv[0]);
                PROFW(50, 9);
                const int wgi = warp - 9;
                mbar_wait(sb + SM_BARS + (B_HD + wgi * 2) * 8, 0);
                flag_add(&g_flag_h[(i * 2 + 0) * 8]);
                mbar_wait(sb + SM_BARS + (B_HD + wgi * 2 + 1) * 8, 0);
                flag_add(&g_flag_h[(i * 2 + 1) * 8]);
                if (wgi == 1 && convCTA) {
                    mbar_wait(sb + SM_BARS + B_YST * 8, 0);
                    flag_add(&g_cnt_y[(cidx >> 4) * 32]);
                    PROF(46);
                }
                if (wgi == 1 && !convCTA) {
                    const unsigned ep = lds32(sb + SM_EPOCH);
                    mbar_wait(sb + SM_BARS + B_G1DONE * 8, 0);
                    mbar_expect_tx(sb + SM_BARS + B_XR * 8, 32768);
                    tma3d(sb + SM_XE, &p.tm_xe, 0, 128 * i, 2 * cb, sb + SM_BARS + B_XR * 8);
                    flag_wait(&g_flag_h[(i * 2 + 1) * 8], ep * 16);
                    mbar_arrive(sb + SM_BARS + (B_HRDY + 1) * 8);
                    __nanosleep(3000);
                    flag_wait(&g_cnt_y[cb * 32], ep * 16);
                    PROF(49);
                    asm volatile("fence.proxy.async.global;" ::: "memory");
                    mbar_expect_tx(sb + SM_BARS + B_YT * 8, 32768);
                    tma2d(sb + SM_YT, &p.tm_yT, 128 * i, 128 * cb, sb + SM_BARS + B_YT * 8);
                    tma2d(sb + SM_YT + 16384, &p.tm_yT, 128 * i + 64, 128 * cb, sb + SM_BARS + B_YT * 8);
                }
            }
        } else {
            if (lane == 0) {
                l2_prefetch(p.wg + (size_t)b * (FF * DM / NCTA), FF * DM / NCTA * 2);
                l2_prefetch(p.wu + (size_t)b * (FF * DM / NCTA), FF * DM / NCTA * 2);
                const unsigned ep = g_launch[b] + 1;
                g_launch[b] = ep;
                sts32(sb + SM_EPOCH, ep);
                tmap_prefetch(rank ? &p.tm_uA : &p.tm_gA);
                tmap_prefetch(rank ? &p.tm_uB : &p.tm_gB);
                tmap_prefetch(&p.tm_w2); tmap_prefetch(&p.tm_yT); tmap_prefetch(&p.tm_out); tmap_prefetch(&p.tm_xe);
                mbar_wait(sb + SM_BARS + B_KVLD * 8, 0);
                l2_prefetch(p.ssm_k + (size_t)(4 * b) * SEQ, 4 * SEQ * 2);
                l2_prefetch(p.wd + (size_t)b * (FF * DM / NCTA), FF * DM / NCTA * 2);
                mbar_wait(sb + SM_BARS + (B_HD + 0) * 8, 0);
                if (convCTA) {
                    flag_wait(&g_cnt_kv[0], ep * 256);
                    asm volatile("fence.proxy.async.global;" ::: "memory");
                    PROF(53);
                    mbar_wait(sb + SM_BARS + B_XFREE * 8, 0);
                    PROF(54);
                    mbar_expect_tx(sb + SM_BARS + B_CONV * 8, 65536);
                    bulk_g2s(sb + SM_CVX, g_kvT + (size_t)(8 * cidx) * SEQ, 32768, sb + SM_BARS + B_CONV * 8);
                    bulk_g2s(sb + SM_CVH, p.ssm_k + (size_t)(8 * cidx) * SEQ, 32768, sb + SM_BARS + B_CONV * 8);
                } else {
                    flag_wait(&g_flag_h[(i * 2 + 0) * 8], ep * 16);
                }
            }
            __syncwarp();
            if (!convCTA) {
                asm volatile("fence.proxy.async.global;" ::: "memory");
                int st = 3; uint32_t eph = 1;
                const uint8_t* hsrc = (const uint8_t*)g_h + (size_t)i * 56 * 8192;
                #pragma unroll 1
                for (int u = 0; u < 28; u++) {
                    mbar_wait(sb + SM_BARS + (B_EMPTY + st) * 8, (eph >> st) & 1);
                    eph ^= 1u << st;
                    if (u == 16) {
                        mbar_wait(sb + SM_BARS + (B_HRDY + 1) * 8, 0);
                        asm volatile("fence.proxy.async.global;" ::: "memory");
                    }
                    if (elect_one()) bulk_g2s(sb + stage_off_rt(st) + 16384, hsrc + u * 16384, 16384, sb + SM_BARS + (B_FULL + st) * 8);
                    st = next_st2(st);
                }
            }
        }
    }
}

typedef CUresult (*EncodeFn)(CUtensorMap*, CUtensorMapDataType, cuuint32_t, void*, const cuuint64_t*, const cuuint64_t*,
                             const cuuint32_t*, const cuuint32_t*, CUtensorMapInterleave, CUtensorMapSwizzle,
                             CUtensorMapL2promotion, CUtensorMapFloatOOBfill);

void encode(EncodeFn fn, CUtensorMap* tm, const void* base, int rank, const cuuint64_t* dims, const cuuint64_t* strides,
            const cuuint32_t* box, CUtensorMapSwizzle swz) {
    cuuint32_t es[5] = {1, 1, 1, 1, 1};
    fn(tm, CU_TENSOR_MAP_DATA_TYPE_BFLOAT16, rank, (void*)base, dims, strides, box, es, CU_TENSOR_MAP_INTERLEAVE_NONE, swz,
       CU_TENSOR_MAP_L2_PROMOTION_L2_128B, CU_TENSOR_MAP_FLOAT_OOB_FILL_NONE);
}

}

extern "C" void kernel_launch(void* const* d_in, const int* in_sizes, int n_in, void* d_out, int out_size) {
    (void)in_sizes; (void)n_in; (void)out_size;
    static EncodeFn enc = nullptr;
    static void* yT_ptr = nullptr;
    if (!enc) {
        void* fn = nullptr; cudaDriverEntryPointQueryResult qr;
        cudaGetDriverEntryPoint("cuTensorMapEncodeTiled", &fn, cudaEnableDefault, &qr);
        enc = (EncodeFn)fn;
        cudaGetSymbolAddress(&yT_ptr, g_yT);
        cudaFuncSetAttribute(fused_kernel, cudaFuncAttributeMaxDynamicSharedMemorySize, SM_TOTAL);
    }
    Params p;
    p.q = (const __nv_bfloat16*)d_in[0]; p.k = (const __nv_bfloat16*)d_in[1]; p.v = (const __nv_bfloat16*)d_in[2];
    p.shift_k = (const __nv_bfloat16*)d_in[3]; p.ssm_k = (const __nv_bfloat16*)d_in[4]; p.ssm_D = (const __nv_bfloat16*)d_in[5];
    p.wg = (const __nv_bfloat16*)d_in[7]; p.wu = (const __nv_bfloat16*)d_in[8]; p.wd = (const __nv_bfloat16*)d_in[9];
    {
        cuuint64_t dims[2] = {DM, SEQ}; cuuint64_t str[1] = {DM * 2};
        cuuint64_t dims3[3] = {64, SEQ, DM / 64}; cuuint64_t str3[2] = {DM * 2, 128};
        cuuint32_t box[3] = {64, 64, 8}, boxe[3] = {64, 128, 2};
        encode(enc, &p.tm_x, p.q, 3, dims3, str3, box, CU_TENSOR_MAP_SWIZZLE_128B);
        encode(enc, &p.tm_xe, p.q, 3, dims3, str3, boxe, CU_TENSOR_MAP_SWIZZLE_128B);
        cuuint32_t box2[2] = {64, 64};
        encode(enc, &p.tm_out, d_out, 2, dims, str, box2, CU_TENSOR_MAP_SWIZZLE_128B);
    }
    {
        cuuint64_t dims[3] = {32, DM, FF / 32}; cuuint64_t str[2] = {FF * 2, 64};
        cuuint32_t boxA[3] = {32, 64, 4}, boxB[3] = {32, 64, 3};
        encode(enc, &p.tm_gA, p.wg, 3, dims, str, boxA, CU_TENSOR_MAP_SWIZZLE_64B);
        encode(enc, &p.tm_gB, p.wg, 3, dims, str, boxB, CU_TENSOR_MAP_SWIZZLE_64B);
        encode(enc, &p.tm_uA, p.wu, 3, dims, str, boxA, CU_TENSOR_MAP_SWIZZLE_64B);
        encode(enc, &p.tm_uB, p.wu, 3, dims, str, boxB, CU_TENSOR_MAP_SWIZZLE_64B);
    }
    {
        cuuint64_t dims[3] = {64, FF, DM / 64}; cuuint64_t str[2] = {DM * 2, 128};
        cuuint32_t box[3] = {64, 32, 2};
        encode(enc, &p.tm_w2, p.wd, 3, dims, str, box, CU_TENSOR_MAP_SWIZZLE_128B);
    }
    {
        cuuint64_t dims[2] = {SEQ, DM}; cuuint64_t str[1] = {SEQ * 2};
        cuuint32_t box[2] = {64, 128};
        encode(enc, &p.tm_yT, yT_ptr, 2, dims, str, box, CU_TENSOR_MAP_SWIZZLE_128B);
    }
    fused_kernel<<<NCTA, NTHREADS, SM_TOTAL>>>(p);
}
```

```cpp
#include <cuda_runtime.h>
#include <cuda_bf16.h>
#include <cuda.h>
#include <stdint.h>

namespace {

constexpr int SEQ = 2048, DM = 512, FF = 1792;
constexpr int NCTA = 128;
constexpr int NTHREADS = 384;
constexpr int STAGE_BYTES = 32768;

constexpr uint32_t SM_X = 0;
constexpr uint32_t SM_RING = 131072;
constexpr uint32_t SM_MISC = SM_RING + 3 * STAGE_BYTES;
constexpr uint32_t SM_BARS = SM_MISC;
constexpr uint32_t SM_EPOCH = SM_MISC + 248;
constexpr uint32_t SM_STATS = SM_MISC + 256;
constexpr uint32_t SM_TOTAL = SM_STATS + 1024;
static_assert(SM_TOTAL <= 232448, "smem");
constexpr uint32_t SM_CVX = 0;
constexpr uint32_t SM_CVH = 65536;
constexpr uint32_t SM_YT = 32768;
constexpr uint32_t SM_XE = 98304;

constexpr int B_FULL = 0, B_EMPTY = 5, B_XFULL = 10, B_CONV = 14, B_YT = 15, B_XR = 16, B_G1DONE = 17, B_HD = 18, B_HRDY = 22,
              B_XFREE = 24, B_YST = 25, B_KVLD = 26, B_COUNT = 27;
static_assert(B_COUNT * 8 <= 248, "barrier space");

__device__ __align__(128) uint32_t g_h[16 * 56 * 2048];
__device__ __align__(128) __nv_bfloat16 g_kvT[DM * SEQ];
__device__ __align__(128) __nv_bfloat16 g_yT[DM * SEQ];
__device__ unsigned g_launch[NCTA];
__device__ unsigned g_cnt_kv[32];
__device__ unsigned g_cnt_y[4 * 32];
__device__ unsigned g_flag_h[16 * 2 * 8];

#define PROF(idx)
#define PROF2(a, idx)
#define PROFW(idx, w)

struct Params {
    CUtensorMap tm_x, tm_gA, tm_gB, tm_uA, tm_uB, tm_w2, tm_yT, tm_out, tm_xe;
    const __nv_bfloat16 *q, *k, *v, *shift_k, *ssm_k, *ssm_D, *wg, *wu, *wd;
};

__device__ __forceinline__ void wgmma_rs_n32(float (&d)[16], uint32_t a0, uint32_t a1, uint32_t a2, uint32_t a3, uint64_t db, int sc) {
  asm volatile("{\n.reg .pred p;\nsetp.ne.b32 p, %21, 0;\n"
    "wgmma.mma_async.sync.aligned.m64n32k16.f32.bf16.bf16 {%0,%1,%2,%3,%4,%5,%6,%7,%8,%9,%10,%11,%12,%13,%14,%15}, {%16,%17,%18,%19}, %20, p, 1, 1, 0;\n}\n"
    : "+f"(d[0]),"+f"(d[1]),"+f"(d[2]),"+f"(d[3]),"+f"(d[4]),"+f"(d[5]),"+f"(d[6]),"+f"(d[7]),"+f"(d[8]),"+f"(d[9]),"+f"(d[10]),"+f"(d[11]),"+f"(d[12]),"+f"(d[13]),"+f"(d[14]),"+f"(d[15])
    : "r"(a0),"r"(a1),"r"(a2),"r"(a3),"l"(db),"r"(sc));
}
__device__ __forceinline__ void wgmma_rs_n128_tb(float (&d)[64], uint32_t a0, uint32_t a1, uint32_t a2, uint32_t a3, uint64_t db, int sc) {
  asm volatile("{\n.reg .pred p;\nsetp.ne.b32 p, %69, 0;\n"
    "wgmma.mma_async.sync.aligned.m64n128k16.f32.bf16.bf16 {%0,%1,%2,%3,%4,%5,%6,%7,%8,%9,%10,%11,%12,%13,%14,%15,%16,%17,%18,%19,%20,%21,%22,%23,%24,%25,%26,%27,%28,%29,%30,%31,%32,%33,%34,%35,%36,%37,%38,%39,%40,%41,%42,%43,%44,%45,%46,%47,%48,%49,%50,%51,%52,%53,%54,%55,%56,%57,%58,%59,%60,%61,%62,%63}, {%64,%65,%66,%67}, %68, p, 1, 1, 1;\n}\n"
    : "+f"(d[0]),"+f"(d[1]),"+f"(d[2]),"+f"(d[3]),"+f"(d[4]),"+f"(d[5]),"+f"(d[6]),"+f"(d[7]),"+f"(d[8]),"+f"(d[9]),"+f"(d[10]),"+f"(d[11]),"+f"(d[12]),"+f"(d[13]),"+f"(d[14]),"+f"(d[15]),"+f"(d[16]),"+f"(d[17]),"+f"(d[18]),"+f"(d[19]),"+f"(d[20]),"+f"(d[21]),"+f"(d[22]),"+f"(d[23]),"+f"(d[24]),"+f"(d[25]),"+f"(d[26]),"+f"(d[27]),"+f"(d[28]),"+f"(d[29]),"+f"(d[30]),"+f"(d[31]),"+f"(d[32]),"+f"(d[33]),"+f"(d[34]),"+f"(d[35]),"+f"(d[36]),"+f"(d[37]),"+f"(d[38]),"+f"(d[39]),"+f"(d[40]),"+f"(d[41]),"+f"(d[42]),"+f"(d[43]),"+f"(d[44]),"+f"(d[45]),"+f"(d[46]),"+f"(d[47]),"+f"(d[48]),"+f"(d[49]),"+f"(d[50]),"+f"(d[51]),"+f"(d[52]),"+f"(d[53]),"+f"(d[54]),"+f"(d[55]),"+f"(d[56]),"+f"(d[57]),"+f"(d[58]),"+f"(d[59]),"+f"(d[60]),"+f"(d[61]),"+f"(d[62]),"+f"(d[63])
    : "r"(a0),"r"(a1),"r"(a2),"r"(a3),"l"(db),"r"(sc));
}
__device__ __forceinline__ void wgmma_ss_n256_tb(float (&d)[128], uint64_t da, uint64_t db, int sc) {
  asm volatile("{\n.reg .pred p;\nsetp.ne.b32 p, %130, 0;\n"
    "wgmma.mma_async.sync.aligned.m64n256k16.f32.bf16.bf16 {%0,%1,%2,%3,%4,%5,%6,%7,%8,%9,%10,%11,%12,%13,%14,%15,%16,%17,%18,%19,%20,%21,%22,%23,%24,%25,%26,%27,%28,%29,%30,%31,%32,%33,%34,%35,%36,%37,%38,%39,%40,%41,%42,%43,%44,%45,%46,%47,%48,%49,%50,%51,%52,%53,%54,%55,%56,%57,%58,%59,%60,%61,%62,%63,%64,%65,%66,%67,%68,%69,%70,%71,%72,%73,%74,%75,%76,%77,%78,%79,%80,%81,%82,%83,%84,%85,%86,%87,%88,%89,%90,%91,%92,%93,%94,%95,%96,%97,%98,%99,%100,%101,%102,%103,%104,%105,%106,%107,%108,%109,%110,%111,%112,%113,%114,%115,%116,%117,%118,%119,%120,%121,%122,%123,%124,%125,%126,%127}, %128, %129, p, 1, 1, 0, 1;\n}\n"
    : "+f"(d[0]),"+f"(d[1]),"+f"(d[2]),"+f"(d[3]),"+f"(d[4]),"+f"(d[5]),"+f"(d[6]),"+f"(d[7]),"+f"(d[8]),"+f"(d[9]),"+f"(d[10]),"+f"(d[11]),"+f"(d[12]),"+f"(d[13]),"+f"(d[14]),"+f"(d[15]),"+f"(d[16]),"+f"(d[17]),"+f"(d[18]),"+f"(d[19]),"+f"(d[20]),"+f"(d[21]),"+f"(d[22]),"+f"(d[23]),"+f"(d[24]),"+f"(d[25]),"+f"(d[26]),"+f"(d[27]),"+f"(d[28]),"+f"(d[29]),"+f"(d[30]),"+f"(d[31]),"+f"(d[32]),"+f"(d[33]),"+f"(d[34]),"+f"(d[35]),"+f"(d[36]),"+f"(d[37]),"+f"(d[38]),"+f"(d[39]),"+f"(d[40]),"+f"(d[41]),"+f"(d[42]),"+f"(d[43]),"+f"(d[44]),"+f"(d[45]),"+f"(d[46]),"+f"(d[47]),"+f"(d[48]),"+f"(d[49]),"+f"(d[50]),"+f"(d[51]),"+f"(d[52]),"+f"(d[53]),"+f"(d[54]),"+f"(d[55]),"+f"(d[56]),"+f"(d[57]),"+f"(d[58]),"+f"(d[59]),"+f"(d[60]),"+f"(d[61]),"+f"(d[62]),"+f"(d[63]),"+f"(d[64]),"+f"(d[65]),"+f"(d[66]),"+f"(d[67]),"+f"(d[68]),"+f"(d[69]),"+f"(d[70]),"+f"(d[71]),"+f"(d[72]),"+f"(d[73]),"+f"(d[74]),"+f"(d[75]),"+f"(d[76]),"+f"(d[77]),"+f"(d[78]),"+f"(d[79]),"+f"(d[80]),"+f"(d[81]),"+f"(d[82]),"+f"(d[83]),"+f"(d[84]),"+f"(d[85]),"+f"(d[86]),"+f"(d[87]),"+f"(d[88]),"+f"(d[89]),"+f"(d[90]),"+f"(d[91]),"+f"(d[92]),"+f"(d[93]),"+f"(d[94]),"+f"(d[95]),"+f"(d[96]),"+f"(d[97]),"+f"(d[98]),"+f"(d[99]),"+f"(d[100]),"+f"(d[101]),"+f"(d[102]),"+f"(d[103]),"+f"(d[104]),"+f"(d[105]),"+f"(d[106]),"+f"(d[107]),"+f"(d[108]),"+f"(d[109]),"+f"(d[110]),"+f"(d[111]),"+f"(d[112]),"+f"(d[113]),"+f"(d[114]),"+f"(d[115]),"+f"(d[116]),"+f"(d[117]),"+f"(d[118]),"+f"(d[119]),"+f"(d[120]),"+f"(d[121]),"+f"(d[122]),"+f"(d[123]),"+f"(d[124]),"+f"(d[125]),"+f"(d[126]),"+f"(d[127])
    : "l"(da),"l"(db),"r"(sc));
}
__device__ __forceinline__ void wgmma_ss_n192_tb(float (&d)[96], uint64_t da, uint64_t db, int sc) {
  asm volatile("{\n.reg .pred p;\nsetp.ne.b32 p, %98, 0;\n"
    "wgmma.mma_async.sync.aligned.m64n192k16.f32.bf16.bf16 {%0,%1,%2,%3,%4,%5,%6,%7,%8,%9,%10,%11,%12,%13,%14,%15,%16,%17,%18,%19,%20,%21,%22,%23,%24,%25,%26,%27,%28,%29,%30,%31,%32,%33,%34,%35,%36,%37,%38,%39,%40,%41,%42,%43,%44,%45,%46,%47,%48,%49,%50,%51,%52,%53,%54,%55,%56,%57,%58,%59,%60,%61,%62,%63,%64,%65,%66,%67,%68,%69,%70,%71,%72,%73,%74,%75,%76,%77,%78,%79,%80,%81,%82,%83,%84,%85,%86,%87,%88,%89,%90,%91,%92,%93,%94,%95}, %96, %97, p, 1, 1, 0, 1;\n}\n"
    : "+f"(d[0]),"+f"(d[1]),"+f"(d[2]),"+f"(d[3]),"+f"(d[4]),"+f"(d[5]),"+f"(d[6]),"+f"(d[7]),"+f"(d[8]),"+f"(d[9]),"+f"(d[10]),"+f"(d[11]),"+f"(d[12]),"+f"(d[13]),"+f"(d[14]),"+f"(d[15]),"+f"(d[16]),"+f"(d[17]),"+f"(d[18]),"+f"(d[19]),"+f"(d[20]),"+f"(d[21]),"+f"(d[22]),"+f"(d[23]),"+f"(d[24]),"+f"(d[25]),"+f"(d[26]),"+f"(d[27]),"+f"(d[28]),"+f"(d[29]),"+f"(d[30]),"+f"(d[31]),"+f"(d[32]),"+f"(d[33]),"+f"(d[34]),"+f"(d[35]),"+f"(d[36]),"+f"(d[37]),"+f"(d[38]),"+f"(d[39]),"+f"(d[40]),"+f"(d[41]),"+f"(d[42]),"+f"(d[43]),"+f"(d[44]),"+f"(d[45]),"+f"(d[46]),"+f"(d[47]),"+f"(d[48]),"+f"(d[49]),"+f"(d[50]),"+f"(d[51]),"+f"(d[52]),"+f"(d[53]),"+f"(d[54]),"+f"(d[55]),"+f"(d[56]),"+f"(d[57]),"+f"(d[58]),"+f"(d[59]),"+f"(d[60]),"+f"(d[61]),"+f"(d[62]),"+f"(d[63]),"+f"(d[64]),"+f"(d[65]),"+f"(d[66]),"+f"(d[67]),"+f"(d[68]),"+f"(d[69]),"+f"(d[70]),"+f"(d[71]),"+f"(d[72]),"+f"(d[73]),"+f"(d[74]),"+f"(d[75]),"+f"(d[76]),"+f"(d[77]),"+f"(d[78]),"+f"(d[79]),"+f"(d[80]),"+f"(d[81]),"+f"(d[82]),"+f"(d[83]),"+f"(d[84]),"+f"(d[85]),"+f"(d[86]),"+f"(d[87]),"+f"(d[88]),"+f"(d[89]),"+f"(d[90]),"+f"(d[91]),"+f"(d[92]),"+f"(d[93]),"+f"(d[94]),"+f"(d[95])
    : "l"(da),"l"(db),"r"(sc));
}

__device__ __forceinline__ uint32_t smem_u32(const void* p) { return (uint32_t)__cvta_generic_to_shared(p); }
__device__ __forceinline__ void mbar_init(uint32_t bar, uint32_t cnt) { asm volatile("mbarrier.init.shared::cta.b64 [%0], %1;" :: "r"(bar), "r"(cnt)); }
__device__ __forceinline__ void mbar_expect_tx(uint32_t bar, uint32_t bytes) { asm volatile("mbarrier.arrive.expect_tx.shared::cta.b64 _, [%0], %1;" :: "r"(bar), "r"(bytes) : "memory"); }
__device__ __forceinline__ void mbar_arrive(uint32_t bar) { asm volatile("mbarrier.arrive.shared::cta.b64 _, [%0];" :: "r"(bar) : "memory"); }
__device__ __forceinline__ void mbar_arrive_cluster(uint32_t cbar, uint32_t cnt) { asm volatile("mbarrier.arrive.shared::cluster.b64 _, [%0], %1;" :: "r"(cbar), "r"(cnt) : "memory"); }
__device__ __forceinline__ uint32_t mapa(uint32_t a, uint32_t rank) { uint32_t r; asm volatile("mapa.shared::cluster.u32 %0, %1, %2;" : "=r"(r) : "r"(a), "r"(rank)); return r; }
__device__ __forceinline__ void mbar_wait(uint32_t bar, uint32_t parity) {
    uint32_t ok; uint32_t n = 0;
    do {
        asm volatile("{\n.reg .pred p;\nmbarrier.try_wait.parity.shared::cta.b64 p, [%1], %2;\nselp.u32 %0, 1, 0, p;\n}" : "=r"(ok) : "r"(bar), "r"(parity) : "memory");
    } while (!ok && ++n < (1u << 17));
}
__device__ __forceinline__ void pace_wait(uint32_t a, uint32_t target) {
    uint32_t v, n = 0;
    do {
        asm volatile("ld.volatile.shared.u32 %0, [%1];" : "=r"(v) : "r"(a) : "memory");
        if (v < target) __nanosleep(150);
    } while (v < target && ++n < (1u << 14));
}
__device__ __forceinline__ void flag_wait(const unsigned* p, unsigned target) {
    unsigned v; uint32_t n = 0;
    while (true) {
        asm volatile("ld.acquire.gpu.global.u32 %0, [%1];" : "=r"(v) : "l"(p) : "memory");
        if ((int)(v - target) >= 0 || ++n >= (1u << 17)) break;
        __nanosleep(100);
    }
}
__device__ __forceinline__ void flag_add(unsigned* p) {
    asm volatile("fence.acq_rel.gpu;\nred.relaxed.gpu.global.add.u32 [%0], 1;" :: "l"(p) : "memory");
}
__device__ __forceinline__ uint64_t make_desc(uint32_t addr, uint32_t lbo, uint32_t sbo, uint32_t swz) {
    return (uint64_t)((addr & 0x3FFFF) >> 4) | ((uint64_t)((lbo & 0x3FFFF) >> 4) << 16) | ((uint64_t)((sbo & 0x3FFFF) >> 4) << 32) | ((uint64_t)swz << 62);
}
__device__ __forceinline__ uint64_t desc_add(uint64_t d, uint32_t off16) {
    return (d & 0xFFFFFFFF00000000ull) | (uint64_t)((uint32_t)d + off16);
}
__device__ __forceinline__ void tma2d(uint32_t dst, const CUtensorMap* tm, int c0, int c1, uint32_t bar) {
    asm volatile("cp.async.bulk.tensor.2d.shared::cluster.global.mbarrier::complete_tx::bytes [%0], [%1, {%3, %4}], [%2];"
        :: "r"(dst), "l"((uint64_t)tm), "r"(bar), "r"(c0), "r"(c1) : "memory");
}
__device__ __forceinline__ void tma3d(uint32_t dst, const CUtensorMap* tm, int c0, int c1, int c2, uint32_t bar) {
    asm volatile("cp.async.bulk.tensor.3d.shared::cluster.global.mbarrier::complete_tx::bytes [%0], [%1, {%3, %4, %5}], [%2];"
        :: "r"(dst), "l"((uint64_t)tm), "r"(bar), "r"(c0), "r"(c1), "r"(c2) : "memory");
}
__device__ __forceinline__ void tma3d_mc(uint32_t dst, const CUtensorMap* tm, int c0, int c1, int c2, uint32_t bar) {
    asm volatile("cp.async.bulk.tensor.3d.shared::cluster.global.mbarrier::complete_tx::bytes.multicast::cluster [%0], [%1, {%3, %4, %5}], [%2], %6;"
        :: "r"(dst), "l"((uint64_t)tm), "r"(bar), "r"(c0), "r"(c1), "r"(c2), "h"((uint16_t)3) : "memory");
}
__device__ __forceinline__ void bulk_g2s(uint32_t dst, const void* src, uint32_t bytes, uint32_t bar) {
    asm volatile("cp.async.bulk.shared::cluster.global.mbarrier::complete_tx::bytes [%0], [%1], %2, [%3];"
        :: "r"(dst), "l"(src), "r"(bytes), "r"(bar) : "memory");
}
__device__ __forceinline__ void bulk_s2g(void* dst, uint32_t src, uint32_t bytes) {
    asm volatile("cp.async.bulk.global.shared::cta.bulk_group [%0], [%1], %2;" :: "l"(dst), "r"(src), "r"(bytes) : "memory");
}
__device__ __forceinline__ void tma2d_store(const CUtensorMap* tm, int c0, int c1, uint32_t src) {
    asm volatile("cp.async.bulk.tensor.2d.global.shared::cta.bulk_group [%0, {%2, %3}], [%1];"
        :: "l"((uint64_t)tm), "r"(src), "r"(c0), "r"(c1) : "memory");
}
__device__ __forceinline__ void l2_prefetch(const void* p, uint32_t bytes) {
    asm volatile("cp.async.bulk.prefetch.L2.global [%0], %1;" :: "l"(p), "r"(bytes) : "memory");
}
__device__ __forceinline__ void tmap_prefetch(const CUtensorMap* tm) { asm volatile("prefetch.tensormap [%0];" :: "l"((uint64_t)tm) : "memory"); }
__device__ __forceinline__ uint32_t lds32(uint32_t a) { uint32_t v; asm volatile("ld.shared.u32 %0, [%1];" : "=r"(v) : "r"(a)); return v; }
__device__ __forceinline__ uint2 lds64(uint32_t a) { uint2 v; asm volatile("ld.shared.v2.u32 {%0,%1}, [%2];" : "=r"(v.x), "=r"(v.y) : "r"(a)); return v; }
__device__ __forceinline__ uint4 lds128(uint32_t a) { uint4 v; asm volatile("ld.shared.v4.u32 {%0,%1,%2,%3}, [%4];" : "=r"(v.x), "=r"(v.y), "=r"(v.z), "=r"(v.w) : "r"(a)); return v; }
__device__ __forceinline__ float2 lds64f(uint32_t a) { float2 v; asm volatile("ld.shared.v2.f32 {%0,%1}, [%2];" : "=f"(v.x), "=f"(v.y) : "r"(a)); return v; }
__device__ __forceinline__ void sts32(uint32_t a, uint32_t v) { asm volatile("st.shared.u32 [%0], %1;" :: "r"(a), "r"(v) : "memory"); }
__device__ __forceinline__ void sts128(uint32_t a, uint4 v) { asm volatile("st.shared.v4.u32 [%0], {%1,%2,%3,%4};" :: "r"(a), "r"(v.x), "r"(v.y), "r"(v.z), "r"(v.w) : "memory"); }
__device__ __forceinline__ uint4 ldg_cg128(const void* p) { uint4 v; asm volatile("ld.global.cg.v4.u32 {%0,%1,%2,%3}, [%4];" : "=r"(v.x), "=r"(v.y), "=r"(v.z), "=r"(v.w) : "l"(p)); return v; }
__device__ __forceinline__ uint4 ldg_nc128(const void* p) { uint4 v; asm volatile("ld.global.nc.L1::no_allocate.v4.u32 {%0,%1,%2,%3}, [%4];" : "=r"(v.x), "=r"(v.y), "=r"(v.z), "=r"(v.w) : "l"(p)); return v; }
__device__ __forceinline__ uint2 ldg_nc64(const void* p) { uint2 v; asm volatile("ld.global.nc.L1::no_allocate.v2.u32 {%0,%1}, [%2];" : "=r"(v.x), "=r"(v.y) : "l"(p)); return v; }
#define WG_FENCE() asm volatile("wgmma.fence.sync.aligned;\n" ::: "memory")
#define WG_COMMIT() asm volatile("wgmma.commit_group.sync.aligned;\n" ::: "memory")
template<int N> __device__ __forceinline__ void wg_wait() { asm volatile("wgmma.wait_group.sync.aligned %0;\n" :: "n"(N) : "memory"); }
__device__ __forceinline__ bool elect_one() {
    uint32_t pr;
    asm volatile("{\n.reg .pred p;\nelect.sync _|p, 0xffffffff;\nselp.u32 %0, 1, 0, p;\n}" : "=r"(pr));
    return pr != 0;
}
__device__ __forceinline__ void named_bar(int id, int n) { asm volatile("bar.sync %0, %1;" :: "r"(id), "r"(n) : "memory"); }

__device__ __forceinline__ float bf_lo(uint32_t u) { return __uint_as_float(u << 16); }
__device__ __forceinline__ float bf_hi(uint32_t u) { return __uint_as_float(u & 0xFFFF0000u); }
__device__ __forceinline__ uint32_t pack_bf(float lo, float hi) { uint32_t r; asm("cvt.rn.bf16x2.f32 %0, %1, %2;" : "=r"(r) : "f"(hi), "f"(lo)); return r; }
__device__ __forceinline__ float bf_round(float x) { return __bfloat162float(__float2bfloat16_rn(x)); }
__device__ __forceinline__ uint32_t bmul2(uint32_t a, uint32_t b) { uint32_t r; asm("mul.rn.bf16x2 %0, %1, %2;" : "=r"(r) : "r"(a), "r"(b)); return r; }
__device__ __forceinline__ uint32_t badd2(uint32_t a, uint32_t b) { uint32_t r; asm("add.rn.bf16x2 %0, %1, %2;" : "=r"(r) : "r"(a), "r"(b)); return r; }
__device__ __forceinline__ uint32_t bsub2(uint32_t a, uint32_t b) { uint32_t r; asm("sub.rn.bf16x2 %0, %1, %2;" : "=r"(r) : "r"(a), "r"(b)); return r; }
__device__ __forceinline__ void mma16816(float (&d)[4], uint32_t a0, uint32_t a1, uint32_t a2, uint32_t a3, uint2 b) {
    asm volatile("mma.sync.aligned.m16n8k16.row.col.f32.bf16.bf16.f32 {%0,%1,%2,%3}, {%4,%5,%6,%7}, {%8,%9}, {%0,%1,%2,%3};\n"
        : "+f"(d[0]), "+f"(d[1]), "+f"(d[2]), "+f"(d[3]) : "r"(a0), "r"(a1), "r"(a2), "r"(a3), "r"(b.x), "r"(b.y));
}

template<int HS> __device__ __forceinline__ void xreduce(float (&v)[8], int lane) {
    const int up = lane & HS;
    #pragma unroll
    for (int e = 0; e < HS; e++) {
        float keep, send;
        asm("{\n.reg .pred p;\nsetp.ne.b32 p, %4, 0;\nselp.f32 %0, %3, %2, p;\nselp.f32 %1, %2, %3, p;\n}"
            : "=f"(keep), "=f"(send) : "f"(v[e]), "f"(v[e + HS]), "r"(up));
        v[e] = keep + __shfl_xor_sync(0xffffffffu, send, HS);
    }
}

__device__ __forceinline__ int blk_f0(int bi, int j) {
    if (bi < 32) return 224 * ((j + (bi >> 2)) & 7) + 32 * (bi & 3);
    int b2 = bi - 32; int q3 = (b2 * 11) >> 5;
    return 224 * ((j + q3) & 7) + 128 + 32 * (b2 - 3 * q3);
}
__device__ __forceinline__ int next_st2(int s) { return (0x14023 >> (4 * s)) & 7; }
__device__ __forceinline__ uint32_t stage_off_rt(int s) { return s < 3 ? SM_RING + s * STAGE_BYTES : (uint32_t)(s - 3) * 65536; }

template<int NB>
__device__ __forceinline__ void gemm1_pass(uint32_t sb, int wgi, int warp4, int lane, int& st, uint32_t& fph, uint32_t e_cl,
                                           int rb64, int ks0, bool convCTA) {
    constexpr bool passA = (NB == 4);
    float acc[NB * 32];
    const uint64_t descA0 = make_desc(sb + SM_X + wgi * 65536, 16, 1024, 1);
    const uint64_t descB0 = make_desc(sb + SM_RING, 4096, 512, 2);
    int prev = 0;
    #pragma unroll 1
    for (int sl = 0; sl < 8; sl++) {
        if (warp4 == 0 && wgi == 0) PROF2(2, sl + (passA ? 0 : 8));
        mbar_wait(sb + SM_BARS + (B_FULL + st) * 8, (fph >> st) & 1);
        fph ^= 1u << st;
        if (sl == 0 && warp4 == 0) PROF(2 + wgi * 8 + (passA ? 0 : 3));
        if (warp4 == 0 && wgi == 0) PROF2(1, sl + (passA ? 0 : 8));
        const uint64_t da = desc_add(descA0, sl * 512), db = desc_add(descB0, st * 2048);
        WG_FENCE();
        #pragma unroll
        for (int kk = 0; kk < 4; kk++) {
            int sc = (sl | kk) ? 1 : 0;
            if constexpr (NB == 4) wgmma_ss_n256_tb(acc, da + kk * 2, db + kk * 64, sc); else wgmma_ss_n192_tb(acc, da + kk * 2, db + kk * 64, sc);
        }
        WG_COMMIT();
        wg_wait<1>();
        if (warp4 == 0 && wgi == 0) PROF2(3, sl + (passA ? 0 : 8));
        if (lane < 2 && sl && (passA || !convCTA || sl < 6)) mbar_arrive_cluster(e_cl + prev * 8, 1);
        if (!passA) {
            if (sl == 4) {
                if (convCTA) { if (lane == 0) mbar_arrive(sb + SM_BARS + B_XFREE * 8); }
                else if (lane < 4) mbar_arrive_cluster(e_cl + (3 + (lane >> 1)) * 8, 1);
            }
        }
        prev = st;
        st = (st == 2) ? 0 : st + 1;
    }
    wg_wait<0>();
    if (lane < 2 && (passA || !convCTA)) mbar_arrive_cluster(e_cl + prev * 8, 1);
    if (!passA && lane == 0) mbar_arrive(sb + SM_BARS + B_G1DONE * 8);
    if (warp4 == 0) PROF(3 + wgi * 8 + (passA ? 0 : 3));
    const int g = lane >> 2;
    const int r0 = wgi * 64 + warp4 * 16 + g;
    const float s0 = __uint_as_float(lds32(sb + SM_STATS + r0 * 8 + 4)), s1 = __uint_as_float(lds32(sb + SM_STATS + (r0 + 8) * 8 + 4));
    uint32_t* dst = g_h + (size_t)((rb64 >> 1) * 56 + ks0) * 2048 + wgi * 1024 + warp4 * 128 + lane;
    #pragma unroll
    for (int kk = 0; kk < NB * 2; kk++) {
        uint32_t h[4];
        #pragma unroll
        for (int tt = 0; tt < 2; tt++) {
            const int t = 2 * kk + tt;
            const float* ag = &acc[4 * t];
            const float* au = &acc[NB * 16 + 4 * t];
            h[2 * tt] = bmul2(pack_bf(ag[0] * s0, ag[1] * s0), pack_bf(au[0] * s0, au[1] * s0));
            h[2 * tt + 1] = bmul2(pack_bf(ag[2] * s1, ag[3] * s1), pack_bf(au[2] * s1, au[3] * s1));
        }
        uint32_t* d2 = dst + (kk >> 1) * 2048 + (kk & 1) * 512;
        d2[0] = h[0]; d2[64] = h[1]; d2[32] = h[2]; d2[96] = h[3];
    }
    __syncwarp();
    if (lane == 0) mbar_arrive(sb + SM_BARS + (B_HD + wgi * 2 + (passA ? 0 : 1)) * 8);
    if (warp4 == 0) PROF(4 + wgi * 8 + (passA ? 0 : 3));
}

__global__ void __cluster_dims__(2, 1, 1) __launch_bounds__(NTHREADS, 1)
fused_kernel(const __grid_constant__ Params p) {
    extern __shared__ __align__(1024) uint8_t smem_raw[];
    const uint32_t sb = smem_u32(smem_raw);
    const int tid = threadIdx.x, warp = tid >> 5, lane = tid & 31;
    const int b = blockIdx.x;
    const int rank = b & 1;
    const int j = (b >> 1) & 7;
    const int i = ((b >> 4) << 1) | rank;
    const int cb = j >> 1;
    const bool convCTA = j & 1;
    const int cidx = 4 * i + cb;

    if (tid == 256) {
        mbar_init(sb + SM_BARS + B_XFULL * 8, 1);
        mbar_init(sb + SM_BARS + (B_XFULL + 1) * 8, 1);
        asm volatile("fence.proxy.async.shared::cta;" ::: "memory");
        mbar_expect_tx(sb + SM_BARS + B_XFULL * 8, 65536);
        tma3d(sb + SM_X, &p.tm_x, 0, 128 * i, 0, sb + SM_BARS + B_XFULL * 8);
        mbar_expect_tx(sb + SM_BARS + (B_XFULL + 1) * 8, 65536);
        tma3d(sb + SM_X + 65536, &p.tm_x, 0, 128 * i + 64, 0, sb + SM_BARS + (B_XFULL + 1) * 8);
    }
    if (tid == 288) {
        for (int s = 0; s < 5; s++) { mbar_init(sb + SM_BARS + (B_FULL + s) * 8, 1); mbar_init(sb + SM_BARS + (B_EMPTY + s) * 8, 16); }
        mbar_init(sb + SM_BARS + B_CONV * 8, 1);
        mbar_init(sb + SM_BARS + B_YT * 8, 1);
        mbar_init(sb + SM_BARS + B_XR * 8, 1);
        mbar_init(sb + SM_BARS + B_G1DONE * 8, 8);
        mbar_init(sb + SM_BARS + B_XFREE * 8, 8);
        mbar_init(sb + SM_BARS + B_YST * 8, 8);
        mbar_init(sb + SM_BARS + B_KVLD * 8, 2);
        for (int s = 0; s < 4; s++) mbar_init(sb + SM_BARS + (B_HD + s) * 8, 4);
        for (int s = 0; s < 2; s++) mbar_init(sb + SM_BARS + (B_HRDY + s) * 8, 1);
        asm volatile("fence.mbarrier_init.release.cluster;" ::: "memory");
        asm volatile("fence.proxy.async.shared::cta;" ::: "memory");
    }
    __syncwarp();
    asm volatile("barrier.cluster.arrive.relaxed.aligned;\n" ::: "memory");
    asm volatile("barrier.cluster.wait.aligned;\n" ::: "memory");
    PROFW(1, 0);

    if (warp < 8) {
        asm volatile("setmaxnreg.inc.sync.aligned.u32 200;");
        const int wgi = warp >> 2, warp4 = warp & 3;
        const int g = lane >> 2, c = lane & 3;
        const uint32_t e_cl = mapa(sb + SM_BARS + B_EMPTY * 8, lane & 1);
        {
            const int lr16 = (lane & 7) + ((lane >> 3) & 1) * 8;
            const uint32_t xa = sb + SM_X + wgi * 65536 + (warp4 * 16 + lr16) * 128;
            uint32_t xf[32][4];
            float aS[4][4], aQ0[4][4], aQ1[4][4];
            #pragma unroll
            for (int e = 0; e < 4; e++) {
                #pragma unroll
                for (int f = 0; f < 4; f++) { aS[e][f] = 0.f; aQ0[e][f] = 0.f; aQ1[e][f] = 0.f; }
            }
            mbar_wait(sb + SM_BARS + (B_XFULL + wgi) * 8, 0);
            PROFW(16, 0); PROFW(18, 4);
            #pragma unroll
            for (int ks = 0; ks < 32; ks++) {
                const uint32_t a = xa + (ks >> 2) * 8192 + (((2 * (ks & 3) + (lane >> 4)) ^ (lane & 7)) << 4);
                asm volatile("ldmatrix.sync.aligned.m8n8.x4.shared.b16 {%0,%1,%2,%3}, [%4];"
                    : "=r"(xf[ks][0]), "=r"(xf[ks][1]), "=r"(xf[ks][2]), "=r"(xf[ks][3]) : "r"(a) : "memory");
            }
            #pragma unroll
            for (int ks = 0; ks < 32; ks++) {
                mma16816(aS[ks & 3], xf[ks][0], xf[ks][1], xf[ks][2], xf[ks][3], make_uint2(0x3F803F80u, 0x3F803F80u));
                mma16816(aQ0[ks & 3], xf[ks][0], xf[ks][1], xf[ks][2], xf[ks][3], make_uint2(xf[ks][0], xf[ks][2]));
                mma16816(aQ1[ks & 3], xf[ks][0], xf[ks][1], xf[ks][2], xf[ks][3], make_uint2(xf[ks][1], xf[ks][3]));
            }
            const float mean0 = ((aS[0][0] + aS[1][0]) + (aS[2][0] + aS[3][0])) * (1.0f / DM);
            const float mean1 = ((aS[0][2] + aS[1][2]) + (aS[2][2] + aS[3][2])) * (1.0f / DM);
            const uint32_t m0 = pack_bf(mean0, mean0), m1 = pack_bf(mean1, mean1);
            #pragma unroll
            for (int ks = 0; ks < 32; ks++) {
                const uint32_t a = xa + (ks >> 2) * 8192 + (((2 * (ks & 3) + (lane >> 4)) ^ (lane & 7)) << 4);
                asm volatile("stmatrix.sync.aligned.m8n8.x4.shared.b16 [%0], {%1,%2,%3,%4};"
                    :: "r"(a), "r"(bsub2(xf[ks][0], m0)), "r"(bsub2(xf[ks][1], m1)), "r"(bsub2(xf[ks][2], m0)), "r"(bsub2(xf[ks][3], m1)) : "memory");
            }
            if (c == (g >> 1)) {
                const float q0 = (g & 1) ? (aQ0[0][1] + aQ0[1][1]) + (aQ0[2][1] + aQ0[3][1]) : (aQ0[0][0] + aQ0[1][0]) + (aQ0[2][0] + aQ0[3][0]);
                const float q1 = (g & 1) ? (aQ1[0][3] + aQ1[1][3]) + (aQ1[2][3] + aQ1[3][3]) : (aQ1[0][2] + aQ1[1][2]) + (aQ1[2][2] + aQ1[3][2]);
                const float sd0 = bf_round(sqrtf(bf_round(bf_round(fmaxf(q0 * (1.0f / DM) - mean0 * mean0, 0.f)) + 1e-5f)));
                const float sd1 = bf_round(sqrtf(bf_round(bf_round(fmaxf(q1 * (1.0f / DM) - mean1 * mean1, 0.f)) + 1e-5f)));
                const uint32_t sa = sb + SM_STATS + (warp * 16 + g) * 8;
                sts32(sa, m0); sts32(sa + 4, __float_as_uint(1.0f / sd0));
                sts32(sa + 64, m1); sts32(sa + 68, __float_as_uint(1.0f / sd1));
            }
            asm volatile("fence.proxy.async.shared::cta;" ::: "memory");
            named_bar(1 + wgi, 128);
            PROFW(19, 4);
            PROFW(17, 0);
        }
        int st = 0; uint32_t fph = 0;
        const int rb64 = 2 * i + wgi;
        gemm1_pass<4>(sb, wgi, warp4, lane, st, fph, e_cl, rb64, 4 * j, convCTA);
        gemm1_pass<3>(sb, wgi, warp4, lane, st, fph, e_cl, rb64, 32 + 3 * j, convCTA);

        if (convCTA) {
            const int gch = 8 * cidx + warp;
            const uint32_t xb = sb + SM_CVX + warp * 4096;
            const uint32_t hb = sb + SM_CVH + warp * 4096;
            const uint32_t dw = ((const unsigned short*)p.ssm_D)[gch];
            const uint32_t d2 = dw | (dw << 16);
            mbar_wait(sb + SM_BARS + B_CONV * 8, 0);
            PROFW(32, 4);
            float acc[16][4];
            #pragma unroll
            for (int jj = 0; jj < 16; jj++) { acc[jj][0] = 0.f; acc[jj][1] = 0.f; acc[jj][2] = 0.f; acc[jj][3] = 0.f; }
            uint2 bh[8], bl0[8], bl1[8];
            uint32_t xl = xb + g * 32 + c * 8;
            uint32_t hl = hb + (g + 2 * c - 8) * 4;
            #pragma unroll
            for (int d = 0; d < 8; d++) { bl0[d] = lds64(xl + d * 256); bh[d] = lds64(xl + (8 + d) * 256); }
            uint32_t w[6];
            w[0] = 0; w[1] = 0; w[2] = 0;
            if (g + 2 * c >= 8) w[0] = lds32(hl);
            if (g + 2 * c >= 7) w[1] = lds32(hl + 4);
            if (g + 2 * c >= 6) w[2] = lds32(hl + 8);
            w[3] = lds32(hl + 2048); w[4] = lds32(hl + 2052); w[5] = lds32(hl + 2056);
            auto conv_m0 = [&](int m0, uint2 (&bl)[8], uint2 (&bn)[8]) {
                xl -= 32;
                #pragma unroll
                for (int k = 0; k < 8; k++) {
                    const uint32_t a0 = w[1], a1 = __byte_perm(w[0], w[1], 0x5432), a2 = w[2], a3 = __byte_perm(w[1], w[2], 0x5432);
                    const uint32_t c0 = w[4], c1 = __byte_perm(w[3], w[4], 0x5432), c2 = w[5], c3 = __byte_perm(w[4], w[5], 0x5432);
                    const uint32_t nx = (k < 7) ? hl + (k + 1) * 256 : hl + 32;
                    w[0] = lds32(nx); w[1] = lds32(nx + 4); w[2] = lds32(nx + 8);
                    w[3] = lds32(nx + 2048); w[4] = lds32(nx + 2052); w[5] = lds32(nx + 2056);
                    if (k > 0) bn[k] = lds64(xl + k * 256);
                    else { bn[0] = make_uint2(0, 0); if (g > m0) bn[0] = lds64(xl); }
                    #pragma unroll
                    for (int jj = k; jj < 16; jj++) mma16816(acc[jj], a0, a1, a2, a3, (jj - k < 8) ? bl[(jj - k) & 7] : bh[(jj - k) & 7]);
                    bh[7 - k] = lds64(xl + (15 - k) * 256);
                    #pragma unroll
                    for (int jj = k + 8; jj < 16; jj++) mma16816(acc[jj], c0, c1, c2, c3, bl[jj - k - 8]);
                }
                hl += 32;
            };
            #pragma unroll 1
            for (int m0 = 0; m0 < 8; m0 += 2) {
                conv_m0(m0, bl0, bl1);
                conv_m0(m0 + 1, bl1, bl0);
                PROFW(34 + (m0 >> 1), 4);
            }
            PROFW(33, 4);
            const uint32_t kvl = xb + c * 64 + (7 - g) * 4;
            uint32_t* ydst = (uint32_t*)(g_yT + (size_t)gch * SEQ + 32 * c + 2 * g);
            uint32_t kk0[16], kk1[16];
            #pragma unroll
            for (int jj = 0; jj < 16; jj++) { kk0[jj] = lds32(kvl + jj * 256); kk1[jj] = lds32(kvl + jj * 256 + 32); }
            #pragma unroll
            for (int jj = 0; jj < 16; jj++) {
                ydst[jj * 64] = badd2(pack_bf(acc[jj][2], acc[jj][0]), bmul2(__byte_perm(kk0[jj], kk0[jj], 0x1032), d2));
                ydst[jj * 64 + 8] = badd2(pack_bf(acc[jj][3], acc[jj][1]), bmul2(__byte_perm(kk1[jj], kk1[jj], 0x1032), d2));
            }
            __syncwarp();
            PROFW(44, 4);
            if (lane == 0) mbar_arrive(sb + SM_BARS + B_YST * 8);
        } else {
            float acc[64];
            const uint64_t descB0 = make_desc(sb, 4096, 1024, 1);
            const uint64_t descA0 = make_desc(sb + 16384 + wgi * 4096, 128, 256, 0);
            int sg = 3, p0 = 0; uint32_t ph = 6;
            PROFW(20, 0);
            #pragma unroll 1
            for (int u = 0; u < 28; u++) {
                if (warp == 0 && !(u & 1)) PROF2(2, 16 + (u >> 1));
                mbar_wait(sb + SM_BARS + (B_FULL + sg) * 8, (ph >> sg) & 1);
                ph ^= 1u << sg;
                if (warp == 0 && !(u & 1)) PROF2(1, 16 + (u >> 1));
                const uint32_t o0 = stage_off_rt(sg) >> 4;
                const uint64_t da0 = desc_add(descA0, o0), db0 = desc_add(descB0, o0);
                WG_FENCE();
                #pragma unroll
                for (int kk = 0; kk < 4; kk++) wgmma_ss_n128_tb(acc, da0 + ((kk >> 1) * 512 + (kk & 1) * 128), db0 + ((kk >> 1) * 512 + (kk & 1) * 128), (u | kk) ? 1 : 0);
                WG_COMMIT();
                wg_wait<1>();
                if (warp == 0 && !(u & 1)) PROF2(3, 16 + (u >> 1));
                if (lane < 2 && u > 0 && u + 4 < 28) mbar_arrive_cluster(e_cl + p0 * 8, 1);
                p0 = sg;
                sg = next_st2(sg);
            }
            wg_wait<0>();
            PROFW(27, 0);
            mbar_wait(sb + SM_BARS + B_XR * 8, 0);
            const int r0 = wgi * 64 + warp4 * 16 + g;
            const float2 st0 = lds64f(sb + SM_STATS + r0 * 8), st1 = lds64f(sb + SM_STATS + (r0 + 8) * 8);
            const uint32_t m0 = __float_as_uint(st0.x), m1 = __float_as_uint(st1.x);
            const uint32_t xrow0 = sb + SM_XE + r0 * 128 + c * 4;
            const int mi = lane >> 3, lr = lane & 7;
            const uint32_t yaddr = sb + SM_YT + wgi * 16384 + ((mi >> 1) * 8 + lr) * 128 + (((2 * warp4 + (mi & 1)) ^ lr) << 4);
            uint32_t y[8][4], xv[16][2], nv[16][2], bv[16][2];
            #pragma unroll
            for (int t = 0; t < 16; t++) {
                const uint32_t off = (t >> 3) * 16384 + (((t & 7) ^ g) << 4);
                xv[t][0] = lds32(xrow0 + off); xv[t][1] = lds32(xrow0 + 1024 + off);
            }
            #pragma unroll
            for (int t = 0; t < 16; t++) {
                const uint32_t d0 = bsub2(xv[t][0], m0), d1 = bsub2(xv[t][1], m1);
                nv[t][0] = pack_bf(bf_lo(d0) * st0.y, bf_hi(d0) * st0.y); nv[t][1] = pack_bf(bf_lo(d1) * st1.y, bf_hi(d1) * st1.y);
                bv[t][0] = pack_bf(acc[4 * t], acc[4 * t + 1]); bv[t][1] = pack_bf(acc[4 * t + 2], acc[4 * t + 3]);
            }
            mbar_wait(sb + SM_BARS + B_YT * 8, 0);
            PROFW(28, 0);
            #pragma unroll
            for (int t2 = 0; t2 < 8; t2++)
                asm volatile("ldmatrix.sync.aligned.m8n8.x4.trans.shared.b16 {%0,%1,%2,%3}, [%4];"
                    : "=r"(y[t2][0]), "=r"(y[t2][1]), "=r"(y[t2][2]), "=r"(y[t2][3]) : "r"(yaddr + t2 * 2048) : "memory");
            #pragma unroll
            for (int t = 0; t < 16; t++) {
                const uint32_t off = (t >> 3) * 16384 + (((t & 7) ^ g) << 4);
                sts32(xrow0 + off, badd2(badd2(xv[t][0], bmul2(nv[t][0], y[t >> 1][2 * (t & 1)])), bv[t][0]));
                sts32(xrow0 + 1024 + off, badd2(badd2(xv[t][1], bmul2(nv[t][1], y[t >> 1][2 * (t & 1) + 1])), bv[t][1]));
            }
            asm volatile("fence.proxy.async.shared::cta;" ::: "memory");
            named_bar(1 + wgi, 128);
            if ((tid & 127) == 0) {
                tma2d_store(&p.tm_out, 128 * cb, 128 * i + 64 * wgi, sb + SM_XE + wgi * 8192);
                tma2d_store(&p.tm_out, 128 * cb + 64, 128 * i + 64 * wgi, sb + SM_XE + 16384 + wgi * 8192);
                asm volatile("cp.async.bulk.commit_group;" ::: "memory");
                asm volatile("cp.async.bulk.wait_group.read 0;" ::: "memory");
                PROFW(29, 0);
            }
        }
    } else {
        asm volatile("setmaxnreg.dec.sync.aligned.u32 104;");
        if (warp == 8) {
            int st = 0; uint32_t eph = 7;
            #pragma unroll 1
            for (int it = 0; it < 16; it++) {
                const int pass = it >> 3, sl = it & 7;
                const int nb = pass ? 3 : 4;
                const CUtensorMap* tm = pass ? (rank ? &p.tm_uB : &p.tm_gB) : (rank ? &p.tm_uA : &p.tm_gA);
                mbar_wait(sb + SM_BARS + (B_EMPTY + st) * 8, (eph >> st) & 1);
                eph ^= 1u << st;
                if (it == 1) mbar_wait(sb + SM_BARS + B_XFULL * 8, 0);
                PROF2(0, it);
                if (elect_one()) {
                    mbar_expect_tx(sb + SM_BARS + (B_FULL + st) * 8, nb * 8192);
                    tma3d_mc(sb + SM_RING + st * STAGE_BYTES + rank * nb * 4096, tm, 0, sl * 64, 7 * j + 4 * pass, sb + SM_BARS + (B_FULL + st) * 8);
                }
                st = (st == 2) ? 0 : st + 1;
            }
            if (!convCTA) {
                st = 3;
                int f0 = 32 * rank, t3 = rank;
                #pragma unroll 1
                for (int u = 0; u < 28; u++) {
                    const uint32_t bar = sb + SM_BARS + (B_FULL + st) * 8;
                    mbar_wait(sb + SM_BARS + (B_EMPTY + st) * 8, (eph >> st) & 1);
                    eph ^= 1u << st;
                    if ((u & 1) == 0) PROF2(0, 16 + (u >> 1));
                    if (elect_one()) {
                        mbar_expect_tx(bar, 32768);
                        tma3d_mc(sb + stage_off_rt(st) + rank * 8192, &p.tm_w2, 0, f0, 2 * cb, bar);
                    }
                    st = next_st2(st);
                    if (u < 15) f0 += (u & 1) ? 160 : 64;
                    else if (u == 15) f0 = 128 + 32 * rank;
                    else { f0 += (t3 == 0) ? 64 : 192; t3 = (t3 == 0) ? 2 : t3 - 1; }
                }
                PROF(48);
            }
        } else if (warp < 11) {
            mbar_wait(sb + SM_BARS + (B_XFULL + 1) * 8, 0);
            #pragma unroll 1
            for (int rnd = 0; rnd < 2; rnd++) {
                const int tt = (tid - 288) + 64 * rnd;
                uint32_t sk[4][2];
                uint4 skw[2];
                skw[0] = ldg_nc128(p.shift_k + 16 * tt); skw[1] = ldg_nc128(p.shift_k + 16 * tt + 8);
                const __nv_bfloat16* kp = p.k + (size_t)(16 * b) * DM + 4 * tt;
                const __nv_bfloat16* vp = p.v + (size_t)(16 * b) * DM + 4 * tt;
                uint2 kr[19];
                uint2 kv[16];
                #pragma unroll
                for (int r = 0; r < 3; r++) kr[r] = (b > 0) ? ldg_nc64(kp + (r - 3) * DM) : make_uint2(0, 0);
                #pragma unroll
                for (int r = 0; r < 16; r++) { kr[3 + r] = ldg_nc64(kp + r * DM); kv[r] = ldg_nc64(vp + r * DM); }
                {
                    const uint4 w0 = skw[0], w1 = skw[1];
                    sk[0][0] = __byte_perm(w0.x, w0.z, 0x5410); sk[1][0] = __byte_perm(w0.x, w0.z, 0x7632);
                    sk[2][0] = __byte_perm(w0.y, w0.w, 0x5410); sk[3][0] = __byte_perm(w0.y, w0.w, 0x7632);
                    sk[0][1] = __byte_perm(w1.x, w1.z, 0x5410); sk[1][1] = __byte_perm(w1.x, w1.z, 0x7632);
                    sk[2][1] = __byte_perm(w1.y, w1.w, 0x5410); sk[3][1] = __byte_perm(w1.y, w1.w, 0x7632);
                }
                #pragma unroll
                for (int s = 0; s < 16; s++) {
                    uint32_t a = bmul2(kr[s].x, sk[3][0]);
                    a = badd2(a, bmul2(kr[s + 1].x, sk[2][0]));
                    a = badd2(a, bmul2(kr[s + 2].x, sk[1][0]));
                    a = badd2(a, bmul2(kr[s + 3].x, sk[0][0]));
                    kv[s].x = bmul2(a, kv[s].x);
                    a = bmul2(kr[s].y, sk[3][1]);
                    a = badd2(a, bmul2(kr[s + 1].y, sk[2][1]));
                    a = badd2(a, bmul2(kr[s + 2].y, sk[1][1]));
                    a = badd2(a, bmul2(kr[s + 3].y, sk[0][1]));
                    kv[s].y = bmul2(a, kv[s].y);
                }
                PROFW(57 + 2 * rnd, 9);
                if (rnd == 1 && lane == 0) mbar_arrive(sb + SM_BARS + B_KVLD * 8);
                #pragma unroll
                for (int cc = 0; cc < 4; cc++) {
                    const uint32_t sel = (cc & 1) ? 0x7632 : 0x5410;
                    #define KVW(r) ((cc & 2) ? kv[r].y : kv[r].x)
                    uint4* dst = (uint4*)(g_kvT + (size_t)(4 * tt + cc) * SEQ + 16 * b);
                    dst[0] = make_uint4(__byte_perm(KVW(15), KVW(14), sel), __byte_perm(KVW(13), KVW(12), sel),
                                        __byte_perm(KVW(11), KVW(10), sel), __byte_perm(KVW(9), KVW(8), sel));
                    dst[1] = make_uint4(__byte_perm(KVW(7), KVW(6), sel), __byte_perm(KVW(5), KVW(4), sel),
                                        __byte_perm(KVW(3), KVW(2), sel), __byte_perm(KVW(1), KVW(0), sel));
                    #undef KVW
                }
                PROFW(58 + 2 * rnd, 9);
            }
            asm volatile("fence.proxy.async.global;" ::: "memory");
            __syncwarp();
            if (lane == 0) {
                flag_add(&g_cnt_kv[0]);
                PROFW(50, 9);
                const int wgi = warp - 9;
                mbar_wait(sb + SM_BARS + (B_HD + wgi * 2) * 8, 0);
                flag_add(&g_flag_h[(i * 2 + 0) * 8]);
                mbar_wait(sb + SM_BARS + (B_HD + wgi * 2 + 1) * 8, 0);
                flag_add(&g_flag_h[(i * 2 + 1) * 8]);
                if (wgi == 1 && convCTA) {
                    mbar_wait(sb + SM_BARS + B_YST * 8, 0);
                    flag_add(&g_cnt_y[(cidx >> 4) * 32]);
                    PROF(46);
                }
                if (wgi == 1 && !convCTA) {
                    const unsigned ep = lds32(sb + SM_EPOCH);
                    mbar_wait(sb + SM_BARS + B_G1DONE * 8, 0);
                    mbar_expect_tx(sb + SM_BARS + B_XR * 8, 32768);
                    tma3d(sb + SM_XE, &p.tm_xe, 0, 128 * i, 2 * cb, sb + SM_BARS + B_XR * 8);
                    flag_wait(&g_flag_h[(i * 2 + 1) * 8], ep * 16);
                    mbar_arrive(sb + SM_BARS + (B_HRDY + 1) * 8);
                    __nanosleep(3000);
                    flag_wait(&g_cnt_y[cb * 32], ep * 16);
                    PROF(49);
                    asm volatile("fence.proxy.async.global;" ::: "memory");
                    mbar_expect_tx(sb + SM_BARS + B_YT * 8, 32768);
                    tma2d(sb + SM_YT, &p.tm_yT, 128 * i, 128 * cb, sb + SM_BARS + B_YT * 8);
                    tma2d(sb + SM_YT + 16384, &p.tm_yT, 128 * i + 64, 128 * cb, sb + SM_BARS + B_YT * 8);
                }
            }
        } else {
            if (lane == 0) {
                l2_prefetch(p.wg + (size_t)b * (FF * DM / NCTA), FF * DM / NCTA * 2);
                l2_prefetch(p.wu + (size_t)b * (FF * DM / NCTA), FF * DM / NCTA * 2);
                const unsigned ep = g_launch[b] + 1;
                g_launch[b] = ep;
                sts32(sb + SM_EPOCH, ep);
                tmap_prefetch(rank ? &p.tm_uA : &p.tm_gA);
                tmap_prefetch(rank ? &p.tm_uB : &p.tm_gB);
                tmap_prefetch(&p.tm_w2); tmap_prefetch(&p.tm_yT); tmap_prefetch(&p.tm_out); tmap_prefetch(&p.tm_xe);
                mbar_wait(sb + SM_BARS + B_KVLD * 8, 0);
                l2_prefetch(p.ssm_k + (size_t)(4 * b) * SEQ, 4 * SEQ * 2);
                l2_prefetch(p.wd + (size_t)b * (FF * DM / NCTA), FF * DM / NCTA * 2);
                mbar_wait(sb + SM_BARS + (B_HD + 0) * 8, 0);
                if (convCTA) {
                    flag_wait(&g_cnt_kv[0], ep * 256);
                    asm volatile("fence.proxy.async.global;" ::: "memory");
                    PROF(53);
                    mbar_wait(sb + SM_BARS + B_XFREE * 8, 0);
                    PROF(54);
                    mbar_expect_tx(sb + SM_BARS + B_CONV * 8, 65536);
                    bulk_g2s(sb + SM_CVX, g_kvT + (size_t)(8 * cidx) * SEQ, 32768, sb + SM_BARS + B_CONV * 8);
                    bulk_g2s(sb + SM_CVH, p.ssm_k + (size_t)(8 * cidx) * SEQ, 32768, sb + SM_BARS + B_CONV * 8);
                } else {
                    flag_wait(&g_flag_h[(i * 2 + 0) * 8], ep * 16);
                }
            }
            __syncwarp();
            if (!convCTA) {
                asm volatile("fence.proxy.async.global;" ::: "memory");
                int st = 3; uint32_t eph = 1;
                const uint8_t* hsrc = (const uint8_t*)g_h + (size_t)i * 56 * 8192;
                #pragma unroll 1
                for (int u = 0; u < 28; u++) {
                    mbar_wait(sb + SM_BARS + (B_EMPTY + st) * 8, (eph >> st) & 1);
                    eph ^= 1u << st;
                    if (u == 16) {
                        mbar_wait(sb + SM_BARS + (B_HRDY + 1) * 8, 0);
                        asm volatile("fence.proxy.async.global;" ::: "memory");
                    }
                    if (elect_one()) bulk_g2s(sb + stage_off_rt(st) + 16384, hsrc + u * 16384, 16384, sb + SM_BARS + (B_FULL + st) * 8);
                    st = next_st2(st);
                }
            }
        }
    }
}

typedef CUresult (*EncodeFn)(CUtensorMap*, CUtensorMapDataType, cuuint32_t, void*, const cuuint64_t*, const cuuint64_t*,
                             const cuuint32_t*, const cuuint32_t*, CUtensorMapInterleave, CUtensorMapSwizzle,
                             CUtensorMapL2promotion, CUtensorMapFloatOOBfill);

void encode(EncodeFn fn, CUtensorMap* tm, const void* base, int rank, const cuuint64_t* dims, const cuuint64_t* strides,
            const cuuint32_t* box, CUtensorMapSwizzle swz) {
    cuuint32_t es[5] = {1, 1, 1, 1, 1};
    fn(tm, CU_TENSOR_MAP_DATA_TYPE_BFLOAT16, rank, (void*)base, dims, strides, box, es, CU_TENSOR_MAP_INTERLEAVE_NONE, swz,
       CU_TENSOR_MAP_L2_PROMOTION_L2_128B, CU_TENSOR_MAP_FLOAT_OOB_FILL_NONE);
}

}

extern "C" void kernel_launch(void* const* d_in, const int* in_sizes, int n_in, void* d_out, int out_size) {
    (void)in_sizes; (void)n_in; (void)out_size;
    static EncodeFn enc = nullptr;
    static void* yT_ptr = nullptr;
    if (!enc) {
        void* fn = nullptr; cudaDriverEntryPointQueryResult qr;
        cudaGetDriverEntryPoint("cuTensorMapEncodeTiled", &fn, cudaEnableDefault, &qr);
        enc = (EncodeFn)fn;
        cudaGetSymbolAddress(&yT_ptr, g_yT);
        cudaFuncSetAttribute(fused_kernel, cudaFuncAttributeMaxDynamicSharedMemorySize, SM_TOTAL);
    }
    Params p;
    p.q = (const __nv_bfloat16*)d_in[0]; p.k = (const __nv_bfloat16*)d_in[1]; p.v = (const __nv_bfloat16*)d_in[2];
    p.shift_k = (const __nv_bfloat16*)d_in[3]; p.ssm_k = (const __nv_bfloat16*)d_in[4]; p.ssm_D = (const __nv_bfloat16*)d_in[5];
    p.wg = (const __nv_bfloat16*)d_in[7]; p.wu = (const __nv_bfloat16*)d_in[8]; p.wd = (const __nv_bfloat16*)d_in[9];
    {
        cuuint64_t dims[2] = {DM, SEQ}; cuuint64_t str[1] = {DM * 2};
        cuuint64_t dims3[3] = {64, SEQ, DM / 64}; cuuint64_t str3[2] = {DM * 2, 128};
        cuuint32_t box[3] = {64, 64, 8}, boxe[3] = {64, 128, 2};
        encode(enc, &p.tm_x, p.q, 3, dims3, str3, box, CU_TENSOR_MAP_SWIZZLE_128B);
        encode(enc, &p.tm_xe, p.q, 3, dims3, str3, boxe, CU_TENSOR_MAP_SWIZZLE_128B);
        cuuint32_t box2[2] = {64, 64};
        encode(enc, &p.tm_out, d_out, 2, dims, str, box2, CU_TENSOR_MAP_SWIZZLE_128B);
    }
    {
        cuuint64_t dims[3] = {32, DM, FF / 32}; cuuint64_t str[2] = {FF * 2, 64};
        cuuint32_t boxA[3] = {32, 64, 4}, boxB[3] = {32, 64, 3};
        encode(enc, &p.tm_gA, p.wg, 3, dims, str, boxA, CU_TENSOR_MAP_SWIZZLE_64B);
        encode(enc, &p.tm_gB, p.wg, 3, dims, str, boxB, CU_TENSOR_MAP_SWIZZLE_64B);
        encode(enc, &p.tm_uA, p.wu, 3, dims, str, boxA, CU_TENSOR_MAP_SWIZZLE_64B);
        encode(enc, &p.tm_uB, p.wu, 3, dims, str, boxB, CU_TENSOR_MAP_SWIZZLE_64B);
    }
    {
        cuuint64_t dims[3] = {64, FF, DM / 64}; cuuint64_t str[2] = {DM * 2, 128};
        cuuint32_t box[3] = {64, 32, 2};
        encode(enc, &p.tm_w2, p.wd, 3, dims, str, box, CU_TENSOR_MAP_SWIZZLE_128B);
    }
    {
        cuuint64_t dims[2] = {SEQ, DM}; cuuint64_t str[1] = {SEQ * 2};
        cuuint32_t box[2] = {64, 128};
        encode(enc, &p.tm_yT, yT_ptr, 2, dims, str, box, CU_TENSOR_MAP_SWIZZLE_128B);
    }
    fused_kernel<<<NCTA, NTHREADS, SM_TOTAL>>>(p);
}
```

```cpp
#include <cuda_runtime.h>
#include <cuda_bf16.h>
#include <cuda.h>
#include <stdint.h>

namespace {

constexpr int SEQ = 2048, DM = 512, FF = 1792;
constexpr int NCTA = 128;
constexpr int NTHREADS = 384;
constexpr int STAGE_BYTES = 32768;

constexpr uint32_t SM_X = 0;
constexpr uint32_t SM_RING = 131072;
constexpr uint32_t SM_MISC = SM_RING + 3 * STAGE_BYTES;
constexpr uint32_t SM_BARS = SM_MISC;
constexpr uint32_t SM_EPOCH = SM_MISC + 248;
constexpr uint32_t SM_STATS = SM_MISC + 256;
constexpr uint32_t SM_TOTAL = SM_STATS + 1024;
static_assert(SM_TOTAL <= 232448, "smem");
constexpr uint32_t SM_CVX = 0;
constexpr uint32_t SM_CVH = 65536;
constexpr uint32_t SM_YT = 32768;
constexpr uint32_t SM_XE = 98304;

constexpr int B_FULL = 0, B_EMPTY = 5, B_XFULL = 10, B_CONV = 14, B_YT = 15, B_XR = 16, B_G1DONE = 17, B_HD = 18, B_HRDY = 22,
              B_XFREE = 24, B_YST = 25, B_KVLD = 26, B_COUNT = 27;
static_assert(B_COUNT * 8 <= 248, "barrier space");

__device__ __align__(128) uint32_t g_h[16 * 56 * 2048];
__device__ __align__(128) __nv_bfloat16 g_kvT[DM * SEQ];
__device__ __align__(128) __nv_bfloat16 g_yT[DM * SEQ];
__device__ unsigned g_launch[NCTA];
__device__ unsigned g_cnt_kv[32];
__device__ unsigned g_cnt_y[4 * 32];
__device__ unsigned g_flag_h[16 * 2 * 8];

#define PROF(idx)
#define PROF2(a, idx)
#define PROFW(idx, w)

struct Params {
    CUtensorMap tm_x, tm_gA, tm_gB, tm_uA, tm_uB, tm_w2, tm_yT, tm_out, tm_xe;
    const __nv_bfloat16 *q, *k, *v, *shift_k, *ssm_k, *ssm_D, *wg, *wu, *wd;
};

__device__ __forceinline__ void wgmma_rs_n32(float (&d)[16], uint32_t a0, uint32_t a1, uint32_t a2, uint32_t a3, uint64_t db, int sc) {
  asm volatile("{\n.reg .pred p;\nsetp.ne.b32 p, %21, 0;\n"
    "wgmma.mma_async.sync.aligned.m64n32k16.f32.bf16.bf16 {%0,%1,%2,%3,%4,%5,%6,%7,%8,%9,%10,%11,%12,%13,%14,%15}, {%16,%17,%18,%19}, %20, p, 1, 1, 0;\n}\n"
    : "+f"(d[0]),"+f"(d[1]),"+f"(d[2]),"+f"(d[3]),"+f"(d[4]),"+f"(d[5]),"+f"(d[6]),"+f"(d[7]),"+f"(d[8]),"+f"(d[9]),"+f"(d[10]),"+f"(d[11]),"+f"(d[12]),"+f"(d[13]),"+f"(d[14]),"+f"(d[15])
    : "r"(a0),"r"(a1),"r"(a2),"r"(a3),"l"(db),"r"(sc));
}
__device__ __forceinline__ void wgmma_rs_n128_tb(float (&d)[64], uint32_t a0, uint32_t a1, uint32_t a2, uint32_t a3, uint64_t db, int sc) {
  asm volatile("{\n.reg .pred p;\nsetp.ne.b32 p, %69, 0;\n"
    "wgmma.mma_async.sync.aligned.m64n128k16.f32.bf16.bf16 {%0,%1,%2,%3,%4,%5,%6,%7,%8,%9,%10,%11,%12,%13,%14,%15,%16,%17,%18,%19,%20,%21,%22,%23,%24,%25,%26,%27,%28,%29,%30,%31,%32,%33,%34,%35,%36,%37,%38,%39,%40,%41,%42,%43,%44,%45,%46,%47,%48,%49,%50,%51,%52,%53,%54,%55,%56,%57,%58,%59,%60,%61,%62,%63}, {%64,%65,%66,%67}, %68, p, 1, 1, 1;\n}\n"
    : "+f"(d[0]),"+f"(d[1]),"+f"(d[2]),"+f"(d[3]),"+f"(d[4]),"+f"(d[5]),"+f"(d[6]),"+f"(d[7]),"+f"(d[8]),"+f"(d[9]),"+f"(d[10]),"+f"(d[11]),"+f"(d[12]),"+f"(d[13]),"+f"(d[14]),"+f"(d[15]),"+f"(d[16]),"+f"(d[17]),"+f"(d[18]),"+f"(d[19]),"+f"(d[20]),"+f"(d[21]),"+f"(d[22]),"+f"(d[23]),"+f"(d[24]),"+f"(d[25]),"+f"(d[26]),"+f"(d[27]),"+f"(d[28]),"+f"(d[29]),"+f"(d[30]),"+f"(d[31]),"+f"(d[32]),"+f"(d[33]),"+f"(d[34]),"+f"(d[35]),"+f"(d[36]),"+f"(d[37]),"+f"(d[38]),"+f"(d[39]),"+f"(d[40]),"+f"(d[41]),"+f"(d[42]),"+f"(d[43]),"+f"(d[44]),"+f"(d[45]),"+f"(d[46]),"+f"(d[47]),"+f"(d[48]),"+f"(d[49]),"+f"(d[50]),"+f"(d[51]),"+f"(d[52]),"+f"(d[53]),"+f"(d[54]),"+f"(d[55]),"+f"(d[56]),"+f"(d[57]),"+f"(d[58]),"+f"(d[59]),"+f"(d[60]),"+f"(d[61]),"+f"(d[62]),"+f"(d[63])
    : "r"(a0),"r"(a1),"r"(a2),"r"(a3),"l"(db),"r"(sc));
}
__device__ __forceinline__ void wgmma_ss_n256_tb(float (&d)[128], uint64_t da, uint64_t db, int sc) {
  asm volatile("{\n.reg .pred p;\nsetp.ne.b32 p, %130, 0;\n"
    "wgmma.mma_async.sync.aligned.m64n256k16.f32.bf16.bf16 {%0,%1,%2,%3,%4,%5,%6,%7,%8,%9,%10,%11,%12,%13,%14,%15,%16,%17,%18,%19,%20,%21,%22,%23,%24,%25,%26,%27,%28,%29,%30,%31,%32,%33,%34,%35,%36,%37,%38,%39,%40,%41,%42,%43,%44,%45,%46,%47,%48,%49,%50,%51,%52,%53,%54,%55,%56,%57,%58,%59,%60,%61,%62,%63,%64,%65,%66,%67,%68,%69,%70,%71,%72,%73,%74,%75,%76,%77,%78,%79,%80,%81,%82,%83,%84,%85,%86,%87,%88,%89,%90,%91,%92,%93,%94,%95,%96,%97,%98,%99,%100,%101,%102,%103,%104,%105,%106,%107,%108,%109,%110,%111,%112,%113,%114,%115,%116,%117,%118,%119,%120,%121,%122,%123,%124,%125,%126,%127}, %128, %129, p, 1, 1, 0, 1;\n}\n"
    : "+f"(d[0]),"+f"(d[1]),"+f"(d[2]),"+f"(d[3]),"+f"(d[4]),"+f"(d[5]),"+f"(d[6]),"+f"(d[7]),"+f"(d[8]),"+f"(d[9]),"+f"(d[10]),"+f"(d[11]),"+f"(d[12]),"+f"(d[13]),"+f"(d[14]),"+f"(d[15]),"+f"(d[16]),"+f"(d[17]),"+f"(d[18]),"+f"(d[19]),"+f"(d[20]),"+f"(d[21]),"+f"(d[22]),"+f"(d[23]),"+f"(d[24]),"+f"(d[25]),"+f"(d[26]),"+f"(d[27]),"+f"(d[28]),"+f"(d[29]),"+f"(d[30]),"+f"(d[31]),"+f"(d[32]),"+f"(d[33]),"+f"(d[34]),"+f"(d[35]),"+f"(d[36]),"+f"(d[37]),"+f"(d[38]),"+f"(d[39]),"+f"(d[40]),"+f"(d[41]),"+f"(d[42]),"+f"(d[43]),"+f"(d[44]),"+f"(d[45]),"+f"(d[46]),"+f"(d[47]),"+f"(d[48]),"+f"(d[49]),"+f"(d[50]),"+f"(d[51]),"+f"(d[52]),"+f"(d[53]),"+f"(d[54]),"+f"(d[55]),"+f"(d[56]),"+f"(d[57]),"+f"(d[58]),"+f"(d[59]),"+f"(d[60]),"+f"(d[61]),"+f"(d[62]),"+f"(d[63]),"+f"(d[64]),"+f"(d[65]),"+f"(d[66]),"+f"(d[67]),"+f"(d[68]),"+f"(d[69]),"+f"(d[70]),"+f"(d[71]),"+f"(d[72]),"+f"(d[73]),"+f"(d[74]),"+f"(d[75]),"+f"(d[76]),"+f"(d[77]),"+f"(d[78]),"+f"(d[79]),"+f"(d[80]),"+f"(d[81]),"+f"(d[82]),"+f"(d[83]),"+f"(d[84]),"+f"(d[85]),"+f"(d[86]),"+f"(d[87]),"+f"(d[88]),"+f"(d[89]),"+f"(d[90]),"+f"(d[91]),"+f"(d[92]),"+f"(d[93]),"+f"(d[94]),"+f"(d[95]),"+f"(d[96]),"+f"(d[97]),"+f"(d[98]),"+f"(d[99]),"+f"(d[100]),"+f"(d[101]),"+f"(d[102]),"+f"(d[103]),"+f"(d[104]),"+f"(d[105]),"+f"(d[106]),"+f"(d[107]),"+f"(d[108]),"+f"(d[109]),"+f"(d[110]),"+f"(d[111]),"+f"(d[112]),"+f"(d[113]),"+f"(d[114]),"+f"(d[115]),"+f"(d[116]),"+f"(d[117]),"+f"(d[118]),"+f"(d[119]),"+f"(d[120]),"+f"(d[121]),"+f"(d[122]),"+f"(d[123]),"+f"(d[124]),"+f"(d[125]),"+f"(d[126]),"+f"(d[127])
    : "l"(da),"l"(db),"r"(sc));
}
__device__ __forceinline__ void wgmma_ss_n192_tb(float (&d)[96], uint64_t da, uint64_t db, int sc) {
  asm volatile("{\n.reg .pred p;\nsetp.ne.b32 p, %98, 0;\n"
    "wgmma.mma_async.sync.aligned.m64n192k16.f32.bf16.bf16 {%0,%1,%2,%3,%4,%5,%6,%7,%8,%9,%10,%11,%12,%13,%14,%15,%16,%17,%18,%19,%20,%21,%22,%23,%24,%25,%26,%27,%28,%29,%30,%31,%32,%33,%34,%35,%36,%37,%38,%39,%40,%41,%42,%43,%44,%45,%46,%47,%48,%49,%50,%51,%52,%53,%54,%55,%56,%57,%58,%59,%60,%61,%62,%63,%64,%65,%66,%67,%68,%69,%70,%71,%72,%73,%74,%75,%76,%77,%78,%79,%80,%81,%82,%83,%84,%85,%86,%87,%88,%89,%90,%91,%92,%93,%94,%95}, %96, %97, p, 1, 1, 0, 1;\n}\n"
    : "+f"(d[0]),"+f"(d[1]),"+f"(d[2]),"+f"(d[3]),"+f"(d[4]),"+f"(d[5]),"+f"(d[6]),"+f"(d[7]),"+f"(d[8]),"+f"(d[9]),"+f"(d[10]),"+f"(d[11]),"+f"(d[12]),"+f"(d[13]),"+f"(d[14]),"+f"(d[15]),"+f"(d[16]),"+f"(d[17]),"+f"(d[18]),"+f"(d[19]),"+f"(d[20]),"+f"(d[21]),"+f"(d[22]),"+f"(d[23]),"+f"(d[24]),"+f"(d[25]),"+f"(d[26]),"+f"(d[27]),"+f"(d[28]),"+f"(d[29]),"+f"(d[30]),"+f"(d[31]),"+f"(d[32]),"+f"(d[33]),"+f"(d[34]),"+f"(d[35]),"+f"(d[36]),"+f"(d[37]),"+f"(d[38]),"+f"(d[39]),"+f"(d[40]),"+f"(d[41]),"+f"(d[42]),"+f"(d[43]),"+f"(d[44]),"+f"(d[45]),"+f"(d[46]),"+f"(d[47]),"+f"(d[48]),"+f"(d[49]),"+f"(d[50]),"+f"(d[51]),"+f"(d[52]),"+f"(d[53]),"+f"(d[54]),"+f"(d[55]),"+f"(d[56]),"+f"(d[57]),"+f"(d[58]),"+f"(d[59]),"+f"(d[60]),"+f"(d[61]),"+f"(d[62]),"+f"(d[63]),"+f"(d[64]),"+f"(d[65]),"+f"(d[66]),"+f"(d[67]),"+f"(d[68]),"+f"(d[69]),"+f"(d[70]),"+f"(d[71]),"+f"(d[72]),"+f"(d[73]),"+f"(d[74]),"+f"(d[75]),"+f"(d[76]),"+f"(d[77]),"+f"(d[78]),"+f"(d[79]),"+f"(d[80]),"+f"(d[81]),"+f"(d[82]),"+f"(d[83]),"+f"(d[84]),"+f"(d[85]),"+f"(d[86]),"+f"(d[87]),"+f"(d[88]),"+f"(d[89]),"+f"(d[90]),"+f"(d[91]),"+f"(d[92]),"+f"(d[93]),"+f"(d[94]),"+f"(d[95])
    : "l"(da),"l"(db),"r"(sc));
}

__device__ __forceinline__ uint32_t smem_u32(const void* p) { return (uint32_t)__cvta_generic_to_shared(p); }
__device__ __forceinline__ void mbar_init(uint32_t bar, uint32_t cnt) { asm volatile("mbarrier.init.shared::cta.b64 [%0], %1;" :: "r"(bar), "r"(cnt)); }
__device__ __forceinline__ void mbar_expect_tx(uint32_t bar, uint32_t bytes) { asm volatile("mbarrier.arrive.expect_tx.shared::cta.b64 _, [%0], %1;" :: "r"(bar), "r"(bytes) : "memory"); }
__device__ __forceinline__ void mbar_arrive(uint32_t bar) { asm volatile("mbarrier.arrive.shared::cta.b64 _, [%0];" :: "r"(bar) : "memory"); }
__device__ __forceinline__ void mbar_arrive_cluster(uint32_t cbar, uint32_t cnt) { asm volatile("mbarrier.arrive.shared::cluster.b64 _, [%0], %1;" :: "r"(cbar), "r"(cnt) : "memory"); }
__device__ __forceinline__ uint32_t mapa(uint32_t a, uint32_t rank) { uint32_t r; asm volatile("mapa.shared::cluster.u32 %0, %1, %2;" : "=r"(r) : "r"(a), "r"(rank)); return r; }
__device__ __forceinline__ void mbar_wait(uint32_t bar, uint32_t parity) {
    uint32_t ok; uint32_t n = 0;
    do {
        asm volatile("{\n.reg .pred p;\nmbarrier.try_wait.parity.shared::cta.b64 p, [%1], %2;\nselp.u32 %0, 1, 0, p;\n}" : "=r"(ok) : "r"(bar), "r"(parity) : "memory");
    } while (!ok && ++n < (1u << 17));
}
__device__ __forceinline__ void pace_wait(uint32_t a, uint32_t target) {
    uint32_t v, n = 0;
    do {
        asm volatile("ld.volatile.shared.u32 %0, [%1];" : "=r"(v) : "r"(a) : "memory");
        if (v < target) __nanosleep(150);
    } while (v < target && ++n < (1u << 14));
}
__device__ __forceinline__ void flag_wait(const unsigned* p, unsigned target) {
    unsigned v; uint32_t n = 0;
    while (true) {
        asm volatile("ld.acquire.gpu.global.u32 %0, [%1];" : "=r"(v) : "l"(p) : "memory");
        if ((int)(v - target) >= 0 || ++n >= (1u << 17)) break;
        __nanosleep(100);
    }
}
__device__ __forceinline__ void flag_add(unsigned* p) {
    asm volatile("fence.acq_rel.gpu;\nred.relaxed.gpu.global.add.u32 [%0], 1;" :: "l"(p) : "memory");
}
__device__ __forceinline__ uint64_t make_desc(uint32_t addr, uint32_t lbo, uint32_t sbo, uint32_t swz) {
    return (uint64_t)((addr & 0x3FFFF) >> 4) | ((uint64_t)((lbo & 0x3FFFF) >> 4) << 16) | ((uint64_t)((sbo & 0x3FFFF) >> 4) << 32) | ((uint64_t)swz << 62);
}
__device__ __forceinline__ uint64_t desc_add(uint64_t d, uint32_t off16) {
    return (d & 0xFFFFFFFF00000000ull) | (uint64_t)((uint32_t)d + off16);
}
__device__ __forceinline__ void tma2d(uint32_t dst, const CUtensorMap* tm, int c0, int c1, uint32_t bar) {
    asm volatile("cp.async.bulk.tensor.2d.shared::cluster.global.mbarrier::complete_tx::bytes [%0], [%1, {%3, %4}], [%2];"
        :: "r"(dst), "l"((uint64_t)tm), "r"(bar), "r"(c0), "r"(c1) : "memory");
}
__device__ __forceinline__ void tma3d(uint32_t dst, const CUtensorMap* tm, int c0, int c1, int c2, uint32_t bar) {
    asm volatile("cp.async.bulk.tensor.3d.shared::cluster.global.mbarrier::complete_tx::bytes [%0], [%1, {%3, %4, %5}], [%2];"
        :: "r"(dst), "l"((uint64_t)tm), "r"(bar), "r"(c0), "r"(c1), "r"(c2) : "memory");
}
__device__ __forceinline__ void tma3d_mc(uint32_t dst, const CUtensorMap* tm, int c0, int c1, int c2, uint32_t bar) {
    asm volatile("cp.async.bulk.tensor.3d.shared::cluster.global.mbarrier::complete_tx::bytes.multicast::cluster [%0], [%1, {%3, %4, %5}], [%2], %6;"
        :: "r"(dst), "l"((uint64_t)tm), "r"(bar), "r"(c0), "r"(c1), "r"(c2), "h"((uint16_t)3) : "memory");
}
__device__ __forceinline__ void bulk_g2s(uint32_t dst, const void* src, uint32_t bytes, uint32_t bar) {
    asm volatile("cp.async.bulk.shared::cluster.global.mbarrier::complete_tx::bytes [%0], [%1], %2, [%3];"
        :: "r"(dst), "l"(src), "r"(bytes), "r"(bar) : "memory");
}
__device__ __forceinline__ void bulk_s2g(void* dst, uint32_t src, uint32_t bytes) {
    asm volatile("cp.async.bulk.global.shared::cta.bulk_group [%0], [%1], %2;" :: "l"(dst), "r"(src), "r"(bytes) : "memory");
}
__device__ __forceinline__ void tma2d_store(const CUtensorMap* tm, int c0, int c1, uint32_t src) {
    asm volatile("cp.async.bulk.tensor.2d.global.shared::cta.bulk_group [%0, {%2, %3}], [%1];"
        :: "l"((uint64_t)tm), "r"(src), "r"(c0), "r"(c1) : "memory");
}
__device__ __forceinline__ void l2_prefetch(const void* p, uint32_t bytes) {
    asm volatile("cp.async.bulk.prefetch.L2.global [%0], %1;" :: "l"(p), "r"(bytes) : "memory");
}
__device__ __forceinline__ void tmap_prefetch(const CUtensorMap* tm) { asm volatile("prefetch.tensormap [%0];" :: "l"((uint64_t)tm) : "memory"); }
__device__ __forceinline__ uint32_t lds32(uint32_t a) { uint32_t v; asm volatile("ld.shared.u32 %0, [%1];" : "=r"(v) : "r"(a)); return v; }
__device__ __forceinline__ uint2 lds64(uint32_t a) { uint2 v; asm volatile("ld.shared.v2.u32 {%0,%1}, [%2];" : "=r"(v.x), "=r"(v.y) : "r"(a)); return v; }
__device__ __forceinline__ uint4 lds128(uint32_t a) { uint4 v; asm volatile("ld.shared.v4.u32 {%0,%1,%2,%3}, [%4];" : "=r"(v.x), "=r"(v.y), "=r"(v.z), "=r"(v.w) : "r"(a)); return v; }
__device__ __forceinline__ float2 lds64f(uint32_t a) { float2 v; asm volatile("ld.shared.v2.f32 {%0,%1}, [%2];" : "=f"(v.x), "=f"(v.y) : "r"(a)); return v; }
__device__ __forceinline__ void sts32(uint32_t a, uint32_t v) { asm volatile("st.shared.u32 [%0], %1;" :: "r"(a), "r"(v) : "memory"); }
__device__ __forceinline__ void sts128(uint32_t a, uint4 v) { asm volatile("st.shared.v4.u32 [%0], {%1,%2,%3,%4};" :: "r"(a), "r"(v.x), "r"(v.y), "r"(v.z), "r"(v.w) : "memory"); }
__device__ __forceinline__ uint4 ldg_cg128(const void* p) { uint4 v; asm volatile("ld.global.cg.v4.u32 {%0,%1,%2,%3}, [%4];" : "=r"(v.x), "=r"(v.y), "=r"(v.z), "=r"(v.w) : "l"(p)); return v; }
__device__ __forceinline__ uint4 ldg_nc128(const void* p) { uint4 v; asm volatile("ld.global.nc.L1::no_allocate.v4.u32 {%0,%1,%2,%3}, [%4];" : "=r"(v.x), "=r"(v.y), "=r"(v.z), "=r"(v.w) : "l"(p)); return v; }
__device__ __forceinline__ uint2 ldg_nc64(const void* p) { uint2 v; asm volatile("ld.global.nc.L1::no_allocate.v2.u32 {%0,%1}, [%2];" : "=r"(v.x), "=r"(v.y) : "l"(p)); return v; }
#define WG_FENCE() asm volatile("wgmma.fence.sync.aligned;\n" ::: "memory")
#define WG_COMMIT() asm volatile("wgmma.commit_group.sync.aligned;\n" ::: "memory")
template<int N> __device__ __forceinline__ void wg_wait() { asm volatile("wgmma.wait_group.sync.aligned %0;\n" :: "n"(N) : "memory"); }
__device__ __forceinline__ bool elect_one() {
    uint32_t pr;
    asm volatile("{\n.reg .pred p;\nelect.sync _|p, 0xffffffff;\nselp.u32 %0, 1, 0, p;\n}" : "=r"(pr));
    return pr != 0;
}
__device__ __forceinline__ void named_bar(int id, int n) { asm volatile("bar.sync %0, %1;" :: "r"(id), "r"(n) : "memory"); }

__device__ __forceinline__ float bf_lo(uint32_t u) { return __uint_as_float(u << 16); }
__device__ __forceinline__ float bf_hi(uint32_t u) { return __uint_as_float(u & 0xFFFF0000u); }
__device__ __forceinline__ uint32_t pack_bf(float lo, float hi) { uint32_t r; asm("cvt.rn.bf16x2.f32 %0, %1, %2;" : "=r"(r) : "f"(hi), "f"(lo)); return r; }
__device__ __forceinline__ float bf_round(float x) { return __bfloat162float(__float2bfloat16_rn(x)); }
__device__ __forceinline__ uint32_t bmul2(uint32_t a, uint32_t b) { uint32_t r; asm("mul.rn.bf16x2 %0, %1, %2;" : "=r"(r) : "r"(a), "r"(b)); return r; }
__device__ __forceinline__ uint32_t badd2(uint32_t a, uint32_t b) { uint32_t r; asm("add.rn.bf16x2 %0, %1, %2;" : "=r"(r) : "r"(a), "r"(b)); return r; }
__device__ __forceinline__ uint32_t bsub2(uint32_t a, uint32_t b) { uint32_t r; asm("sub.rn.bf16x2 %0, %1, %2;" : "=r"(r) : "r"(a), "r"(b)); return r; }
__device__ __forceinline__ void mma16816(float (&d)[4], uint32_t a0, uint32_t a1, uint32_t a2, uint32_t a3, uint2 b) {
    asm volatile("mma.sync.aligned.m16n8k16.row.col.f32.bf16.bf16.f32 {%0,%1,%2,%3}, {%4,%5,%6,%7}, {%8,%9}, {%0,%1,%2,%3};\n"
        : "+f"(d[0]), "+f"(d[1]), "+f"(d[2]), "+f"(d[3]) : "r"(a0), "r"(a1), "r"(a2), "r"(a3), "r"(b.x), "r"(b.y));
}

template<int HS> __device__ __forceinline__ void xreduce(float (&v)[8], int lane) {
    const int up = lane & HS;
    #pragma unroll
    for (int e = 0; e < HS; e++) {
        float keep, send;
        asm("{\n.reg .pred p;\nsetp.ne.b32 p, %4, 0;\nselp.f32 %0, %3, %2, p;\nselp.f32 %1, %2, %3, p;\n}"
            : "=f"(keep), "=f"(send) : "f"(v[e]), "f"(v[e + HS]), "r"(up));
        v[e] = keep + __shfl_xor_sync(0xffffffffu, send, HS);
    }
}

__device__ __forceinline__ int blk_f0(int s) {
    if (s < 32) return 32 * (14 * (s >> 3) + 8 * ((s >> 2) & 1) + (s & 3));
    const int s2 = s - 32, c6 = (s2 * 11) >> 6, t = s2 - 6 * c6;
    return 32 * (14 * c6 + (t < 4 ? 4 + t : 8 + t));
}
__device__ __forceinline__ int next_st2(int s) { return (0x14023 >> (4 * s)) & 7; }
__device__ __forceinline__ uint32_t stage_off_rt(int s) { return s < 3 ? SM_RING + s * STAGE_BYTES : (uint32_t)(s - 3) * 65536; }

template<int NB, bool passA>
__device__ __forceinline__ void gemm1_pass(uint32_t sb, int wgi, int warp4, int lane, int& st, uint32_t& fph, uint32_t e_cl,
                                           int rb64, int ks0, bool convCTA) {
    float acc[NB * 32];
    const uint64_t descA0 = make_desc(sb + SM_X + wgi * 65536, 16, 1024, 1);
    const uint64_t descB0 = make_desc(sb + SM_RING, 4096, 512, 2);
    int prev = 0;
    #pragma unroll 1
    for (int sl = 0; sl < 8; sl++) {
        if (warp4 == 0 && wgi == 0) PROF2(2, sl + (passA ? 0 : 8));
        mbar_wait(sb + SM_BARS + (B_FULL + st) * 8, (fph >> st) & 1);
        fph ^= 1u << st;
        if (sl == 0 && warp4 == 0) PROF(2 + wgi * 8 + (passA ? 0 : 3));
        if (warp4 == 0 && wgi == 0) PROF2(1, sl + (passA ? 0 : 8));
        const uint64_t da = desc_add(descA0, sl * 512), db = desc_add(descB0, st * 2048);
        WG_FENCE();
        #pragma unroll
        for (int kk = 0; kk < 4; kk++) {
            int sc = (sl | kk) ? 1 : 0;
            if constexpr (NB == 4) wgmma_ss_n256_tb(acc, da + kk * 2, db + kk * 64, sc); else wgmma_ss_n128_tb(acc, da + kk * 2, db + kk * 64, sc);
        }
        WG_COMMIT();
        wg_wait<1>();
        if (warp4 == 0 && wgi == 0) PROF2(3, sl + (passA ? 0 : 8));
        if (lane < 2 && sl && (passA || !convCTA || sl < 6)) mbar_arrive_cluster(e_cl + prev * 8, 1);
        if (!passA) {
            if (sl == 4) {
                if (convCTA) { if (lane == 0) mbar_arrive(sb + SM_BARS + B_XFREE * 8); }
                else if (lane < 4) mbar_arrive_cluster(e_cl + (3 + (lane >> 1)) * 8, 1);
            }
        }
        prev = st;
        st = (st == 2) ? 0 : st + 1;
    }
    wg_wait<0>();
    if (lane < 2 && (passA || !convCTA)) mbar_arrive_cluster(e_cl + prev * 8, 1);
    if (!passA && lane == 0) mbar_arrive(sb + SM_BARS + B_G1DONE * 8);
    if (warp4 == 0) PROF(3 + wgi * 8 + (passA ? 0 : 3));
    const int g = lane >> 2;
    const int r0 = wgi * 64 + warp4 * 16 + g;
    const float s0 = __uint_as_float(lds32(sb + SM_STATS + r0 * 8 + 4)), s1 = __uint_as_float(lds32(sb + SM_STATS + (r0 + 8) * 8 + 4));
    uint32_t* dst = g_h + (size_t)((rb64 >> 1) * 56 + ks0) * 2048 + wgi * 1024 + warp4 * 128 + lane;
    #pragma unroll
    for (int kk = 0; kk < NB * 2; kk++) {
        uint32_t h[4];
        #pragma unroll
        for (int tt = 0; tt < 2; tt++) {
            const int t = 2 * kk + tt;
            const float* ag = &acc[4 * t];
            const float* au = &acc[NB * 16 + 4 * t];
            h[2 * tt] = bmul2(pack_bf(ag[0] * s0, ag[1] * s0), pack_bf(au[0] * s0, au[1] * s0));
            h[2 * tt + 1] = bmul2(pack_bf(ag[2] * s1, ag[3] * s1), pack_bf(au[2] * s1, au[3] * s1));
        }
        uint32_t* d2 = dst + (kk >> 1) * 2048 + (kk & 1) * 512;
        d2[0] = h[0]; d2[64] = h[1]; d2[32] = h[2]; d2[96] = h[3];
    }
    __syncwarp();
    if (lane == 0) mbar_arrive(sb + SM_BARS + (B_HD + wgi * 2 + (passA ? 0 : 1)) * 8);
    if (warp4 == 0) PROF(4 + wgi * 8 + (passA ? 0 : 3));
}

__global__ void __cluster_dims__(2, 1, 1) __launch_bounds__(NTHREADS, 1)
fused_kernel(const __grid_constant__ Params p) {
    extern __shared__ __align__(1024) uint8_t smem_raw[];
    const uint32_t sb = smem_u32(smem_raw);
    const int tid = threadIdx.x, warp = tid >> 5, lane = tid & 31;
    const int b = blockIdx.x;
    const int rank = b & 1;
    const int j = (b >> 1) & 7;
    const int i = ((b >> 4) << 1) | rank;
    const int cb = j >> 1;
    const bool convCTA = j & 1;
    const int cidx = 4 * i + cb;

    if (tid == 256) {
        mbar_init(sb + SM_BARS + B_XFULL * 8, 1);
        mbar_init(sb + SM_BARS + (B_XFULL + 1) * 8, 1);
        asm volatile("fence.proxy.async.shared::cta;" ::: "memory");
        mbar_expect_tx(sb + SM_BARS + B_XFULL * 8, 65536);
        tma3d(sb + SM_X, &p.tm_x, 0, 128 * i, 0, sb + SM_BARS + B_XFULL * 8);
        mbar_expect_tx(sb + SM_BARS + (B_XFULL + 1) * 8, 65536);
        tma3d(sb + SM_X + 65536, &p.tm_x, 0, 128 * i + 64, 0, sb + SM_BARS + (B_XFULL + 1) * 8);
    }
    if (tid == 288) {
        for (int s = 0; s < 5; s++) { mbar_init(sb + SM_BARS + (B_FULL + s) * 8, 1); mbar_init(sb + SM_BARS + (B_EMPTY + s) * 8, 16); }
        mbar_init(sb + SM_BARS + B_CONV * 8, 1);
        mbar_init(sb + SM_BARS + B_YT * 8, 1);
        mbar_init(sb + SM_BARS + B_XR * 8, 1);
        mbar_init(sb + SM_BARS + B_G1DONE * 8, 8);
        mbar_init(sb + SM_BARS + B_XFREE * 8, 8);
        mbar_init(sb + SM_BARS + B_YST * 8, 8);
        mbar_init(sb + SM_BARS + B_KVLD * 8, 2);
        for (int s = 0; s < 4; s++) mbar_init(sb + SM_BARS + (B_HD + s) * 8, 4);
        for (int s = 0; s < 2; s++) mbar_init(sb + SM_BARS + (B_HRDY + s) * 8, 1);
        asm volatile("fence.mbarrier_init.release.cluster;" ::: "memory");
        asm volatile("fence.proxy.async.shared::cta;" ::: "memory");
    }
    __syncwarp();
    asm volatile("barrier.cluster.arrive.relaxed.aligned;\n" ::: "memory");
    asm volatile("barrier.cluster.wait.aligned;\n" ::: "memory");
    PROFW(1, 0);

    if (warp < 8) {
        asm volatile("setmaxnreg.inc.sync.aligned.u32 200;");
        const int wgi = warp >> 2, warp4 = warp & 3;
        const int g = lane >> 2, c = lane & 3;
        const uint32_t e_cl = mapa(sb + SM_BARS + B_EMPTY * 8, lane & 1);
        {
            const int lr16 = (lane & 7) + ((lane >> 3) & 1) * 8;
            const uint32_t xa = sb + SM_X + wgi * 65536 + (warp4 * 16 + lr16) * 128;
            uint32_t xf[32][4];
            float aS[4][4], aQ0[4][4], aQ1[4][4];
            #pragma unroll
            for (int e = 0; e < 4; e++) {
                #pragma unroll
                for (int f = 0; f < 4; f++) { aS[e][f] = 0.f; aQ0[e][f] = 0.f; aQ1[e][f] = 0.f; }
            }
            mbar_wait(sb + SM_BARS + (B_XFULL + wgi) * 8, 0);
            PROFW(16, 0); PROFW(18, 4);
            #pragma unroll
            for (int ks = 0; ks < 32; ks++) {
                const uint32_t a = xa + (ks >> 2) * 8192 + (((2 * (ks & 3) + (lane >> 4)) ^ (lane & 7)) << 4);
                asm volatile("ldmatrix.sync.aligned.m8n8.x4.shared.b16 {%0,%1,%2,%3}, [%4];"
                    : "=r"(xf[ks][0]), "=r"(xf[ks][1]), "=r"(xf[ks][2]), "=r"(xf[ks][3]) : "r"(a) : "memory");
            }
            #pragma unroll
            for (int ks = 0; ks < 32; ks++) {
                mma16816(aS[ks & 3], xf[ks][0], xf[ks][1], xf[ks][2], xf[ks][3], make_uint2(0x3F803F80u, 0x3F803F80u));
                mma16816(aQ0[ks & 3], xf[ks][0], xf[ks][1], xf[ks][2], xf[ks][3], make_uint2(xf[ks][0], xf[ks][2]));
                mma16816(aQ1[ks & 3], xf[ks][0], xf[ks][1], xf[ks][2], xf[ks][3], make_uint2(xf[ks][1], xf[ks][3]));
            }
            const float mean0 = ((aS[0][0] + aS[1][0]) + (aS[2][0] + aS[3][0])) * (1.0f / DM);
            const float mean1 = ((aS[0][2] + aS[1][2]) + (aS[2][2] + aS[3][2])) * (1.0f / DM);
            const uint32_t m0 = pack_bf(mean0, mean0), m1 = pack_bf(mean1, mean1);
            #pragma unroll
            for (int ks = 0; ks < 32; ks++) {
                const uint32_t a = xa + (ks >> 2) * 8192 + (((2 * (ks & 3) + (lane >> 4)) ^ (lane & 7)) << 4);
                asm volatile("stmatrix.sync.aligned.m8n8.x4.shared.b16 [%0], {%1,%2,%3,%4};"
                    :: "r"(a), "r"(bsub2(xf[ks][0], m0)), "r"(bsub2(xf[ks][1], m1)), "r"(bsub2(xf[ks][2], m0)), "r"(bsub2(xf[ks][3], m1)) : "memory");
            }
            if (c == (g >> 1)) {
                const float q0 = (g & 1) ? (aQ0[0][1] + aQ0[1][1]) + (aQ0[2][1] + aQ0[3][1]) : (aQ0[0][0] + aQ0[1][0]) + (aQ0[2][0] + aQ0[3][0]);
                const float q1 = (g & 1) ? (aQ1[0][3] + aQ1[1][3]) + (aQ1[2][3] + aQ1[3][3]) : (aQ1[0][2] + aQ1[1][2]) + (aQ1[2][2] + aQ1[3][2]);
                const float sd0 = bf_round(sqrtf(bf_round(bf_round(fmaxf(q0 * (1.0f / DM) - mean0 * mean0, 0.f)) + 1e-5f)));
                const float sd1 = bf_round(sqrtf(bf_round(bf_round(fmaxf(q1 * (1.0f / DM) - mean1 * mean1, 0.f)) + 1e-5f)));
                const uint32_t sa = sb + SM_STATS + (warp * 16 + g) * 8;
                sts32(sa, m0); sts32(sa + 4, __float_as_uint(1.0f / sd0));
                sts32(sa + 64, m1); sts32(sa + 68, __float_as_uint(1.0f / sd1));
            }
            asm volatile("fence.proxy.async.shared::cta;" ::: "memory");
            named_bar(1 + wgi, 128);
            PROFW(19, 4);
            PROFW(17, 0);
        }
        int st = 0; uint32_t fph = 0;
        const int rb64 = 2 * i + wgi;
        gemm1_pass<4, true>(sb, wgi, warp4, lane, st, fph, e_cl, rb64, 4 * j, convCTA);
        if (convCTA) gemm1_pass<2, false>(sb, wgi, warp4, lane, st, fph, e_cl, rb64, 36 + 6 * cb, true);
        else gemm1_pass<4, false>(sb, wgi, warp4, lane, st, fph, e_cl, rb64, 32 + 6 * cb, false);

        if (convCTA) {
            const int gch = 8 * cidx + warp;
            const uint32_t xb = sb + SM_CVX + warp * 4096;
            const uint32_t hb = sb + SM_CVH + warp * 4096;
            const uint32_t dw = ((const unsigned short*)p.ssm_D)[gch];
            const uint32_t d2 = dw | (dw << 16);
            mbar_wait(sb + SM_BARS + B_CONV * 8, 0);
            PROFW(32, 4);
            float acc[16][4];
            #pragma unroll
            for (int jj = 0; jj < 16; jj++) { acc[jj][0] = 0.f; acc[jj][1] = 0.f; acc[jj][2] = 0.f; acc[jj][3] = 0.f; }
            uint2 bh[8], bl0[8], bl1[8];
            uint32_t xl = xb + g * 32 + c * 8;
            uint32_t hl = hb + (g + 2 * c - 8) * 4;
            #pragma unroll
            for (int d = 0; d < 8; d++) { bl0[d] = lds64(xl + d * 256); bh[d] = lds64(xl + (8 + d) * 256); }
            uint32_t w[6];
            w[0] = 0; w[1] = 0; w[2] = 0;
            if (g + 2 * c >= 8) w[0] = lds32(hl);
            if (g + 2 * c >= 7) w[1] = lds32(hl + 4);
            if (g + 2 * c >= 6) w[2] = lds32(hl + 8);
            w[3] = lds32(hl + 2048); w[4] = lds32(hl + 2052); w[5] = lds32(hl + 2056);
            auto conv_m0 = [&](int m0, uint2 (&bl)[8], uint2 (&bn)[8]) {
                xl -= 32;
                #pragma unroll
                for (int k = 0; k < 8; k++) {
                    const uint32_t a0 = w[1], a1 = __byte_perm(w[0], w[1], 0x5432), a2 = w[2], a3 = __byte_perm(w[1], w[2], 0x5432);
                    const uint32_t c0 = w[4], c1 = __byte_perm(w[3], w[4], 0x5432), c2 = w[5], c3 = __byte_perm(w[4], w[5], 0x5432);
                    const uint32_t nx = (k < 7) ? hl + (k + 1) * 256 : hl + 32;
                    w[0] = lds32(nx); w[1] = lds32(nx + 4); w[2] = lds32(nx + 8);
                    w[3] = lds32(nx + 2048); w[4] = lds32(nx + 2052); w[5] = lds32(nx + 2056);
                    if (k > 0) bn[k] = lds64(xl + k * 256);
                    else { bn[0] = make_uint2(0, 0); if (g > m0) bn[0] = lds64(xl); }
                    #pragma unroll
                    for (int jj = k; jj < 16; jj++) mma16816(acc[jj], a0, a1, a2, a3, (jj - k < 8) ? bl[(jj - k) & 7] : bh[(jj - k) & 7]);
                    bh[7 - k] = lds64(xl + (15 - k) * 256);
                    #pragma unroll
                    for (int jj = k + 8; jj < 16; jj++) mma16816(acc[jj], c0, c1, c2, c3, bl[jj - k - 8]);
                }
                hl += 32;
            };
            #pragma unroll 1
            for (int m0 = 0; m0 < 8; m0 += 2) {
                conv_m0(m0, bl0, bl1);
                conv_m0(m0 + 1, bl1, bl0);
                PROFW(34 + (m0 >> 1), 4);
            }
            PROFW(33, 4);
            const uint32_t kvl = xb + c * 64 + (7 - g) * 4;
            uint32_t* ydst = (uint32_t*)(g_yT + (size_t)gch * SEQ + 32 * c + 2 * g);
            uint32_t kk0[16], kk1[16];
            #pragma unroll
            for (int jj = 0; jj < 16; jj++) { kk0[jj] = lds32(kvl + jj * 256); kk1[jj] = lds32(kvl + jj * 256 + 32); }
            #pragma unroll
            for (int jj = 0; jj < 16; jj++) {
                ydst[jj * 64] = badd2(pack_bf(acc[jj][2], acc[jj][0]), bmul2(__byte_perm(kk0[jj], kk0[jj], 0x1032), d2));
                ydst[jj * 64 + 8] = badd2(pack_bf(acc[jj][3], acc[jj][1]), bmul2(__byte_perm(kk1[jj], kk1[jj], 0x1032), d2));
            }
            __syncwarp();
            PROFW(44, 4);
            if (lane == 0) mbar_arrive(sb + SM_BARS + B_YST * 8);
        } else {
            float acc[64];
            const uint64_t descB0 = make_desc(sb, 4096, 1024, 1);
            const uint64_t descA0 = make_desc(sb + 16384 + wgi * 4096, 128, 256, 0);
            int sg = 3, p0 = 0; uint32_t ph = 6;
            PROFW(20, 0);
            #pragma unroll 1
            for (int u = 0; u < 28; u++) {
                if (warp == 0 && !(u & 1)) PROF2(2, 16 + (u >> 1));
                mbar_wait(sb + SM_BARS + (B_FULL + sg) * 8, (ph >> sg) & 1);
                ph ^= 1u << sg;
                if (warp == 0 && !(u & 1)) PROF2(1, 16 + (u >> 1));
                const uint32_t o0 = stage_off_rt(sg) >> 4;
                const uint64_t da0 = desc_add(descA0, o0), db0 = desc_add(descB0, o0);
                WG_FENCE();
                #pragma unroll
                for (int kk = 0; kk < 4; kk++) wgmma_ss_n128_tb(acc, da0 + ((kk >> 1) * 512 + (kk & 1) * 128), db0 + ((kk >> 1) * 512 + (kk & 1) * 128), (u | kk) ? 1 : 0);
                WG_COMMIT();
                wg_wait<1>();
                if (warp == 0 && !(u & 1)) PROF2(3, 16 + (u >> 1));
                if (lane < 2 && u > 0 && u + 4 < 28) mbar_arrive_cluster(e_cl + p0 * 8, 1);
                p0 = sg;
                sg = next_st2(sg);
            }
            wg_wait<0>();
            PROFW(27, 0);
            mbar_wait(sb + SM_BARS + B_XR * 8, 0);
            const int r0 = wgi * 64 + warp4 * 16 + g;
            const float2 st0 = lds64f(sb + SM_STATS + r0 * 8), st1 = lds64f(sb + SM_STATS + (r0 + 8) * 8);
            const uint32_t m0 = __float_as_uint(st0.x), m1 = __float_as_uint(st1.x);
            const uint32_t xrow0 = sb + SM_XE + r0 * 128 + c * 4;
            const int mi = lane >> 3, lr = lane & 7;
            const uint32_t yaddr = sb + SM_YT + wgi * 16384 + ((mi >> 1) * 8 + lr) * 128 + (((2 * warp4 + (mi & 1)) ^ lr) << 4);
            uint32_t y[8][4], xv[16][2], nv[16][2], bv[16][2];
            #pragma unroll
            for (int t = 0; t < 16; t++) {
                const uint32_t off = (t >> 3) * 16384 + (((t & 7) ^ g) << 4);
                xv[t][0] = lds32(xrow0 + off); xv[t][1] = lds32(xrow0 + 1024 + off);
            }
            #pragma unroll
            for (int t = 0; t < 16; t++) {
                const uint32_t d0 = bsub2(xv[t][0], m0), d1 = bsub2(xv[t][1], m1);
                nv[t][0] = pack_bf(bf_lo(d0) * st0.y, bf_hi(d0) * st0.y); nv[t][1] = pack_bf(bf_lo(d1) * st1.y, bf_hi(d1) * st1.y);
                bv[t][0] = pack_bf(acc[4 * t], acc[4 * t + 1]); bv[t][1] = pack_bf(acc[4 * t + 2], acc[4 * t + 3]);
            }
            mbar_wait(sb + SM_BARS + B_YT * 8, 0);
            PROFW(28, 0);
            #pragma unroll
            for (int t2 = 0; t2 < 8; t2++)
                asm volatile("ldmatrix.sync.aligned.m8n8.x4.trans.shared.b16 {%0,%1,%2,%3}, [%4];"
                    : "=r"(y[t2][0]), "=r"(y[t2][1]), "=r"(y[t2][2]), "=r"(y[t2][3]) : "r"(yaddr + t2 * 2048) : "memory");
            #pragma unroll
            for (int t = 0; t < 16; t++) {
                const uint32_t off = (t >> 3) * 16384 + (((t & 7) ^ g) << 4);
                sts32(xrow0 + off, badd2(badd2(xv[t][0], bmul2(nv[t][0], y[t >> 1][2 * (t & 1)])), bv[t][0]));
                sts32(xrow0 + 1024 + off, badd2(badd2(xv[t][1], bmul2(nv[t][1], y[t >> 1][2 * (t & 1) + 1])), bv[t][1]));
            }
            asm volatile("fence.proxy.async.shared::cta;" ::: "memory");
            named_bar(1 + wgi, 128);
            if ((tid & 127) == 0) {
                tma2d_store(&p.tm_out, 128 * cb, 128 * i + 64 * wgi, sb + SM_XE + wgi * 8192);
                tma2d_store(&p.tm_out, 128 * cb + 64, 128 * i + 64 * wgi, sb + SM_XE + 16384 + wgi * 8192);
                asm volatile("cp.async.bulk.commit_group;" ::: "memory");
                asm volatile("cp.async.bulk.wait_group.read 0;" ::: "memory");
                PROFW(29, 0);
            }
        }
    } else {
        asm volatile("setmaxnreg.dec.sync.aligned.u32 104;");
        if (warp == 8) {
            int st = 0; uint32_t eph = 7;
            #pragma unroll 1
            for (int it = 0; it < 16; it++) {
                const int pass = it >> 3, sl = it & 7;
                const bool narrow = pass && convCTA;
                const int nb = narrow ? 2 : 4;
                const CUtensorMap* tm = narrow ? (rank ? &p.tm_uB : &p.tm_gB) : (rank ? &p.tm_uA : &p.tm_gA);
                mbar_wait(sb + SM_BARS + (B_EMPTY + st) * 8, (eph >> st) & 1);
                eph ^= 1u << st;
                if (it == 1) mbar_wait(sb + SM_BARS + B_XFULL * 8, 0);
                PROF2(0, it);
                if (elect_one()) {
                    mbar_expect_tx(sb + SM_BARS + (B_FULL + st) * 8, nb * 8192);
                    tma3d_mc(sb + SM_RING + st * STAGE_BYTES + rank * nb * 4096, tm, 0, sl * 64, 14 * cb + 8 * (j & 1) + 4 * pass, sb + SM_BARS + (B_FULL + st) * 8);
                }
                st = (st == 2) ? 0 : st + 1;
            }
            if (!convCTA) {
                st = 3;
                const int f0_lane = blk_f0(2 * lane + rank);
                #pragma unroll 1
                for (int u = 0; u < 28; u++) {
                    const uint32_t bar = sb + SM_BARS + (B_FULL + st) * 8;
                    const int f0 = __shfl_sync(0xffffffffu, f0_lane, u);
                    mbar_wait(sb + SM_BARS + (B_EMPTY + st) * 8, (eph >> st) & 1);
                    eph ^= 1u << st;
                    if ((u & 1) == 0) PROF2(0, 16 + (u >> 1));
                    if (elect_one()) {
                        mbar_expect_tx(bar, 32768);
                        tma3d_mc(sb + stage_off_rt(st) + rank * 8192, &p.tm_w2, 0, f0, 2 * cb, bar);
                    }
                    st = next_st2(st);
                }
                PROF(48);
            }
        } else if (warp < 11) {
            mbar_wait(sb + SM_BARS + (B_XFULL + 1) * 8, 0);
            #pragma unroll 1
            for (int rnd = 0; rnd < 2; rnd++) {
                const int tt = (tid - 288) + 64 * rnd;
                uint32_t sk[4][2];
                uint4 skw[2];
                skw[0] = ldg_nc128(p.shift_k + 16 * tt); skw[1] = ldg_nc128(p.shift_k + 16 * tt + 8);
                const __nv_bfloat16* kp = p.k + (size_t)(16 * b) * DM + 4 * tt;
                const __nv_bfloat16* vp = p.v + (size_t)(16 * b) * DM + 4 * tt;
                uint2 kr[19];
                uint2 kv[16];
                #pragma unroll
                for (int r = 0; r < 3; r++) kr[r] = (b > 0) ? ldg_nc64(kp + (r - 3) * DM) : make_uint2(0, 0);
                #pragma unroll
                for (int r = 0; r < 16; r++) { kr[3 + r] = ldg_nc64(kp + r * DM); kv[r] = ldg_nc64(vp + r * DM); }
                {
                    const uint4 w0 = skw[0], w1 = skw[1];
                    sk[0][0] = __byte_perm(w0.x, w0.z, 0x5410); sk[1][0] = __byte_perm(w0.x, w0.z, 0x7632);
                    sk[2][0] = __byte_perm(w0.y, w0.w, 0x5410); sk[3][0] = __byte_perm(w0.y, w0.w, 0x7632);
                    sk[0][1] = __byte_perm(w1.x, w1.z, 0x5410); sk[1][1] = __byte_perm(w1.x, w1.z, 0x7632);
                    sk[2][1] = __byte_perm(w1.y, w1.w, 0x5410); sk[3][1] = __byte_perm(w1.y, w1.w, 0x7632);
                }
                #pragma unroll
                for (int s = 0; s < 16; s++) {
                    uint32_t a = bmul2(kr[s].x, sk[3][0]);
                    a = badd2(a, bmul2(kr[s + 1].x, sk[2][0]));
                    a = badd2(a, bmul2(kr[s + 2].x, sk[1][0]));
                    a = badd2(a, bmul2(kr[s + 3].x, sk[0][0]));
                    kv[s].x = bmul2(a, kv[s].x);
                    a = bmul2(kr[s].y, sk[3][1]);
                    a = badd2(a, bmul2(kr[s + 1].y, sk[2][1]));
                    a = badd2(a, bmul2(kr[s + 2].y, sk[1][1]));
                    a = badd2(a, bmul2(kr[s + 3].y, sk[0][1]));
                    kv[s].y = bmul2(a, kv[s].y);
                }
                PROFW(57 + 2 * rnd, 9);
                if (rnd == 1 && lane == 0) mbar_arrive(sb + SM_BARS + B_KVLD * 8);
                #pragma unroll
                for (int cc = 0; cc < 4; cc++) {
                    const uint32_t sel = (cc & 1) ? 0x7632 : 0x5410;
                    #define KVW(r) ((cc & 2) ? kv[r].y : kv[r].x)
                    uint4* dst = (uint4*)(g_kvT + (size_t)(4 * tt + cc) * SEQ + 16 * b);
                    dst[0] = make_uint4(__byte_perm(KVW(15), KVW(14), sel), __byte_perm(KVW(13), KVW(12), sel),
                                        __byte_perm(KVW(11), KVW(10), sel), __byte_perm(KVW(9), KVW(8), sel));
                    dst[1] = make_uint4(__byte_perm(KVW(7), KVW(6), sel), __byte_perm(KVW(5), KVW(4), sel),
                                        __byte_perm(KVW(3), KVW(2), sel), __byte_perm(KVW(1), KVW(0), sel));
                    #undef KVW
                }
                PROFW(58 + 2 * rnd, 9);
            }
            asm volatile("fence.proxy.async.global;" ::: "memory");
            __syncwarp();
            if (lane == 0) {
                flag_add(&g_cnt_kv[0]);
                PROFW(50, 9);
                const int wgi = warp - 9;
                mbar_wait(sb + SM_BARS + (B_HD + wgi * 2) * 8, 0);
                flag_add(&g_flag_h[(i * 2 + 0) * 8]);
                mbar_wait(sb + SM_BARS + (B_HD + wgi * 2 + 1) * 8, 0);
                flag_add(&g_flag_h[(i * 2 + 1) * 8]);
                if (wgi == 1 && convCTA) {
                    mbar_wait(sb + SM_BARS + B_YST * 8, 0);
                    flag_add(&g_cnt_y[(cidx >> 4) * 32]);
                    PROF(46);
                }
                if (wgi == 1 && !convCTA) {
                    const unsigned ep = lds32(sb + SM_EPOCH);
                    mbar_wait(sb + SM_BARS + B_G1DONE * 8, 0);
                    mbar_expect_tx(sb + SM_BARS + B_XR * 8, 32768);
                    tma3d(sb + SM_XE, &p.tm_xe, 0, 128 * i, 2 * cb, sb + SM_BARS + B_XR * 8);
                    flag_wait(&g_flag_h[(i * 2 + 1) * 8], ep * 16);
                    mbar_arrive(sb + SM_BARS + (B_HRDY + 1) * 8);
                    __nanosleep(3000);
                    flag_wait(&g_cnt_y[cb * 32], ep * 16);
                    PROF(49);
                    asm volatile("fence.proxy.async.global;" ::: "memory");
                    mbar_expect_tx(sb + SM_BARS + B_YT * 8, 32768);
                    tma2d(sb + SM_YT, &p.tm_yT, 128 * i, 128 * cb, sb + SM_BARS + B_YT * 8);
                    tma2d(sb + SM_YT + 16384, &p.tm_yT, 128 * i + 64, 128 * cb, sb + SM_BARS + B_YT * 8);
                }
            }
        } else {
            if (lane == 0) {
                l2_prefetch(p.wg + (size_t)b * (FF * DM / NCTA), FF * DM / NCTA * 2);
                l2_prefetch(p.wu + (size_t)b * (FF * DM / NCTA), FF * DM / NCTA * 2);
                const unsigned ep = g_launch[b] + 1;
                g_launch[b] = ep;
                sts32(sb + SM_EPOCH, ep);
                tmap_prefetch(rank ? &p.tm_uA : &p.tm_gA);
                tmap_prefetch(rank ? &p.tm_uB : &p.tm_gB);
                tmap_prefetch(&p.tm_w2); tmap_prefetch(&p.tm_yT); tmap_prefetch(&p.tm_out); tmap_prefetch(&p.tm_xe);
                mbar_wait(sb + SM_BARS + B_KVLD * 8, 0);
                l2_prefetch(p.ssm_k + (size_t)(4 * b) * SEQ, 4 * SEQ * 2);
                l2_prefetch(p.wd + (size_t)b * (FF * DM / NCTA), FF * DM / NCTA * 2);
                mbar_wait(sb + SM_BARS + (B_HD + 0) * 8, 0);
                if (convCTA) {
                    flag_wait(&g_cnt_kv[0], ep * 256);
                    asm volatile("fence.proxy.async.global;" ::: "memory");
                    PROF(53);
                    mbar_wait(sb + SM_BARS + B_XFREE * 8, 0);
                    PROF(54);
                    mbar_expect_tx(sb + SM_BARS + B_CONV * 8, 65536);
                    bulk_g2s(sb + SM_CVX, g_kvT + (size_t)(8 * cidx) * SEQ, 32768, sb + SM_BARS + B_CONV * 8);
                    bulk_g2s(sb + SM_CVH, p.ssm_k + (size_t)(8 * cidx) * SEQ, 32768, sb + SM_BARS + B_CONV * 8);
                } else {
                    flag_wait(&g_flag_h[(i * 2 + 0) * 8], ep * 16);
                }
            }
            __syncwarp();
            if (!convCTA) {
                asm volatile("fence.proxy.async.global;" ::: "memory");
                int st = 3; uint32_t eph = 1;
                const uint8_t* hsrc = (const uint8_t*)g_h + (size_t)i * 56 * 8192;
                #pragma unroll 1
                for (int u = 0; u < 28; u++) {
                    mbar_wait(sb + SM_BARS + (B_EMPTY + st) * 8, (eph >> st) & 1);
                    eph ^= 1u << st;
                    if (u == 16) {
                        mbar_wait(sb + SM_BARS + (B_HRDY + 1) * 8, 0);
                        asm volatile("fence.proxy.async.global;" ::: "memory");
                    }
                    if (elect_one()) bulk_g2s(sb + stage_off_rt(st) + 16384, hsrc + u * 16384, 16384, sb + SM_BARS + (B_FULL + st) * 8);
                    st = next_st2(st);
                }
            }
        }
    }
}

typedef CUresult (*EncodeFn)(CUtensorMap*, CUtensorMapDataType, cuuint32_t, void*, const cuuint64_t*, const cuuint64_t*,
                             const cuuint32_t*, const cuuint32_t*, CUtensorMapInterleave, CUtensorMapSwizzle,
                             CUtensorMapL2promotion, CUtensorMapFloatOOBfill);

void encode(EncodeFn fn, CUtensorMap* tm, const void* base, int rank, const cuuint64_t* dims, const cuuint64_t* strides,
            const cuuint32_t* box, CUtensorMapSwizzle swz) {
    cuuint32_t es[5] = {1, 1, 1, 1, 1};
    fn(tm, CU_TENSOR_MAP_DATA_TYPE_BFLOAT16, rank, (void*)base, dims, strides, box, es, CU_TENSOR_MAP_INTERLEAVE_NONE, swz,
       CU_TENSOR_MAP_L2_PROMOTION_L2_128B, CU_TENSOR_MAP_FLOAT_OOB_FILL_NONE);
}

}

extern "C" void kernel_launch(void* const* d_in, const int* in_sizes, int n_in, void* d_out, int out_size) {
    (void)in_sizes; (void)n_in; (void)out_size;
    static EncodeFn enc = nullptr;
    static void* yT_ptr = nullptr;
    if (!enc) {
        void* fn = nullptr; cudaDriverEntryPointQueryResult qr;
        cudaGetDriverEntryPoint("cuTensorMapEncodeTiled", &fn, cudaEnableDefault, &qr);
        enc = (EncodeFn)fn;
        cudaGetSymbolAddress(&yT_ptr, g_yT);
        cudaFuncSetAttribute(fused_kernel, cudaFuncAttributeMaxDynamicSharedMemorySize, SM_TOTAL);
    }
    Params p;
    p.q = (const __nv_bfloat16*)d_in[0]; p.k = (const __nv_bfloat16*)d_in[1]; p.v = (const __nv_bfloat16*)d_in[2];
    p.shift_k = (const __nv_bfloat16*)d_in[3]; p.ssm_k = (const __nv_bfloat16*)d_in[4]; p.ssm_D = (const __nv_bfloat16*)d_in[5];
    p.wg = (const __nv_bfloat16*)d_in[7]; p.wu = (const __nv_bfloat16*)d_in[8]; p.wd = (const __nv_bfloat16*)d_in[9];
    {
        cuuint64_t dims[2] = {DM, SEQ}; cuuint64_t str[1] = {DM * 2};
        cuuint64_t dims3[3] = {64, SEQ, DM / 64}; cuuint64_t str3[2] = {DM * 2, 128};
        cuuint32_t box[3] = {64, 64, 8}, boxe[3] = {64, 128, 2};
        encode(enc, &p.tm_x, p.q, 3, dims3, str3, box, CU_TENSOR_MAP_SWIZZLE_128B);
        encode(enc, &p.tm_xe, p.q, 3, dims3, str3, boxe, CU_TENSOR_MAP_SWIZZLE_128B);
        cuuint32_t box2[2] = {64, 64};
        encode(enc, &p.tm_out, d_out, 2, dims, str, box2, CU_TENSOR_MAP_SWIZZLE_128B);
    }
    {
        cuuint64_t dims[3] = {32, DM, FF / 32}; cuuint64_t str[2] = {FF * 2, 64};
        cuuint32_t boxA[3] = {32, 64, 4}, boxB[3] = {32, 64, 2};
        encode(enc, &p.tm_gA, p.wg, 3, dims, str, boxA, CU_TENSOR_MAP_SWIZZLE_64B);
        encode(enc, &p.tm_gB, p.wg, 3, dims, str, boxB, CU_TENSOR_MAP_SWIZZLE_64B);
        encode(enc, &p.tm_uA, p.wu, 3, dims, str, boxA, CU_TENSOR_MAP_SWIZZLE_64B);
        encode(enc, &p.tm_uB, p.wu, 3, dims, str, boxB, CU_TENSOR_MAP_SWIZZLE_64B);
    }
    {
        cuuint64_t dims[3] = {64, FF, DM / 64}; cuuint64_t str[2] = {DM * 2, 128};
        cuuint32_t box[3] = {64, 32, 2};
        encode(enc, &p.tm_w2, p.wd, 3, dims, str, box, CU_TENSOR_MAP_SWIZZLE_128B);
    }
    {
        cuuint64_t dims[2] = {SEQ, DM}; cuuint64_t str[1] = {SEQ * 2};
        cuuint32_t box[2] = {64, 128};
        encode(enc, &p.tm_yT, yT_ptr, 2, dims, str, box, CU_TENSOR_MAP_SWIZZLE_128B);
    }
    fused_kernel<<<NCTA, NTHREADS, SM_TOTAL>>>(p);
}
```

```cpp
#include <cuda_runtime.h>
#include <cuda_bf16.h>
#include <cuda.h>
#include <stdint.h>

namespace {

constexpr int SEQ = 2048, DM = 512, FF = 1792;
constexpr int NCTA = 128;
constexpr int NTHREADS = 384;
constexpr int STAGE_BYTES = 32768;
#define KV_STAGGER 300
#define KV_GAP 150

constexpr uint32_t SM_X = 0;
constexpr uint32_t SM_RING = 131072;
constexpr uint32_t SM_MISC = SM_RING + 3 * STAGE_BYTES;
constexpr uint32_t SM_BARS = SM_MISC;
constexpr uint32_t SM_EPOCH = SM_MISC + 248;
constexpr uint32_t SM_STATS = SM_MISC + 256;
constexpr uint32_t SM_TOTAL = SM_STATS + 1024;
static_assert(SM_TOTAL <= 232448, "smem");
constexpr uint32_t SM_CVX = 0;
constexpr uint32_t SM_CVH = 65536;
constexpr uint32_t SM_YT = 32768;
constexpr uint32_t SM_XE = 98304;

constexpr int B_FULL = 0, B_EMPTY = 5, B_XFULL = 10, B_CONV = 14, B_YT = 15, B_XR = 16, B_G1DONE = 17, B_HD = 18, B_HRDY = 22,
              B_XFREE = 24, B_YST = 25, B_KVLD = 26, B_COUNT = 27;
static_assert(B_COUNT * 8 <= 248, "barrier space");

__device__ __align__(128) uint32_t g_h[16 * 56 * 2048];
__device__ __align__(128) __nv_bfloat16 g_kvT[DM * SEQ];
__device__ __align__(128) __nv_bfloat16 g_yT[DM * SEQ];
__device__ unsigned g_launch[NCTA];
__device__ unsigned g_cnt_kv[32];
__device__ unsigned g_cnt_y[4 * 32];
__device__ unsigned g_flag_h[16 * 2 * 8];

#define PROF(idx)
#define PROF2(a, idx)
#define PROFW(idx, w)

struct Params {
    CUtensorMap tm_x, tm_gA, tm_gB, tm_uA, tm_uB, tm_w2, tm_yT, tm_out, tm_xe;
    const __nv_bfloat16 *q, *k, *v, *shift_k, *ssm_k, *ssm_D, *wg, *wu, *wd;
};

__device__ __forceinline__ void wgmma_rs_n32(float (&d)[16], uint32_t a0, uint32_t a1, uint32_t a2, uint32_t a3, uint64_t db, int sc) {
  asm volatile("{\n.reg .pred p;\nsetp.ne.b32 p, %21, 0;\n"
    "wgmma.mma_async.sync.aligned.m64n32k16.f32.bf16.bf16 {%0,%1,%2,%3,%4,%5,%6,%7,%8,%9,%10,%11,%12,%13,%14,%15}, {%16,%17,%18,%19}, %20, p, 1, 1, 0;\n}\n"
    : "+f"(d[0]),"+f"(d[1]),"+f"(d[2]),"+f"(d[3]),"+f"(d[4]),"+f"(d[5]),"+f"(d[6]),"+f"(d[7]),"+f"(d[8]),"+f"(d[9]),"+f"(d[10]),"+f"(d[11]),"+f"(d[12]),"+f"(d[13]),"+f"(d[14]),"+f"(d[15])
    : "r"(a0),"r"(a1),"r"(a2),"r"(a3),"l"(db),"r"(sc));
}
__device__ __forceinline__ void wgmma_rs_n128_tb(float (&d)[64], uint32_t a0, uint32_t a1, uint32_t a2, uint32_t a3, uint64_t db, int sc) {
  asm volatile("{\n.reg .pred p;\nsetp.ne.b32 p, %69, 0;\n"
    "wgmma.mma_async.sync.aligned.m64n128k16.f32.bf16.bf16 {%0,%1,%2,%3,%4,%5,%6,%7,%8,%9,%10,%11,%12,%13,%14,%15,%16,%17,%18,%19,%20,%21,%22,%23,%24,%25,%26,%27,%28,%29,%30,%31,%32,%33,%34,%35,%36,%37,%38,%39,%40,%41,%42,%43,%44,%45,%46,%47,%48,%49,%50,%51,%52,%53,%54,%55,%56,%57,%58,%59,%60,%61,%62,%63}, {%64,%65,%66,%67}, %68, p, 1, 1, 1;\n}\n"
    : "+f"(d[0]),"+f"(d[1]),"+f"(d[2]),"+f"(d[3]),"+f"(d[4]),"+f"(d[5]),"+f"(d[6]),"+f"(d[7]),"+f"(d[8]),"+f"(d[9]),"+f"(d[10]),"+f"(d[11]),"+f"(d[12]),"+f"(d[13]),"+f"(d[14]),"+f"(d[15]),"+f"(d[16]),"+f"(d[17]),"+f"(d[18]),"+f"(d[19]),"+f"(d[20]),"+f"(d[21]),"+f"(d[22]),"+f"(d[23]),"+f"(d[24]),"+f"(d[25]),"+f"(d[26]),"+f"(d[27]),"+f"(d[28]),"+f"(d[29]),"+f"(d[30]),"+f"(d[31]),"+f"(d[32]),"+f"(d[33]),"+f"(d[34]),"+f"(d[35]),"+f"(d[36]),"+f"(d[37]),"+f"(d[38]),"+f"(d[39]),"+f"(d[40]),"+f"(d[41]),"+f"(d[42]),"+f"(d[43]),"+f"(d[44]),"+f"(d[45]),"+f"(d[46]),"+f"(d[47]),"+f"(d[48]),"+f"(d[49]),"+f"(d[50]),"+f"(d[51]),"+f"(d[52]),"+f"(d[53]),"+f"(d[54]),"+f"(d[55]),"+f"(d[56]),"+f"(d[57]),"+f"(d[58]),"+f"(d[59]),"+f"(d[60]),"+f"(d[61]),"+f"(d[62]),"+f"(d[63])
    : "r"(a0),"r"(a1),"r"(a2),"r"(a3),"l"(db),"r"(sc));
}
__device__ __forceinline__ void wgmma_ss_n256_tb(float (&d)[128], uint64_t da, uint64_t db, int sc) {
  asm volatile("{\n.reg .pred p;\nsetp.ne.b32 p, %130, 0;\n"
    "wgmma.mma_async.sync.aligned.m64n256k16.f32.bf16.bf16 {%0,%1,%2,%3,%4,%5,%6,%7,%8,%9,%10,%11,%12,%13,%14,%15,%16,%17,%18,%19,%20,%21,%22,%23,%24,%25,%26,%27,%28,%29,%30,%31,%32,%33,%34,%35,%36,%37,%38,%39,%40,%41,%42,%43,%44,%45,%46,%47,%48,%49,%50,%51,%52,%53,%54,%55,%56,%57,%58,%59,%60,%61,%62,%63,%64,%65,%66,%67,%68,%69,%70,%71,%72,%73,%74,%75,%76,%77,%78,%79,%80,%81,%82,%83,%84,%85,%86,%87,%88,%89,%90,%91,%92,%93,%94,%95,%96,%97,%98,%99,%100,%101,%102,%103,%104,%105,%106,%107,%108,%109,%110,%111,%112,%113,%114,%115,%116,%117,%118,%119,%120,%121,%122,%123,%124,%125,%126,%127}, %128, %129, p, 1, 1, 0, 1;\n}\n"
    : "+f"(d[0]),"+f"(d[1]),"+f"(d[2]),"+f"(d[3]),"+f"(d[4]),"+f"(d[5]),"+f"(d[6]),"+f"(d[7]),"+f"(d[8]),"+f"(d[9]),"+f"(d[10]),"+f"(d[11]),"+f"(d[12]),"+f"(d[13]),"+f"(d[14]),"+f"(d[15]),"+f"(d[16]),"+f"(d[17]),"+f"(d[18]),"+f"(d[19]),"+f"(d[20]),"+f"(d[21]),"+f"(d[22]),"+f"(d[23]),"+f"(d[24]),"+f"(d[25]),"+f"(d[26]),"+f"(d[27]),"+f"(d[28]),"+f"(d[29]),"+f"(d[30]),"+f"(d[31]),"+f"(d[32]),"+f"(d[33]),"+f"(d[34]),"+f"(d[35]),"+f"(d[36]),"+f"(d[37]),"+f"(d[38]),"+f"(d[39]),"+f"(d[40]),"+f"(d[41]),"+f"(d[42]),"+f"(d[43]),"+f"(d[44]),"+f"(d[45]),"+f"(d[46]),"+f"(d[47]),"+f"(d[48]),"+f"(d[49]),"+f"(d[50]),"+f"(d[51]),"+f"(d[52]),"+f"(d[53]),"+f"(d[54]),"+f"(d[55]),"+f"(d[56]),"+f"(d[57]),"+f"(d[58]),"+f"(d[59]),"+f"(d[60]),"+f"(d[61]),"+f"(d[62]),"+f"(d[63]),"+f"(d[64]),"+f"(d[65]),"+f"(d[66]),"+f"(d[67]),"+f"(d[68]),"+f"(d[69]),"+f"(d[70]),"+f"(d[71]),"+f"(d[72]),"+f"(d[73]),"+f"(d[74]),"+f"(d[75]),"+f"(d[76]),"+f"(d[77]),"+f"(d[78]),"+f"(d[79]),"+f"(d[80]),"+f"(d[81]),"+f"(d[82]),"+f"(d[83]),"+f"(d[84]),"+f"(d[85]),"+f"(d[86]),"+f"(d[87]),"+f"(d[88]),"+f"(d[89]),"+f"(d[90]),"+f"(d[91]),"+f"(d[92]),"+f"(d[93]),"+f"(d[94]),"+f"(d[95]),"+f"(d[96]),"+f"(d[97]),"+f"(d[98]),"+f"(d[99]),"+f"(d[100]),"+f"(d[101]),"+f"(d[102]),"+f"(d[103]),"+f"(d[104]),"+f"(d[105]),"+f"(d[106]),"+f"(d[107]),"+f"(d[108]),"+f"(d[109]),"+f"(d[110]),"+f"(d[111]),"+f"(d[112]),"+f"(d[113]),"+f"(d[114]),"+f"(d[115]),"+f"(d[116]),"+f"(d[117]),"+f"(d[118]),"+f"(d[119]),"+f"(d[120]),"+f"(d[121]),"+f"(d[122]),"+f"(d[123]),"+f"(d[124]),"+f"(d[125]),"+f"(d[126]),"+f"(d[127])
    : "l"(da),"l"(db),"r"(sc));
}
__device__ __forceinline__ void wgmma_ss_n192_tb(float (&d)[96], uint64_t da, uint64_t db, int sc) {
  asm volatile("{\n.reg .pred p;\nsetp.ne.b32 p, %98, 0;\n"
    "wgmma.mma_async.sync.aligned.m64n192k16.f32.bf16.bf16 {%0,%1,%2,%3,%4,%5,%6,%7,%8,%9,%10,%11,%12,%13,%14,%15,%16,%17,%18,%19,%20,%21,%22,%23,%24,%25,%26,%27,%28,%29,%30,%31,%32,%33,%34,%35,%36,%37,%38,%39,%40,%41,%42,%43,%44,%45,%46,%47,%48,%49,%50,%51,%52,%53,%54,%55,%56,%57,%58,%59,%60,%61,%62,%63,%64,%65,%66,%67,%68,%69,%70,%71,%72,%73,%74,%75,%76,%77,%78,%79,%80,%81,%82,%83,%84,%85,%86,%87,%88,%89,%90,%91,%92,%93,%94,%95}, %96, %97, p, 1, 1, 0, 1;\n}\n"
    : "+f"(d[0]),"+f"(d[1]),"+f"(d[2]),"+f"(d[3]),"+f"(d[4]),"+f"(d[5]),"+f"(d[6]),"+f"(d[7]),"+f"(d[8]),"+f"(d[9]),"+f"(d[10]),"+f"(d[11]),"+f"(d[12]),"+f"(d[13]),"+f"(d[14]),"+f"(d[15]),"+f"(d[16]),"+f"(d[17]),"+f"(d[18]),"+f"(d[19]),"+f"(d[20]),"+f"(d[21]),"+f"(d[22]),"+f"(d[23]),"+f"(d[24]),"+f"(d[25]),"+f"(d[26]),"+f"(d[27]),"+f"(d[28]),"+f"(d[29]),"+f"(d[30]),"+f"(d[31]),"+f"(d[32]),"+f"(d[33]),"+f"(d[34]),"+f"(d[35]),"+f"(d[36]),"+f"(d[37]),"+f"(d[38]),"+f"(d[39]),"+f"(d[40]),"+f"(d[41]),"+f"(d[42]),"+f"(d[43]),"+f"(d[44]),"+f"(d[45]),"+f"(d[46]),"+f"(d[47]),"+f"(d[48]),"+f"(d[49]),"+f"(d[50]),"+f"(d[51]),"+f"(d[52]),"+f"(d[53]),"+f"(d[54]),"+f"(d[55]),"+f"(d[56]),"+f"(d[57]),"+f"(d[58]),"+f"(d[59]),"+f"(d[60]),"+f"(d[61]),"+f"(d[62]),"+f"(d[63]),"+f"(d[64]),"+f"(d[65]),"+f"(d[66]),"+f"(d[67]),"+f"(d[68]),"+f"(d[69]),"+f"(d[70]),"+f"(d[71]),"+f"(d[72]),"+f"(d[73]),"+f"(d[74]),"+f"(d[75]),"+f"(d[76]),"+f"(d[77]),"+f"(d[78]),"+f"(d[79]),"+f"(d[80]),"+f"(d[81]),"+f"(d[82]),"+f"(d[83]),"+f"(d[84]),"+f"(d[85]),"+f"(d[86]),"+f"(d[87]),"+f"(d[88]),"+f"(d[89]),"+f"(d[90]),"+f"(d[91]),"+f"(d[92]),"+f"(d[93]),"+f"(d[94]),"+f"(d[95])
    : "l"(da),"l"(db),"r"(sc));
}

__device__ __forceinline__ uint32_t smem_u32(const void* p) { return (uint32_t)__cvta_generic_to_shared(p); }
__device__ __forceinline__ void mbar_init(uint32_t bar, uint32_t cnt) { asm volatile("mbarrier.init.shared::cta.b64 [%0], %1;" :: "r"(bar), "r"(cnt)); }
__device__ __forceinline__ void mbar_expect_tx(uint32_t bar, uint32_t bytes) { asm volatile("mbarrier.arrive.expect_tx.shared::cta.b64 _, [%0], %1;" :: "r"(bar), "r"(bytes) : "memory"); }
__device__ __forceinline__ void mbar_arrive(uint32_t bar) { asm volatile("mbarrier.arrive.shared::cta.b64 _, [%0];" :: "r"(bar) : "memory"); }
__device__ __forceinline__ void mbar_arrive_cluster(uint32_t cbar, uint32_t cnt) { asm volatile("mbarrier.arrive.shared::cluster.b64 _, [%0], %1;" :: "r"(cbar), "r"(cnt) : "memory"); }
__device__ __forceinline__ uint32_t mapa(uint32_t a, uint32_t rank) { uint32_t r; asm volatile("mapa.shared::cluster.u32 %0, %1, %2;" : "=r"(r) : "r"(a), "r"(rank)); return r; }
__device__ __forceinline__ void mbar_wait(uint32_t bar, uint32_t parity) {
    uint32_t ok; uint32_t n = 0;
    do {
        asm volatile("{\n.reg .pred p;\nmbarrier.try_wait.parity.shared::cta.b64 p, [%1], %2;\nselp.u32 %0, 1, 0, p;\n}" : "=r"(ok) : "r"(bar), "r"(parity) : "memory");
    } while (!ok && ++n < (1u << 17));
}
__device__ __forceinline__ void pace_wait(uint32_t a, uint32_t target) {
    uint32_t v, n = 0;
    do {
        asm volatile("ld.volatile.shared.u32 %0, [%1];" : "=r"(v) : "r"(a) : "memory");
        if (v < target) __nanosleep(150);
    } while (v < target && ++n < (1u << 14));
}
__device__ __forceinline__ void flag_wait(const unsigned* p, unsigned target) {
    unsigned v; uint32_t n = 0;
    while (true) {
        asm volatile("ld.acquire.gpu.global.u32 %0, [%1];" : "=r"(v) : "l"(p) : "memory");
        if ((int)(v - target) >= 0 || ++n >= (1u << 17)) break;
        __nanosleep(100);
    }
}
__device__ __forceinline__ void flag_add(unsigned* p) {
    asm volatile("fence.acq_rel.gpu;\nred.relaxed.gpu.global.add.u32 [%0], 1;" :: "l"(p) : "memory");
}
__device__ __forceinline__ uint64_t make_desc(uint32_t addr, uint32_t lbo, uint32_t sbo, uint32_t swz) {
    return (uint64_t)((addr & 0x3FFFF) >> 4) | ((uint64_t)((lbo & 0x3FFFF) >> 4) << 16) | ((uint64_t)((sbo & 0x3FFFF) >> 4) << 32) | ((uint64_t)swz << 62);
}
__device__ __forceinline__ uint64_t desc_add(uint64_t d, uint32_t off16) {
    return (d & 0xFFFFFFFF00000000ull) | (uint64_t)((uint32_t)d + off16);
}
__device__ __forceinline__ void tma2d(uint32_t dst, const CUtensorMap* tm, int c0, int c1, uint32_t bar) {
    asm volatile("cp.async.bulk.tensor.2d.shared::cluster.global.mbarrier::complete_tx::bytes [%0], [%1, {%3, %4}], [%2];"
        :: "r"(dst), "l"((uint64_t)tm), "r"(bar), "r"(c0), "r"(c1) : "memory");
}
__device__ __forceinline__ void tma3d(uint32_t dst, const CUtensorMap* tm, int c0, int c1, int c2, uint32_t bar) {
    asm volatile("cp.async.bulk.tensor.3d.shared::cluster.global.mbarrier::complete_tx::bytes [%0], [%1, {%3, %4, %5}], [%2];"
        :: "r"(dst), "l"((uint64_t)tm), "r"(bar), "r"(c0), "r"(c1), "r"(c2) : "memory");
}
__device__ __forceinline__ void tma3d_mc(uint32_t dst, const CUtensorMap* tm, int c0, int c1, int c2, uint32_t bar) {
    asm volatile("cp.async.bulk.tensor.3d.shared::cluster.global.mbarrier::complete_tx::bytes.multicast::cluster [%0], [%1, {%3, %4, %5}], [%2], %6;"
        :: "r"(dst), "l"((uint64_t)tm), "r"(bar), "r"(c0), "r"(c1), "r"(c2), "h"((uint16_t)3) : "memory");
}
__device__ __forceinline__ void bulk_g2s(uint32_t dst, const void* src, uint32_t bytes, uint32_t bar) {
    asm volatile("cp.async.bulk.shared::cluster.global.mbarrier::complete_tx::bytes [%0], [%1], %2, [%3];"
        :: "r"(dst), "l"(src), "r"(bytes), "r"(bar) : "memory");
}
__device__ __forceinline__ void bulk_s2g(void* dst, uint32_t src, uint32_t bytes) {
    asm volatile("cp.async.bulk.global.shared::cta.bulk_group [%0], [%1], %2;" :: "l"(dst), "r"(src), "r"(bytes) : "memory");
}
__device__ __forceinline__ void tma2d_store(const CUtensorMap* tm, int c0, int c1, uint32_t src) {
    asm volatile("cp.async.bulk.tensor.2d.global.shared::cta.bulk_group [%0, {%2, %3}], [%1];"
        :: "l"((uint64_t)tm), "r"(src), "r"(c0), "r"(c1) : "memory");
}
__device__ __forceinline__ void l2_prefetch(const void* p, uint32_t bytes) {
    asm volatile("cp.async.bulk.prefetch.L2.global [%0], %1;" :: "l"(p), "r"(bytes) : "memory");
}
__device__ __forceinline__ void tmap_prefetch(const CUtensorMap* tm) { asm volatile("prefetch.tensormap [%0];" :: "l"((uint64_t)tm) : "memory"); }
__device__ __forceinline__ uint32_t lds32(uint32_t a) { uint32_t v; asm volatile("ld.shared.u32 %0, [%1];" : "=r"(v) : "r"(a)); return v; }
__device__ __forceinline__ uint2 lds64(uint32_t a) { uint2 v; asm volatile("ld.shared.v2.u32 {%0,%1}, [%2];" : "=r"(v.x), "=r"(v.y) : "r"(a)); return v; }
__device__ __forceinline__ uint4 lds128(uint32_t a) { uint4 v; asm volatile("ld.shared.v4.u32 {%0,%1,%2,%3}, [%4];" : "=r"(v.x), "=r"(v.y), "=r"(v.z), "=r"(v.w) : "r"(a)); return v; }
__device__ __forceinline__ float2 lds64f(uint32_t a) { float2 v; asm volatile("ld.shared.v2.f32 {%0,%1}, [%2];" : "=f"(v.x), "=f"(v.y) : "r"(a)); return v; }
__device__ __forceinline__ void sts32(uint32_t a, uint32_t v) { asm volatile("st.shared.u32 [%0], %1;" :: "r"(a), "r"(v) : "memory"); }
__device__ __forceinline__ void sts128(uint32_t a, uint4 v) { asm volatile("st.shared.v4.u32 [%0], {%1,%2,%3,%4};" :: "r"(a), "r"(v.x), "r"(v.y), "r"(v.z), "r"(v.w) : "memory"); }
__device__ __forceinline__ uint4 ldg_cg128(const void* p) { uint4 v; asm volatile("ld.global.cg.v4.u32 {%0,%1,%2,%3}, [%4];" : "=r"(v.x), "=r"(v.y), "=r"(v.z), "=r"(v.w) : "l"(p)); return v; }
__device__ __forceinline__ uint4 ldg_nc128(const void* p) { uint4 v; asm volatile("ld.global.nc.L1::no_allocate.v4.u32 {%0,%1,%2,%3}, [%4];" : "=r"(v.x), "=r"(v.y), "=r"(v.z), "=r"(v.w) : "l"(p)); return v; }
__device__ __forceinline__ uint32_t ldg_nc32(const void* p) { uint32_t v; asm volatile("ld.global.nc.u32 %0, [%1];" : "=r"(v) : "l"(p)); return v; }
__device__ __forceinline__ uint2 ldg_nc64(const void* p) { uint2 v; asm volatile("ld.global.nc.L1::no_allocate.v2.u32 {%0,%1}, [%2];" : "=r"(v.x), "=r"(v.y) : "l"(p)); return v; }
#define WG_FENCE() asm volatile("wgmma.fence.sync.aligned;\n" ::: "memory")
#define WG_COMMIT() asm volatile("wgmma.commit_group.sync.aligned;\n" ::: "memory")
template<int N> __device__ __forceinline__ void wg_wait() { asm volatile("wgmma.wait_group.sync.aligned %0;\n" :: "n"(N) : "memory"); }
__device__ __forceinline__ bool elect_one() {
    uint32_t pr;
    asm volatile("{\n.reg .pred p;\nelect.sync _|p, 0xffffffff;\nselp.u32 %0, 1, 0, p;\n}" : "=r"(pr));
    return pr != 0;
}
__device__ __forceinline__ void named_bar(int id, int n) { asm volatile("bar.sync %0, %1;" :: "r"(id), "r"(n) : "memory"); }

__device__ __forceinline__ float bf_lo(uint32_t u) { return __uint_as_float(u << 16); }
__device__ __forceinline__ float bf_hi(uint32_t u) { return __uint_as_float(u & 0xFFFF0000u); }
__device__ __forceinline__ uint32_t pack_bf(float lo, float hi) { uint32_t r; asm("cvt.rn.bf16x2.f32 %0, %1, %2;" : "=r"(r) : "f"(hi), "f"(lo)); return r; }
__device__ __forceinline__ float bf_round(float x) { return __bfloat162float(__float2bfloat16_rn(x)); }
__device__ __forceinline__ uint32_t bmul2(uint32_t a, uint32_t b) { uint32_t r; asm("mul.rn.bf16x2 %0, %1, %2;" : "=r"(r) : "r"(a), "r"(b)); return r; }
__device__ __forceinline__ uint32_t badd2(uint32_t a, uint32_t b) { uint32_t r; asm("add.rn.bf16x2 %0, %1, %2;" : "=r"(r) : "r"(a), "r"(b)); return r; }
__device__ __forceinline__ uint32_t bsub2(uint32_t a, uint32_t b) { uint32_t r; asm("sub.rn.bf16x2 %0, %1, %2;" : "=r"(r) : "r"(a), "r"(b)); return r; }
__device__ __forceinline__ void mma16816(float (&d)[4], uint32_t a0, uint32_t a1, uint32_t a2, uint32_t a3, uint2 b) {
    asm volatile("mma.sync.aligned.m16n8k16.row.col.f32.bf16.bf16.f32 {%0,%1,%2,%3}, {%4,%5,%6,%7}, {%8,%9}, {%0,%1,%2,%3};\n"
        : "+f"(d[0]), "+f"(d[1]), "+f"(d[2]), "+f"(d[3]) : "r"(a0), "r"(a1), "r"(a2), "r"(a3), "r"(b.x), "r"(b.y));
}

template<int HS> __device__ __forceinline__ void xreduce(float (&v)[8], int lane) {
    const int up = lane & HS;
    #pragma unroll
    for (int e = 0; e < HS; e++) {
        float keep, send;
        asm("{\n.reg .pred p;\nsetp.ne.b32 p, %4, 0;\nselp.f32 %0, %3, %2, p;\nselp.f32 %1, %2, %3, p;\n}"
            : "=f"(keep), "=f"(send) : "f"(v[e]), "f"(v[e + HS]), "r"(up));
        v[e] = keep + __shfl_xor_sync(0xffffffffu, send, HS);
    }
}

__device__ __forceinline__ int blk_f0(int s) {
    if (s < 32) return 32 * (14 * (s >> 3) + 8 * ((s >> 2) & 1) + (s & 3));
    const int s2 = s - 32, c6 = (s2 * 11) >> 6, t = s2 - 6 * c6;
    return 32 * (14 * c6 + (t < 4 ? 4 + t : 8 + t));
}
__device__ __forceinline__ int next_st2(int s) { return (0x14023 >> (4 * s)) & 7; }
__device__ __forceinline__ uint32_t stage_off_rt(int s) { return s < 3 ? SM_RING + s * STAGE_BYTES : (uint32_t)(s - 3) * 65536; }

template<int NB, bool passA>
__device__ __forceinline__ void gemm1_pass(uint32_t sb, int wgi, int warp4, int lane, int& st, uint32_t& fph, uint32_t e_cl,
                                           int rb64, int ks0, bool convCTA) {
    float acc[NB * 32];
    const uint64_t descA0 = make_desc(sb + SM_X + wgi * 65536, 16, 1024, 1);
    const uint64_t descB0 = make_desc(sb + SM_RING, 4096, 512, 2);
    int prev = 0;
    #pragma unroll 1
    for (int sl = 0; sl < 8; sl++) {
        if (warp4 == 0 && wgi == 0) PROF2(2, sl + (passA ? 0 : 8));
        mbar_wait(sb + SM_BARS + (B_FULL + st) * 8, (fph >> st) & 1);
        fph ^= 1u << st;
        if (sl == 0 && warp4 == 0) PROF(2 + wgi * 8 + (passA ? 0 : 3));
        if (warp4 == 0 && wgi == 0) PROF2(1, sl + (passA ? 0 : 8));
        const uint64_t da = desc_add(descA0, sl * 512), db = desc_add(descB0, st * 2048);
        WG_FENCE();
        #pragma unroll
        for (int kk = 0; kk < 4; kk++) {
            int sc = (sl | kk) ? 1 : 0;
            if constexpr (NB == 4) wgmma_ss_n256_tb(acc, da + kk * 2, db + kk * 64, sc); else wgmma_ss_n128_tb(acc, da + kk * 2, db + kk * 64, sc);
        }
        WG_COMMIT();
        wg_wait<1>();
        if (warp4 == 0 && wgi == 0) PROF2(3, sl + (passA ? 0 : 8));
        if (lane < 2 && sl && (passA || !convCTA || sl < 6)) mbar_arrive_cluster(e_cl + prev * 8, 1);
        if (!passA) {
            if (sl == 4) {
                if (convCTA) { if (lane == 0) mbar_arrive(sb + SM_BARS + B_XFREE * 8); }
                else if (lane < 4) mbar_arrive_cluster(e_cl + (3 + (lane >> 1)) * 8, 1);
            }
        }
        prev = st;
        st = (st == 2) ? 0 : st + 1;
    }
    wg_wait<0>();
    if (lane < 2 && (passA || !convCTA)) mbar_arrive_cluster(e_cl + prev * 8, 1);
    if (!passA && lane == 0) mbar_arrive(sb + SM_BARS + B_G1DONE * 8);
    if (warp4 == 0) PROF(3 + wgi * 8 + (passA ? 0 : 3));
    const int g = lane >> 2;
    const int r0 = wgi * 64 + warp4 * 16 + g;
    const float s0 = __uint_as_float(lds32(sb + SM_STATS + r0 * 8 + 4)), s1 = __uint_as_float(lds32(sb + SM_STATS + (r0 + 8) * 8 + 4));
    uint32_t* dst = g_h + (size_t)((rb64 >> 1) * 56 + ks0) * 2048 + wgi * 1024 + warp4 * 128 + lane;
    #pragma unroll
    for (int kk = 0; kk < NB * 2; kk++) {
        uint32_t h[4];
        #pragma unroll
        for (int tt = 0; tt < 2; tt++) {
            const int t = 2 * kk + tt;
            const float* ag = &acc[4 * t];
            const float* au = &acc[NB * 16 + 4 * t];
            h[2 * tt] = bmul2(pack_bf(ag[0] * s0, ag[1] * s0), pack_bf(au[0] * s0, au[1] * s0));
            h[2 * tt + 1] = bmul2(pack_bf(ag[2] * s1, ag[3] * s1), pack_bf(au[2] * s1, au[3] * s1));
        }
        uint32_t* d2 = dst + (kk >> 1) * 2048 + (kk & 1) * 512;
        d2[0] = h[0]; d2[64] = h[1]; d2[32] = h[2]; d2[96] = h[3];
    }
    __syncwarp();
    if (lane == 0) mbar_arrive(sb + SM_BARS + (B_HD + wgi * 2 + (passA ? 0 : 1)) * 8);
    if (warp4 == 0) PROF(4 + wgi * 8 + (passA ? 0 : 3));
}

__global__ void __cluster_dims__(2, 1, 1) __launch_bounds__(NTHREADS, 1)
fused_kernel(const __grid_constant__ Params p) {
    extern __shared__ __align__(1024) uint8_t smem_raw[];
    const uint32_t sb = smem_u32(smem_raw);
    const int tid = threadIdx.x, warp = tid >> 5, lane = tid & 31;
    const int b = blockIdx.x;
    const int rank = b & 1;
    const int j = (b >> 1) & 7;
    const int i = ((b >> 4) << 1) | rank;
    const int cb = j >> 1;
    const bool convCTA = j & 1;
    const int cidx = 4 * i + cb;

    if (tid == 256) {
        mbar_init(sb + SM_BARS + B_XFULL * 8, 1);
        mbar_init(sb + SM_BARS + (B_XFULL + 1) * 8, 1);
        asm volatile("fence.proxy.async.shared::cta;" ::: "memory");
        mbar_expect_tx(sb + SM_BARS + B_XFULL * 8, 65536);
        tma3d(sb + SM_X, &p.tm_x, 0, 128 * i, 0, sb + SM_BARS + B_XFULL * 8);
        mbar_expect_tx(sb + SM_BARS + (B_XFULL + 1) * 8, 65536);
        tma3d(sb + SM_X + 65536, &p.tm_x, 0, 128 * i + 64, 0, sb + SM_BARS + (B_XFULL + 1) * 8);
    }
    if (tid == 288) {
        for (int s = 0; s < 5; s++) { mbar_init(sb + SM_BARS + (B_FULL + s) * 8, 1); mbar_init(sb + SM_BARS + (B_EMPTY + s) * 8, 16); }
        mbar_init(sb + SM_BARS + B_CONV * 8, 1);
        mbar_init(sb + SM_BARS + B_YT * 8, 1);
        mbar_init(sb + SM_BARS + B_XR * 8, 1);
        mbar_init(sb + SM_BARS + B_G1DONE * 8, 8);
        mbar_init(sb + SM_BARS + B_XFREE * 8, 8);
        mbar_init(sb + SM_BARS + B_YST * 8, 8);
        mbar_init(sb + SM_BARS + B_KVLD * 8, 2);
        for (int s = 0; s < 4; s++) mbar_init(sb + SM_BARS + (B_HD + s) * 8, 4);
        for (int s = 0; s < 2; s++) mbar_init(sb + SM_BARS + (B_HRDY + s) * 8, 1);
        asm volatile("fence.mbarrier_init.release.cluster;" ::: "memory");
        asm volatile("fence.proxy.async.shared::cta;" ::: "memory");
    }
    __syncwarp();
    asm volatile("barrier.cluster.arrive.relaxed.aligned;\n" ::: "memory");
    asm volatile("barrier.cluster.wait.aligned;\n" ::: "memory");
    PROFW(1, 0);

    if (warp < 8) {
        asm volatile("setmaxnreg.inc.sync.aligned.u32 200;");
        const int wgi = warp >> 2, warp4 = warp & 3;
        const int g = lane >> 2, c = lane & 3;
        const uint32_t e_cl = mapa(sb + SM_BARS + B_EMPTY * 8, lane & 1);
        {
            const int lr16 = (lane & 7) + ((lane >> 3) & 1) * 8;
            const uint32_t xa = sb + SM_X + wgi * 65536 + (warp4 * 16 + lr16) * 128;
            uint32_t xf[32][4];
            float aS[4][4], aQ0[4][4], aQ1[4][4];
            #pragma unroll
            for (int e = 0; e < 4; e++) {
                #pragma unroll
                for (int f = 0; f < 4; f++) { aS[e][f] = 0.f; aQ0[e][f] = 0.f; aQ1[e][f] = 0.f; }
            }
            mbar_wait(sb + SM_BARS + (B_XFULL + wgi) * 8, 0);
            PROFW(16, 0); PROFW(18, 4);
            #pragma unroll
            for (int ks = 0; ks < 32; ks++) {
                const uint32_t a = xa + (ks >> 2) * 8192 + (((2 * (ks & 3) + (lane >> 4)) ^ (lane & 7)) << 4);
                asm volatile("ldmatrix.sync.aligned.m8n8.x4.shared.b16 {%0,%1,%2,%3}, [%4];"
                    : "=r"(xf[ks][0]), "=r"(xf[ks][1]), "=r"(xf[ks][2]), "=r"(xf[ks][3]) : "r"(a) : "memory");
            }
            #pragma unroll
            for (int ks = 0; ks < 32; ks++) {
                mma16816(aS[ks & 3], xf[ks][0], xf[ks][1], xf[ks][2], xf[ks][3], make_uint2(0x3F803F80u, 0x3F803F80u));
                mma16816(aQ0[ks & 3], xf[ks][0], xf[ks][1], xf[ks][2], xf[ks][3], make_uint2(xf[ks][0], xf[ks][2]));
                mma16816(aQ1[ks & 3], xf[ks][0], xf[ks][1], xf[ks][2], xf[ks][3], make_uint2(xf[ks][1], xf[ks][3]));
            }
            const float mean0 = ((aS[0][0] + aS[1][0]) + (aS[2][0] + aS[3][0])) * (1.0f / DM);
            const float mean1 = ((aS[0][2] + aS[1][2]) + (aS[2][2] + aS[3][2])) * (1.0f / DM);
            const uint32_t m0 = pack_bf(mean0, mean0), m1 = pack_bf(mean1, mean1);
            #pragma unroll
            for (int ks = 0; ks < 32; ks++) {
                const uint32_t a = xa + (ks >> 2) * 8192 + (((2 * (ks & 3) + (lane >> 4)) ^ (lane & 7)) << 4);
                asm volatile("stmatrix.sync.aligned.m8n8.x4.shared.b16 [%0], {%1,%2,%3,%4};"
                    :: "r"(a), "r"(bsub2(xf[ks][0], m0)), "r"(bsub2(xf[ks][1], m1)), "r"(bsub2(xf[ks][2], m0)), "r"(bsub2(xf[ks][3], m1)) : "memory");
            }
            if (c == (g >> 1)) {
                const float q0 = (g & 1) ? (aQ0[0][1] + aQ0[1][1]) + (aQ0[2][1] + aQ0[3][1]) : (aQ0[0][0] + aQ0[1][0]) + (aQ0[2][0] + aQ0[3][0]);
                const float q1 = (g & 1) ? (aQ1[0][3] + aQ1[1][3]) + (aQ1[2][3] + aQ1[3][3]) : (aQ1[0][2] + aQ1[1][2]) + (aQ1[2][2] + aQ1[3][2]);
                const float sd0 = bf_round(sqrtf(bf_round(bf_round(fmaxf(q0 * (1.0f / DM) - mean0 * mean0, 0.f)) + 1e-5f)));
                const float sd1 = bf_round(sqrtf(bf_round(bf_round(fmaxf(q1 * (1.0f / DM) - mean1 * mean1, 0.f)) + 1e-5f)));
                const uint32_t sa = sb + SM_STATS + (warp * 16 + g) * 8;
                sts32(sa, m0); sts32(sa + 4, __float_as_uint(1.0f / sd0));
                sts32(sa + 64, m1); sts32(sa + 68, __float_as_uint(1.0f / sd1));
            }
            asm volatile("fence.proxy.async.shared::cta;" ::: "memory");
            named_bar(3, 256);
            PROFW(19, 4);
            PROFW(17, 0);
        }
        int st = 0; uint32_t fph = 0;
        const int rb64 = 2 * i + wgi;
        gemm1_pass<4, true>(sb, wgi, warp4, lane, st, fph, e_cl, rb64, 4 * j, convCTA);
        if (convCTA) gemm1_pass<2, false>(sb, wgi, warp4, lane, st, fph, e_cl, rb64, 36 + 6 * cb, true);
        else gemm1_pass<4, false>(sb, wgi, warp4, lane, st, fph, e_cl, rb64, 32 + 6 * cb, false);

        if (convCTA) {
            const int gch = 8 * cidx + warp;
            const uint32_t xb = sb + SM_CVX + warp * 4096;
            const uint32_t hb = sb + SM_CVH + warp * 4096;
            const uint32_t dw = ((const unsigned short*)p.ssm_D)[gch];
            const uint32_t d2 = dw | (dw << 16);
            mbar_wait(sb + SM_BARS + B_CONV * 8, 0);
            PROFW(32, 4);
            float acc[16][4];
            #pragma unroll
            for (int jj = 0; jj < 16; jj++) { acc[jj][0] = 0.f; acc[jj][1] = 0.f; acc[jj][2] = 0.f; acc[jj][3] = 0.f; }
            uint2 bh[8], bl0[8], bl1[8];
            uint32_t xl = xb + g * 32 + c * 8;
            uint32_t hl = hb + (g + 2 * c - 8) * 4;
            #pragma unroll
            for (int d = 0; d < 8; d++) { bl0[d] = lds64(xl + d * 256); bh[d] = lds64(xl + (8 + d) * 256); }
            uint32_t w[6];
            w[0] = 0; w[1] = 0; w[2] = 0;
            if (g + 2 * c >= 8) w[0] = lds32(hl);
            if (g + 2 * c >= 7) w[1] = lds32(hl + 4);
            if (g + 2 * c >= 6) w[2] = lds32(hl + 8);
            w[3] = lds32(hl + 2048); w[4] = lds32(hl + 2052); w[5] = lds32(hl + 2056);
            auto conv_m0 = [&](int m0, uint2 (&bl)[8], uint2 (&bn)[8]) {
                xl -= 32;
                #pragma unroll
                for (int k = 0; k < 8; k++) {
                    const uint32_t a0 = w[1], a1 = __byte_perm(w[0], w[1], 0x5432), a2 = w[2], a3 = __byte_perm(w[1], w[2], 0x5432);
                    const uint32_t c0 = w[4], c1 = __byte_perm(w[3], w[4], 0x5432), c2 = w[5], c3 = __byte_perm(w[4], w[5], 0x5432);
                    const uint32_t nx = (k < 7) ? hl + (k + 1) * 256 : hl + 32;
                    w[0] = lds32(nx); w[1] = lds32(nx + 4); w[2] = lds32(nx + 8);
                    w[3] = lds32(nx + 2048); w[4] = lds32(nx + 2052); w[5] = lds32(nx + 2056);
                    if (k > 0) bn[k] = lds64(xl + k * 256);
                    else { bn[0] = make_uint2(0, 0); if (g > m0) bn[0] = lds64(xl); }
                    #pragma unroll
                    for (int jj = k; jj < 16; jj++) mma16816(acc[jj], a0, a1, a2, a3, (jj - k < 8) ? bl[(jj - k) & 7] : bh[(jj - k) & 7]);
                    bh[7 - k] = lds64(xl + (15 - k) * 256);
                    #pragma unroll
                    for (int jj = k + 8; jj < 16; jj++) mma16816(acc[jj], c0, c1, c2, c3, bl[jj - k - 8]);
                }
                hl += 32;
            };
            #pragma unroll 1
            for (int m0 = 0; m0 < 8; m0 += 2) {
                conv_m0(m0, bl0, bl1);
                conv_m0(m0 + 1, bl1, bl0);
                PROFW(34 + (m0 >> 1), 4);
            }
            PROFW(33, 4);
            const uint32_t kvl = xb + c * 64 + (7 - g) * 4;
            uint32_t* ydst = (uint32_t*)(g_yT + (size_t)gch * SEQ + 32 * c + 2 * g);
            uint32_t kk0[16], kk1[16];
            #pragma unroll
            for (int jj = 0; jj < 16; jj++) { kk0[jj] = lds32(kvl + jj * 256); kk1[jj] = lds32(kvl + jj * 256 + 32); }
            #pragma unroll
            for (int jj = 0; jj < 16; jj++) {
                ydst[jj * 64] = badd2(pack_bf(acc[jj][2], acc[jj][0]), bmul2(__byte_perm(kk0[jj], kk0[jj], 0x1032), d2));
                ydst[jj * 64 + 8] = badd2(pack_bf(acc[jj][3], acc[jj][1]), bmul2(__byte_perm(kk1[jj], kk1[jj], 0x1032), d2));
            }
            __syncwarp();
            PROFW(44, 4);
            if (lane == 0) mbar_arrive(sb + SM_BARS + B_YST * 8);
        } else {
            float acc[64];
            const uint64_t descB0 = make_desc(sb, 4096, 1024, 1);
            const uint64_t descA0 = make_desc(sb + 16384 + wgi * 4096, 128, 256, 0);
            int sg = 3, p0 = 0; uint32_t ph = 6;
            PROFW(20, 0);
            #pragma unroll 1
            for (int u = 0; u < 28; u++) {
                if (warp == 0 && !(u & 1)) PROF2(2, 16 + (u >> 1));
                mbar_wait(sb + SM_BARS + (B_FULL + sg) * 8, (ph >> sg) & 1);
                ph ^= 1u << sg;
                if (warp == 0 && !(u & 1)) PROF2(1, 16 + (u >> 1));
                const uint32_t o0 = stage_off_rt(sg) >> 4;
                const uint64_t da0 = desc_add(descA0, o0), db0 = desc_add(descB0, o0);
                WG_FENCE();
                #pragma unroll
                for (int kk = 0; kk < 4; kk++) wgmma_ss_n128_tb(acc, da0 + ((kk >> 1) * 512 + (kk & 1) * 128), db0 + ((kk >> 1) * 512 + (kk & 1) * 128), (u | kk) ? 1 : 0);
                WG_COMMIT();
                wg_wait<1>();
                if (warp == 0 && !(u & 1)) PROF2(3, 16 + (u >> 1));
                if (lane < 2 && u > 0 && u + 4 < 28) mbar_arrive_cluster(e_cl + p0 * 8, 1);
                p0 = sg;
                sg = next_st2(sg);
            }
            wg_wait<0>();
            PROFW(27, 0);
            mbar_wait(sb + SM_BARS + B_XR * 8, 0);
            const int r0 = wgi * 64 + warp4 * 16 + g;
            const float2 st0 = lds64f(sb + SM_STATS + r0 * 8), st1 = lds64f(sb + SM_STATS + (r0 + 8) * 8);
            const uint32_t m0 = __float_as_uint(st0.x), m1 = __float_as_uint(st1.x);
            const uint32_t xrow0 = sb + SM_XE + r0 * 128 + c * 4;
            const int mi = lane >> 3, lr = lane & 7;
            const uint32_t yaddr = sb + SM_YT + wgi * 16384 + ((mi >> 1) * 8 + lr) * 128 + (((2 * warp4 + (mi & 1)) ^ lr) << 4);
            uint32_t y[8][4], xv[16][2], nv[16][2], bv[16][2];
            #pragma unroll
            for (int t = 0; t < 16; t++) {
                const uint32_t off = (t >> 3) * 16384 + (((t & 7) ^ g) << 4);
                xv[t][0] = lds32(xrow0 + off); xv[t][1] = lds32(xrow0 + 1024 + off);
            }
            #pragma unroll
            for (int t = 0; t < 16; t++) {
                const uint32_t d0 = bsub2(xv[t][0], m0), d1 = bsub2(xv[t][1], m1);
                nv[t][0] = pack_bf(bf_lo(d0) * st0.y, bf_hi(d0) * st0.y); nv[t][1] = pack_bf(bf_lo(d1) * st1.y, bf_hi(d1) * st1.y);
                bv[t][0] = pack_bf(acc[4 * t], acc[4 * t + 1]); bv[t][1] = pack_bf(acc[4 * t + 2], acc[4 * t + 3]);
            }
            mbar_wait(sb + SM_BARS + B_YT * 8, 0);
            PROFW(28, 0);
            #pragma unroll
            for (int t2 = 0; t2 < 8; t2++)
                asm volatile("ldmatrix.sync.aligned.m8n8.x4.trans.shared.b16 {%0,%1,%2,%3}, [%4];"
                    : "=r"(y[t2][0]), "=r"(y[t2][1]), "=r"(y[t2][2]), "=r"(y[t2][3]) : "r"(yaddr + t2 * 2048) : "memory");
            #pragma unroll
            for (int t = 0; t < 16; t++) {
                const uint32_t off = (t >> 3) * 16384 + (((t & 7) ^ g) << 4);
                sts32(xrow0 + off, badd2(badd2(xv[t][0], bmul2(nv[t][0], y[t >> 1][2 * (t & 1)])), bv[t][0]));
                sts32(xrow0 + 1024 + off, badd2(badd2(xv[t][1], bmul2(nv[t][1], y[t >> 1][2 * (t & 1) + 1])), bv[t][1]));
            }
            asm volatile("fence.proxy.async.shared::cta;" ::: "memory");
            named_bar(1 + wgi, 128);
            if ((tid & 127) == 0) {
                tma2d_store(&p.tm_out, 128 * cb, 128 * i + 64 * wgi, sb + SM_XE + wgi * 8192);
                tma2d_store(&p.tm_out, 128 * cb + 64, 128 * i + 64 * wgi, sb + SM_XE + 16384 + wgi * 8192);
                asm volatile("cp.async.bulk.commit_group;" ::: "memory");
                asm volatile("cp.async.bulk.wait_group.read 0;" ::: "memory");
                PROFW(29, 0);
            }
        }
    } else {
        asm volatile("setmaxnreg.dec.sync.aligned.u32 104;");
        if (warp == 8) {
            int st = 0; uint32_t eph = 7;
            #pragma unroll 1
            for (int it = 0; it < 16; it++) {
                const int pass = it >> 3, sl = it & 7;
                const bool narrow = pass && convCTA;
                const int nb = narrow ? 2 : 4;
                const CUtensorMap* tm = narrow ? (rank ? &p.tm_uB : &p.tm_gB) : (rank ? &p.tm_uA : &p.tm_gA);
                mbar_wait(sb + SM_BARS + (B_EMPTY + st) * 8, (eph >> st) & 1);
                eph ^= 1u << st;
                if (it == 1) mbar_wait(sb + SM_BARS + B_XFULL * 8, 0);
                PROF2(0, it);
                if (elect_one()) {
                    mbar_expect_tx(sb + SM_BARS + (B_FULL + st) * 8, nb * 8192);
                    tma3d_mc(sb + SM_RING + st * STAGE_BYTES + rank * nb * 4096, tm, 0, sl * 64, 14 * cb + 8 * (j & 1) + 4 * pass, sb + SM_BARS + (B_FULL + st) * 8);
                }
                st = (st == 2) ? 0 : st + 1;
            }
            if (!convCTA) {
                st = 3;
                const int f0_lane = blk_f0(2 * lane + rank);
                #pragma unroll 1
                for (int u = 0; u < 28; u++) {
                    const uint32_t bar = sb + SM_BARS + (B_FULL + st) * 8;
                    const int f0 = __shfl_sync(0xffffffffu, f0_lane, u);
                    mbar_wait(sb + SM_BARS + (B_EMPTY + st) * 8, (eph >> st) & 1);
                    eph ^= 1u << st;
                    if ((u & 1) == 0) PROF2(0, 16 + (u >> 1));
                    if (elect_one()) {
                        mbar_expect_tx(bar, 32768);
                        tma3d_mc(sb + stage_off_rt(st) + rank * 8192, &p.tm_w2, 0, f0, 2 * cb, bar);
                    }
                    st = next_st2(st);
                }
                PROF(48);
            }
        } else if (warp < 11) {
            mbar_wait(sb + SM_BARS + (B_XFULL + 1) * 8, 0);
            {
                const int q = lane & 3;
                const int t0 = 32 * (b >> 1) + 8 * q;
                const int ch0 = 256 * (b & 1) + 16 * (warp - 9) + 2 * (lane >> 2);
                const uint32_t* kp = (const uint32_t*)(p.k + (size_t)t0 * DM + ch0);
                const uint32_t* vp = (const uint32_t*)(p.v + (size_t)t0 * DM + ch0);
                __nv_bfloat16* dst0 = g_kvT + (size_t)ch0 * SEQ + (t0 ^ 8);
                #pragma unroll 1
                for (int rnd = 0; rnd < 2; rnd++) {
                    uint32_t kr[4][11], vr[4][8]; uint4 skw[4];
                    #pragma unroll
                    for (int u = 0; u < 4; u++) {
                        const int co = (rnd * 4 + u) * 16;
                        skw[u] = ldg_nc128(p.shift_k + 4 * (ch0 + 2 * co));
                        #pragma unroll
                        for (int r = 0; r < 11; r++) kr[u][r] = (r >= 3 || t0 > 0) ? ldg_nc32(kp + co + (r - 3) * (DM / 2)) : 0u;
                        #pragma unroll
                        for (int r = 0; r < 8; r++) vr[u][r] = ldg_nc32(vp + co + r * (DM / 2));
                    }
                    #pragma unroll
                    for (int u = 0; u < 4; u++) {
                        const uint32_t s0 = __byte_perm(skw[u].x, skw[u].z, 0x5410), s1 = __byte_perm(skw[u].x, skw[u].z, 0x7632);
                        const uint32_t s2 = __byte_perm(skw[u].y, skw[u].w, 0x5410), s3 = __byte_perm(skw[u].y, skw[u].w, 0x7632);
                        #pragma unroll
                        for (int r = 0; r < 8; r++) {
                            uint32_t a = bmul2(kr[u][r], s3);
                            a = badd2(a, bmul2(kr[u][r + 1], s2));
                            a = badd2(a, bmul2(kr[u][r + 2], s1));
                            a = badd2(a, bmul2(kr[u][r + 3], s0));
                            vr[u][r] = bmul2(a, vr[u][r]);
                        }
                        __nv_bfloat16* dst = dst0 + (size_t)((rnd * 4 + u) * 32) * SEQ;
                        *(uint4*)dst = make_uint4(__byte_perm(vr[u][7], vr[u][6], 0x5410), __byte_perm(vr[u][5], vr[u][4], 0x5410),
                                                  __byte_perm(vr[u][3], vr[u][2], 0x5410), __byte_perm(vr[u][1], vr[u][0], 0x5410));
                        *(uint4*)(dst + SEQ) = make_uint4(__byte_perm(vr[u][7], vr[u][6], 0x7632), __byte_perm(vr[u][5], vr[u][4], 0x7632),
                                                          __byte_perm(vr[u][3], vr[u][2], 0x7632), __byte_perm(vr[u][1], vr[u][0], 0x7632));
                    }
                    PROFW(57 + 2 * rnd, 9);
                }
                if (lane == 0) mbar_arrive(sb + SM_BARS + B_KVLD * 8);
            }
            asm volatile("fence.proxy.async.global;" ::: "memory");
            __syncwarp();
            if (lane == 0) {
                flag_add(&g_cnt_kv[0]);
                PROFW(50, 9);
                const int wgi = warp - 9;
                mbar_wait(sb + SM_BARS + (B_HD + wgi * 2) * 8, 0);
                flag_add(&g_flag_h[(i * 2 + 0) * 8]);
                mbar_wait(sb + SM_BARS + (B_HD + wgi * 2 + 1) * 8, 0);
                flag_add(&g_flag_h[(i * 2 + 1) * 8]);
                if (wgi == 1 && convCTA) {
                    mbar_wait(sb + SM_BARS + B_YST * 8, 0);
                    flag_add(&g_cnt_y[(cidx >> 4) * 32]);
                    PROF(46);
                }
                if (wgi == 1 && !convCTA) {
                    const unsigned ep = lds32(sb + SM_EPOCH);
                    mbar_wait(sb + SM_BARS + B_G1DONE * 8, 0);
                    mbar_expect_tx(sb + SM_BARS + B_XR * 8, 32768);
                    tma3d(sb + SM_XE, &p.tm_xe, 0, 128 * i, 2 * cb, sb + SM_BARS + B_XR * 8);
                    flag_wait(&g_flag_h[(i * 2 + 1) * 8], ep * 16);
                    mbar_arrive(sb + SM_BARS + (B_HRDY + 1) * 8);
                    __nanosleep(3000);
                    flag_wait(&g_cnt_y[cb * 32], ep * 16);
                    PROF(49);
                    asm volatile("fence.proxy.async.global;" ::: "memory");
                    mbar_expect_tx(sb + SM_BARS + B_YT * 8, 32768);
                    tma2d(sb + SM_YT, &p.tm_yT, 128 * i, 128 * cb, sb + SM_BARS + B_YT * 8);
                    tma2d(sb + SM_YT + 16384, &p.tm_yT, 128 * i + 64, 128 * cb, sb + SM_BARS + B_YT * 8);
                }
            }
        } else {
            if (lane == 0) {
                l2_prefetch(p.wg + (size_t)b * (FF * DM / NCTA), FF * DM / NCTA * 2);
                l2_prefetch(p.wu + (size_t)b * (FF * DM / NCTA), FF * DM / NCTA * 2);
                const unsigned ep = g_launch[b] + 1;
                g_launch[b] = ep;
                sts32(sb + SM_EPOCH, ep);
                tmap_prefetch(rank ? &p.tm_uA : &p.tm_gA);
                tmap_prefetch(rank ? &p.tm_uB : &p.tm_gB);
                tmap_prefetch(&p.tm_w2); tmap_prefetch(&p.tm_yT); tmap_prefetch(&p.tm_out); tmap_prefetch(&p.tm_xe);
                mbar_wait(sb + SM_BARS + B_KVLD * 8, 0);
                l2_prefetch(p.ssm_k + (size_t)(4 * b) * SEQ, 4 * SEQ * 2);
                l2_prefetch(p.wd + (size_t)b * (FF * DM / NCTA), FF * DM / NCTA * 2);
                mbar_wait(sb + SM_BARS + (B_HD + 0) * 8, 0);
                if (convCTA) {
                    flag_wait(&g_cnt_kv[0], ep * 256);
                    asm volatile("fence.proxy.async.global;" ::: "memory");
                    PROF(53);
                    mbar_wait(sb + SM_BARS + B_XFREE * 8, 0);
                    PROF(54);
                    mbar_expect_tx(sb + SM_BARS + B_CONV * 8, 65536);
                    bulk_g2s(sb + SM_CVX, g_kvT + (size_t)(8 * cidx) * SEQ, 32768, sb + SM_BARS + B_CONV * 8);
                    bulk_g2s(sb + SM_CVH, p.ssm_k + (size_t)(8 * cidx) * SEQ, 32768, sb + SM_BARS + B_CONV * 8);
                } else {
                    flag_wait(&g_flag_h[(i * 2 + 0) * 8], ep * 16);
                }
            }
            __syncwarp();
            if (!convCTA) {
                asm volatile("fence.proxy.async.global;" ::: "memory");
                int st = 3; uint32_t eph = 1;
                const uint8_t* hsrc = (const uint8_t*)g_h + (size_t)i * 56 * 8192;
                #pragma unroll 1
                for (int u = 0; u < 28; u++) {
                    mbar_wait(sb + SM_BARS + (B_EMPTY + st) * 8, (eph >> st) & 1);
                    eph ^= 1u << st;
                    if (u == 16) {
                        mbar_wait(sb + SM_BARS + (B_HRDY + 1) * 8, 0);
                        asm volatile("fence.proxy.async.global;" ::: "memory");
                    }
                    if (elect_one()) bulk_g2s(sb + stage_off_rt(st) + 16384, hsrc + u * 16384, 16384, sb + SM_BARS + (B_FULL + st) * 8);
                    st = next_st2(st);
                }
            }
        }
    }
}

typedef CUresult (*EncodeFn)(CUtensorMap*, CUtensorMapDataType, cuuint32_t, void*, const cuuint64_t*, const cuuint64_t*,
                             const cuuint32_t*, const cuuint32_t*, CUtensorMapInterleave, CUtensorMapSwizzle,
                             CUtensorMapL2promotion, CUtensorMapFloatOOBfill);

void encode(EncodeFn fn, CUtensorMap* tm, const void* base, int rank, const cuuint64_t* dims, const cuuint64_t* strides,
            const cuuint32_t* box, CUtensorMapSwizzle swz) {
    cuuint32_t es[5] = {1, 1, 1, 1, 1};
    fn(tm, CU_TENSOR_MAP_DATA_TYPE_BFLOAT16, rank, (void*)base, dims, strides, box, es, CU_TENSOR_MAP_INTERLEAVE_NONE, swz,
       CU_TENSOR_MAP_L2_PROMOTION_L2_128B, CU_TENSOR_MAP_FLOAT_OOB_FILL_NONE);
}

}

extern "C" void kernel_launch(void* const* d_in, const int* in_sizes, int n_in, void* d_out, int out_size) {
    (void)in_sizes; (void)n_in; (void)out_size;
    static EncodeFn enc = nullptr;
    static void* yT_ptr = nullptr;
    if (!enc) {
        void* fn = nullptr; cudaDriverEntryPointQueryResult qr;
        cudaGetDriverEntryPoint("cuTensorMapEncodeTiled", &fn, cudaEnableDefault, &qr);
        enc = (EncodeFn)fn;
        cudaGetSymbolAddress(&yT_ptr, g_yT);
        cudaFuncSetAttribute(fused_kernel, cudaFuncAttributeMaxDynamicSharedMemorySize, SM_TOTAL);
    }
    Params p;
    p.q = (const __nv_bfloat16*)d_in[0]; p.k = (const __nv_bfloat16*)d_in[1]; p.v = (const __nv_bfloat16*)d_in[2];
    p.shift_k = (const __nv_bfloat16*)d_in[3]; p.ssm_k = (const __nv_bfloat16*)d_in[4]; p.ssm_D = (const __nv_bfloat16*)d_in[5];
    p.wg = (const __nv_bfloat16*)d_in[7]; p.wu = (const __nv_bfloat16*)d_in[8]; p.wd = (const __nv_bfloat16*)d_in[9];
    {
        cuuint64_t dims[2] = {DM, SEQ}; cuuint64_t str[1] = {DM * 2};
        cuuint64_t dims3[3] = {64, SEQ, DM / 64}; cuuint64_t str3[2] = {DM * 2, 128};
        cuuint32_t box[3] = {64, 64, 8}, boxe[3] = {64, 128, 2};
        encode(enc, &p.tm_x, p.q, 3, dims3, str3, box, CU_TENSOR_MAP_SWIZZLE_128B);
        encode(enc, &p.tm_xe, p.q, 3, dims3, str3, boxe, CU_TENSOR_MAP_SWIZZLE_128B);
        cuuint32_t box2[2] = {64, 64};
        encode(enc, &p.tm_out, d_out, 2, dims, str, box2, CU_TENSOR_MAP_SWIZZLE_128B);
    }
    {
        cuuint64_t dims[3] = {32, DM, FF / 32}; cuuint64_t str[2] = {FF * 2, 64};
        cuuint32_t boxA[3] = {32, 64, 4}, boxB[3] = {32, 64, 2};
        encode(enc, &p.tm_gA, p.wg, 3, dims, str, boxA, CU_TENSOR_MAP_SWIZZLE_64B);
        encode(enc, &p.tm_gB, p.wg, 3, dims, str, boxB, CU_TENSOR_MAP_SWIZZLE_64B);
        encode(enc, &p.tm_uA, p.wu, 3, dims, str, boxA, CU_TENSOR_MAP_SWIZZLE_64B);
        encode(enc, &p.tm_uB, p.wu, 3, dims, str, boxB, CU_TENSOR_MAP_SWIZZLE_64B);
    }
    {
        cuuint64_t dims[3] = {64, FF, DM / 64}; cuuint64_t str[2] = {DM * 2, 128};
        cuuint32_t box[3] = {64, 32, 2};
        encode(enc, &p.tm_w2, p.wd, 3, dims, str, box, CU_TENSOR_MAP_SWIZZLE_128B);
    }
    {
        cuuint64_t dims[2] = {SEQ, DM}; cuuint64_t str[1] = {SEQ * 2};
        cuuint32_t box[2] = {64, 128};
        encode(enc, &p.tm_yT, yT_ptr, 2, dims, str, box, CU_TENSOR_MAP_SWIZZLE_128B);
    }
    fused_kernel<<<NCTA, NTHREADS, SM_TOTAL>>>(p);
}
```

```cpp
#include <cuda_runtime.h>
#include <cuda_bf16.h>
#include <cuda.h>
#include <stdint.h>

namespace {

constexpr int SEQ = 2048, DM = 512, FF = 1792;
constexpr int NCTA = 128;
constexpr int NTHREADS = 384;
constexpr int STAGE_BYTES = 32768;
#define KV_STAGGER 300
#define KV_GAP 150

constexpr uint32_t SM_X = 0;
constexpr uint32_t SM_RING = 131072;
constexpr uint32_t SM_MISC = SM_RING + 3 * STAGE_BYTES;
constexpr uint32_t SM_BARS = SM_MISC;
constexpr uint32_t SM_EPOCH = SM_MISC + 248;
constexpr uint32_t SM_STATS = SM_MISC + 256;
constexpr uint32_t SM_TOTAL = SM_STATS + 1024;
static_assert(SM_TOTAL <= 232448, "smem");
constexpr uint32_t SM_CVX = 0;
constexpr uint32_t SM_CVH = 65536;
constexpr uint32_t SM_YT = 32768;
constexpr uint32_t SM_XE = 98304;

constexpr int B_FULL = 0, B_EMPTY = 5, B_XFULL = 10, B_CONV = 14, B_YT = 15, B_XR = 16, B_G1DONE = 17, B_HD = 18, B_HRDY = 22,
              B_XFREE = 24, B_YST = 25, B_KVLD = 26, B_COUNT = 27;
static_assert(B_COUNT * 8 <= 248, "barrier space");

__device__ __align__(128) uint32_t g_h[16 * 56 * 2048];
__device__ __align__(128) __nv_bfloat16 g_kvT[DM * SEQ];
__device__ __align__(128) __nv_bfloat16 g_yT[DM * SEQ];
__device__ unsigned g_launch[NCTA];
__device__ unsigned g_cnt_kv[32];
__device__ unsigned g_cnt_y[4 * 32];
__device__ unsigned g_flag_h[16 * 2 * 8];

#define PROF(idx)
#define PROF2(a, idx)
#define PROFW(idx, w)

struct Params {
    CUtensorMap tm_x, tm_gA, tm_gB, tm_uA, tm_uB, tm_w2, tm_yT, tm_out, tm_xe;
    const __nv_bfloat16 *q, *k, *v, *shift_k, *ssm_k, *ssm_D, *wg, *wu, *wd;
};

__device__ __forceinline__ void wgmma_rs_n32(float (&d)[16], uint32_t a0, uint32_t a1, uint32_t a2, uint32_t a3, uint64_t db, int sc) {
  asm volatile("{\n.reg .pred p;\nsetp.ne.b32 p, %21, 0;\n"
    "wgmma.mma_async.sync.aligned.m64n32k16.f32.bf16.bf16 {%0,%1,%2,%3,%4,%5,%6,%7,%8,%9,%10,%11,%12,%13,%14,%15}, {%16,%17,%18,%19}, %20, p, 1, 1, 0;\n}\n"
    : "+f"(d[0]),"+f"(d[1]),"+f"(d[2]),"+f"(d[3]),"+f"(d[4]),"+f"(d[5]),"+f"(d[6]),"+f"(d[7]),"+f"(d[8]),"+f"(d[9]),"+f"(d[10]),"+f"(d[11]),"+f"(d[12]),"+f"(d[13]),"+f"(d[14]),"+f"(d[15])
    : "r"(a0),"r"(a1),"r"(a2),"r"(a3),"l"(db),"r"(sc));
}
__device__ __forceinline__ void wgmma_rs_n128_tb(float (&d)[64], uint32_t a0, uint32_t a1, uint32_t a2, uint32_t a3, uint64_t db, int sc) {
  asm volatile("{\n.reg .pred p;\nsetp.ne.b32 p, %69, 0;\n"
    "wgmma.mma_async.sync.aligned.m64n128k16.f32.bf16.bf16 {%0,%1,%2,%3,%4,%5,%6,%7,%8,%9,%10,%11,%12,%13,%14,%15,%16,%17,%18,%19,%20,%21,%22,%23,%24,%25,%26,%27,%28,%29,%30,%31,%32,%33,%34,%35,%36,%37,%38,%39,%40,%41,%42,%43,%44,%45,%46,%47,%48,%49,%50,%51,%52,%53,%54,%55,%56,%57,%58,%59,%60,%61,%62,%63}, {%64,%65,%66,%67}, %68, p, 1, 1, 1;\n}\n"
    : "+f"(d[0]),"+f"(d[1]),"+f"(d[2]),"+f"(d[3]),"+f"(d[4]),"+f"(d[5]),"+f"(d[6]),"+f"(d[7]),"+f"(d[8]),"+f"(d[9]),"+f"(d[10]),"+f"(d[11]),"+f"(d[12]),"+f"(d[13]),"+f"(d[14]),"+f"(d[15]),"+f"(d[16]),"+f"(d[17]),"+f"(d[18]),"+f"(d[19]),"+f"(d[20]),"+f"(d[21]),"+f"(d[22]),"+f"(d[23]),"+f"(d[24]),"+f"(d[25]),"+f"(d[26]),"+f"(d[27]),"+f"(d[28]),"+f"(d[29]),"+f"(d[30]),"+f"(d[31]),"+f"(d[32]),"+f"(d[33]),"+f"(d[34]),"+f"(d[35]),"+f"(d[36]),"+f"(d[37]),"+f"(d[38]),"+f"(d[39]),"+f"(d[40]),"+f"(d[41]),"+f"(d[42]),"+f"(d[43]),"+f"(d[44]),"+f"(d[45]),"+f"(d[46]),"+f"(d[47]),"+f"(d[48]),"+f"(d[49]),"+f"(d[50]),"+f"(d[51]),"+f"(d[52]),"+f"(d[53]),"+f"(d[54]),"+f"(d[55]),"+f"(d[56]),"+f"(d[57]),"+f"(d[58]),"+f"(d[59]),"+f"(d[60]),"+f"(d[61]),"+f"(d[62]),"+f"(d[63])
    : "r"(a0),"r"(a1),"r"(a2),"r"(a3),"l"(db),"r"(sc));
}
__device__ __forceinline__ void wgmma_ss_n256_tb(float (&d)[128], uint64_t da, uint64_t db, int sc) {
  asm volatile("{\n.reg .pred p;\nsetp.ne.b32 p, %130, 0;\n"
    "wgmma.mma_async.sync.aligned.m64n256k16.f32.bf16.bf16 {%0,%1,%2,%3,%4,%5,%6,%7,%8,%9,%10,%11,%12,%13,%14,%15,%16,%17,%18,%19,%20,%21,%22,%23,%24,%25,%26,%27,%28,%29,%30,%31,%32,%33,%34,%35,%36,%37,%38,%39,%40,%41,%42,%43,%44,%45,%46,%47,%48,%49,%50,%51,%52,%53,%54,%55,%56,%57,%58,%59,%60,%61,%62,%63,%64,%65,%66,%67,%68,%69,%70,%71,%72,%73,%74,%75,%76,%77,%78,%79,%80,%81,%82,%83,%84,%85,%86,%87,%88,%89,%90,%91,%92,%93,%94,%95,%96,%97,%98,%99,%100,%101,%102,%103,%104,%105,%106,%107,%108,%109,%110,%111,%112,%113,%114,%115,%116,%117,%118,%119,%120,%121,%122,%123,%124,%125,%126,%127}, %128, %129, p, 1, 1, 0, 1;\n}\n"
    : "+f"(d[0]),"+f"(d[1]),"+f"(d[2]),"+f"(d[3]),"+f"(d[4]),"+f"(d[5]),"+f"(d[6]),"+f"(d[7]),"+f"(d[8]),"+f"(d[9]),"+f"(d[10]),"+f"(d[11]),"+f"(d[12]),"+f"(d[13]),"+f"(d[14]),"+f"(d[15]),"+f"(d[16]),"+f"(d[17]),"+f"(d[18]),"+f"(d[19]),"+f"(d[20]),"+f"(d[21]),"+f"(d[22]),"+f"(d[23]),"+f"(d[24]),"+f"(d[25]),"+f"(d[26]),"+f"(d[27]),"+f"(d[28]),"+f"(d[29]),"+f"(d[30]),"+f"(d[31]),"+f"(d[32]),"+f"(d[33]),"+f"(d[34]),"+f"(d[35]),"+f"(d[36]),"+f"(d[37]),"+f"(d[38]),"+f"(d[39]),"+f"(d[40]),"+f"(d[41]),"+f"(d[42]),"+f"(d[43]),"+f"(d[44]),"+f"(d[45]),"+f"(d[46]),"+f"(d[47]),"+f"(d[48]),"+f"(d[49]),"+f"(d[50]),"+f"(d[51]),"+f"(d[52]),"+f"(d[53]),"+f"(d[54]),"+f"(d[55]),"+f"(d[56]),"+f"(d[57]),"+f"(d[58]),"+f"(d[59]),"+f"(d[60]),"+f"(d[61]),"+f"(d[62]),"+f"(d[63]),"+f"(d[64]),"+f"(d[65]),"+f"(d[66]),"+f"(d[67]),"+f"(d[68]),"+f"(d[69]),"+f"(d[70]),"+f"(d[71]),"+f"(d[72]),"+f"(d[73]),"+f"(d[74]),"+f"(d[75]),"+f"(d[76]),"+f"(d[77]),"+f"(d[78]),"+f"(d[79]),"+f"(d[80]),"+f"(d[81]),"+f"(d[82]),"+f"(d[83]),"+f"(d[84]),"+f"(d[85]),"+f"(d[86]),"+f"(d[87]),"+f"(d[88]),"+f"(d[89]),"+f"(d[90]),"+f"(d[91]),"+f"(d[92]),"+f"(d[93]),"+f"(d[94]),"+f"(d[95]),"+f"(d[96]),"+f"(d[97]),"+f"(d[98]),"+f"(d[99]),"+f"(d[100]),"+f"(d[101]),"+f"(d[102]),"+f"(d[103]),"+f"(d[104]),"+f"(d[105]),"+f"(d[106]),"+f"(d[107]),"+f"(d[108]),"+f"(d[109]),"+f"(d[110]),"+f"(d[111]),"+f"(d[112]),"+f"(d[113]),"+f"(d[114]),"+f"(d[115]),"+f"(d[116]),"+f"(d[117]),"+f"(d[118]),"+f"(d[119]),"+f"(d[120]),"+f"(d[121]),"+f"(d[122]),"+f"(d[123]),"+f"(d[124]),"+f"(d[125]),"+f"(d[126]),"+f"(d[127])
    : "l"(da),"l"(db),"r"(sc));
}
__device__ __forceinline__ void wgmma_ss_n192_tb(float (&d)[96], uint64_t da, uint64_t db, int sc) {
  asm volatile("{\n.reg .pred p;\nsetp.ne.b32 p, %98, 0;\n"
    "wgmma.mma_async.sync.aligned.m64n192k16.f32.bf16.bf16 {%0,%1,%2,%3,%4,%5,%6,%7,%8,%9,%10,%11,%12,%13,%14,%15,%16,%17,%18,%19,%20,%21,%22,%23,%24,%25,%26,%27,%28,%29,%30,%31,%32,%33,%34,%35,%36,%37,%38,%39,%40,%41,%42,%43,%44,%45,%46,%47,%48,%49,%50,%51,%52,%53,%54,%55,%56,%57,%58,%59,%60,%61,%62,%63,%64,%65,%66,%67,%68,%69,%70,%71,%72,%73,%74,%75,%76,%77,%78,%79,%80,%81,%82,%83,%84,%85,%86,%87,%88,%89,%90,%91,%92,%93,%94,%95}, %96, %97, p, 1, 1, 0, 1;\n}\n"
    : "+f"(d[0]),"+f"(d[1]),"+f"(d[2]),"+f"(d[3]),"+f"(d[4]),"+f"(d[5]),"+f"(d[6]),"+f"(d[7]),"+f"(d[8]),"+f"(d[9]),"+f"(d[10]),"+f"(d[11]),"+f"(d[12]),"+f"(d[13]),"+f"(d[14]),"+f"(d[15]),"+f"(d[16]),"+f"(d[17]),"+f"(d[18]),"+f"(d[19]),"+f"(d[20]),"+f"(d[21]),"+f"(d[22]),"+f"(d[23]),"+f"(d[24]),"+f"(d[25]),"+f"(d[26]),"+f"(d[27]),"+f"(d[28]),"+f"(d[29]),"+f"(d[30]),"+f"(d[31]),"+f"(d[32]),"+f"(d[33]),"+f"(d[34]),"+f"(d[35]),"+f"(d[36]),"+f"(d[37]),"+f"(d[38]),"+f"(d[39]),"+f"(d[40]),"+f"(d[41]),"+f"(d[42]),"+f"(d[43]),"+f"(d[44]),"+f"(d[45]),"+f"(d[46]),"+f"(d[47]),"+f"(d[48]),"+f"(d[49]),"+f"(d[50]),"+f"(d[51]),"+f"(d[52]),"+f"(d[53]),"+f"(d[54]),"+f"(d[55]),"+f"(d[56]),"+f"(d[57]),"+f"(d[58]),"+f"(d[59]),"+f"(d[60]),"+f"(d[61]),"+f"(d[62]),"+f"(d[63]),"+f"(d[64]),"+f"(d[65]),"+f"(d[66]),"+f"(d[67]),"+f"(d[68]),"+f"(d[69]),"+f"(d[70]),"+f"(d[71]),"+f"(d[72]),"+f"(d[73]),"+f"(d[74]),"+f"(d[75]),"+f"(d[76]),"+f"(d[77]),"+f"(d[78]),"+f"(d[79]),"+f"(d[80]),"+f"(d[81]),"+f"(d[82]),"+f"(d[83]),"+f"(d[84]),"+f"(d[85]),"+f"(d[86]),"+f"(d[87]),"+f"(d[88]),"+f"(d[89]),"+f"(d[90]),"+f"(d[91]),"+f"(d[92]),"+f"(d[93]),"+f"(d[94]),"+f"(d[95])
    : "l"(da),"l"(db),"r"(sc));
}

__device__ __forceinline__ uint32_t smem_u32(const void* p) { return (uint32_t)__cvta_generic_to_shared(p); }
__device__ __forceinline__ void mbar_init(uint32_t bar, uint32_t cnt) { asm volatile("mbarrier.init.shared::cta.b64 [%0], %1;" :: "r"(bar), "r"(cnt)); }
__device__ __forceinline__ void mbar_expect_tx(uint32_t bar, uint32_t bytes) { asm volatile("mbarrier.arrive.expect_tx.shared::cta.b64 _, [%0], %1;" :: "r"(bar), "r"(bytes) : "memory"); }
__device__ __forceinline__ void mbar_arrive(uint32_t bar) { asm volatile("mbarrier.arrive.shared::cta.b64 _, [%0];" :: "r"(bar) : "memory"); }
__device__ __forceinline__ void mbar_arrive_cluster(uint32_t cbar, uint32_t cnt) { asm volatile("mbarrier.arrive.shared::cluster.b64 _, [%0], %1;" :: "r"(cbar), "r"(cnt) : "memory"); }
__device__ __forceinline__ uint32_t mapa(uint32_t a, uint32_t rank) { uint32_t r; asm volatile("mapa.shared::cluster.u32 %0, %1, %2;" : "=r"(r) : "r"(a), "r"(rank)); return r; }
__device__ __forceinline__ void mbar_wait(uint32_t bar, uint32_t parity) {
    uint32_t ok; uint32_t n = 0;
    do {
        asm volatile("{\n.reg .pred p;\nmbarrier.try_wait.parity.shared::cta.b64 p, [%1], %2;\nselp.u32 %0, 1, 0, p;\n}" : "=r"(ok) : "r"(bar), "r"(parity) : "memory");
    } while (!ok && ++n < (1u << 17));
}
__device__ __forceinline__ void pace_wait(uint32_t a, uint32_t target) {
    uint32_t v, n = 0;
    do {
        asm volatile("ld.volatile.shared.u32 %0, [%1];" : "=r"(v) : "r"(a) : "memory");
        if (v < target) __nanosleep(150);
    } while (v < target && ++n < (1u << 14));
}
__device__ __forceinline__ void flag_wait(const unsigned* p, unsigned target) {
    unsigned v; uint32_t n = 0;
    while (true) {
        asm volatile("ld.acquire.gpu.global.u32 %0, [%1];" : "=r"(v) : "l"(p) : "memory");
        if ((int)(v - target) >= 0 || ++n >= (1u << 17)) break;
        __nanosleep(100);
    }
}
__device__ __forceinline__ void flag_add(unsigned* p) {
    asm volatile("fence.acq_rel.gpu;\nred.relaxed.gpu.global.add.u32 [%0], 1;" :: "l"(p) : "memory");
}
__device__ __forceinline__ uint64_t make_desc(uint32_t addr, uint32_t lbo, uint32_t sbo, uint32_t swz) {
    return (uint64_t)((addr & 0x3FFFF) >> 4) | ((uint64_t)((lbo & 0x3FFFF) >> 4) << 16) | ((uint64_t)((sbo & 0x3FFFF) >> 4) << 32) | ((uint64_t)swz << 62);
}
__device__ __forceinline__ uint64_t desc_add(uint64_t d, uint32_t off16) {
    return (d & 0xFFFFFFFF00000000ull) | (uint64_t)((uint32_t)d + off16);
}
__device__ __forceinline__ void tma2d(uint32_t dst, const CUtensorMap* tm, int c0, int c1, uint32_t bar) {
    asm volatile("cp.async.bulk.tensor.2d.shared::cluster.global.mbarrier::complete_tx::bytes [%0], [%1, {%3, %4}], [%2];"
        :: "r"(dst), "l"((uint64_t)tm), "r"(bar), "r"(c0), "r"(c1) : "memory");
}
__device__ __forceinline__ void tma3d(uint32_t dst, const CUtensorMap* tm, int c0, int c1, int c2, uint32_t bar) {
    asm volatile("cp.async.bulk.tensor.3d.shared::cluster.global.mbarrier::complete_tx::bytes [%0], [%1, {%3, %4, %5}], [%2];"
        :: "r"(dst), "l"((uint64_t)tm), "r"(bar), "r"(c0), "r"(c1), "r"(c2) : "memory");
}
__device__ __forceinline__ void tma3d_mc(uint32_t dst, const CUtensorMap* tm, int c0, int c1, int c2, uint32_t bar) {
    asm volatile("cp.async.bulk.tensor.3d.shared::cluster.global.mbarrier::complete_tx::bytes.multicast::cluster [%0], [%1, {%3, %4, %5}], [%2], %6;"
        :: "r"(dst), "l"((uint64_t)tm), "r"(bar), "r"(c0), "r"(c1), "r"(c2), "h"((uint16_t)3) : "memory");
}
__device__ __forceinline__ void bulk_g2s(uint32_t dst, const void* src, uint32_t bytes, uint32_t bar) {
    asm volatile("cp.async.bulk.shared::cluster.global.mbarrier::complete_tx::bytes [%0], [%1], %2, [%3];"
        :: "r"(dst), "l"(src), "r"(bytes), "r"(bar) : "memory");
}
__device__ __forceinline__ void bulk_s2g(void* dst, uint32_t src, uint32_t bytes) {
    asm volatile("cp.async.bulk.global.shared::cta.bulk_group [%0], [%1], %2;" :: "l"(dst), "r"(src), "r"(bytes) : "memory");
}
__device__ __forceinline__ void tma2d_store(const CUtensorMap* tm, int c0, int c1, uint32_t src) {
    asm volatile("cp.async.bulk.tensor.2d.global.shared::cta.bulk_group [%0, {%2, %3}], [%1];"
        :: "l"((uint64_t)tm), "r"(src), "r"(c0), "r"(c1) : "memory");
}
__device__ __forceinline__ void l2_prefetch(const void* p, uint32_t bytes) {
    asm volatile("cp.async.bulk.prefetch.L2.global [%0], %1;" :: "l"(p), "r"(bytes) : "memory");
}
__device__ __forceinline__ void tmap_prefetch(const CUtensorMap* tm) { asm volatile("prefetch.tensormap [%0];" :: "l"((uint64_t)tm) : "memory"); }
__device__ __forceinline__ uint32_t lds32(uint32_t a) { uint32_t v; asm volatile("ld.shared.u32 %0, [%1];" : "=r"(v) : "r"(a)); return v; }
__device__ __forceinline__ uint2 lds64(uint32_t a) { uint2 v; asm volatile("ld.shared.v2.u32 {%0,%1}, [%2];" : "=r"(v.x), "=r"(v.y) : "r"(a)); return v; }
__device__ __forceinline__ uint4 lds128(uint32_t a) { uint4 v; asm volatile("ld.shared.v4.u32 {%0,%1,%2,%3}, [%4];" : "=r"(v.x), "=r"(v.y), "=r"(v.z), "=r"(v.w) : "r"(a)); return v; }
__device__ __forceinline__ float2 lds64f(uint32_t a) { float2 v; asm volatile("ld.shared.v2.f32 {%0,%1}, [%2];" : "=f"(v.x), "=f"(v.y) : "r"(a)); return v; }
__device__ __forceinline__ void sts32(uint32_t a, uint32_t v) { asm volatile("st.shared.u32 [%0], %1;" :: "r"(a), "r"(v) : "memory"); }
__device__ __forceinline__ void sts128(uint32_t a, uint4 v) { asm volatile("st.shared.v4.u32 [%0], {%1,%2,%3,%4};" :: "r"(a), "r"(v.x), "r"(v.y), "r"(v.z), "r"(v.w) : "memory"); }
__device__ __forceinline__ uint4 ldg_cg128(const void* p) { uint4 v; asm volatile("ld.global.cg.v4.u32 {%0,%1,%2,%3}, [%4];" : "=r"(v.x), "=r"(v.y), "=r"(v.z), "=r"(v.w) : "l"(p)); return v; }
__device__ __forceinline__ uint4 ldg_nc128(const void* p) { uint4 v; asm volatile("ld.global.nc.L1::no_allocate.v4.u32 {%0,%1,%2,%3}, [%4];" : "=r"(v.x), "=r"(v.y), "=r"(v.z), "=r"(v.w) : "l"(p)); return v; }
__device__ __forceinline__ uint32_t ldg_nc32(const void* p) { uint32_t v; asm volatile("ld.global.nc.u32 %0, [%1];" : "=r"(v) : "l"(p)); return v; }
__device__ __forceinline__ uint2 ldg_nc64(const void* p) { uint2 v; asm volatile("ld.global.nc.L1::no_allocate.v2.u32 {%0,%1}, [%2];" : "=r"(v.x), "=r"(v.y) : "l"(p)); return v; }
#define WG_FENCE() asm volatile("wgmma.fence.sync.aligned;\n" ::: "memory")
#define WG_COMMIT() asm volatile("wgmma.commit_group.sync.aligned;\n" ::: "memory")
template<int N> __device__ __forceinline__ void wg_wait() { asm volatile("wgmma.wait_group.sync.aligned %0;\n" :: "n"(N) : "memory"); }
__device__ __forceinline__ bool elect_one() {
    uint32_t pr;
    asm volatile("{\n.reg .pred p;\nelect.sync _|p, 0xffffffff;\nselp.u32 %0, 1, 0, p;\n}" : "=r"(pr));
    return pr != 0;
}
__device__ __forceinline__ void named_bar(int id, int n) { asm volatile("bar.sync %0, %1;" :: "r"(id), "r"(n) : "memory"); }

__device__ __forceinline__ float bf_lo(uint32_t u) { return __uint_as_float(u << 16); }
__device__ __forceinline__ float bf_hi(uint32_t u) { return __uint_as_float(u & 0xFFFF0000u); }
__device__ __forceinline__ uint32_t pack_bf(float lo, float hi) { uint32_t r; asm("cvt.rn.bf16x2.f32 %0, %1, %2;" : "=r"(r) : "f"(hi), "f"(lo)); return r; }
__device__ __forceinline__ float bf_round(float x) { return __bfloat162float(__float2bfloat16_rn(x)); }
__device__ __forceinline__ uint32_t bmul2(uint32_t a, uint32_t b) { uint32_t r; asm("mul.rn.bf16x2 %0, %1, %2;" : "=r"(r) : "r"(a), "r"(b)); return r; }
__device__ __forceinline__ uint32_t badd2(uint32_t a, uint32_t b) { uint32_t r; asm("add.rn.bf16x2 %0, %1, %2;" : "=r"(r) : "r"(a), "r"(b)); return r; }
__device__ __forceinline__ uint32_t bsub2(uint32_t a, uint32_t b) { uint32_t r; asm("sub.rn.bf16x2 %0, %1, %2;" : "=r"(r) : "r"(a), "r"(b)); return r; }
__device__ __forceinline__ void mma16816(float (&d)[4], uint32_t a0, uint32_t a1, uint32_t a2, uint32_t a3, uint2 b) {
    asm volatile("mma.sync.aligned.m16n8k16.row.col.f32.bf16.bf16.f32 {%0,%1,%2,%3}, {%4,%5,%6,%7}, {%8,%9}, {%0,%1,%2,%3};\n"
        : "+f"(d[0]), "+f"(d[1]), "+f"(d[2]), "+f"(d[3]) : "r"(a0), "r"(a1), "r"(a2), "r"(a3), "r"(b.x), "r"(b.y));
}

template<int HS> __device__ __forceinline__ void xreduce(float (&v)[8], int lane) {
    const int up = lane & HS;
    #pragma unroll
    for (int e = 0; e < HS; e++) {
        float keep, send;
        asm("{\n.reg .pred p;\nsetp.ne.b32 p, %4, 0;\nselp.f32 %0, %3, %2, p;\nselp.f32 %1, %2, %3, p;\n}"
            : "=f"(keep), "=f"(send) : "f"(v[e]), "f"(v[e + HS]), "r"(up));
        v[e] = keep + __shfl_xor_sync(0xffffffffu, send, HS);
    }
}

__device__ __forceinline__ int blk_f0(int s) {
    if (s < 32) return 32 * (14 * (s >> 3) + 8 * ((s >> 2) & 1) + (s & 3));
    const int s2 = s - 32, c6 = (s2 * 11) >> 6, t = s2 - 6 * c6;
    return 32 * (14 * c6 + (t < 4 ? 4 + t : 8 + t));
}
__device__ __forceinline__ int next_st2(int s) { return (0x14023 >> (4 * s)) & 7; }
__device__ __forceinline__ uint32_t stage_off_rt(int s) { return s < 3 ? SM_RING + s * STAGE_BYTES : (uint32_t)(s - 3) * 65536; }

__device__ __forceinline__ void store_h(uint32_t* dst, const uint32_t (&hp)[32], int q) {
    #pragma unroll
    for (int kk = 0; kk < 2; kk++) {
        uint32_t* d2 = dst + q * 2048 + kk * 512;
        d2[0] = hp[8 * q + 4 * kk]; d2[64] = hp[8 * q + 4 * kk + 1]; d2[32] = hp[8 * q + 4 * kk + 2]; d2[96] = hp[8 * q + 4 * kk + 3];
    }
}
template<int NB, bool passA>
__device__ __forceinline__ void gemm1_pass(uint32_t sb, int wgi, int warp4, int lane, int& st, uint32_t& fph, uint32_t e_cl,
                                           uint32_t (&hp)[32], uint32_t* prev_dst, bool convCTA) {
    float acc[NB * 32];
    const uint64_t descA0 = make_desc(sb + SM_X + wgi * 65536, 16, 1024, 1);
    const uint64_t descB0 = make_desc(sb + SM_RING, 4096, 512, 2);
    int prev = 0;
    auto group = [&](int sl) {
        if (warp4 == 0 && wgi == 0) PROF2(2, sl + (passA ? 0 : 8));
        mbar_wait(sb + SM_BARS + (B_FULL + st) * 8, (fph >> st) & 1);
        fph ^= 1u << st;
        if (sl == 0 && warp4 == 0) PROF(2 + wgi * 8 + (passA ? 0 : 3));
        if (warp4 == 0 && wgi == 0) PROF2(1, sl + (passA ? 0 : 8));
        const uint64_t da = desc_add(descA0, sl * 512), db = desc_add(descB0, st * 2048);
        WG_FENCE();
        #pragma unroll
        for (int kk = 0; kk < 4; kk++) {
            int sc = (sl | kk) ? 1 : 0;
            if constexpr (NB == 4) wgmma_ss_n256_tb(acc, da + kk * 2, db + kk * 64, sc); else wgmma_ss_n128_tb(acc, da + kk * 2, db + kk * 64, sc);
        }
        WG_COMMIT();
        wg_wait<1>();
        if (warp4 == 0 && wgi == 0) PROF2(3, sl + (passA ? 0 : 8));
        if (lane < 2 && sl && (passA || !convCTA || sl < 6)) mbar_arrive_cluster(e_cl + prev * 8, 1);
        if (!passA && sl == 4) {
            if (convCTA) { if (lane == 0) mbar_arrive(sb + SM_BARS + B_XFREE * 8); }
            else if (lane < 4) mbar_arrive_cluster(e_cl + (3 + (lane >> 1)) * 8, 1);
        }
        prev = st;
        st = (st == 2) ? 0 : st + 1;
    };
    if constexpr (passA) {
        #pragma unroll 1
        for (int sl = 0; sl < 8; sl++) group(sl);
    } else {
        #pragma unroll
        for (int sl = 0; sl < 4; sl++) { group(sl); store_h(prev_dst, hp, sl); }
        __syncwarp();
        if (lane == 0) mbar_arrive(sb + SM_BARS + (B_HD + wgi * 2) * 8);
        #pragma unroll 1
        for (int sl = 4; sl < 8; sl++) group(sl);
    }
    wg_wait<0>();
    if (lane < 2 && (passA || !convCTA)) mbar_arrive_cluster(e_cl + prev * 8, 1);
    if (!passA && lane == 0) mbar_arrive(sb + SM_BARS + B_G1DONE * 8);
    if (warp4 == 0) PROF(3 + wgi * 8 + (passA ? 0 : 3));
    const int g = lane >> 2;
    const int r0 = wgi * 64 + warp4 * 16 + g;
    const float s0 = __uint_as_float(lds32(sb + SM_STATS + r0 * 8 + 4)), s1 = __uint_as_float(lds32(sb + SM_STATS + (r0 + 8) * 8 + 4));
    #pragma unroll
    for (int t = 0; t < NB * 4; t++) {
        const float* ag = &acc[4 * t];
        const float* au = &acc[NB * 16 + 4 * t];
        hp[2 * t] = bmul2(pack_bf(ag[0] * s0, ag[1] * s0), pack_bf(au[0] * s0, au[1] * s0));
        hp[2 * t + 1] = bmul2(pack_bf(ag[2] * s1, ag[3] * s1), pack_bf(au[2] * s1, au[3] * s1));
    }
    if (warp4 == 0) PROF(4 + wgi * 8 + (passA ? 0 : 3));
}

__global__ void __cluster_dims__(2, 1, 1) __launch_bounds__(NTHREADS, 1)
fused_kernel(const __grid_constant__ Params p) {
    extern __shared__ __align__(1024) uint8_t smem_raw[];
    const uint32_t sb = smem_u32(smem_raw);
    const int tid = threadIdx.x, warp = tid >> 5, lane = tid & 31;
    const int b = blockIdx.x;
    const int rank = b & 1;
    const int j = (b >> 1) & 7;
    const int i = ((b >> 4) << 1) | rank;
    const int cb = j >> 1;
    const bool convCTA = j & 1;
    const int cidx = 4 * i + cb;

    if (tid == 256) {
        mbar_init(sb + SM_BARS + B_XFULL * 8, 1);
        mbar_init(sb + SM_BARS + (B_XFULL + 1) * 8, 1);
        asm volatile("fence.proxy.async.shared::cta;" ::: "memory");
        mbar_expect_tx(sb + SM_BARS + B_XFULL * 8, 65536);
        tma3d(sb + SM_X, &p.tm_x, 0, 128 * i, 0, sb + SM_BARS + B_XFULL * 8);
        mbar_expect_tx(sb + SM_BARS + (B_XFULL + 1) * 8, 65536);
        tma3d(sb + SM_X + 65536, &p.tm_x, 0, 128 * i + 64, 0, sb + SM_BARS + (B_XFULL + 1) * 8);
    }
    if (tid == 288) {
        for (int s = 0; s < 5; s++) { mbar_init(sb + SM_BARS + (B_FULL + s) * 8, 1); mbar_init(sb + SM_BARS + (B_EMPTY + s) * 8, 16); }
        mbar_init(sb + SM_BARS + B_CONV * 8, 1);
        mbar_init(sb + SM_BARS + B_YT * 8, 1);
        mbar_init(sb + SM_BARS + B_XR * 8, 1);
        mbar_init(sb + SM_BARS + B_G1DONE * 8, 8);
        mbar_init(sb + SM_BARS + B_XFREE * 8, 8);
        mbar_init(sb + SM_BARS + B_YST * 8, 8);
        mbar_init(sb + SM_BARS + B_KVLD * 8, 2);
        for (int s = 0; s < 4; s++) mbar_init(sb + SM_BARS + (B_HD + s) * 8, 4);
        for (int s = 0; s < 2; s++) mbar_init(sb + SM_BARS + (B_HRDY + s) * 8, 1);
        asm volatile("fence.mbarrier_init.release.cluster;" ::: "memory");
        asm volatile("fence.proxy.async.shared::cta;" ::: "memory");
    }
    __syncwarp();
    asm volatile("barrier.cluster.arrive.relaxed.aligned;\n" ::: "memory");
    asm volatile("barrier.cluster.wait.aligned;\n" ::: "memory");
    PROFW(1, 0);

    if (warp < 8) {
        asm volatile("setmaxnreg.inc.sync.aligned.u32 200;");
        const int wgi = warp >> 2, warp4 = warp & 3;
        const int g = lane >> 2, c = lane & 3;
        const uint32_t e_cl = mapa(sb + SM_BARS + B_EMPTY * 8, lane & 1);
        {
            const int lr16 = (lane & 7) + ((lane >> 3) & 1) * 8;
            const uint32_t xa = sb + SM_X + wgi * 65536 + (warp4 * 16 + lr16) * 128;
            uint32_t xf[32][4];
            float aS[4][4], aQ0[4][4], aQ1[4][4];
            #pragma unroll
            for (int e = 0; e < 4; e++) {
                #pragma unroll
                for (int f = 0; f < 4; f++) { aS[e][f] = 0.f; aQ0[e][f] = 0.f; aQ1[e][f] = 0.f; }
            }
            mbar_wait(sb + SM_BARS + (B_XFULL + wgi) * 8, 0);
            PROFW(16, 0); PROFW(18, 4);
            #pragma unroll
            for (int ks = 0; ks < 32; ks++) {
                const uint32_t a = xa + (ks >> 2) * 8192 + (((2 * (ks & 3) + (lane >> 4)) ^ (lane & 7)) << 4);
                asm volatile("ldmatrix.sync.aligned.m8n8.x4.shared.b16 {%0,%1,%2,%3}, [%4];"
                    : "=r"(xf[ks][0]), "=r"(xf[ks][1]), "=r"(xf[ks][2]), "=r"(xf[ks][3]) : "r"(a) : "memory");
            }
            #pragma unroll
            for (int ks = 0; ks < 32; ks++) {
                mma16816(aS[ks & 3], xf[ks][0], xf[ks][1], xf[ks][2], xf[ks][3], make_uint2(0x3F803F80u, 0x3F803F80u));
                mma16816(aQ0[ks & 3], xf[ks][0], xf[ks][1], xf[ks][2], xf[ks][3], make_uint2(xf[ks][0], xf[ks][2]));
                mma16816(aQ1[ks & 3], xf[ks][0], xf[ks][1], xf[ks][2], xf[ks][3], make_uint2(xf[ks][1], xf[ks][3]));
            }
            const float mean0 = ((aS[0][0] + aS[1][0]) + (aS[2][0] + aS[3][0])) * (1.0f / DM);
            const float mean1 = ((aS[0][2] + aS[1][2]) + (aS[2][2] + aS[3][2])) * (1.0f / DM);
            const uint32_t m0 = pack_bf(mean0, mean0), m1 = pack_bf(mean1, mean1);
            #pragma unroll
            for (int ks = 0; ks < 32; ks++) {
                const uint32_t a = xa + (ks >> 2) * 8192 + (((2 * (ks & 3) + (lane >> 4)) ^ (lane & 7)) << 4);
                asm volatile("stmatrix.sync.aligned.m8n8.x4.shared.b16 [%0], {%1,%2,%3,%4};"
                    :: "r"(a), "r"(bsub2(xf[ks][0], m0)), "r"(bsub2(xf[ks][1], m1)), "r"(bsub2(xf[ks][2], m0)), "r"(bsub2(xf[ks][3], m1)) : "memory");
            }
            if (c == (g >> 1)) {
                const float q0 = (g & 1) ? (aQ0[0][1] + aQ0[1][1]) + (aQ0[2][1] + aQ0[3][1]) : (aQ0[0][0] + aQ0[1][0]) + (aQ0[2][0] + aQ0[3][0]);
                const float q1 = (g & 1) ? (aQ1[0][3] + aQ1[1][3]) + (aQ1[2][3] + aQ1[3][3]) : (aQ1[0][2] + aQ1[1][2]) + (aQ1[2][2] + aQ1[3][2]);
                const float sd0 = bf_round(sqrtf(bf_round(bf_round(fmaxf(q0 * (1.0f / DM) - mean0 * mean0, 0.f)) + 1e-5f)));
                const float sd1 = bf_round(sqrtf(bf_round(bf_round(fmaxf(q1 * (1.0f / DM) - mean1 * mean1, 0.f)) + 1e-5f)));
                const uint32_t sa = sb + SM_STATS + (warp * 16 + g) * 8;
                sts32(sa, m0); sts32(sa + 4, __float_as_uint(1.0f / sd0));
                sts32(sa + 64, m1); sts32(sa + 68, __float_as_uint(1.0f / sd1));
            }
            asm volatile("fence.proxy.async.shared::cta;" ::: "memory");
            named_bar(3, 256);
            PROFW(19, 4);
            PROFW(17, 0);
        }
        int st = 0; uint32_t fph = 0;
        uint32_t hp[32];
        uint32_t* const hdst = g_h + (size_t)(i * 56) * 2048 + wgi * 1024 + warp4 * 128 + lane;
        gemm1_pass<4, true>(sb, wgi, warp4, lane, st, fph, e_cl, hp, hdst, convCTA);

        if (convCTA) {
            gemm1_pass<2, false>(sb, wgi, warp4, lane, st, fph, e_cl, hp, hdst + 4 * j * 2048, true);
            store_h(hdst + (36 + 6 * cb) * 2048, hp, 0); store_h(hdst + (36 + 6 * cb) * 2048, hp, 1);
            __syncwarp();
            if (lane == 0) mbar_arrive(sb + SM_BARS + (B_HD + wgi * 2 + 1) * 8);
            const int gch = 8 * cidx + warp;
            const uint32_t xb = sb + SM_CVX + warp * 4096;
            const uint32_t hb = sb + SM_CVH + warp * 4096;
            const uint32_t dw = ((const unsigned short*)p.ssm_D)[gch];
            const uint32_t d2 = dw | (dw << 16);
            mbar_wait(sb + SM_BARS + B_CONV * 8, 0);
            PROFW(32, 4);
            float acc[16][4];
            #pragma unroll
            for (int jj = 0; jj < 16; jj++) { acc[jj][0] = 0.f; acc[jj][1] = 0.f; acc[jj][2] = 0.f; acc[jj][3] = 0.f; }
            uint2 bh[8], bl0[8], bl1[8];
            uint32_t xl = xb + g * 32 + c * 8;
            uint32_t hl = hb + (g + 2 * c - 8) * 4;
            #pragma unroll
            for (int d = 0; d < 8; d++) { bl0[d] = lds64(xl + d * 256); bh[d] = lds64(xl + (8 + d) * 256); }
            uint32_t w[6];
            w[0] = 0; w[1] = 0; w[2] = 0;
            if (g + 2 * c >= 8) w[0] = lds32(hl);
            if (g + 2 * c >= 7) w[1] = lds32(hl + 4);
            if (g + 2 * c >= 6) w[2] = lds32(hl + 8);
            w[3] = lds32(hl + 2048); w[4] = lds32(hl + 2052); w[5] = lds32(hl + 2056);
            auto conv_m0 = [&](int m0, uint2 (&bl)[8], uint2 (&bn)[8]) {
                xl -= 32;
                #pragma unroll
                for (int k = 0; k < 8; k++) {
                    const uint32_t a0 = w[1], a1 = __byte_perm(w[0], w[1], 0x5432), a2 = w[2], a3 = __byte_perm(w[1], w[2], 0x5432);
                    const uint32_t c0 = w[4], c1 = __byte_perm(w[3], w[4], 0x5432), c2 = w[5], c3 = __byte_perm(w[4], w[5], 0x5432);
                    const uint32_t nx = (k < 7) ? hl + (k + 1) * 256 : hl + 32;
                    w[0] = lds32(nx); w[1] = lds32(nx + 4); w[2] = lds32(nx + 8);
                    w[3] = lds32(nx + 2048); w[4] = lds32(nx + 2052); w[5] = lds32(nx + 2056);
                    if (k > 0) bn[k] = lds64(xl + k * 256);
                    else { bn[0] = make_uint2(0, 0); if (g > m0) bn[0] = lds64(xl); }
                    #pragma unroll
                    for (int jj = k; jj < 16; jj++) mma16816(acc[jj], a0, a1, a2, a3, (jj - k < 8) ? bl[(jj - k) & 7] : bh[(jj - k) & 7]);
                    bh[7 - k] = lds64(xl + (15 - k) * 256);
                    #pragma unroll
                    for (int jj = k + 8; jj < 16; jj++) mma16816(acc[jj], c0, c1, c2, c3, bl[jj - k - 8]);
                }
                hl += 32;
            };
            #pragma unroll 1
            for (int m0 = 0; m0 < 8; m0 += 2) {
                conv_m0(m0, bl0, bl1);
                conv_m0(m0 + 1, bl1, bl0);
                PROFW(34 + (m0 >> 1), 4);
            }
            PROFW(33, 4);
            const uint32_t kvl = xb + c * 64 + (7 - g) * 4;
            uint32_t* ydst = (uint32_t*)(g_yT + (size_t)gch * SEQ + 32 * c + 2 * g);
            uint32_t kk0[16], kk1[16];
            #pragma unroll
            for (int jj = 0; jj < 16; jj++) { kk0[jj] = lds32(kvl + jj * 256); kk1[jj] = lds32(kvl + jj * 256 + 32); }
            #pragma unroll
            for (int jj = 0; jj < 16; jj++) {
                ydst[jj * 64] = badd2(pack_bf(acc[jj][2], acc[jj][0]), bmul2(__byte_perm(kk0[jj], kk0[jj], 0x1032), d2));
                ydst[jj * 64 + 8] = badd2(pack_bf(acc[jj][3], acc[jj][1]), bmul2(__byte_perm(kk1[jj], kk1[jj], 0x1032), d2));
            }
            __syncwarp();
            PROFW(44, 4);
            if (lane == 0) mbar_arrive(sb + SM_BARS + B_YST * 8);
        } else {
            gemm1_pass<4, false>(sb, wgi, warp4, lane, st, fph, e_cl, hp, hdst + 4 * j * 2048, false);
            float acc[64];
            const uint64_t descB0 = make_desc(sb, 4096, 1024, 1);
            const uint64_t descA0 = make_desc(sb + 16384 + wgi * 4096, 128, 256, 0);
            int sg = 3, p0 = 0; uint32_t ph = 6;
            PROFW(20, 0);
            auto g2 = [&](int u) {
                if (warp == 0 && !(u & 1)) PROF2(2, 16 + (u >> 1));
                mbar_wait(sb + SM_BARS + (B_FULL + sg) * 8, (ph >> sg) & 1);
                ph ^= 1u << sg;
                if (warp == 0 && !(u & 1)) PROF2(1, 16 + (u >> 1));
                const uint32_t o0 = stage_off_rt(sg) >> 4;
                const uint64_t da0 = desc_add(descA0, o0), db0 = desc_add(descB0, o0);
                WG_FENCE();
                #pragma unroll
                for (int kk = 0; kk < 4; kk++) wgmma_ss_n128_tb(acc, da0 + ((kk >> 1) * 512 + (kk & 1) * 128), db0 + ((kk >> 1) * 512 + (kk & 1) * 128), (u | kk) ? 1 : 0);
                WG_COMMIT();
                wg_wait<1>();
                if (warp == 0 && !(u & 1)) PROF2(3, 16 + (u >> 1));
                if (lane < 2 && u > 0 && u + 4 < 28) mbar_arrive_cluster(e_cl + p0 * 8, 1);
                p0 = sg;
                sg = next_st2(sg);
            };
            #pragma unroll
            for (int u = 0; u < 4; u++) { g2(u); store_h(hdst + (32 + 6 * cb) * 2048, hp, u); }
            __syncwarp();
            if (lane == 0) mbar_arrive(sb + SM_BARS + (B_HD + wgi * 2 + 1) * 8);
            #pragma unroll 1
            for (int u = 4; u < 28; u++) g2(u);
            wg_wait<0>();
            PROFW(27, 0);
            mbar_wait(sb + SM_BARS + B_XR * 8, 0);
            const int r0 = wgi * 64 + warp4 * 16 + g;
            const float2 st0 = lds64f(sb + SM_STATS + r0 * 8), st1 = lds64f(sb + SM_STATS + (r0 + 8) * 8);
            const uint32_t m0 = __float_as_uint(st0.x), m1 = __float_as_uint(st1.x);
            const uint32_t xrow0 = sb + SM_XE + r0 * 128 + c * 4;
            const int mi = lane >> 3, lr = lane & 7;
            const uint32_t yaddr = sb + SM_YT + wgi * 16384 + ((mi >> 1) * 8 + lr) * 128 + (((2 * warp4 + (mi & 1)) ^ lr) << 4);
            uint32_t y[8][4], xv[16][2], nv[16][2], bv[16][2];
            #pragma unroll
            for (int t = 0; t < 16; t++) {
                const uint32_t off = (t >> 3) * 16384 + (((t & 7) ^ g) << 4);
                xv[t][0] = lds32(xrow0 + off); xv[t][1] = lds32(xrow0 + 1024 + off);
            }
            #pragma unroll
            for (int t = 0; t < 16; t++) {
                const uint32_t d0 = bsub2(xv[t][0], m0), d1 = bsub2(xv[t][1], m1);
                nv[t][0] = pack_bf(bf_lo(d0) * st0.y, bf_hi(d0) * st0.y); nv[t][1] = pack_bf(bf_lo(d1) * st1.y, bf_hi(d1) * st1.y);
                bv[t][0] = pack_bf(acc[4 * t], acc[4 * t + 1]); bv[t][1] = pack_bf(acc[4 * t + 2], acc[4 * t + 3]);
            }
            mbar_wait(sb + SM_BARS + B_YT * 8, 0);
            PROFW(28, 0);
            #pragma unroll
            for (int t2 = 0; t2 < 8; t2++)
                asm volatile("ldmatrix.sync.aligned.m8n8.x4.trans.shared.b16 {%0,%1,%2,%3}, [%4];"
                    : "=r"(y[t2][0]), "=r"(y[t2][1]), "=r"(y[t2][2]), "=r"(y[t2][3]) : "r"(yaddr + t2 * 2048) : "memory");
            #pragma unroll
            for (int t = 0; t < 16; t++) {
                const uint32_t off = (t >> 3) * 16384 + (((t & 7) ^ g) << 4);
                sts32(xrow0 + off, badd2(badd2(xv[t][0], bmul2(nv[t][0], y[t >> 1][2 * (t & 1)])), bv[t][0]));
                sts32(xrow0 + 1024 + off, badd2(badd2(xv[t][1], bmul2(nv[t][1], y[t >> 1][2 * (t & 1) + 1])), bv[t][1]));
            }
            asm volatile("fence.proxy.async.shared::cta;" ::: "memory");
            named_bar(1 + wgi, 128);
            if ((tid & 127) == 0) {
                tma2d_store(&p.tm_out, 128 * cb, 128 * i + 64 * wgi, sb + SM_XE + wgi * 8192);
                tma2d_store(&p.tm_out, 128 * cb + 64, 128 * i + 64 * wgi, sb + SM_XE + 16384 + wgi * 8192);
                asm volatile("cp.async.bulk.commit_group;" ::: "memory");
                asm volatile("cp.async.bulk.wait_group.read 0;" ::: "memory");
                PROFW(29, 0);
            }
        }
    } else {
        asm volatile("setmaxnreg.dec.sync.aligned.u32 104;");
        if (warp == 8) {
            int st = 0; uint32_t eph = 7;
            #pragma unroll 1
            for (int it = 0; it < 16; it++) {
                const int pass = it >> 3, sl = it & 7;
                const bool narrow = pass && convCTA;
                const int nb = narrow ? 2 : 4;
                const CUtensorMap* tm = narrow ? (rank ? &p.tm_uB : &p.tm_gB) : (rank ? &p.tm_uA : &p.tm_gA);
                mbar_wait(sb + SM_BARS + (B_EMPTY + st) * 8, (eph >> st) & 1);
                eph ^= 1u << st;
                if (it == 1) mbar_wait(sb + SM_BARS + B_XFULL * 8, 0);
                PROF2(0, it);
                if (elect_one()) {
                    mbar_expect_tx(sb + SM_BARS + (B_FULL + st) * 8, nb * 8192);
                    tma3d_mc(sb + SM_RING + st * STAGE_BYTES + rank * nb * 4096, tm, 0, sl * 64, 14 * cb + 8 * (j & 1) + 4 * pass, sb + SM_BARS + (B_FULL + st) * 8);
                }
                st = (st == 2) ? 0 : st + 1;
            }
            if (!convCTA) {
                st = 3;
                const int f0_lane = blk_f0(2 * lane + rank);
                #pragma unroll 1
                for (int u = 0; u < 28; u++) {
                    const uint32_t bar = sb + SM_BARS + (B_FULL + st) * 8;
                    const int f0 = __shfl_sync(0xffffffffu, f0_lane, u);
                    mbar_wait(sb + SM_BARS + (B_EMPTY + st) * 8, (eph >> st) & 1);
                    eph ^= 1u << st;
                    if ((u & 1) == 0) PROF2(0, 16 + (u >> 1));
                    if (elect_one()) {
                        mbar_expect_tx(bar, 32768);
                        tma3d_mc(sb + stage_off_rt(st) + rank * 8192, &p.tm_w2, 0, f0, 2 * cb, bar);
                    }
                    st = next_st2(st);
                }
                PROF(48);
            }
        } else if (warp < 11) {
            mbar_wait(sb + SM_BARS + (B_XFULL + 1) * 8, 0);
            {
                const int q = lane & 3;
                const int t0 = 32 * (b >> 1) + 8 * q;
                const int ch0 = 256 * (b & 1) + 16 * (warp - 9) + 2 * (lane >> 2);
                const uint32_t* kp = (const uint32_t*)(p.k + (size_t)t0 * DM + ch0);
                const uint32_t* vp = (const uint32_t*)(p.v + (size_t)t0 * DM + ch0);
                __nv_bfloat16* dst0 = g_kvT + (size_t)ch0 * SEQ + (t0 ^ 8);
                #pragma unroll 1
                for (int rnd = 0; rnd < 2; rnd++) {
                    uint32_t kr[4][11], vr[4][8]; uint4 skw[4];
                    #pragma unroll
                    for (int u = 0; u < 4; u++) {
                        const int co = (rnd * 4 + u) * 16;
                        skw[u] = ldg_nc128(p.shift_k + 4 * (ch0 + 2 * co));
                        #pragma unroll
                        for (int r = 0; r < 11; r++) kr[u][r] = (r >= 3 || t0 > 0) ? ldg_nc32(kp + co + (r - 3) * (DM / 2)) : 0u;
                        #pragma unroll
                        for (int r = 0; r < 8; r++) vr[u][r] = ldg_nc32(vp + co + r * (DM / 2));
                    }
                    #pragma unroll
                    for (int u = 0; u < 4; u++) {
                        const uint32_t s0 = __byte_perm(skw[u].x, skw[u].z, 0x5410), s1 = __byte_perm(skw[u].x, skw[u].z, 0x7632);
                        const uint32_t s2 = __byte_perm(skw[u].y, skw[u].w, 0x5410), s3 = __byte_perm(skw[u].y, skw[u].w, 0x7632);
                        #pragma unroll
                        for (int r = 0; r < 8; r++) {
                            uint32_t a = bmul2(kr[u][r], s3);
                            a = badd2(a, bmul2(kr[u][r + 1], s2));
                            a = badd2(a, bmul2(kr[u][r + 2], s1));
                            a = badd2(a, bmul2(kr[u][r + 3], s0));
                            vr[u][r] = bmul2(a, vr[u][r]);
                        }
                        __nv_bfloat16* dst = dst0 + (size_t)((rnd * 4 + u) * 32) * SEQ;
                        *(uint4*)dst = make_uint4(__byte_perm(vr[u][7], vr[u][6], 0x5410), __byte_perm(vr[u][5], vr[u][4], 0x5410),
                                                  __byte_perm(vr[u][3], vr[u][2], 0x5410), __byte_perm(vr[u][1], vr[u][0], 0x5410));
                        *(uint4*)(dst + SEQ) = make_uint4(__byte_perm(vr[u][7], vr[u][6], 0x7632), __byte_perm(vr[u][5], vr[u][4], 0x7632),
                                                          __byte_perm(vr[u][3], vr[u][2], 0x7632), __byte_perm(vr[u][1], vr[u][0], 0x7632));
                    }
                    PROFW(57 + 2 * rnd, 9);
                }
                if (lane == 0) mbar_arrive(sb + SM_BARS + B_KVLD * 8);
            }
            asm volatile("fence.proxy.async.global;" ::: "memory");
            __syncwarp();
            if (lane == 0) {
                flag_add(&g_cnt_kv[0]);
                PROFW(50, 9);
                const int wgi = warp - 9;
                mbar_wait(sb + SM_BARS + (B_HD + wgi * 2) * 8, 0);
                flag_add(&g_flag_h[(i * 2 + 0) * 8]);
                mbar_wait(sb + SM_BARS + (B_HD + wgi * 2 + 1) * 8, 0);
                flag_add(&g_flag_h[(i * 2 + 1) * 8]);
                if (wgi == 1 && convCTA) {
                    mbar_wait(sb + SM_BARS + B_YST * 8, 0);
                    flag_add(&g_cnt_y[(cidx >> 4) * 32]);
                    PROF(46);
                }
                if (wgi == 1 && !convCTA) {
                    const unsigned ep = lds32(sb + SM_EPOCH);
                    mbar_wait(sb + SM_BARS + B_G1DONE * 8, 0);
                    mbar_expect_tx(sb + SM_BARS + B_XR * 8, 32768);
                    tma3d(sb + SM_XE, &p.tm_xe, 0, 128 * i, 2 * cb, sb + SM_BARS + B_XR * 8);
                    flag_wait(&g_flag_h[(i * 2 + 1) * 8], ep * 16);
                    mbar_arrive(sb + SM_BARS + (B_HRDY + 1) * 8);
                    __nanosleep(3000);
                    flag_wait(&g_cnt_y[cb * 32], ep * 16);
                    PROF(49);
                    asm volatile("fence.proxy.async.global;" ::: "memory");
                    mbar_expect_tx(sb + SM_BARS + B_YT * 8, 32768);
                    tma2d(sb + SM_YT, &p.tm_yT, 128 * i, 128 * cb, sb + SM_BARS + B_YT * 8);
                    tma2d(sb + SM_YT + 16384, &p.tm_yT, 128 * i + 64, 128 * cb, sb + SM_BARS + B_YT * 8);
                }
            }
        } else {
            if (lane == 0) {
                l2_prefetch(p.wg + (size_t)b * (FF * DM / NCTA), FF * DM / NCTA * 2);
                l2_prefetch(p.wu + (size_t)b * (FF * DM / NCTA), FF * DM / NCTA * 2);
                const unsigned ep = g_launch[b] + 1;
                g_launch[b] = ep;
                sts32(sb + SM_EPOCH, ep);
                tmap_prefetch(rank ? &p.tm_uA : &p.tm_gA);
                tmap_prefetch(rank ? &p.tm_uB : &p.tm_gB);
                tmap_prefetch(&p.tm_w2); tmap_prefetch(&p.tm_yT); tmap_prefetch(&p.tm_out); tmap_prefetch(&p.tm_xe);
                mbar_wait(sb + SM_BARS + B_KVLD * 8, 0);
                l2_prefetch(p.ssm_k + (size_t)(4 * b) * SEQ, 4 * SEQ * 2);
                l2_prefetch(p.wd + (size_t)b * (FF * DM / NCTA), FF * DM / NCTA * 2);
                mbar_wait(sb + SM_BARS + (B_HD + 0) * 8, 0);
                if (convCTA) {
                    flag_wait(&g_cnt_kv[0], ep * 256);
                    asm volatile("fence.proxy.async.global;" ::: "memory");
                    PROF(53);
                    mbar_wait(sb + SM_BARS + B_XFREE * 8, 0);
                    PROF(54);
                    mbar_expect_tx(sb + SM_BARS + B_CONV * 8, 65536);
                    bulk_g2s(sb + SM_CVX, g_kvT + (size_t)(8 * cidx) * SEQ, 32768, sb + SM_BARS + B_CONV * 8);
                    bulk_g2s(sb + SM_CVH, p.ssm_k + (size_t)(8 * cidx) * SEQ, 32768, sb + SM_BARS + B_CONV * 8);
                } else {
                    flag_wait(&g_flag_h[(i * 2 + 0) * 8], ep * 16);
                }
            }
            __syncwarp();
            if (!convCTA) {
                asm volatile("fence.proxy.async.global;" ::: "memory");
                int st = 3; uint32_t eph = 1;
                const uint8_t* hsrc = (const uint8_t*)g_h + (size_t)i * 56 * 8192;
                #pragma unroll 1
                for (int u = 0; u < 28; u++) {
                    mbar_wait(sb + SM_BARS + (B_EMPTY + st) * 8, (eph >> st) & 1);
                    eph ^= 1u << st;
                    if (u == 16) {
                        mbar_wait(sb + SM_BARS + (B_HRDY + 1) * 8, 0);
                        asm volatile("fence.proxy.async.global;" ::: "memory");
                    }
                    if (elect_one()) bulk_g2s(sb + stage_off_rt(st) + 16384, hsrc + u * 16384, 16384, sb + SM_BARS + (B_FULL + st) * 8);
                    st = next_st2(st);
                }
            }
        }
    }
}

typedef CUresult (*EncodeFn)(CUtensorMap*, CUtensorMapDataType, cuuint32_t, void*, const cuuint64_t*, const cuuint64_t*,
                             const cuuint32_t*, const cuuint32_t*, CUtensorMapInterleave, CUtensorMapSwizzle,
                             CUtensorMapL2promotion, CUtensorMapFloatOOBfill);

void encode(EncodeFn fn, CUtensorMap* tm, const void* base, int rank, const cuuint64_t* dims, const cuuint64_t* strides,
            const cuuint32_t* box, CUtensorMapSwizzle swz) {
    cuuint32_t es[5] = {1, 1, 1, 1, 1};
    fn(tm, CU_TENSOR_MAP_DATA_TYPE_BFLOAT16, rank, (void*)base, dims, strides, box, es, CU_TENSOR_MAP_INTERLEAVE_NONE, swz,
       CU_TENSOR_MAP_L2_PROMOTION_L2_128B, CU_TENSOR_MAP_FLOAT_OOB_FILL_NONE);
}

}

extern "C" void kernel_launch(void* const* d_in, const int* in_sizes, int n_in, void* d_out, int out_size) {
    (void)in_sizes; (void)n_in; (void)out_size;
    static EncodeFn enc = nullptr;
    static void* yT_ptr = nullptr;
    if (!enc) {
        void* fn = nullptr; cudaDriverEntryPointQueryResult qr;
        cudaGetDriverEntryPoint("cuTensorMapEncodeTiled", &fn, cudaEnableDefault, &qr);
        enc = (EncodeFn)fn;
        cudaGetSymbolAddress(&yT_ptr, g_yT);
        cudaFuncSetAttribute(fused_kernel, cudaFuncAttributeMaxDynamicSharedMemorySize, SM_TOTAL);
    }
    Params p;
    p.q = (const __nv_bfloat16*)d_in[0]; p.k = (const __nv_bfloat16*)d_in[1]; p.v = (const __nv_bfloat16*)d_in[2];
    p.shift_k = (const __nv_bfloat16*)d_in[3]; p.ssm_k = (const __nv_bfloat16*)d_in[4]; p.ssm_D = (const __nv_bfloat16*)d_in[5];
    p.wg = (const __nv_bfloat16*)d_in[7]; p.wu = (const __nv_bfloat16*)d_in[8]; p.wd = (const __nv_bfloat16*)d_in[9];
    {
        cuuint64_t dims[2] = {DM, SEQ}; cuuint64_t str[1] = {DM * 2};
        cuuint64_t dims3[3] = {64, SEQ, DM / 64}; cuuint64_t str3[2] = {DM * 2, 128};
        cuuint32_t box[3] = {64, 64, 8}, boxe[3] = {64, 128, 2};
        encode(enc, &p.tm_x, p.q, 3, dims3, str3, box, CU_TENSOR_MAP_SWIZZLE_128B);
        encode(enc, &p.tm_xe, p.q, 3, dims3, str3, boxe, CU_TENSOR_MAP_SWIZZLE_128B);
        cuuint32_t box2[2] = {64, 64};
        encode(enc, &p.tm_out, d_out, 2, dims, str, box2, CU_TENSOR_MAP_SWIZZLE_128B);
    }
    {
        cuuint64_t dims[3] = {32, DM, FF / 32}; cuuint64_t str[2] = {FF * 2, 64};
        cuuint32_t boxA[3] = {32, 64, 4}, boxB[3] = {32, 64, 2};
        encode(enc, &p.tm_gA, p.wg, 3, dims, str, boxA, CU_TENSOR_MAP_SWIZZLE_64B);
        encode(enc, &p.tm_gB, p.wg, 3, dims, str, boxB, CU_TENSOR_MAP_SWIZZLE_64B);
        encode(enc, &p.tm_uA, p.wu, 3, dims, str, boxA, CU_TENSOR_MAP_SWIZZLE_64B);
        encode(enc, &p.tm_uB, p.wu, 3, dims, str, boxB, CU_TENSOR_MAP_SWIZZLE_64B);
    }
    {
        cuuint64_t dims[3] = {64, FF, DM / 64}; cuuint64_t str[2] = {DM * 2, 128};
        cuuint32_t box[3] = {64, 32, 2};
        encode(enc, &p.tm_w2, p.wd, 3, dims, str, box, CU_TENSOR_MAP_SWIZZLE_128B);
    }
    {
        cuuint64_t dims[2] = {SEQ, DM}; cuuint64_t str[1] = {SEQ * 2};
        cuuint32_t box[2] = {64, 128};
        encode(enc, &p.tm_yT, yT_ptr, 2, dims, str, box, CU_TENSOR_MAP_SWIZZLE_128B);
    }
    fused_kernel<<<NCTA, NTHREADS, SM_TOTAL>>>(p);
}
```

```cpp
#include <cuda_runtime.h>
#include <cuda_bf16.h>
#include <cuda.h>
#include <stdint.h>

namespace {

constexpr int SEQ = 2048, DM = 512, FF = 1792;
constexpr int NCTA = 128;
constexpr int NTHREADS = 384;
constexpr int STAGE_BYTES = 32768;
#define KV_STAGGER 300
#define KV_GAP 150

constexpr uint32_t SM_X = 0;
constexpr uint32_t SM_RING = 131072;
constexpr uint32_t SM_MISC = SM_RING + 3 * STAGE_BYTES;
constexpr uint32_t SM_BARS = SM_MISC;
constexpr uint32_t SM_EPOCH = SM_MISC + 248;
constexpr uint32_t SM_STATS = SM_MISC + 256;
constexpr uint32_t SM_TOTAL = SM_STATS + 1024;
static_assert(SM_TOTAL <= 232448, "smem");
constexpr uint32_t SM_CVX = 0;
constexpr uint32_t SM_CVH = 65536;
constexpr uint32_t SM_YT = 32768;
constexpr uint32_t SM_XE = 98304;

constexpr int B_FULL = 0, B_EMPTY = 5, B_XFULL = 10, B_CONV = 14, B_YT = 15, B_XR = 16, B_G1DONE = 17, B_HD = 18, B_HRDY = 22,
              B_XFREE = 24, B_YST = 25, B_KVLD = 26, B_LN = 27, B_COUNT = 28;
static_assert(B_COUNT * 8 <= 248, "barrier space");

__device__ __align__(128) uint32_t g_h[16 * 56 * 2048];
__device__ __align__(128) __nv_bfloat16 g_kvT[DM * SEQ];
__device__ __align__(128) __nv_bfloat16 g_yT[DM * SEQ];
__device__ unsigned g_launch[NCTA];
__device__ unsigned g_cnt_kv[32];
__device__ unsigned g_cnt_y[4 * 32];
__device__ unsigned g_flag_h[16 * 2 * 8];

#define PROF(idx)
#define PROF2(a, idx)
#define PROFW(idx, w)

struct Params {
    CUtensorMap tm_x, tm_gA, tm_gB, tm_uA, tm_uB, tm_w2, tm_yT, tm_out, tm_xe;
    const __nv_bfloat16 *q, *k, *v, *shift_k, *ssm_k, *ssm_D, *wg, *wu, *wd;
};

__device__ __forceinline__ void wgmma_rs_n32(float (&d)[16], uint32_t a0, uint32_t a1, uint32_t a2, uint32_t a3, uint64_t db, int sc) {
  asm volatile("{\n.reg .pred p;\nsetp.ne.b32 p, %21, 0;\n"
    "wgmma.mma_async.sync.aligned.m64n32k16.f32.bf16.bf16 {%0,%1,%2,%3,%4,%5,%6,%7,%8,%9,%10,%11,%12,%13,%14,%15}, {%16,%17,%18,%19}, %20, p, 1, 1, 0;\n}\n"
    : "+f"(d[0]),"+f"(d[1]),"+f"(d[2]),"+f"(d[3]),"+f"(d[4]),"+f"(d[5]),"+f"(d[6]),"+f"(d[7]),"+f"(d[8]),"+f"(d[9]),"+f"(d[10]),"+f"(d[11]),"+f"(d[12]),"+f"(d[13]),"+f"(d[14]),"+f"(d[15])
    : "r"(a0),"r"(a1),"r"(a2),"r"(a3),"l"(db),"r"(sc));
}
__device__ __forceinline__ void wgmma_rs_n128_tb(float (&d)[64], uint32_t a0, uint32_t a1, uint32_t a2, uint32_t a3, uint64_t db, int sc) {
  asm volatile("{\n.reg .pred p;\nsetp.ne.b32 p, %69, 0;\n"
    "wgmma.mma_async.sync.aligned.m64n128k16.f32.bf16.bf16 {%0,%1,%2,%3,%4,%5,%6,%7,%8,%9,%10,%11,%12,%13,%14,%15,%16,%17,%18,%19,%20,%21,%22,%23,%24,%25,%26,%27,%28,%29,%30,%31,%32,%33,%34,%35,%36,%37,%38,%39,%40,%41,%42,%43,%44,%45,%46,%47,%48,%49,%50,%51,%52,%53,%54,%55,%56,%57,%58,%59,%60,%61,%62,%63}, {%64,%65,%66,%67}, %68, p, 1, 1, 1;\n}\n"
    : "+f"(d[0]),"+f"(d[1]),"+f"(d[2]),"+f"(d[3]),"+f"(d[4]),"+f"(d[5]),"+f"(d[6]),"+f"(d[7]),"+f"(d[8]),"+f"(d[9]),"+f"(d[10]),"+f"(d[11]),"+f"(d[12]),"+f"(d[13]),"+f"(d[14]),"+f"(d[15]),"+f"(d[16]),"+f"(d[17]),"+f"(d[18]),"+f"(d[19]),"+f"(d[20]),"+f"(d[21]),"+f"(d[22]),"+f"(d[23]),"+f"(d[24]),"+f"(d[25]),"+f"(d[26]),"+f"(d[27]),"+f"(d[28]),"+f"(d[29]),"+f"(d[30]),"+f"(d[31]),"+f"(d[32]),"+f"(d[33]),"+f"(d[34]),"+f"(d[35]),"+f"(d[36]),"+f"(d[37]),"+f"(d[38]),"+f"(d[39]),"+f"(d[40]),"+f"(d[41]),"+f"(d[42]),"+f"(d[43]),"+f"(d[44]),"+f"(d[45]),"+f"(d[46]),"+f"(d[47]),"+f"(d[48]),"+f"(d[49]),"+f"(d[50]),"+f"(d[51]),"+f"(d[52]),"+f"(d[53]),"+f"(d[54]),"+f"(d[55]),"+f"(d[56]),"+f"(d[57]),"+f"(d[58]),"+f"(d[59]),"+f"(d[60]),"+f"(d[61]),"+f"(d[62]),"+f"(d[63])
    : "r"(a0),"r"(a1),"r"(a2),"r"(a3),"l"(db),"r"(sc));
}
__device__ __forceinline__ void wgmma_ss_n256_tb(float (&d)[128], uint64_t da, uint64_t db, int sc) {
  asm volatile("{\n.reg .pred p;\nsetp.ne.b32 p, %130, 0;\n"
    "wgmma.mma_async.sync.aligned.m64n256k16.f32.bf16.bf16 {%0,%1,%2,%3,%4,%5,%6,%7,%8,%9,%10,%11,%12,%13,%14,%15,%16,%17,%18,%19,%20,%21,%22,%23,%24,%25,%26,%27,%28,%29,%30,%31,%32,%33,%34,%35,%36,%37,%38,%39,%40,%41,%42,%43,%44,%45,%46,%47,%48,%49,%50,%51,%52,%53,%54,%55,%56,%57,%58,%59,%60,%61,%62,%63,%64,%65,%66,%67,%68,%69,%70,%71,%72,%73,%74,%75,%76,%77,%78,%79,%80,%81,%82,%83,%84,%85,%86,%87,%88,%89,%90,%91,%92,%93,%94,%95,%96,%97,%98,%99,%100,%101,%102,%103,%104,%105,%106,%107,%108,%109,%110,%111,%112,%113,%114,%115,%116,%117,%118,%119,%120,%121,%122,%123,%124,%125,%126,%127}, %128, %129, p, 1, 1, 0, 1;\n}\n"
    : "+f"(d[0]),"+f"(d[1]),"+f"(d[2]),"+f"(d[3]),"+f"(d[4]),"+f"(d[5]),"+f"(d[6]),"+f"(d[7]),"+f"(d[8]),"+f"(d[9]),"+f"(d[10]),"+f"(d[11]),"+f"(d[12]),"+f"(d[13]),"+f"(d[14]),"+f"(d[15]),"+f"(d[16]),"+f"(d[17]),"+f"(d[18]),"+f"(d[19]),"+f"(d[20]),"+f"(d[21]),"+f"(d[22]),"+f"(d[23]),"+f"(d[24]),"+f"(d[25]),"+f"(d[26]),"+f"(d[27]),"+f"(d[28]),"+f"(d[29]),"+f"(d[30]),"+f"(d[31]),"+f"(d[32]),"+f"(d[33]),"+f"(d[34]),"+f"(d[35]),"+f"(d[36]),"+f"(d[37]),"+f"(d[38]),"+f"(d[39]),"+f"(d[40]),"+f"(d[41]),"+f"(d[42]),"+f"(d[43]),"+f"(d[44]),"+f"(d[45]),"+f"(d[46]),"+f"(d[47]),"+f"(d[48]),"+f"(d[49]),"+f"(d[50]),"+f"(d[51]),"+f"(d[52]),"+f"(d[53]),"+f"(d[54]),"+f"(d[55]),"+f"(d[56]),"+f"(d[57]),"+f"(d[58]),"+f"(d[59]),"+f"(d[60]),"+f"(d[61]),"+f"(d[62]),"+f"(d[63]),"+f"(d[64]),"+f"(d[65]),"+f"(d[66]),"+f"(d[67]),"+f"(d[68]),"+f"(d[69]),"+f"(d[70]),"+f"(d[71]),"+f"(d[72]),"+f"(d[73]),"+f"(d[74]),"+f"(d[75]),"+f"(d[76]),"+f"(d[77]),"+f"(d[78]),"+f"(d[79]),"+f"(d[80]),"+f"(d[81]),"+f"(d[82]),"+f"(d[83]),"+f"(d[84]),"+f"(d[85]),"+f"(d[86]),"+f"(d[87]),"+f"(d[88]),"+f"(d[89]),"+f"(d[90]),"+f"(d[91]),"+f"(d[92]),"+f"(d[93]),"+f"(d[94]),"+f"(d[95]),"+f"(d[96]),"+f"(d[97]),"+f"(d[98]),"+f"(d[99]),"+f"(d[100]),"+f"(d[101]),"+f"(d[102]),"+f"(d[103]),"+f"(d[104]),"+f"(d[105]),"+f"(d[106]),"+f"(d[107]),"+f"(d[108]),"+f"(d[109]),"+f"(d[110]),"+f"(d[111]),"+f"(d[112]),"+f"(d[113]),"+f"(d[114]),"+f"(d[115]),"+f"(d[116]),"+f"(d[117]),"+f"(d[118]),"+f"(d[119]),"+f"(d[120]),"+f"(d[121]),"+f"(d[122]),"+f"(d[123]),"+f"(d[124]),"+f"(d[125]),"+f"(d[126]),"+f"(d[127])
    : "l"(da),"l"(db),"r"(sc));
}
__device__ __forceinline__ void wgmma_ss_n192_tb(float (&d)[96], uint64_t da, uint64_t db, int sc) {
  asm volatile("{\n.reg .pred p;\nsetp.ne.b32 p, %98, 0;\n"
    "wgmma.mma_async.sync.aligned.m64n192k16.f32.bf16.bf16 {%0,%1,%2,%3,%4,%5,%6,%7,%8,%9,%10,%11,%12,%13,%14,%15,%16,%17,%18,%19,%20,%21,%22,%23,%24,%25,%26,%27,%28,%29,%30,%31,%32,%33,%34,%35,%36,%37,%38,%39,%40,%41,%42,%43,%44,%45,%46,%47,%48,%49,%50,%51,%52,%53,%54,%55,%56,%57,%58,%59,%60,%61,%62,%63,%64,%65,%66,%67,%68,%69,%70,%71,%72,%73,%74,%75,%76,%77,%78,%79,%80,%81,%82,%83,%84,%85,%86,%87,%88,%89,%90,%91,%92,%93,%94,%95}, %96, %97, p, 1, 1, 0, 1;\n}\n"
    : "+f"(d[0]),"+f"(d[1]),"+f"(d[2]),"+f"(d[3]),"+f"(d[4]),"+f"(d[5]),"+f"(d[6]),"+f"(d[7]),"+f"(d[8]),"+f"(d[9]),"+f"(d[10]),"+f"(d[11]),"+f"(d[12]),"+f"(d[13]),"+f"(d[14]),"+f"(d[15]),"+f"(d[16]),"+f"(d[17]),"+f"(d[18]),"+f"(d[19]),"+f"(d[20]),"+f"(d[21]),"+f"(d[22]),"+f"(d[23]),"+f"(d[24]),"+f"(d[25]),"+f"(d[26]),"+f"(d[27]),"+f"(d[28]),"+f"(d[29]),"+f"(d[30]),"+f"(d[31]),"+f"(d[32]),"+f"(d[33]),"+f"(d[34]),"+f"(d[35]),"+f"(d[36]),"+f"(d[37]),"+f"(d[38]),"+f"(d[39]),"+f"(d[40]),"+f"(d[41]),"+f"(d[42]),"+f"(d[43]),"+f"(d[44]),"+f"(d[45]),"+f"(d[46]),"+f"(d[47]),"+f"(d[48]),"+f"(d[49]),"+f"(d[50]),"+f"(d[51]),"+f"(d[52]),"+f"(d[53]),"+f"(d[54]),"+f"(d[55]),"+f"(d[56]),"+f"(d[57]),"+f"(d[58]),"+f"(d[59]),"+f"(d[60]),"+f"(d[61]),"+f"(d[62]),"+f"(d[63]),"+f"(d[64]),"+f"(d[65]),"+f"(d[66]),"+f"(d[67]),"+f"(d[68]),"+f"(d[69]),"+f"(d[70]),"+f"(d[71]),"+f"(d[72]),"+f"(d[73]),"+f"(d[74]),"+f"(d[75]),"+f"(d[76]),"+f"(d[77]),"+f"(d[78]),"+f"(d[79]),"+f"(d[80]),"+f"(d[81]),"+f"(d[82]),"+f"(d[83]),"+f"(d[84]),"+f"(d[85]),"+f"(d[86]),"+f"(d[87]),"+f"(d[88]),"+f"(d[89]),"+f"(d[90]),"+f"(d[91]),"+f"(d[92]),"+f"(d[93]),"+f"(d[94]),"+f"(d[95])
    : "l"(da),"l"(db),"r"(sc));
}

__device__ __forceinline__ uint32_t smem_u32(const void* p) { return (uint32_t)__cvta_generic_to_shared(p); }
__device__ __forceinline__ void mbar_init(uint32_t bar, uint32_t cnt) { asm volatile("mbarrier.init.shared::cta.b64 [%0], %1;" :: "r"(bar), "r"(cnt)); }
__device__ __forceinline__ void mbar_expect_tx(uint32_t bar, uint32_t bytes) { asm volatile("mbarrier.arrive.expect_tx.shared::cta.b64 _, [%0], %1;" :: "r"(bar), "r"(bytes) : "memory"); }
__device__ __forceinline__ void mbar_arrive(uint32_t bar) { asm volatile("mbarrier.arrive.shared::cta.b64 _, [%0];" :: "r"(bar) : "memory"); }
__device__ __forceinline__ void mbar_arrive_cluster(uint32_t cbar, uint32_t cnt) { asm volatile("mbarrier.arrive.shared::cluster.b64 _, [%0], %1;" :: "r"(cbar), "r"(cnt) : "memory"); }
__device__ __forceinline__ uint32_t mapa(uint32_t a, uint32_t rank) { uint32_t r; asm volatile("mapa.shared::cluster.u32 %0, %1, %2;" : "=r"(r) : "r"(a), "r"(rank)); return r; }
__device__ __forceinline__ void mbar_wait(uint32_t bar, uint32_t parity) {
    uint32_t ok; uint32_t n = 0;
    do {
        asm volatile("{\n.reg .pred p;\nmbarrier.try_wait.parity.shared::cta.b64 p, [%1], %2;\nselp.u32 %0, 1, 0, p;\n}" : "=r"(ok) : "r"(bar), "r"(parity) : "memory");
    } while (!ok && ++n < (1u << 17));
}
__device__ __forceinline__ void pace_wait(uint32_t a, uint32_t target) {
    uint32_t v, n = 0;
    do {
        asm volatile("ld.volatile.shared.u32 %0, [%1];" : "=r"(v) : "r"(a) : "memory");
        if (v < target) __nanosleep(150);
    } while (v < target && ++n < (1u << 14));
}
__device__ __forceinline__ void flag_wait(const unsigned* p, unsigned target) {
    unsigned v; uint32_t n = 0;
    while (true) {
        asm volatile("ld.acquire.gpu.global.u32 %0, [%1];" : "=r"(v) : "l"(p) : "memory");
        if ((int)(v - target) >= 0 || ++n >= (1u << 17)) break;
        __nanosleep(100);
    }
}
__device__ __forceinline__ void flag_add(unsigned* p) {
    asm volatile("fence.acq_rel.gpu;\nred.relaxed.gpu.global.add.u32 [%0], 1;" :: "l"(p) : "memory");
}
__device__ __forceinline__ uint64_t make_desc(uint32_t addr, uint32_t lbo, uint32_t sbo, uint32_t swz) {
    return (uint64_t)((addr & 0x3FFFF) >> 4) | ((uint64_t)((lbo & 0x3FFFF) >> 4) << 16) | ((uint64_t)((sbo & 0x3FFFF) >> 4) << 32) | ((uint64_t)swz << 62);
}
__device__ __forceinline__ uint64_t desc_add(uint64_t d, uint32_t off16) {
    return (d & 0xFFFFFFFF00000000ull) | (uint64_t)((uint32_t)d + off16);
}
__device__ __forceinline__ void tma2d(uint32_t dst, const CUtensorMap* tm, int c0, int c1, uint32_t bar) {
    asm volatile("cp.async.bulk.tensor.2d.shared::cluster.global.mbarrier::complete_tx::bytes [%0], [%1, {%3, %4}], [%2];"
        :: "r"(dst), "l"((uint64_t)tm), "r"(bar), "r"(c0), "r"(c1) : "memory");
}
__device__ __forceinline__ void tma3d(uint32_t dst, const CUtensorMap* tm, int c0, int c1, int c2, uint32_t bar) {
    asm volatile("cp.async.bulk.tensor.3d.shared::cluster.global.mbarrier::complete_tx::bytes [%0], [%1, {%3, %4, %5}], [%2];"
        :: "r"(dst), "l"((uint64_t)tm), "r"(bar), "r"(c0), "r"(c1), "r"(c2) : "memory");
}
__device__ __forceinline__ void tma3d_mc(uint32_t dst, const CUtensorMap* tm, int c0, int c1, int c2, uint32_t bar) {
    asm volatile("cp.async.bulk.tensor.3d.shared::cluster.global.mbarrier::complete_tx::bytes.multicast::cluster [%0], [%1, {%3, %4, %5}], [%2], %6;"
        :: "r"(dst), "l"((uint64_t)tm), "r"(bar), "r"(c0), "r"(c1), "r"(c2), "h"((uint16_t)3) : "memory");
}
__device__ __forceinline__ void bulk_g2s(uint32_t dst, const void* src, uint32_t bytes, uint32_t bar) {
    asm volatile("cp.async.bulk.shared::cluster.global.mbarrier::complete_tx::bytes [%0], [%1], %2, [%3];"
        :: "r"(dst), "l"(src), "r"(bytes), "r"(bar) : "memory");
}
__device__ __forceinline__ void bulk_s2g(void* dst, uint32_t src, uint32_t bytes) {
    asm volatile("cp.async.bulk.global.shared::cta.bulk_group [%0], [%1], %2;" :: "l"(dst), "r"(src), "r"(bytes) : "memory");
}
__device__ __forceinline__ void tma2d_store(const CUtensorMap* tm, int c0, int c1, uint32_t src) {
    asm volatile("cp.async.bulk.tensor.2d.global.shared::cta.bulk_group [%0, {%2, %3}], [%1];"
        :: "l"((uint64_t)tm), "r"(src), "r"(c0), "r"(c1) : "memory");
}
__device__ __forceinline__ void l2_prefetch(const void* p, uint32_t bytes) {
    asm volatile("cp.async.bulk.prefetch.L2.global [%0], %1;" :: "l"(p), "r"(bytes) : "memory");
}
__device__ __forceinline__ void tmap_prefetch(const CUtensorMap* tm) { asm volatile("prefetch.tensormap [%0];" :: "l"((uint64_t)tm) : "memory"); }
__device__ __forceinline__ uint32_t lds32(uint32_t a) { uint32_t v; asm volatile("ld.shared.u32 %0, [%1];" : "=r"(v) : "r"(a)); return v; }
__device__ __forceinline__ uint2 lds64(uint32_t a) { uint2 v; asm volatile("ld.shared.v2.u32 {%0,%1}, [%2];" : "=r"(v.x), "=r"(v.y) : "r"(a)); return v; }
__device__ __forceinline__ uint4 lds128(uint32_t a) { uint4 v; asm volatile("ld.shared.v4.u32 {%0,%1,%2,%3}, [%4];" : "=r"(v.x), "=r"(v.y), "=r"(v.z), "=r"(v.w) : "r"(a)); return v; }
__device__ __forceinline__ float2 lds64f(uint32_t a) { float2 v; asm volatile("ld.shared.v2.f32 {%0,%1}, [%2];" : "=f"(v.x), "=f"(v.y) : "r"(a)); return v; }
__device__ __forceinline__ void sts32(uint32_t a, uint32_t v) { asm volatile("st.shared.u32 [%0], %1;" :: "r"(a), "r"(v) : "memory"); }
__device__ __forceinline__ void sts128(uint32_t a, uint4 v) { asm volatile("st.shared.v4.u32 [%0], {%1,%2,%3,%4};" :: "r"(a), "r"(v.x), "r"(v.y), "r"(v.z), "r"(v.w) : "memory"); }
__device__ __forceinline__ uint4 ldg_cg128(const void* p) { uint4 v; asm volatile("ld.global.cg.v4.u32 {%0,%1,%2,%3}, [%4];" : "=r"(v.x), "=r"(v.y), "=r"(v.z), "=r"(v.w) : "l"(p)); return v; }
__device__ __forceinline__ uint4 ldg_nc128(const void* p) { uint4 v; asm volatile("ld.global.nc.L1::no_allocate.v4.u32 {%0,%1,%2,%3}, [%4];" : "=r"(v.x), "=r"(v.y), "=r"(v.z), "=r"(v.w) : "l"(p)); return v; }
__device__ __forceinline__ uint32_t ldg_nc32(const void* p) { uint32_t v; asm volatile("ld.global.nc.u32 %0, [%1];" : "=r"(v) : "l"(p)); return v; }
__device__ __forceinline__ uint2 ldg_nc64(const void* p) { uint2 v; asm volatile("ld.global.nc.L1::no_allocate.v2.u32 {%0,%1}, [%2];" : "=r"(v.x), "=r"(v.y) : "l"(p)); return v; }
#define WG_FENCE() asm volatile("wgmma.fence.sync.aligned;\n" ::: "memory")
#define WG_COMMIT() asm volatile("wgmma.commit_group.sync.aligned;\n" ::: "memory")
template<int N> __device__ __forceinline__ void wg_wait() { asm volatile("wgmma.wait_group.sync.aligned %0;\n" :: "n"(N) : "memory"); }
__device__ __forceinline__ bool elect_one() {
    uint32_t pr;
    asm volatile("{\n.reg .pred p;\nelect.sync _|p, 0xffffffff;\nselp.u32 %0, 1, 0, p;\n}" : "=r"(pr));
    return pr != 0;
}
__device__ __forceinline__ void named_bar(int id, int n) { asm volatile("bar.sync %0, %1;" :: "r"(id), "r"(n) : "memory"); }

__device__ __forceinline__ float bf_lo(uint32_t u) { return __uint_as_float(u << 16); }
__device__ __forceinline__ float bf_hi(uint32_t u) { return __uint_as_float(u & 0xFFFF0000u); }
__device__ __forceinline__ uint32_t pack_bf(float lo, float hi) { uint32_t r; asm("cvt.rn.bf16x2.f32 %0, %1, %2;" : "=r"(r) : "f"(hi), "f"(lo)); return r; }
__device__ __forceinline__ float bf_round(float x) { return __bfloat162float(__float2bfloat16_rn(x)); }
__device__ __forceinline__ uint32_t bmul2(uint32_t a, uint32_t b) { uint32_t r; asm("mul.rn.bf16x2 %0, %1, %2;" : "=r"(r) : "r"(a), "r"(b)); return r; }
__device__ __forceinline__ uint32_t badd2(uint32_t a, uint32_t b) { uint32_t r; asm("add.rn.bf16x2 %0, %1, %2;" : "=r"(r) : "r"(a), "r"(b)); return r; }
__device__ __forceinline__ uint32_t bsub2(uint32_t a, uint32_t b) { uint32_t r; asm("sub.rn.bf16x2 %0, %1, %2;" : "=r"(r) : "r"(a), "r"(b)); return r; }
__device__ __forceinline__ void mma16816(float (&d)[4], uint32_t a0, uint32_t a1, uint32_t a2, uint32_t a3, uint2 b) {
    asm volatile("mma.sync.aligned.m16n8k16.row.col.f32.bf16.bf16.f32 {%0,%1,%2,%3}, {%4,%5,%6,%7}, {%8,%9}, {%0,%1,%2,%3};\n"
        : "+f"(d[0]), "+f"(d[1]), "+f"(d[2]), "+f"(d[3]) : "r"(a0), "r"(a1), "r"(a2), "r"(a3), "r"(b.x), "r"(b.y));
}

template<int HS> __device__ __forceinline__ void xreduce(float (&v)[8], int lane) {
    const int up = lane & HS;
    #pragma unroll
    for (int e = 0; e < HS; e++) {
        float keep, send;
        asm("{\n.reg .pred p;\nsetp.ne.b32 p, %4, 0;\nselp.f32 %0, %3, %2, p;\nselp.f32 %1, %2, %3, p;\n}"
            : "=f"(keep), "=f"(send) : "f"(v[e]), "f"(v[e + HS]), "r"(up));
        v[e] = keep + __shfl_xor_sync(0xffffffffu, send, HS);
    }
}

__device__ __forceinline__ int blk_f0(int s) {
    if (s < 32) return 32 * (14 * (s >> 3) + 8 * ((s >> 2) & 1) + (s & 3));
    const int s2 = s - 32, c6 = (s2 * 11) >> 6, t = s2 - 6 * c6;
    return 32 * (14 * c6 + (t < 4 ? 4 + t : 8 + t));
}
__device__ __forceinline__ int next_st2(int s) { return (0x14023 >> (4 * s)) & 7; }
__device__ __forceinline__ uint32_t stage_off_rt(int s) { return s < 3 ? SM_RING + s * STAGE_BYTES : (uint32_t)(s - 3) * 65536; }

__device__ __forceinline__ void store_h(uint32_t* dst, const uint32_t (&hp)[32], int q) {
    #pragma unroll
    for (int kk = 0; kk < 2; kk++) {
        uint32_t* d2 = dst + q * 2048 + kk * 512;
        d2[0] = hp[8 * q + 4 * kk]; d2[64] = hp[8 * q + 4 * kk + 1]; d2[32] = hp[8 * q + 4 * kk + 2]; d2[96] = hp[8 * q + 4 * kk + 3];
    }
}
template<int NB, bool passA>
__device__ __forceinline__ void gemm1_pass(uint32_t sb, int wgi, int warp4, int lane, int& st, uint32_t& fph, uint32_t e_cl,
                                           uint32_t (&hp)[32], uint32_t* prev_dst, bool convCTA) {
    float acc[NB * 32];
    const uint64_t descA0 = make_desc(sb + SM_X + wgi * 65536, 16, 1024, 1);
    const uint64_t descB0 = make_desc(sb + SM_RING, 4096, 512, 2);
    int prev = 0;
    auto group = [&](int sl) {
        if (warp4 == 0 && wgi == 0) PROF2(2, sl + (passA ? 0 : 8));
        mbar_wait(sb + SM_BARS + (B_FULL + st) * 8, (fph >> st) & 1);
        fph ^= 1u << st;
        if (sl == 0 && warp4 == 0) PROF(2 + wgi * 8 + (passA ? 0 : 3));
        if (warp4 == 0 && wgi == 0) PROF2(1, sl + (passA ? 0 : 8));
        const uint64_t da = desc_add(descA0, sl * 512), db = desc_add(descB0, st * 2048);
        WG_FENCE();
        #pragma unroll
        for (int kk = 0; kk < 4; kk++) {
            int sc = (sl | kk) ? 1 : 0;
            if constexpr (NB == 4) wgmma_ss_n256_tb(acc, da + kk * 2, db + kk * 64, sc); else wgmma_ss_n128_tb(acc, da + kk * 2, db + kk * 64, sc);
        }
        WG_COMMIT();
        wg_wait<1>();
        if (warp4 == 0 && wgi == 0) PROF2(3, sl + (passA ? 0 : 8));
        if (lane < 2 && sl && (passA || !convCTA || sl < 6)) mbar_arrive_cluster(e_cl + prev * 8, 1);
        if (!passA && sl == 4) {
            if (convCTA) { if (lane == 0) mbar_arrive(sb + SM_BARS + B_XFREE * 8); }
            else if (lane < 4) mbar_arrive_cluster(e_cl + (3 + (lane >> 1)) * 8, 1);
        }
        prev = st;
        st = (st == 2) ? 0 : st + 1;
    };
    if constexpr (passA) {
        #pragma unroll 1
        for (int sl = 0; sl < 8; sl++) group(sl);
    } else {
        #pragma unroll
        for (int sl = 0; sl < 4; sl++) { group(sl); store_h(prev_dst, hp, sl); }
        __syncwarp();
        if (lane == 0) mbar_arrive(sb + SM_BARS + (B_HD + wgi * 2) * 8);
        #pragma unroll 1
        for (int sl = 4; sl < 8; sl++) group(sl);
    }
    wg_wait<0>();
    if (lane < 2 && (passA || !convCTA)) mbar_arrive_cluster(e_cl + prev * 8, 1);
    if (!passA && lane == 0) mbar_arrive(sb + SM_BARS + B_G1DONE * 8);
    if (warp4 == 0) PROF(3 + wgi * 8 + (passA ? 0 : 3));
    const int g = lane >> 2;
    const int r0 = wgi * 64 + warp4 * 16 + g;
    const float s0 = __uint_as_float(lds32(sb + SM_STATS + r0 * 8 + 4)), s1 = __uint_as_float(lds32(sb + SM_STATS + (r0 + 8) * 8 + 4));
    #pragma unroll
    for (int t = 0; t < NB * 4; t++) {
        const float* ag = &acc[4 * t];
        const float* au = &acc[NB * 16 + 4 * t];
        hp[2 * t] = bmul2(pack_bf(ag[0] * s0, ag[1] * s0), pack_bf(au[0] * s0, au[1] * s0));
        hp[2 * t + 1] = bmul2(pack_bf(ag[2] * s1, ag[3] * s1), pack_bf(au[2] * s1, au[3] * s1));
    }
    if (warp4 == 0) PROF(4 + wgi * 8 + (passA ? 0 : 3));
}

__global__ void __cluster_dims__(2, 1, 1) __launch_bounds__(NTHREADS, 1)
fused_kernel(const __grid_constant__ Params p) {
    extern __shared__ __align__(1024) uint8_t smem_raw[];
    const uint32_t sb = smem_u32(smem_raw);
    const int tid = threadIdx.x, warp = tid >> 5, lane = tid & 31;
    const int b = blockIdx.x;
    const int rank = b & 1;
    const int j = (b >> 1) & 7;
    const int i = ((b >> 4) << 1) | rank;
    const int cb = j >> 1;
    const bool convCTA = j & 1;
    const int cidx = 4 * i + cb;

    if (tid == 256) {
        mbar_init(sb + SM_BARS + B_XFULL * 8, 1);
        mbar_init(sb + SM_BARS + (B_XFULL + 1) * 8, 1);
        asm volatile("fence.proxy.async.shared::cta;" ::: "memory");
        mbar_expect_tx(sb + SM_BARS + B_XFULL * 8, 65536);
        tma3d(sb + SM_X, &p.tm_x, 0, 128 * i, 0, sb + SM_BARS + B_XFULL * 8);
        mbar_expect_tx(sb + SM_BARS + (B_XFULL + 1) * 8, 65536);
        tma3d(sb + SM_X + 65536, &p.tm_x, 0, 128 * i + 64, 0, sb + SM_BARS + (B_XFULL + 1) * 8);
    }
    if (tid == 288) {
        for (int s = 0; s < 5; s++) { mbar_init(sb + SM_BARS + (B_FULL + s) * 8, 1); mbar_init(sb + SM_BARS + (B_EMPTY + s) * 8, 16); }
        mbar_init(sb + SM_BARS + B_CONV * 8, 1);
        mbar_init(sb + SM_BARS + B_YT * 8, 1);
        mbar_init(sb + SM_BARS + B_XR * 8, 1);
        mbar_init(sb + SM_BARS + B_G1DONE * 8, 8);
        mbar_init(sb + SM_BARS + B_XFREE * 8, 8);
        mbar_init(sb + SM_BARS + B_YST * 8, 8);
        mbar_init(sb + SM_BARS + B_KVLD * 8, 2);
        mbar_init(sb + SM_BARS + B_LN * 8, 8);
        for (int s = 0; s < 4; s++) mbar_init(sb + SM_BARS + (B_HD + s) * 8, 4);
        for (int s = 0; s < 2; s++) mbar_init(sb + SM_BARS + (B_HRDY + s) * 8, 1);
        asm volatile("fence.mbarrier_init.release.cluster;" ::: "memory");
        asm volatile("fence.proxy.async.shared::cta;" ::: "memory");
    }
    __syncwarp();
    asm volatile("barrier.cluster.arrive.relaxed.aligned;\n" ::: "memory");
    asm volatile("barrier.cluster.wait.aligned;\n" ::: "memory");
    PROFW(1, 0);

    if (warp < 8) {
        asm volatile("setmaxnreg.inc.sync.aligned.u32 200;");
        const int wgi = warp >> 2, warp4 = warp & 3;
        const int g = lane >> 2, c = lane & 3;
        const uint32_t e_cl = mapa(sb + SM_BARS + B_EMPTY * 8, lane & 1);
        {
            const int lr16 = (lane & 7) + ((lane >> 3) & 1) * 8;
            const uint32_t xa = sb + SM_X + wgi * 65536 + (warp4 * 16 + lr16) * 128;
            uint32_t xf[32][4];
            float aS[4][4], aQ0[4][4], aQ1[4][4];
            #pragma unroll
            for (int e = 0; e < 4; e++) {
                #pragma unroll
                for (int f = 0; f < 4; f++) { aS[e][f] = 0.f; aQ0[e][f] = 0.f; aQ1[e][f] = 0.f; }
            }
            mbar_wait(sb + SM_BARS + (B_XFULL + wgi) * 8, 0);
            PROFW(16, 0); PROFW(18, 4);
            #pragma unroll
            for (int ks = 0; ks < 32; ks++) {
                const uint32_t a = xa + (ks >> 2) * 8192 + (((2 * (ks & 3) + (lane >> 4)) ^ (lane & 7)) << 4);
                asm volatile("ldmatrix.sync.aligned.m8n8.x4.shared.b16 {%0,%1,%2,%3}, [%4];"
                    : "=r"(xf[ks][0]), "=r"(xf[ks][1]), "=r"(xf[ks][2]), "=r"(xf[ks][3]) : "r"(a) : "memory");
            }
            #pragma unroll
            for (int ks = 0; ks < 32; ks++)
                mma16816(aS[ks & 3], xf[ks][0], xf[ks][1], xf[ks][2], xf[ks][3], make_uint2(0x3F803F80u, 0x3F803F80u));
            const float mean0 = ((aS[0][0] + aS[1][0]) + (aS[2][0] + aS[3][0])) * (1.0f / DM);
            const float mean1 = ((aS[0][2] + aS[1][2]) + (aS[2][2] + aS[3][2])) * (1.0f / DM);
            const uint32_t m0 = pack_bf(mean0, mean0), m1 = pack_bf(mean1, mean1);
            #pragma unroll
            for (int ks = 0; ks < 32; ks++) {
                const uint32_t a = xa + (ks >> 2) * 8192 + (((2 * (ks & 3) + (lane >> 4)) ^ (lane & 7)) << 4);
                asm volatile("stmatrix.sync.aligned.m8n8.x4.shared.b16 [%0], {%1,%2,%3,%4};"
                    :: "r"(a), "r"(bsub2(xf[ks][0], m0)), "r"(bsub2(xf[ks][1], m1)), "r"(bsub2(xf[ks][2], m0)), "r"(bsub2(xf[ks][3], m1)) : "memory");
                mma16816(aQ0[ks & 3], xf[ks][0], xf[ks][1], xf[ks][2], xf[ks][3], make_uint2(xf[ks][0], xf[ks][2]));
                mma16816(aQ1[ks & 3], xf[ks][0], xf[ks][1], xf[ks][2], xf[ks][3], make_uint2(xf[ks][1], xf[ks][3]));
            }
            asm volatile("fence.proxy.async.shared::cta;" ::: "memory");
            __syncwarp();
            if (lane == 0) mbar_arrive(sb + SM_BARS + B_LN * 8);
            if (c == (g >> 1)) {
                const float q0 = (g & 1) ? (aQ0[0][1] + aQ0[1][1]) + (aQ0[2][1] + aQ0[3][1]) : (aQ0[0][0] + aQ0[1][0]) + (aQ0[2][0] + aQ0[3][0]);
                const float q1 = (g & 1) ? (aQ1[0][3] + aQ1[1][3]) + (aQ1[2][3] + aQ1[3][3]) : (aQ1[0][2] + aQ1[1][2]) + (aQ1[2][2] + aQ1[3][2]);
                const float sd0 = bf_round(sqrtf(bf_round(bf_round(fmaxf(q0 * (1.0f / DM) - mean0 * mean0, 0.f)) + 1e-5f)));
                const float sd1 = bf_round(sqrtf(bf_round(bf_round(fmaxf(q1 * (1.0f / DM) - mean1 * mean1, 0.f)) + 1e-5f)));
                const uint32_t sa = sb + SM_STATS + (warp * 16 + g) * 8;
                sts32(sa, m0); sts32(sa + 4, __float_as_uint(1.0f / sd0));
                sts32(sa + 64, m1); sts32(sa + 68, __float_as_uint(1.0f / sd1));
            }
            mbar_wait(sb + SM_BARS + B_LN * 8, 0);
            PROFW(19, 4);
            PROFW(17, 0);
        }
        int st = 0; uint32_t fph = 0;
        uint32_t hp[32];
        uint32_t* const hdst = g_h + (size_t)(i * 56) * 2048 + wgi * 1024 + warp4 * 128 + lane;
        gemm1_pass<4, true>(sb, wgi, warp4, lane, st, fph, e_cl, hp, hdst, convCTA);

        if (convCTA) {
            gemm1_pass<2, false>(sb, wgi, warp4, lane, st, fph, e_cl, hp, hdst + 4 * j * 2048, true);
            store_h(hdst + (36 + 6 * cb) * 2048, hp, 0); store_h(hdst + (36 + 6 * cb) * 2048, hp, 1);
            __syncwarp();
            if (lane == 0) mbar_arrive(sb + SM_BARS + (B_HD + wgi * 2 + 1) * 8);
            const int gch = 8 * cidx + warp;
            const uint32_t xb = sb + SM_CVX + warp * 4096;
            const uint32_t hb = sb + SM_CVH + warp * 4096;
            const uint32_t dw = ((const unsigned short*)p.ssm_D)[gch];
            const uint32_t d2 = dw | (dw << 16);
            mbar_wait(sb + SM_BARS + B_CONV * 8, 0);
            PROFW(32, 4);
            float acc[16][4];
            #pragma unroll
            for (int jj = 0; jj < 16; jj++) { acc[jj][0] = 0.f; acc[jj][1] = 0.f; acc[jj][2] = 0.f; acc[jj][3] = 0.f; }
            uint2 bh[8], bl0[8], bl1[8];
            uint32_t xl = xb + g * 32 + c * 8;
            uint32_t hl = hb + (g + 2 * c - 8) * 4;
            #pragma unroll
            for (int d = 0; d < 8; d++) { bl0[d] = lds64(xl + d * 256); bh[d] = lds64(xl + (8 + d) * 256); }
            uint32_t w[6];
            w[0] = 0; w[1] = 0; w[2] = 0;
            if (g + 2 * c >= 8) w[0] = lds32(hl);
            if (g + 2 * c >= 7) w[1] = lds32(hl + 4);
            if (g + 2 * c >= 6) w[2] = lds32(hl + 8);
            w[3] = lds32(hl + 2048); w[4] = lds32(hl + 2052); w[5] = lds32(hl + 2056);
            auto conv_m0 = [&](int m0, uint2 (&bl)[8], uint2 (&bn)[8]) {
                xl -= 32;
                #pragma unroll
                for (int k = 0; k < 8; k++) {
                    const uint32_t a0 = w[1], a1 = __byte_perm(w[0], w[1], 0x5432), a2 = w[2], a3 = __byte_perm(w[1], w[2], 0x5432);
                    const uint32_t c0 = w[4], c1 = __byte_perm(w[3], w[4], 0x5432), c2 = w[5], c3 = __byte_perm(w[4], w[5], 0x5432);
                    const uint32_t nx = (k < 7) ? hl + (k + 1) * 256 : hl + 32;
                    w[0] = lds32(nx); w[1] = lds32(nx + 4); w[2] = lds32(nx + 8);
                    w[3] = lds32(nx + 2048); w[4] = lds32(nx + 2052); w[5] = lds32(nx + 2056);
                    if (k > 0) bn[k] = lds64(xl + k * 256);
                    else { bn[0] = make_uint2(0, 0); if (g > m0) bn[0] = lds64(xl); }
                    #pragma unroll
                    for (int jj = k; jj < 16; jj++) mma16816(acc[jj], a0, a1, a2, a3, (jj - k < 8) ? bl[(jj - k) & 7] : bh[(jj - k) & 7]);
                    bh[7 - k] = lds64(xl + (15 - k) * 256);
                    #pragma unroll
                    for (int jj = k + 8; jj < 16; jj++) mma16816(acc[jj], c0, c1, c2, c3, bl[jj - k - 8]);
                }
                hl += 32;
            };
            #pragma unroll 1
            for (int m0 = 0; m0 < 8; m0 += 2) {
                conv_m0(m0, bl0, bl1);
                conv_m0(m0 + 1, bl1, bl0);
                PROFW(34 + (m0 >> 1), 4);
            }
            PROFW(33, 4);
            const uint32_t kvl = xb + c * 64 + (7 - g) * 4;
            uint32_t* ydst = (uint32_t*)(g_yT + (size_t)gch * SEQ + 32 * c + 2 * g);
            uint32_t kk0[16], kk1[16];
            #pragma unroll
            for (int jj = 0; jj < 16; jj++) { kk0[jj] = lds32(kvl + jj * 256); kk1[jj] = lds32(kvl + jj * 256 + 32); }
            #pragma unroll
            for (int jj = 0; jj < 16; jj++) {
                ydst[jj * 64] = badd2(pack_bf(acc[jj][2], acc[jj][0]), bmul2(__byte_perm(kk0[jj], kk0[jj], 0x1032), d2));
                ydst[jj * 64 + 8] = badd2(pack_bf(acc[jj][3], acc[jj][1]), bmul2(__byte_perm(kk1[jj], kk1[jj], 0x1032), d2));
            }
            __syncwarp();
            PROFW(44, 4);
            if (lane == 0) mbar_arrive(sb + SM_BARS + B_YST * 8);
        } else {
            gemm1_pass<4, false>(sb, wgi, warp4, lane, st, fph, e_cl, hp, hdst + 4 * j * 2048, false);
            float acc[64];
            const uint64_t descB0 = make_desc(sb, 4096, 1024, 1);
            const uint64_t descA0 = make_desc(sb + 16384 + wgi * 4096, 128, 256, 0);
            int sg = 3, p0 = 0; uint32_t ph = 6;
            PROFW(20, 0);
            auto g2 = [&](int u) {
                if (warp == 0 && !(u & 1)) PROF2(2, 16 + (u >> 1));
                mbar_wait(sb + SM_BARS + (B_FULL + sg) * 8, (ph >> sg) & 1);
                ph ^= 1u << sg;
                if (warp == 0 && !(u & 1)) PROF2(1, 16 + (u >> 1));
                const uint32_t o0 = stage_off_rt(sg) >> 4;
                const uint64_t da0 = desc_add(descA0, o0), db0 = desc_add(descB0, o0);
                WG_FENCE();
                #pragma unroll
                for (int kk = 0; kk < 4; kk++) wgmma_ss_n128_tb(acc, da0 + ((kk >> 1) * 512 + (kk & 1) * 128), db0 + ((kk >> 1) * 512 + (kk & 1) * 128), (u | kk) ? 1 : 0);
                WG_COMMIT();
                wg_wait<1>();
                if (warp == 0 && !(u & 1)) PROF2(3, 16 + (u >> 1));
                if (lane < 2 && u > 0 && u + 4 < 28) mbar_arrive_cluster(e_cl + p0 * 8, 1);
                p0 = sg;
                sg = next_st2(sg);
            };
            #pragma unroll
            for (int u = 0; u < 4; u++) { g2(u); store_h(hdst + (32 + 6 * cb) * 2048, hp, u); }
            __syncwarp();
            if (lane == 0) mbar_arrive(sb + SM_BARS + (B_HD + wgi * 2 + 1) * 8);
            #pragma unroll 1
            for (int u = 4; u < 28; u++) g2(u);
            wg_wait<0>();
            PROFW(27, 0);
            mbar_wait(sb + SM_BARS + B_XR * 8, 0);
            const int r0 = wgi * 64 + warp4 * 16 + g;
            const float2 st0 = lds64f(sb + SM_STATS + r0 * 8), st1 = lds64f(sb + SM_STATS + (r0 + 8) * 8);
            const uint32_t m0 = __float_as_uint(st0.x), m1 = __float_as_uint(st1.x);
            const uint32_t xrow0 = sb + SM_XE + r0 * 128 + c * 4;
            const int mi = lane >> 3, lr = lane & 7;
            const uint32_t yaddr = sb + SM_YT + wgi * 16384 + ((mi >> 1) * 8 + lr) * 128 + (((2 * warp4 + (mi & 1)) ^ lr) << 4);
            uint32_t y[8][4], xv[16][2], nv[16][2], bv[16][2];
            #pragma unroll
            for (int t = 0; t < 16; t++) {
                const uint32_t off = (t >> 3) * 16384 + (((t & 7) ^ g) << 4);
                xv[t][0] = lds32(xrow0 + off); xv[t][1] = lds32(xrow0 + 1024 + off);
            }
            #pragma unroll
            for (int t = 0; t < 16; t++) {
                const uint32_t d0 = bsub2(xv[t][0], m0), d1 = bsub2(xv[t][1], m1);
                nv[t][0] = pack_bf(bf_lo(d0) * st0.y, bf_hi(d0) * st0.y); nv[t][1] = pack_bf(bf_lo(d1) * st1.y, bf_hi(d1) * st1.y);
                bv[t][0] = pack_bf(acc[4 * t], acc[4 * t + 1]); bv[t][1] = pack_bf(acc[4 * t + 2], acc[4 * t + 3]);
            }
            mbar_wait(sb + SM_BARS + B_YT * 8, 0);
            PROFW(28, 0);
            #pragma unroll
            for (int t2 = 0; t2 < 8; t2++)
                asm volatile("ldmatrix.sync.aligned.m8n8.x4.trans.shared.b16 {%0,%1,%2,%3}, [%4];"
                    : "=r"(y[t2][0]), "=r"(y[t2][1]), "=r"(y[t2][2]), "=r"(y[t2][3]) : "r"(yaddr + t2 * 2048) : "memory");
            #pragma unroll
            for (int t = 0; t < 16; t++) {
                const uint32_t off = (t >> 3) * 16384 + (((t & 7) ^ g) << 4);
                sts32(xrow0 + off, badd2(badd2(xv[t][0], bmul2(nv[t][0], y[t >> 1][2 * (t & 1)])), bv[t][0]));
                sts32(xrow0 + 1024 + off, badd2(badd2(xv[t][1], bmul2(nv[t][1], y[t >> 1][2 * (t & 1) + 1])), bv[t][1]));
            }
            asm volatile("fence.proxy.async.shared::cta;" ::: "memory");
            named_bar(1 + wgi, 128);
            if ((tid & 127) == 0) {
                tma2d_store(&p.tm_out, 128 * cb, 128 * i + 64 * wgi, sb + SM_XE + wgi * 8192);
                tma2d_store(&p.tm_out, 128 * cb + 64, 128 * i + 64 * wgi, sb + SM_XE + 16384 + wgi * 8192);
                asm volatile("cp.async.bulk.commit_group;" ::: "memory");
                asm volatile("cp.async.bulk.wait_group.read 0;" ::: "memory");
                PROFW(29, 0);
            }
        }
    } else {
        asm volatile("setmaxnreg.dec.sync.aligned.u32 104;");
        if (warp == 8) {
            int st = 0; uint32_t eph = 7;
            #pragma unroll 1
            for (int it = 0; it < 16; it++) {
                const int pass = it >> 3, sl = it & 7;
                const bool narrow = pass && convCTA;
                const int nb = narrow ? 2 : 4;
                const CUtensorMap* tm = narrow ? (rank ? &p.tm_uB : &p.tm_gB) : (rank ? &p.tm_uA : &p.tm_gA);
                mbar_wait(sb + SM_BARS + (B_EMPTY + st) * 8, (eph >> st) & 1);
                eph ^= 1u << st;
                if (it == 1) mbar_wait(sb + SM_BARS + B_XFULL * 8, 0);
                PROF2(0, it);
                if (elect_one()) {
                    mbar_expect_tx(sb + SM_BARS + (B_FULL + st) * 8, nb * 8192);
                    tma3d_mc(sb + SM_RING + st * STAGE_BYTES + rank * nb * 4096, tm, 0, sl * 64, 14 * cb + 8 * (j & 1) + 4 * pass, sb + SM_BARS + (B_FULL + st) * 8);
                }
                st = (st == 2) ? 0 : st + 1;
            }
            if (!convCTA) {
                st = 3;
                const int f0_lane = blk_f0(2 * lane + rank);
                #pragma unroll 1
                for (int u = 0; u < 28; u++) {
                    const uint32_t bar = sb + SM_BARS + (B_FULL + st) * 8;
                    const int f0 = __shfl_sync(0xffffffffu, f0_lane, u);
                    mbar_wait(sb + SM_BARS + (B_EMPTY + st) * 8, (eph >> st) & 1);
                    eph ^= 1u << st;
                    if ((u & 1) == 0) PROF2(0, 16 + (u >> 1));
                    if (elect_one()) {
                        mbar_expect_tx(bar, 32768);
                        tma3d_mc(sb + stage_off_rt(st) + rank * 8192, &p.tm_w2, 0, f0, 2 * cb, bar);
                    }
                    st = next_st2(st);
                }
                PROF(48);
            }
        } else if (warp < 11) {
            mbar_wait(sb + SM_BARS + (B_XFULL + 1) * 8, 0);
            {
                const int q = lane & 3;
                const int t0 = 32 * (b >> 1) + 8 * q;
                const int ch0 = 256 * (b & 1) + 16 * (warp - 9) + 2 * (lane >> 2);
                const uint32_t* kp = (const uint32_t*)(p.k + (size_t)t0 * DM + ch0);
                const uint32_t* vp = (const uint32_t*)(p.v + (size_t)t0 * DM + ch0);
                __nv_bfloat16* dst0 = g_kvT + (size_t)ch0 * SEQ + (t0 ^ 8);
                #pragma unroll 1
                for (int rnd = 0; rnd < 2; rnd++) {
                    uint32_t kr[4][11], vr[4][8]; uint4 skw[4];
                    #pragma unroll
                    for (int u = 0; u < 4; u++) {
                        const int co = (rnd * 4 + u) * 16;
                        skw[u] = ldg_nc128(p.shift_k + 4 * (ch0 + 2 * co));
                        #pragma unroll
                        for (int r = 0; r < 11; r++) kr[u][r] = (r >= 3 || t0 > 0) ? ldg_nc32(kp + co + (r - 3) * (DM / 2)) : 0u;
                        #pragma unroll
                        for (int r = 0; r < 8; r++) vr[u][r] = ldg_nc32(vp + co + r * (DM / 2));
                    }
                    #pragma unroll
                    for (int u = 0; u < 4; u++) {
                        const uint32_t s0 = __byte_perm(skw[u].x, skw[u].z, 0x5410), s1 = __byte_perm(skw[u].x, skw[u].z, 0x7632);
                        const uint32_t s2 = __byte_perm(skw[u].y, skw[u].w, 0x5410), s3 = __byte_perm(skw[u].y, skw[u].w, 0x7632);
                        #pragma unroll
                        for (int r = 0; r < 8; r++) {
                            uint32_t a = bmul2(kr[u][r], s3);
                            a = badd2(a, bmul2(kr[u][r + 1], s2));
                            a = badd2(a, bmul2(kr[u][r + 2], s1));
                            a = badd2(a, bmul2(kr[u][r + 3], s0));
                            vr[u][r] = bmul2(a, vr[u][r]);
                        }
                        __nv_bfloat16* dst = dst0 + (size_t)((rnd * 4 + u) * 32) * SEQ;
                        *(uint4*)dst = make_uint4(__byte_perm(vr[u][7], vr[u][6], 0x5410), __byte_perm(vr[u][5], vr[u][4], 0x5410),
                                                  __byte_perm(vr[u][3], vr[u][2], 0x5410), __byte_perm(vr[u][1], vr[u][0], 0x5410));
                        *(uint4*)(dst + SEQ) = make_uint4(__byte_perm(vr[u][7], vr[u][6], 0x7632), __byte_perm(vr[u][5], vr[u][4], 0x7632),
                                                          __byte_perm(vr[u][3], vr[u][2], 0x7632), __byte_perm(vr[u][1], vr[u][0], 0x7632));
                    }
                    PROFW(57 + 2 * rnd, 9);
                }
                if (lane == 0) mbar_arrive(sb + SM_BARS + B_KVLD * 8);
            }
            asm volatile("fence.proxy.async.global;" ::: "memory");
            __syncwarp();
            if (lane == 0) {
                flag_add(&g_cnt_kv[0]);
                PROFW(50, 9);
                const int wgi = warp - 9;
                mbar_wait(sb + SM_BARS + (B_HD + wgi * 2) * 8, 0);
                flag_add(&g_flag_h[(i * 2 + 0) * 8]);
                mbar_wait(sb + SM_BARS + (B_HD + wgi * 2 + 1) * 8, 0);
                flag_add(&g_flag_h[(i * 2 + 1) * 8]);
                if (wgi == 1 && convCTA) {
                    mbar_wait(sb + SM_BARS + B_YST * 8, 0);
                    flag_add(&g_cnt_y[(cidx >> 4) * 32]);
                    PROF(46);
                }
                if (wgi == 1 && !convCTA) {
                    const unsigned ep = lds32(sb + SM_EPOCH);
                    mbar_wait(sb + SM_BARS + B_G1DONE * 8, 0);
                    mbar_expect_tx(sb + SM_BARS + B_XR * 8, 32768);
                    tma3d(sb + SM_XE, &p.tm_xe, 0, 128 * i, 2 * cb, sb + SM_BARS + B_XR * 8);
                    flag_wait(&g_flag_h[(i * 2 + 1) * 8], ep * 16);
                    mbar_arrive(sb + SM_BARS + (B_HRDY + 1) * 8);
                    __nanosleep(3000);
                    flag_wait(&g_cnt_y[cb * 32], ep * 16);
                    PROF(49);
                    asm volatile("fence.proxy.async.global;" ::: "memory");
                    mbar_expect_tx(sb + SM_BARS + B_YT * 8, 32768);
                    tma2d(sb + SM_YT, &p.tm_yT, 128 * i, 128 * cb, sb + SM_BARS + B_YT * 8);
                    tma2d(sb + SM_YT + 16384, &p.tm_yT, 128 * i + 64, 128 * cb, sb + SM_BARS + B_YT * 8);
                }
            }
        } else {
            if (lane == 0) {
                l2_prefetch(p.wg + (size_t)b * (FF * DM / NCTA), FF * DM / NCTA * 2);
                l2_prefetch(p.wu + (size_t)b * (FF * DM / NCTA), FF * DM / NCTA * 2);
                const unsigned ep = g_launch[b] + 1;
                g_launch[b] = ep;
                sts32(sb + SM_EPOCH, ep);
                tmap_prefetch(rank ? &p.tm_uA : &p.tm_gA);
                tmap_prefetch(rank ? &p.tm_uB : &p.tm_gB);
                tmap_prefetch(&p.tm_w2); tmap_prefetch(&p.tm_yT); tmap_prefetch(&p.tm_out); tmap_prefetch(&p.tm_xe);
                mbar_wait(sb + SM_BARS + B_KVLD * 8, 0);
                l2_prefetch(p.ssm_k + (size_t)(4 * b) * SEQ, 4 * SEQ * 2);
                l2_prefetch(p.wd + (size_t)b * (FF * DM / NCTA), FF * DM / NCTA * 2);
                mbar_wait(sb + SM_BARS + (B_HD + 0) * 8, 0);
                if (convCTA) {
                    flag_wait(&g_cnt_kv[0], ep * 256);
                    asm volatile("fence.proxy.async.global;" ::: "memory");
                    PROF(53);
                    mbar_wait(sb + SM_BARS + B_XFREE * 8, 0);
                    PROF(54);
                    mbar_expect_tx(sb + SM_BARS + B_CONV * 8, 65536);
                    bulk_g2s(sb + SM_CVX, g_kvT + (size_t)(8 * cidx) * SEQ, 32768, sb + SM_BARS + B_CONV * 8);
                    bulk_g2s(sb + SM_CVH, p.ssm_k + (size_t)(8 * cidx) * SEQ, 32768, sb + SM_BARS + B_CONV * 8);
                } else {
                    flag_wait(&g_flag_h[(i * 2 + 0) * 8], ep * 16);
                }
            }
            __syncwarp();
            if (!convCTA) {
                asm volatile("fence.proxy.async.global;" ::: "memory");
                int st = 3; uint32_t eph = 1;
                const uint8_t* hsrc = (const uint8_t*)g_h + (size_t)i * 56 * 8192;
                #pragma unroll 1
                for (int u = 0; u < 28; u++) {
                    mbar_wait(sb + SM_BARS + (B_EMPTY + st) * 8, (eph >> st) & 1);
                    eph ^= 1u << st;
                    if (u == 16) {
                        mbar_wait(sb + SM_BARS + (B_HRDY + 1) * 8, 0);
                        asm volatile("fence.proxy.async.global;" ::: "memory");
                    }
                    if (elect_one()) bulk_g2s(sb + stage_off_rt(st) + 16384, hsrc + u * 16384, 16384, sb + SM_BARS + (B_FULL + st) * 8);
                    st = next_st2(st);
                }
            }
        }
    }
}

typedef CUresult (*EncodeFn)(CUtensorMap*, CUtensorMapDataType, cuuint32_t, void*, const cuuint64_t*, const cuuint64_t*,
                             const cuuint32_t*, const cuuint32_t*, CUtensorMapInterleave, CUtensorMapSwizzle,
                             CUtensorMapL2promotion, CUtensorMapFloatOOBfill);

void encode(EncodeFn fn, CUtensorMap* tm, const void* base, int rank, const cuuint64_t* dims, const cuuint64_t* strides,
            const cuuint32_t* box, CUtensorMapSwizzle swz) {
    cuuint32_t es[5] = {1, 1, 1, 1, 1};
    fn(tm, CU_TENSOR_MAP_DATA_TYPE_BFLOAT16, rank, (void*)base, dims, strides, box, es, CU_TENSOR_MAP_INTERLEAVE_NONE, swz,
       CU_TENSOR_MAP_L2_PROMOTION_L2_128B, CU_TENSOR_MAP_FLOAT_OOB_FILL_NONE);
}

}

extern "C" void kernel_launch(void* const* d_in, const int* in_sizes, int n_in, void* d_out, int out_size) {
    (void)in_sizes; (void)n_in; (void)out_size;
    static EncodeFn enc = nullptr;
    static void* yT_ptr = nullptr;
    if (!enc) {
        void* fn = nullptr; cudaDriverEntryPointQueryResult qr;
        cudaGetDriverEntryPoint("cuTensorMapEncodeTiled", &fn, cudaEnableDefault, &qr);
        enc = (EncodeFn)fn;
        cudaGetSymbolAddress(&yT_ptr, g_yT);
        cudaFuncSetAttribute(fused_kernel, cudaFuncAttributeMaxDynamicSharedMemorySize, SM_TOTAL);
    }
    Params p;
    p.q = (const __nv_bfloat16*)d_in[0]; p.k = (const __nv_bfloat16*)d_in[1]; p.v = (const __nv_bfloat16*)d_in[2];
    p.shift_k = (const __nv_bfloat16*)d_in[3]; p.ssm_k = (const __nv_bfloat16*)d_in[4]; p.ssm_D = (const __nv_bfloat16*)d_in[5];
    p.wg = (const __nv_bfloat16*)d_in[7]; p.wu = (const __nv_bfloat16*)d_in[8]; p.wd = (const __nv_bfloat16*)d_in[9];
    {
        cuuint64_t dims[2] = {DM, SEQ}; cuuint64_t str[1] = {DM * 2};
        cuuint64_t dims3[3] = {64, SEQ, DM / 64}; cuuint64_t str3[2] = {DM * 2, 128};
        cuuint32_t box[3] = {64, 64, 8}, boxe[3] = {64, 128, 2};
        encode(enc, &p.tm_x, p.q, 3, dims3, str3, box, CU_TENSOR_MAP_SWIZZLE_128B);
        encode(enc, &p.tm_xe, p.q, 3, dims3, str3, boxe, CU_TENSOR_MAP_SWIZZLE_128B);
        cuuint32_t box2[2] = {64, 64};
        encode(enc, &p.tm_out, d_out, 2, dims, str, box2, CU_TENSOR_MAP_SWIZZLE_128B);
    }
    {
        cuuint64_t dims[3] = {32, DM, FF / 32}; cuuint64_t str[2] = {FF * 2, 64};
        cuuint32_t boxA[3] = {32, 64, 4}, boxB[3] = {32, 64, 2};
        encode(enc, &p.tm_gA, p.wg, 3, dims, str, boxA, CU_TENSOR_MAP_SWIZZLE_64B);
        encode(enc, &p.tm_gB, p.wg, 3, dims, str, boxB, CU_TENSOR_MAP_SWIZZLE_64B);
        encode(enc, &p.tm_uA, p.wu, 3, dims, str, boxA, CU_TENSOR_MAP_SWIZZLE_64B);
        encode(enc, &p.tm_uB, p.wu, 3, dims, str, boxB, CU_TENSOR_MAP_SWIZZLE_64B);
    }
    {
        cuuint64_t dims[3] = {64, FF, DM / 64}; cuuint64_t str[2] = {DM * 2, 128};
        cuuint32_t box[3] = {64, 32, 2};
        encode(enc, &p.tm_w2, p.wd, 3, dims, str, box, CU_TENSOR_MAP_SWIZZLE_128B);
    }
    {
        cuuint64_t dims[2] = {SEQ, DM}; cuuint64_t str[1] = {SEQ * 2};
        cuuint32_t box[2] = {64, 128};
        encode(enc, &p.tm_yT, yT_ptr, 2, dims, str, box, CU_TENSOR_MAP_SWIZZLE_128B);
    }
    fused_kernel<<<NCTA, NTHREADS, SM_TOTAL>>>(p);
}
```

```cpp
#include <cuda_runtime.h>
#include <cuda_bf16.h>
#include <cuda.h>
#include <stdint.h>

namespace {

constexpr int SEQ = 2048, DM = 512, FF = 1792;
constexpr int NCTA = 128;
constexpr int NTHREADS = 384;
constexpr int STAGE_BYTES = 32768;
#define KV_STAGGER 300
#define KV_GAP 150

constexpr uint32_t SM_X = 0;
constexpr uint32_t SM_RING = 131072;
constexpr uint32_t SM_MISC = SM_RING + 3 * STAGE_BYTES;
constexpr uint32_t SM_BARS = SM_MISC;
constexpr uint32_t SM_EPOCH = SM_MISC + 248;
constexpr uint32_t SM_STATS = SM_MISC + 256;
constexpr uint32_t SM_TOTAL = SM_STATS + 1024;
static_assert(SM_TOTAL <= 232448, "smem");
constexpr uint32_t SM_CVX = 0;
constexpr uint32_t SM_CVH = 65536;
constexpr uint32_t SM_YT = 32768;
constexpr uint32_t SM_XE = 98304;

constexpr int B_FULL = 0, B_EMPTY = 5, B_XFULL = 10, B_CONV = 14, B_YT = 15, B_XR = 16, B_G1DONE = 17, B_HD = 18, B_HRDY = 22,
              B_XFREE = 24, B_YST = 25, B_KVLD = 26, B_LN = 27, B_COUNT = 28;
static_assert(B_COUNT * 8 <= 248, "barrier space");

__device__ __align__(128) uint32_t g_h[16 * 56 * 2048];
__device__ __align__(128) __nv_bfloat16 g_kvT[DM * SEQ];
__device__ __align__(128) __nv_bfloat16 g_yT[DM * SEQ];
__device__ unsigned g_launch[NCTA];
__device__ unsigned g_cnt_kv[32];
__device__ unsigned g_cnt_y[4 * 32];
__device__ unsigned g_flag_h[16 * 2 * 8];

#define PROF(idx)
#define PROF2(a, idx)
#define PROFW(idx, w)

struct Params {
    CUtensorMap tm_x, tm_gA, tm_gB, tm_uA, tm_uB, tm_w2, tm_yT, tm_out, tm_xe;
    const __nv_bfloat16 *q, *k, *v, *shift_k, *ssm_k, *ssm_D, *wg, *wu, *wd;
};

__device__ __forceinline__ void wgmma_rs_n32(float (&d)[16], uint32_t a0, uint32_t a1, uint32_t a2, uint32_t a3, uint64_t db, int sc) {
  asm volatile("{\n.reg .pred p;\nsetp.ne.b32 p, %21, 0;\n"
    "wgmma.mma_async.sync.aligned.m64n32k16.f32.bf16.bf16 {%0,%1,%2,%3,%4,%5,%6,%7,%8,%9,%10,%11,%12,%13,%14,%15}, {%16,%17,%18,%19}, %20, p, 1, 1, 0;\n}\n"
    : "+f"(d[0]),"+f"(d[1]),"+f"(d[2]),"+f"(d[3]),"+f"(d[4]),"+f"(d[5]),"+f"(d[6]),"+f"(d[7]),"+f"(d[8]),"+f"(d[9]),"+f"(d[10]),"+f"(d[11]),"+f"(d[12]),"+f"(d[13]),"+f"(d[14]),"+f"(d[15])
    : "r"(a0),"r"(a1),"r"(a2),"r"(a3),"l"(db),"r"(sc));
}
__device__ __forceinline__ void wgmma_rs_n128_tb(float (&d)[64], uint32_t a0, uint32_t a1, uint32_t a2, uint32_t a3, uint64_t db, int sc) {
  asm volatile("{\n.reg .pred p;\nsetp.ne.b32 p, %69, 0;\n"
    "wgmma.mma_async.sync.aligned.m64n128k16.f32.bf16.bf16 {%0,%1,%2,%3,%4,%5,%6,%7,%8,%9,%10,%11,%12,%13,%14,%15,%16,%17,%18,%19,%20,%21,%22,%23,%24,%25,%26,%27,%28,%29,%30,%31,%32,%33,%34,%35,%36,%37,%38,%39,%40,%41,%42,%43,%44,%45,%46,%47,%48,%49,%50,%51,%52,%53,%54,%55,%56,%57,%58,%59,%60,%61,%62,%63}, {%64,%65,%66,%67}, %68, p, 1, 1, 1;\n}\n"
    : "+f"(d[0]),"+f"(d[1]),"+f"(d[2]),"+f"(d[3]),"+f"(d[4]),"+f"(d[5]),"+f"(d[6]),"+f"(d[7]),"+f"(d[8]),"+f"(d[9]),"+f"(d[10]),"+f"(d[11]),"+f"(d[12]),"+f"(d[13]),"+f"(d[14]),"+f"(d[15]),"+f"(d[16]),"+f"(d[17]),"+f"(d[18]),"+f"(d[19]),"+f"(d[20]),"+f"(d[21]),"+f"(d[22]),"+f"(d[23]),"+f"(d[24]),"+f"(d[25]),"+f"(d[26]),"+f"(d[27]),"+f"(d[28]),"+f"(d[29]),"+f"(d[30]),"+f"(d[31]),"+f"(d[32]),"+f"(d[33]),"+f"(d[34]),"+f"(d[35]),"+f"(d[36]),"+f"(d[37]),"+f"(d[38]),"+f"(d[39]),"+f"(d[40]),"+f"(d[41]),"+f"(d[42]),"+f"(d[43]),"+f"(d[44]),"+f"(d[45]),"+f"(d[46]),"+f"(d[47]),"+f"(d[48]),"+f"(d[49]),"+f"(d[50]),"+f"(d[51]),"+f"(d[52]),"+f"(d[53]),"+f"(d[54]),"+f"(d[55]),"+f"(d[56]),"+f"(d[57]),"+f"(d[58]),"+f"(d[59]),"+f"(d[60]),"+f"(d[61]),"+f"(d[62]),"+f"(d[63])
    : "r"(a0),"r"(a1),"r"(a2),"r"(a3),"l"(db),"r"(sc));
}
__device__ __forceinline__ void wgmma_ss_n256_tb(float (&d)[128], uint64_t da, uint64_t db, int sc) {
  asm volatile("{\n.reg .pred p;\nsetp.ne.b32 p, %130, 0;\n"
    "wgmma.mma_async.sync.aligned.m64n256k16.f32.bf16.bf16 {%0,%1,%2,%3,%4,%5,%6,%7,%8,%9,%10,%11,%12,%13,%14,%15,%16,%17,%18,%19,%20,%21,%22,%23,%24,%25,%26,%27,%28,%29,%30,%31,%32,%33,%34,%35,%36,%37,%38,%39,%40,%41,%42,%43,%44,%45,%46,%47,%48,%49,%50,%51,%52,%53,%54,%55,%56,%57,%58,%59,%60,%61,%62,%63,%64,%65,%66,%67,%68,%69,%70,%71,%72,%73,%74,%75,%76,%77,%78,%79,%80,%81,%82,%83,%84,%85,%86,%87,%88,%89,%90,%91,%92,%93,%94,%95,%96,%97,%98,%99,%100,%101,%102,%103,%104,%105,%106,%107,%108,%109,%110,%111,%112,%113,%114,%115,%116,%117,%118,%119,%120,%121,%122,%123,%124,%125,%126,%127}, %128, %129, p, 1, 1, 0, 1;\n}\n"
    : "+f"(d[0]),"+f"(d[1]),"+f"(d[2]),"+f"(d[3]),"+f"(d[4]),"+f"(d[5]),"+f"(d[6]),"+f"(d[7]),"+f"(d[8]),"+f"(d[9]),"+f"(d[10]),"+f"(d[11]),"+f"(d[12]),"+f"(d[13]),"+f"(d[14]),"+f"(d[15]),"+f"(d[16]),"+f"(d[17]),"+f"(d[18]),"+f"(d[19]),"+f"(d[20]),"+f"(d[21]),"+f"(d[22]),"+f"(d[23]),"+f"(d[24]),"+f"(d[25]),"+f"(d[26]),"+f"(d[27]),"+f"(d[28]),"+f"(d[29]),"+f"(d[30]),"+f"(d[31]),"+f"(d[32]),"+f"(d[33]),"+f"(d[34]),"+f"(d[35]),"+f"(d[36]),"+f"(d[37]),"+f"(d[38]),"+f"(d[39]),"+f"(d[40]),"+f"(d[41]),"+f"(d[42]),"+f"(d[43]),"+f"(d[44]),"+f"(d[45]),"+f"(d[46]),"+f"(d[47]),"+f"(d[48]),"+f"(d[49]),"+f"(d[50]),"+f"(d[51]),"+f"(d[52]),"+f"(d[53]),"+f"(d[54]),"+f"(d[55]),"+f"(d[56]),"+f"(d[57]),"+f"(d[58]),"+f"(d[59]),"+f"(d[60]),"+f"(d[61]),"+f"(d[62]),"+f"(d[63]),"+f"(d[64]),"+f"(d[65]),"+f"(d[66]),"+f"(d[67]),"+f"(d[68]),"+f"(d[69]),"+f"(d[70]),"+f"(d[71]),"+f"(d[72]),"+f"(d[73]),"+f"(d[74]),"+f"(d[75]),"+f"(d[76]),"+f"(d[77]),"+f"(d[78]),"+f"(d[79]),"+f"(d[80]),"+f"(d[81]),"+f"(d[82]),"+f"(d[83]),"+f"(d[84]),"+f"(d[85]),"+f"(d[86]),"+f"(d[87]),"+f"(d[88]),"+f"(d[89]),"+f"(d[90]),"+f"(d[91]),"+f"(d[92]),"+f"(d[93]),"+f"(d[94]),"+f"(d[95]),"+f"(d[96]),"+f"(d[97]),"+f"(d[98]),"+f"(d[99]),"+f"(d[100]),"+f"(d[101]),"+f"(d[102]),"+f"(d[103]),"+f"(d[104]),"+f"(d[105]),"+f"(d[106]),"+f"(d[107]),"+f"(d[108]),"+f"(d[109]),"+f"(d[110]),"+f"(d[111]),"+f"(d[112]),"+f"(d[113]),"+f"(d[114]),"+f"(d[115]),"+f"(d[116]),"+f"(d[117]),"+f"(d[118]),"+f"(d[119]),"+f"(d[120]),"+f"(d[121]),"+f"(d[122]),"+f"(d[123]),"+f"(d[124]),"+f"(d[125]),"+f"(d[126]),"+f"(d[127])
    : "l"(da),"l"(db),"r"(sc));
}
__device__ __forceinline__ void wgmma_ss_n192_tb(float (&d)[96], uint64_t da, uint64_t db, int sc) {
  asm volatile("{\n.reg .pred p;\nsetp.ne.b32 p, %98, 0;\n"
    "wgmma.mma_async.sync.aligned.m64n192k16.f32.bf16.bf16 {%0,%1,%2,%3,%4,%5,%6,%7,%8,%9,%10,%11,%12,%13,%14,%15,%16,%17,%18,%19,%20,%21,%22,%23,%24,%25,%26,%27,%28,%29,%30,%31,%32,%33,%34,%35,%36,%37,%38,%39,%40,%41,%42,%43,%44,%45,%46,%47,%48,%49,%50,%51,%52,%53,%54,%55,%56,%57,%58,%59,%60,%61,%62,%63,%64,%65,%66,%67,%68,%69,%70,%71,%72,%73,%74,%75,%76,%77,%78,%79,%80,%81,%82,%83,%84,%85,%86,%87,%88,%89,%90,%91,%92,%93,%94,%95}, %96, %97, p, 1, 1, 0, 1;\n}\n"
    : "+f"(d[0]),"+f"(d[1]),"+f"(d[2]),"+f"(d[3]),"+f"(d[4]),"+f"(d[5]),"+f"(d[6]),"+f"(d[7]),"+f"(d[8]),"+f"(d[9]),"+f"(d[10]),"+f"(d[11]),"+f"(d[12]),"+f"(d[13]),"+f"(d[14]),"+f"(d[15]),"+f"(d[16]),"+f"(d[17]),"+f"(d[18]),"+f"(d[19]),"+f"(d[20]),"+f"(d[21]),"+f"(d[22]),"+f"(d[23]),"+f"(d[24]),"+f"(d[25]),"+f"(d[26]),"+f"(d[27]),"+f"(d[28]),"+f"(d[29]),"+f"(d[30]),"+f"(d[31]),"+f"(d[32]),"+f"(d[33]),"+f"(d[34]),"+f"(d[35]),"+f"(d[36]),"+f"(d[37]),"+f"(d[38]),"+f"(d[39]),"+f"(d[40]),"+f"(d[41]),"+f"(d[42]),"+f"(d[43]),"+f"(d[44]),"+f"(d[45]),"+f"(d[46]),"+f"(d[47]),"+f"(d[48]),"+f"(d[49]),"+f"(d[50]),"+f"(d[51]),"+f"(d[52]),"+f"(d[53]),"+f"(d[54]),"+f"(d[55]),"+f"(d[56]),"+f"(d[57]),"+f"(d[58]),"+f"(d[59]),"+f"(d[60]),"+f"(d[61]),"+f"(d[62]),"+f"(d[63]),"+f"(d[64]),"+f"(d[65]),"+f"(d[66]),"+f"(d[67]),"+f"(d[68]),"+f"(d[69]),"+f"(d[70]),"+f"(d[71]),"+f"(d[72]),"+f"(d[73]),"+f"(d[74]),"+f"(d[75]),"+f"(d[76]),"+f"(d[77]),"+f"(d[78]),"+f"(d[79]),"+f"(d[80]),"+f"(d[81]),"+f"(d[82]),"+f"(d[83]),"+f"(d[84]),"+f"(d[85]),"+f"(d[86]),"+f"(d[87]),"+f"(d[88]),"+f"(d[89]),"+f"(d[90]),"+f"(d[91]),"+f"(d[92]),"+f"(d[93]),"+f"(d[94]),"+f"(d[95])
    : "l"(da),"l"(db),"r"(sc));
}

__device__ __forceinline__ uint32_t smem_u32(const void* p) { return (uint32_t)__cvta_generic_to_shared(p); }
__device__ __forceinline__ void mbar_init(uint32_t bar, uint32_t cnt) { asm volatile("mbarrier.init.shared::cta.b64 [%0], %1;" :: "r"(bar), "r"(cnt)); }
__device__ __forceinline__ void mbar_expect_tx(uint32_t bar, uint32_t bytes) { asm volatile("mbarrier.arrive.expect_tx.shared::cta.b64 _, [%0], %1;" :: "r"(bar), "r"(bytes) : "memory"); }
__device__ __forceinline__ void mbar_arrive(uint32_t bar) { asm volatile("mbarrier.arrive.shared::cta.b64 _, [%0];" :: "r"(bar) : "memory"); }
__device__ __forceinline__ void mbar_arrive_cluster(uint32_t cbar, uint32_t cnt) { asm volatile("mbarrier.arrive.shared::cluster.b64 _, [%0], %1;" :: "r"(cbar), "r"(cnt) : "memory"); }
__device__ __forceinline__ uint32_t mapa(uint32_t a, uint32_t rank) { uint32_t r; asm volatile("mapa.shared::cluster.u32 %0, %1, %2;" : "=r"(r) : "r"(a), "r"(rank)); return r; }
__device__ __forceinline__ void mbar_wait(uint32_t bar, uint32_t parity) {
    uint32_t ok; uint32_t n = 0;
    do {
        asm volatile("{\n.reg .pred p;\nmbarrier.try_wait.parity.shared::cta.b64 p, [%1], %2;\nselp.u32 %0, 1, 0, p;\n}" : "=r"(ok) : "r"(bar), "r"(parity) : "memory");
    } while (!ok && ++n < (1u << 17));
}
__device__ __forceinline__ void pace_wait(uint32_t a, uint32_t target) {
    uint32_t v, n = 0;
    do {
        asm volatile("ld.volatile.shared.u32 %0, [%1];" : "=r"(v) : "r"(a) : "memory");
        if (v < target) __nanosleep(150);
    } while (v < target && ++n < (1u << 14));
}
__device__ __forceinline__ void flag_wait(const unsigned* p, unsigned target) {
    unsigned v; uint32_t n = 0;
    while (true) {
        asm volatile("ld.acquire.gpu.global.u32 %0, [%1];" : "=r"(v) : "l"(p) : "memory");
        if ((int)(v - target) >= 0 || ++n >= (1u << 17)) break;
        __nanosleep(100);
    }
}
__device__ __forceinline__ void flag_add(unsigned* p) {
    asm volatile("fence.acq_rel.gpu;\nred.relaxed.gpu.global.add.u32 [%0], 1;" :: "l"(p) : "memory");
}
__device__ __forceinline__ uint64_t make_desc(uint32_t addr, uint32_t lbo, uint32_t sbo, uint32_t swz) {
    return (uint64_t)((addr & 0x3FFFF) >> 4) | ((uint64_t)((lbo & 0x3FFFF) >> 4) << 16) | ((uint64_t)((sbo & 0x3FFFF) >> 4) << 32) | ((uint64_t)swz << 62);
}
__device__ __forceinline__ uint64_t desc_add(uint64_t d, uint32_t off16) {
    return (d & 0xFFFFFFFF00000000ull) | (uint64_t)((uint32_t)d + off16);
}
__device__ __forceinline__ void tma2d(uint32_t dst, const CUtensorMap* tm, int c0, int c1, uint32_t bar) {
    asm volatile("cp.async.bulk.tensor.2d.shared::cluster.global.mbarrier::complete_tx::bytes [%0], [%1, {%3, %4}], [%2];"
        :: "r"(dst), "l"((uint64_t)tm), "r"(bar), "r"(c0), "r"(c1) : "memory");
}
__device__ __forceinline__ void tma3d(uint32_t dst, const CUtensorMap* tm, int c0, int c1, int c2, uint32_t bar) {
    asm volatile("cp.async.bulk.tensor.3d.shared::cluster.global.mbarrier::complete_tx::bytes [%0], [%1, {%3, %4, %5}], [%2];"
        :: "r"(dst), "l"((uint64_t)tm), "r"(bar), "r"(c0), "r"(c1), "r"(c2) : "memory");
}
__device__ __forceinline__ void tma3d_mc(uint32_t dst, const CUtensorMap* tm, int c0, int c1, int c2, uint32_t bar) {
    asm volatile("cp.async.bulk.tensor.3d.shared::cluster.global.mbarrier::complete_tx::bytes.multicast::cluster [%0], [%1, {%3, %4, %5}], [%2], %6;"
        :: "r"(dst), "l"((uint64_t)tm), "r"(bar), "r"(c0), "r"(c1), "r"(c2), "h"((uint16_t)3) : "memory");
}
__device__ __forceinline__ void bulk_g2s(uint32_t dst, const void* src, uint32_t bytes, uint32_t bar) {
    asm volatile("cp.async.bulk.shared::cluster.global.mbarrier::complete_tx::bytes [%0], [%1], %2, [%3];"
        :: "r"(dst), "l"(src), "r"(bytes), "r"(bar) : "memory");
}
__device__ __forceinline__ void bulk_s2g(void* dst, uint32_t src, uint32_t bytes) {
    asm volatile("cp.async.bulk.global.shared::cta.bulk_group [%0], [%1], %2;" :: "l"(dst), "r"(src), "r"(bytes) : "memory");
}
__device__ __forceinline__ void tma2d_store(const CUtensorMap* tm, int c0, int c1, uint32_t src) {
    asm volatile("cp.async.bulk.tensor.2d.global.shared::cta.bulk_group [%0, {%2, %3}], [%1];"
        :: "l"((uint64_t)tm), "r"(src), "r"(c0), "r"(c1) : "memory");
}
__device__ __forceinline__ void l2_prefetch(const void* p, uint32_t bytes) {
    asm volatile("cp.async.bulk.prefetch.L2.global [%0], %1;" :: "l"(p), "r"(bytes) : "memory");
}
__device__ __forceinline__ void tmap_prefetch(const CUtensorMap* tm) { asm volatile("prefetch.tensormap [%0];" :: "l"((uint64_t)tm) : "memory"); }
__device__ __forceinline__ uint32_t lds32(uint32_t a) { uint32_t v; asm volatile("ld.shared.u32 %0, [%1];" : "=r"(v) : "r"(a)); return v; }
__device__ __forceinline__ uint2 lds64(uint32_t a) { uint2 v; asm volatile("ld.shared.v2.u32 {%0,%1}, [%2];" : "=r"(v.x), "=r"(v.y) : "r"(a)); return v; }
__device__ __forceinline__ uint4 lds128(uint32_t a) { uint4 v; asm volatile("ld.shared.v4.u32 {%0,%1,%2,%3}, [%4];" : "=r"(v.x), "=r"(v.y), "=r"(v.z), "=r"(v.w) : "r"(a)); return v; }
__device__ __forceinline__ float2 lds64f(uint32_t a) { float2 v; asm volatile("ld.shared.v2.f32 {%0,%1}, [%2];" : "=f"(v.x), "=f"(v.y) : "r"(a)); return v; }
__device__ __forceinline__ void sts32(uint32_t a, uint32_t v) { asm volatile("st.shared.u32 [%0], %1;" :: "r"(a), "r"(v) : "memory"); }
__device__ __forceinline__ void sts128(uint32_t a, uint4 v) { asm volatile("st.shared.v4.u32 [%0], {%1,%2,%3,%4};" :: "r"(a), "r"(v.x), "r"(v.y), "r"(v.z), "r"(v.w) : "memory"); }
__device__ __forceinline__ uint4 ldg_cg128(const void* p) { uint4 v; asm volatile("ld.global.cg.v4.u32 {%0,%1,%2,%3}, [%4];" : "=r"(v.x), "=r"(v.y), "=r"(v.z), "=r"(v.w) : "l"(p)); return v; }
__device__ __forceinline__ uint4 ldg_nc128(const void* p) { uint4 v; asm volatile("ld.global.nc.L1::no_allocate.v4.u32 {%0,%1,%2,%3}, [%4];" : "=r"(v.x), "=r"(v.y), "=r"(v.z), "=r"(v.w) : "l"(p)); return v; }
__device__ __forceinline__ uint32_t ldg_nc32(const void* p) { uint32_t v; asm volatile("ld.global.nc.u32 %0, [%1];" : "=r"(v) : "l"(p)); return v; }
__device__ __forceinline__ uint2 ldg_nc64(const void* p) { uint2 v; asm volatile("ld.global.nc.L1::no_allocate.v2.u32 {%0,%1}, [%2];" : "=r"(v.x), "=r"(v.y) : "l"(p)); return v; }
#define WG_FENCE() asm volatile("wgmma.fence.sync.aligned;\n" ::: "memory")
#define WG_COMMIT() asm volatile("wgmma.commit_group.sync.aligned;\n" ::: "memory")
template<int N> __device__ __forceinline__ void wg_wait() { asm volatile("wgmma.wait_group.sync.aligned %0;\n" :: "n"(N) : "memory"); }
__device__ __forceinline__ bool elect_one() {
    uint32_t pr;
    asm volatile("{\n.reg .pred p;\nelect.sync _|p, 0xffffffff;\nselp.u32 %0, 1, 0, p;\n}" : "=r"(pr));
    return pr != 0;
}
__device__ __forceinline__ void named_bar(int id, int n) { asm volatile("bar.sync %0, %1;" :: "r"(id), "r"(n) : "memory"); }

__device__ __forceinline__ float bf_lo(uint32_t u) { return __uint_as_float(u << 16); }
__device__ __forceinline__ float bf_hi(uint32_t u) { return __uint_as_float(u & 0xFFFF0000u); }
__device__ __forceinline__ uint32_t pack_bf(float lo, float hi) { uint32_t r; asm("cvt.rn.bf16x2.f32 %0, %1, %2;" : "=r"(r) : "f"(hi), "f"(lo)); return r; }
__device__ __forceinline__ float bf_round(float x) { return __bfloat162float(__float2bfloat16_rn(x)); }
__device__ __forceinline__ uint32_t bmul2(uint32_t a, uint32_t b) { uint32_t r; asm("mul.rn.bf16x2 %0, %1, %2;" : "=r"(r) : "r"(a), "r"(b)); return r; }
__device__ __forceinline__ uint32_t badd2(uint32_t a, uint32_t b) { uint32_t r; asm("add.rn.bf16x2 %0, %1, %2;" : "=r"(r) : "r"(a), "r"(b)); return r; }
__device__ __forceinline__ uint32_t bsub2(uint32_t a, uint32_t b) { uint32_t r; asm("sub.rn.bf16x2 %0, %1, %2;" : "=r"(r) : "r"(a), "r"(b)); return r; }
__device__ __forceinline__ void mma16816(float (&d)[4], uint32_t a0, uint32_t a1, uint32_t a2, uint32_t a3, uint2 b) {
    asm volatile("mma.sync.aligned.m16n8k16.row.col.f32.bf16.bf16.f32 {%0,%1,%2,%3}, {%4,%5,%6,%7}, {%8,%9}, {%0,%1,%2,%3};\n"
        : "+f"(d[0]), "+f"(d[1]), "+f"(d[2]), "+f"(d[3]) : "r"(a0), "r"(a1), "r"(a2), "r"(a3), "r"(b.x), "r"(b.y));
}

template<int HS> __device__ __forceinline__ void xreduce(float (&v)[8], int lane) {
    const int up = lane & HS;
    #pragma unroll
    for (int e = 0; e < HS; e++) {
        float keep, send;
        asm("{\n.reg .pred p;\nsetp.ne.b32 p, %4, 0;\nselp.f32 %0, %3, %2, p;\nselp.f32 %1, %2, %3, p;\n}"
            : "=f"(keep), "=f"(send) : "f"(v[e]), "f"(v[e + HS]), "r"(up));
        v[e] = keep + __shfl_xor_sync(0xffffffffu, send, HS);
    }
}

__device__ __forceinline__ int blk_f0(int s) {
    if (s < 32) return 32 * (14 * (s >> 3) + 8 * ((s >> 2) & 1) + (s & 3));
    const int s2 = s - 32, c6 = (s2 * 11) >> 6, t = s2 - 6 * c6;
    return 32 * (14 * c6 + (t < 4 ? 4 + t : 8 + t));
}
__device__ __forceinline__ int next_st2(int s) { return (0x14023 >> (4 * s)) & 7; }
__device__ __forceinline__ uint32_t stage_off_rt(int s) { return s < 3 ? SM_RING + s * STAGE_BYTES : (uint32_t)(s - 3) * 65536; }

__device__ __forceinline__ void store_h(uint32_t* dst, const uint32_t (&hp)[32], int q) {
    #pragma unroll
    for (int kk = 0; kk < 2; kk++) {
        uint32_t* d2 = dst + q * 2048 + kk * 512;
        d2[0] = hp[8 * q + 4 * kk]; d2[64] = hp[8 * q + 4 * kk + 1]; d2[32] = hp[8 * q + 4 * kk + 2]; d2[96] = hp[8 * q + 4 * kk + 3];
    }
}
template<int NB, bool passA>
__device__ __forceinline__ void gemm1_pass(uint32_t sb, int wgi, int warp4, int lane, int& st, uint32_t& fph, uint32_t e_cl,
                                           uint32_t (&hp)[32], uint32_t* prev_dst, bool convCTA) {
    float acc[NB * 32];
    const uint64_t descA0 = make_desc(sb + SM_X + wgi * 65536, 16, 1024, 1);
    const uint64_t descB0 = make_desc(sb + SM_RING, 4096, 512, 2);
    int prev = 0;
    auto group = [&](int sl) {
        if (warp4 == 0 && wgi == 0) PROF2(2, sl + (passA ? 0 : 8));
        mbar_wait(sb + SM_BARS + (B_FULL + st) * 8, (fph >> st) & 1);
        fph ^= 1u << st;
        if (sl == 0 && warp4 == 0) PROF(2 + wgi * 8 + (passA ? 0 : 3));
        if (warp4 == 0 && wgi == 0) PROF2(1, sl + (passA ? 0 : 8));
        const uint64_t da = desc_add(descA0, sl * 512), db = desc_add(descB0, st * 2048);
        WG_FENCE();
        #pragma unroll
        for (int kk = 0; kk < 4; kk++) {
            int sc = (sl | kk) ? 1 : 0;
            if constexpr (NB == 4) wgmma_ss_n256_tb(acc, da + kk * 2, db + kk * 64, sc); else wgmma_ss_n128_tb(acc, da + kk * 2, db + kk * 64, sc);
        }
        WG_COMMIT();
        wg_wait<1>();
        if (warp4 == 0 && wgi == 0) PROF2(3, sl + (passA ? 0 : 8));
        if (lane < 2 && sl && (passA || !convCTA || sl < 6)) mbar_arrive_cluster(e_cl + prev * 8, 1);
        if (!passA && sl == 4) {
            if (convCTA) { if (lane == 0) mbar_arrive(sb + SM_BARS + B_XFREE * 8); }
            else if (lane < 4) mbar_arrive_cluster(e_cl + (3 + (lane >> 1)) * 8, 1);
        }
        prev = st;
        st = (st == 2) ? 0 : st + 1;
    };
    if constexpr (passA) {
        #pragma unroll 1
        for (int sl = 0; sl < 8; sl++) group(sl);
    } else {
        #pragma unroll
        for (int sl = 0; sl < 4; sl++) { group(sl); store_h(prev_dst, hp, sl); }
        __syncwarp();
        if (lane == 0) mbar_arrive(sb + SM_BARS + (B_HD + wgi * 2) * 8);
        #pragma unroll 1
        for (int sl = 4; sl < 8; sl++) group(sl);
    }
    wg_wait<0>();
    if (lane < 2 && (passA || !convCTA)) mbar_arrive_cluster(e_cl + prev * 8, 1);
    if (!passA && lane == 0) mbar_arrive(sb + SM_BARS + B_G1DONE * 8);
    if (warp4 == 0) PROF(3 + wgi * 8 + (passA ? 0 : 3));
    const int g = lane >> 2;
    const int r0 = wgi * 64 + warp4 * 16 + g;
    const float s0 = __uint_as_float(lds32(sb + SM_STATS + r0 * 8 + 4)), s1 = __uint_as_float(lds32(sb + SM_STATS + (r0 + 8) * 8 + 4));
    #pragma unroll
    for (int t = 0; t < NB * 4; t++) {
        const float* ag = &acc[4 * t];
        const float* au = &acc[NB * 16 + 4 * t];
        hp[2 * t] = bmul2(pack_bf(ag[0] * s0, ag[1] * s0), pack_bf(au[0] * s0, au[1] * s0));
        hp[2 * t + 1] = bmul2(pack_bf(ag[2] * s1, ag[3] * s1), pack_bf(au[2] * s1, au[3] * s1));
    }
    if (warp4 == 0) PROF(4 + wgi * 8 + (passA ? 0 : 3));
}

__global__ void __cluster_dims__(2, 1, 1) __launch_bounds__(NTHREADS, 1)
fused_kernel(const __grid_constant__ Params p) {
    extern __shared__ __align__(1024) uint8_t smem_raw[];
    const uint32_t sb = smem_u32(smem_raw);
    const int tid = threadIdx.x, warp = tid >> 5, lane = tid & 31;
    const int b = blockIdx.x;
    const int rank = b & 1;
    const int j = (b >> 1) & 7;
    const int i = ((b >> 4) << 1) | rank;
    const int cb = j >> 1;
    const bool convCTA = j & 1;
    const int cidx = 4 * i + cb;

    if (tid == 256) {
        mbar_init(sb + SM_BARS + B_XFULL * 8, 1);
        mbar_init(sb + SM_BARS + (B_XFULL + 1) * 8, 1);
        asm volatile("fence.proxy.async.shared::cta;" ::: "memory");
        mbar_expect_tx(sb + SM_BARS + B_XFULL * 8, 65536);
        tma3d(sb + SM_X, &p.tm_x, 0, 128 * i, 0, sb + SM_BARS + B_XFULL * 8);
        mbar_expect_tx(sb + SM_BARS + (B_XFULL + 1) * 8, 65536);
        tma3d(sb + SM_X + 65536, &p.tm_x, 0, 128 * i + 64, 0, sb + SM_BARS + (B_XFULL + 1) * 8);
    }
    if (tid == 288) {
        for (int s = 0; s < 5; s++) { mbar_init(sb + SM_BARS + (B_FULL + s) * 8, 1); mbar_init(sb + SM_BARS + (B_EMPTY + s) * 8, 16); }
        mbar_init(sb + SM_BARS + B_CONV * 8, 1);
        mbar_init(sb + SM_BARS + B_YT * 8, 1);
        mbar_init(sb + SM_BARS + B_XR * 8, 1);
        mbar_init(sb + SM_BARS + B_G1DONE * 8, 8);
        mbar_init(sb + SM_BARS + B_XFREE * 8, 8);
        mbar_init(sb + SM_BARS + B_YST * 8, 8);
        mbar_init(sb + SM_BARS + B_KVLD * 8, 2);
        mbar_init(sb + SM_BARS + B_LN * 8, 8);
        for (int s = 0; s < 4; s++) mbar_init(sb + SM_BARS + (B_HD + s) * 8, 4);
        for (int s = 0; s < 2; s++) mbar_init(sb + SM_BARS + (B_HRDY + s) * 8, 1);
        asm volatile("fence.mbarrier_init.release.cluster;" ::: "memory");
        asm volatile("fence.proxy.async.shared::cta;" ::: "memory");
    }
    __syncwarp();
    asm volatile("barrier.cluster.arrive.relaxed.aligned;\n" ::: "memory");
    asm volatile("barrier.cluster.wait.aligned;\n" ::: "memory");
    PROFW(1, 0);

    if (warp < 8) {
        asm volatile("setmaxnreg.inc.sync.aligned.u32 200;");
        const int wgi = warp >> 2, warp4 = warp & 3;
        const int g = lane >> 2, c = lane & 3;
        const uint32_t e_cl = mapa(sb + SM_BARS + B_EMPTY * 8, lane & 1);
        {
            const int lr16 = (lane & 7) + ((lane >> 3) & 1) * 8;
            const uint32_t xa = sb + SM_X + wgi * 65536 + (warp4 * 16 + lr16) * 128;
            uint32_t xf[32][4];
            float aS[4][4], aQ0[4][4], aQ1[4][4];
            #pragma unroll
            for (int e = 0; e < 4; e++) {
                #pragma unroll
                for (int f = 0; f < 4; f++) { aS[e][f] = 0.f; aQ0[e][f] = 0.f; aQ1[e][f] = 0.f; }
            }
            mbar_wait(sb + SM_BARS + (B_XFULL + wgi) * 8, 0);
            PROFW(16, 0); PROFW(18, 4);
            #pragma unroll
            for (int ks = 0; ks < 32; ks++) {
                const uint32_t a = xa + (ks >> 2) * 8192 + (((2 * (ks & 3) + (lane >> 4)) ^ (lane & 7)) << 4);
                asm volatile("ldmatrix.sync.aligned.m8n8.x4.shared.b16 {%0,%1,%2,%3}, [%4];"
                    : "=r"(xf[ks][0]), "=r"(xf[ks][1]), "=r"(xf[ks][2]), "=r"(xf[ks][3]) : "r"(a) : "memory");
            }
            PROFW(40, 4);
            #pragma unroll
            for (int ks = 0; ks < 32; ks++)
                mma16816(aS[ks & 3], xf[ks][0], xf[ks][1], xf[ks][2], xf[ks][3], make_uint2(0x3F803F80u, 0x3F803F80u));
            const float mean0 = ((aS[0][0] + aS[1][0]) + (aS[2][0] + aS[3][0])) * (1.0f / DM);
            const float mean1 = ((aS[0][2] + aS[1][2]) + (aS[2][2] + aS[3][2])) * (1.0f / DM);
            const uint32_t m0 = pack_bf(mean0, mean0), m1 = pack_bf(mean1, mean1);
            PROFW(41, 4);
            #pragma unroll
            for (int ks = 0; ks < 32; ks++) {
                const uint32_t a = xa + (ks >> 2) * 8192 + (((2 * (ks & 3) + (lane >> 4)) ^ (lane & 7)) << 4);
                asm volatile("stmatrix.sync.aligned.m8n8.x4.shared.b16 [%0], {%1,%2,%3,%4};"
                    :: "r"(a), "r"(bsub2(xf[ks][0], m0)), "r"(bsub2(xf[ks][1], m1)), "r"(bsub2(xf[ks][2], m0)), "r"(bsub2(xf[ks][3], m1)) : "memory");
            }
            PROFW(42, 4);
            asm volatile("fence.proxy.async.shared::cta;" ::: "memory");
            __syncwarp();
            if (lane == 0) mbar_arrive(sb + SM_BARS + B_LN * 8);
            #pragma unroll
            for (int ks = 0; ks < 32; ks++) {
                mma16816(aQ0[ks & 3], xf[ks][0], xf[ks][1], xf[ks][2], xf[ks][3], make_uint2(xf[ks][0], xf[ks][2]));
                mma16816(aQ1[ks & 3], xf[ks][0], xf[ks][1], xf[ks][2], xf[ks][3], make_uint2(xf[ks][1], xf[ks][3]));
            }
            if (c == (g >> 1)) {
                const float q0 = (g & 1) ? (aQ0[0][1] + aQ0[1][1]) + (aQ0[2][1] + aQ0[3][1]) : (aQ0[0][0] + aQ0[1][0]) + (aQ0[2][0] + aQ0[3][0]);
                const float q1 = (g & 1) ? (aQ1[0][3] + aQ1[1][3]) + (aQ1[2][3] + aQ1[3][3]) : (aQ1[0][2] + aQ1[1][2]) + (aQ1[2][2] + aQ1[3][2]);
                const float sd0 = bf_round(sqrtf(bf_round(bf_round(fmaxf(q0 * (1.0f / DM) - mean0 * mean0, 0.f)) + 1e-5f)));
                const float sd1 = bf_round(sqrtf(bf_round(bf_round(fmaxf(q1 * (1.0f / DM) - mean1 * mean1, 0.f)) + 1e-5f)));
                const uint32_t sa = sb + SM_STATS + (warp * 16 + g) * 8;
                sts32(sa, m0); sts32(sa + 4, __float_as_uint(1.0f / sd0));
                sts32(sa + 64, m1); sts32(sa + 68, __float_as_uint(1.0f / sd1));
            }
            mbar_wait(sb + SM_BARS + B_LN * 8, 0);
            PROFW(19, 4);
            PROFW(17, 0);
        }
        int st = 0; uint32_t fph = 0;
        uint32_t hp[32];
        uint32_t* const hdst = g_h + (size_t)(i * 56) * 2048 + wgi * 1024 + warp4 * 128 + lane;
        gemm1_pass<4, true>(sb, wgi, warp4, lane, st, fph, e_cl, hp, hdst, convCTA);

        if (convCTA) {
            gemm1_pass<2, false>(sb, wgi, warp4, lane, st, fph, e_cl, hp, hdst + 4 * j * 2048, true);
            store_h(hdst + (36 + 6 * cb) * 2048, hp, 0); store_h(hdst + (36 + 6 * cb) * 2048, hp, 1);
            __syncwarp();
            if (lane == 0) mbar_arrive(sb + SM_BARS + (B_HD + wgi * 2 + 1) * 8);
            const int gch = 8 * cidx + warp;
            const uint32_t xb = sb + SM_CVX + warp * 4096;
            const uint32_t hb = sb + SM_CVH + warp * 4096;
            const uint32_t dw = ((const unsigned short*)p.ssm_D)[gch];
            const uint32_t d2 = dw | (dw << 16);
            mbar_wait(sb + SM_BARS + B_CONV * 8, 0);
            PROFW(32, 4);
            float acc[16][4];
            #pragma unroll
            for (int jj = 0; jj < 16; jj++) { acc[jj][0] = 0.f; acc[jj][1] = 0.f; acc[jj][2] = 0.f; acc[jj][3] = 0.f; }
            uint2 bh[8], bl0[8], bl1[8];
            uint32_t xl = xb + g * 32 + c * 8;
            uint32_t hl = hb + (g + 2 * c - 8) * 4;
            #pragma unroll
            for (int d = 0; d < 8; d++) { bl0[d] = lds64(xl + d * 256); bh[d] = lds64(xl + (8 + d) * 256); }
            uint32_t w[6];
            w[0] = 0; w[1] = 0; w[2] = 0;
            if (g + 2 * c >= 8) w[0] = lds32(hl);
            if (g + 2 * c >= 7) w[1] = lds32(hl + 4);
            if (g + 2 * c >= 6) w[2] = lds32(hl + 8);
            w[3] = lds32(hl + 2048); w[4] = lds32(hl + 2052); w[5] = lds32(hl + 2056);
            auto conv_m0 = [&](int m0, uint2 (&bl)[8], uint2 (&bn)[8]) {
                xl -= 32;
                #pragma unroll
                for (int k = 0; k < 8; k++) {
                    const uint32_t a0 = w[1], a1 = __byte_perm(w[0], w[1], 0x5432), a2 = w[2], a3 = __byte_perm(w[1], w[2], 0x5432);
                    const uint32_t c0 = w[4], c1 = __byte_perm(w[3], w[4], 0x5432), c2 = w[5], c3 = __byte_perm(w[4], w[5], 0x5432);
                    const uint32_t nx = (k < 7) ? hl + (k + 1) * 256 : hl + 32;
                    w[0] = lds32(nx); w[1] = lds32(nx + 4); w[2] = lds32(nx + 8);
                    w[3] = lds32(nx + 2048); w[4] = lds32(nx + 2052); w[5] = lds32(nx + 2056);
                    if (k > 0) bn[k] = lds64(xl + k * 256);
                    else { bn[0] = make_uint2(0, 0); if (g > m0) bn[0] = lds64(xl); }
                    #pragma unroll
                    for (int jj = k; jj < 16; jj++) mma16816(acc[jj], a0, a1, a2, a3, (jj - k < 8) ? bl[(jj - k) & 7] : bh[(jj - k) & 7]);
                    bh[7 - k] = lds64(xl + (15 - k) * 256);
                    #pragma unroll
                    for (int jj = k + 8; jj < 16; jj++) mma16816(acc[jj], c0, c1, c2, c3, bl[jj - k - 8]);
                }
                hl += 32;
            };
            #pragma unroll 1
            for (int m0 = 0; m0 < 8; m0 += 2) {
                conv_m0(m0, bl0, bl1);
                conv_m0(m0 + 1, bl1, bl0);
                PROFW(34 + (m0 >> 1), 4);
            }
            PROFW(33, 4);
            const uint32_t kvl = xb + c * 64 + (7 - g) * 4;
            uint32_t* ydst = (uint32_t*)(g_yT + (size_t)gch * SEQ + 32 * c + 2 * g);
            uint32_t kk0[16], kk1[16];
            #pragma unroll
            for (int jj = 0; jj < 16; jj++) { kk0[jj] = lds32(kvl + jj * 256); kk1[jj] = lds32(kvl + jj * 256 + 32); }
            #pragma unroll
            for (int jj = 0; jj < 16; jj++) {
                ydst[jj * 64] = badd2(pack_bf(acc[jj][2], acc[jj][0]), bmul2(__byte_perm(kk0[jj], kk0[jj], 0x1032), d2));
                ydst[jj * 64 + 8] = badd2(pack_bf(acc[jj][3], acc[jj][1]), bmul2(__byte_perm(kk1[jj], kk1[jj], 0x1032), d2));
            }
            __syncwarp();
            PROFW(44, 4);
            if (lane == 0) mbar_arrive(sb + SM_BARS + B_YST * 8);
        } else {
            gemm1_pass<4, false>(sb, wgi, warp4, lane, st, fph, e_cl, hp, hdst + 4 * j * 2048, false);
            float acc[64];
            const uint64_t descB0 = make_desc(sb, 4096, 1024, 1);
            const uint64_t descA0 = make_desc(sb + 16384 + wgi * 4096, 128, 256, 0);
            int sg = 3; uint32_t ph = 6;
            PROFW(20, 0);
            int p1 = 0;
            auto g2 = [&](int o) {
                const int s0 = sg, s1 = next_st2(sg);
                sg = next_st2(s1);
                if (warp == 0) PROF2(2, 16 + o);
                mbar_wait(sb + SM_BARS + (B_FULL + s0) * 8, (ph >> s0) & 1);
                if (warp == 0) PROF2(1, 16 + o);
                const uint32_t o0 = stage_off_rt(s0) >> 4, o1 = stage_off_rt(s1) >> 4;
                const uint64_t da0 = desc_add(descA0, o0), db0 = desc_add(descB0, o0), da1 = desc_add(descA0, o1), db1 = desc_add(descB0, o1);
                WG_FENCE();
                #pragma unroll
                for (int kk = 0; kk < 4; kk++) wgmma_ss_n128_tb(acc, da0 + ((kk >> 1) * 512 + (kk & 1) * 128), db0 + ((kk >> 1) * 512 + (kk & 1) * 128), (o | kk) ? 1 : 0);
                WG_COMMIT();
                mbar_wait(sb + SM_BARS + (B_FULL + s1) * 8, (ph >> s1) & 1);
                ph ^= (1u << s0) | (1u << s1);
                #pragma unroll
                for (int kk = 0; kk < 4; kk++) wgmma_ss_n128_tb(acc, da1 + ((kk >> 1) * 512 + (kk & 1) * 128), db1 + ((kk >> 1) * 512 + (kk & 1) * 128), 1);
                WG_COMMIT();
                wg_wait<1>();
                if (warp == 0) PROF2(3, 16 + o);
                if (lane < 2 && o > 0 && 2 * o + 4 < 28) mbar_arrive_cluster(e_cl + p1 * 8, 1);
                if (lane < 2 && 2 * o + 5 < 28) mbar_arrive_cluster(e_cl + s0 * 8, 1);
                p1 = s1;
            };
            #pragma unroll
            for (int o = 0; o < 2; o++) { g2(o); store_h(hdst + (32 + 6 * cb) * 2048, hp, 2 * o); store_h(hdst + (32 + 6 * cb) * 2048, hp, 2 * o + 1); }
            __syncwarp();
            if (lane == 0) mbar_arrive(sb + SM_BARS + (B_HD + wgi * 2 + 1) * 8);
            #pragma unroll 1
            for (int o = 2; o < 14; o++) g2(o);
            wg_wait<0>();
            PROFW(27, 0);
            mbar_wait(sb + SM_BARS + B_XR * 8, 0);
            const int r0 = wgi * 64 + warp4 * 16 + g;
            const float2 st0 = lds64f(sb + SM_STATS + r0 * 8), st1 = lds64f(sb + SM_STATS + (r0 + 8) * 8);
            const uint32_t m0 = __float_as_uint(st0.x), m1 = __float_as_uint(st1.x);
            const uint32_t xrow0 = sb + SM_XE + r0 * 128 + c * 4;
            const int mi = lane >> 3, lr = lane & 7;
            const uint32_t yaddr = sb + SM_YT + wgi * 16384 + ((mi >> 1) * 8 + lr) * 128 + (((2 * warp4 + (mi & 1)) ^ lr) << 4);
            uint32_t y[8][4], xv[16][2], nv[16][2], bv[16][2];
            #pragma unroll
            for (int t = 0; t < 16; t++) {
                const uint32_t off = (t >> 3) * 16384 + (((t & 7) ^ g) << 4);
                xv[t][0] = lds32(xrow0 + off); xv[t][1] = lds32(xrow0 + 1024 + off);
            }
            #pragma unroll
            for (int t = 0; t < 16; t++) {
                const uint32_t d0 = bsub2(xv[t][0], m0), d1 = bsub2(xv[t][1], m1);
                nv[t][0] = pack_bf(bf_lo(d0) * st0.y, bf_hi(d0) * st0.y); nv[t][1] = pack_bf(bf_lo(d1) * st1.y, bf_hi(d1) * st1.y);
                bv[t][0] = pack_bf(acc[4 * t], acc[4 * t + 1]); bv[t][1] = pack_bf(acc[4 * t + 2], acc[4 * t + 3]);
            }
            mbar_wait(sb + SM_BARS + B_YT * 8, 0);
            PROFW(28, 0);
            #pragma unroll
            for (int t2 = 0; t2 < 8; t2++)
                asm volatile("ldmatrix.sync.aligned.m8n8.x4.trans.shared.b16 {%0,%1,%2,%3}, [%4];"
                    : "=r"(y[t2][0]), "=r"(y[t2][1]), "=r"(y[t2][2]), "=r"(y[t2][3]) : "r"(yaddr + t2 * 2048) : "memory");
            #pragma unroll
            for (int t = 0; t < 16; t++) {
                const uint32_t off = (t >> 3) * 16384 + (((t & 7) ^ g) << 4);
                sts32(xrow0 + off, badd2(badd2(xv[t][0], bmul2(nv[t][0], y[t >> 1][2 * (t & 1)])), bv[t][0]));
                sts32(xrow0 + 1024 + off, badd2(badd2(xv[t][1], bmul2(nv[t][1], y[t >> 1][2 * (t & 1) + 1])), bv[t][1]));
            }
            asm volatile("fence.proxy.async.shared::cta;" ::: "memory");
            named_bar(1 + wgi, 128);
            if ((tid & 127) == 0) {
                tma2d_store(&p.tm_out, 128 * cb, 128 * i + 64 * wgi, sb + SM_XE + wgi * 8192);
                tma2d_store(&p.tm_out, 128 * cb + 64, 128 * i + 64 * wgi, sb + SM_XE + 16384 + wgi * 8192);
                asm volatile("cp.async.bulk.commit_group;" ::: "memory");
                asm volatile("cp.async.bulk.wait_group.read 0;" ::: "memory");
                PROFW(29, 0);
            }
        }
    } else {
        asm volatile("setmaxnreg.dec.sync.aligned.u32 104;");
        if (warp == 8) {
            int st = 0; uint32_t eph = 7;
            #pragma unroll 1
            for (int it = 0; it < 16; it++) {
                const int pass = it >> 3, sl = it & 7;
                const bool narrow = pass && convCTA;
                const int nb = narrow ? 2 : 4;
                const CUtensorMap* tm = narrow ? (rank ? &p.tm_uB : &p.tm_gB) : (rank ? &p.tm_uA : &p.tm_gA);
                mbar_wait(sb + SM_BARS + (B_EMPTY + st) * 8, (eph >> st) & 1);
                eph ^= 1u << st;
                if (it == 1) mbar_wait(sb + SM_BARS + B_XFULL * 8, 0);
                PROF2(0, it);
                if (elect_one()) {
                    mbar_expect_tx(sb + SM_BARS + (B_FULL + st) * 8, nb * 8192);
                    tma3d_mc(sb + SM_RING + st * STAGE_BYTES + rank * nb * 4096, tm, 0, sl * 64, 14 * cb + 8 * (j & 1) + 4 * pass, sb + SM_BARS + (B_FULL + st) * 8);
                }
                st = (st == 2) ? 0 : st + 1;
            }
            if (!convCTA) {
                st = 3;
                const int f0_lane = blk_f0(2 * lane + rank);
                #pragma unroll 1
                for (int u = 0; u < 28; u++) {
                    const uint32_t bar = sb + SM_BARS + (B_FULL + st) * 8;
                    const int f0 = __shfl_sync(0xffffffffu, f0_lane, u);
                    mbar_wait(sb + SM_BARS + (B_EMPTY + st) * 8, (eph >> st) & 1);
                    eph ^= 1u << st;
                    if ((u & 1) == 0) PROF2(0, 16 + (u >> 1));
                    if (elect_one()) {
                        mbar_expect_tx(bar, 32768);
                        tma3d_mc(sb + stage_off_rt(st) + rank * 8192, &p.tm_w2, 0, f0, 2 * cb, bar);
                    }
                    st = next_st2(st);
                }
                PROF(48);
            }
        } else if (warp < 11) {
            mbar_wait(sb + SM_BARS + (B_XFULL + 1) * 8, 0);
            {
                const int q = lane & 3;
                const int t0 = 32 * (b >> 1) + 8 * q;
                const int ch0 = 256 * (b & 1) + 16 * (warp - 9) + 2 * (lane >> 2);
                const uint32_t* kp = (const uint32_t*)(p.k + (size_t)t0 * DM + ch0);
                const uint32_t* vp = (const uint32_t*)(p.v + (size_t)t0 * DM + ch0);
                __nv_bfloat16* dst0 = g_kvT + (size_t)ch0 * SEQ + (t0 ^ 8);
                #pragma unroll 1
                for (int rnd = 0; rnd < 2; rnd++) {
                    uint32_t kr[4][11], vr[4][8]; uint4 skw[4];
                    #pragma unroll
                    for (int u = 0; u < 4; u++) {
                        const int co = (rnd * 4 + u) * 16;
                        skw[u] = ldg_nc128(p.shift_k + 4 * (ch0 + 2 * co));
                        #pragma unroll
                        for (int r = 0; r < 11; r++) kr[u][r] = (r >= 3 || t0 > 0) ? ldg_nc32(kp + co + (r - 3) * (DM / 2)) : 0u;
                        #pragma unroll
                        for (int r = 0; r < 8; r++) vr[u][r] = ldg_nc32(vp + co + r * (DM / 2));
                    }
                    #pragma unroll
                    for (int u = 0; u < 4; u++) {
                        const uint32_t s0 = __byte_perm(skw[u].x, skw[u].z, 0x5410), s1 = __byte_perm(skw[u].x, skw[u].z, 0x7632);
                        const uint32_t s2 = __byte_perm(skw[u].y, skw[u].w, 0x5410), s3 = __byte_perm(skw[u].y, skw[u].w, 0x7632);
                        #pragma unroll
                        for (int r = 0; r < 8; r++) {
                            uint32_t a = bmul2(kr[u][r], s3);
                            a = badd2(a, bmul2(kr[u][r + 1], s2));
                            a = badd2(a, bmul2(kr[u][r + 2], s1));
                            a = badd2(a, bmul2(kr[u][r + 3], s0));
                            vr[u][r] = bmul2(a, vr[u][r]);
                        }
                        __nv_bfloat16* dst = dst0 + (size_t)((rnd * 4 + u) * 32) * SEQ;
                        *(uint4*)dst = make_uint4(__byte_perm(vr[u][7], vr[u][6], 0x5410), __byte_perm(vr[u][5], vr[u][4], 0x5410),
                                                  __byte_perm(vr[u][3], vr[u][2], 0x5410), __byte_perm(vr[u][1], vr[u][0], 0x5410));
                        *(uint4*)(dst + SEQ) = make_uint4(__byte_perm(vr[u][7], vr[u][6], 0x7632), __byte_perm(vr[u][5], vr[u][4], 0x7632),
                                                          __byte_perm(vr[u][3], vr[u][2], 0x7632), __byte_perm(vr[u][1], vr[u][0], 0x7632));
                    }
                    PROFW(57 + 2 * rnd, 9);
                }
                if (lane == 0) mbar_arrive(sb + SM_BARS + B_KVLD * 8);
            }
            asm volatile("fence.proxy.async.global;" ::: "memory");
            __syncwarp();
            if (lane == 0) {
                flag_add(&g_cnt_kv[0]);
                PROFW(50, 9);
                const int wgi = warp - 9;
                mbar_wait(sb + SM_BARS + (B_HD + wgi * 2) * 8, 0);
                flag_add(&g_flag_h[(i * 2 + 0) * 8]);
                mbar_wait(sb + SM_BARS + (B_HD + wgi * 2 + 1) * 8, 0);
                flag_add(&g_flag_h[(i * 2 + 1) * 8]);
                if (wgi == 1 && convCTA) {
                    mbar_wait(sb + SM_BARS + B_YST * 8, 0);
                    flag_add(&g_cnt_y[(cidx >> 4) * 32]);
                    PROF(46);
                }
                if (wgi == 1 && !convCTA) {
                    const unsigned ep = lds32(sb + SM_EPOCH);
                    mbar_wait(sb + SM_BARS + B_G1DONE * 8, 0);
                    mbar_expect_tx(sb + SM_BARS + B_XR * 8, 32768);
                    tma3d(sb + SM_XE, &p.tm_xe, 0, 128 * i, 2 * cb, sb + SM_BARS + B_XR * 8);
                    flag_wait(&g_flag_h[(i * 2 + 1) * 8], ep * 16);
                    mbar_arrive(sb + SM_BARS + (B_HRDY + 1) * 8);
                    __nanosleep(3000);
                    flag_wait(&g_cnt_y[cb * 32], ep * 16);
                    PROF(49);
                    asm volatile("fence.proxy.async.global;" ::: "memory");
                    mbar_expect_tx(sb + SM_BARS + B_YT * 8, 32768);
                    tma2d(sb + SM_YT, &p.tm_yT, 128 * i, 128 * cb, sb + SM_BARS + B_YT * 8);
                    tma2d(sb + SM_YT + 16384, &p.tm_yT, 128 * i + 64, 128 * cb, sb + SM_BARS + B_YT * 8);
                }
            }
        } else {
            if (lane == 0) {
                l2_prefetch(p.wg + (size_t)b * (FF * DM / NCTA), FF * DM / NCTA * 2);
                l2_prefetch(p.wu + (size_t)b * (FF * DM / NCTA), FF * DM / NCTA * 2);
                const unsigned ep = g_launch[b] + 1;
                g_launch[b] = ep;
                sts32(sb + SM_EPOCH, ep);
                tmap_prefetch(rank ? &p.tm_uA : &p.tm_gA);
                tmap_prefetch(rank ? &p.tm_uB : &p.tm_gB);
                tmap_prefetch(&p.tm_w2); tmap_prefetch(&p.tm_yT); tmap_prefetch(&p.tm_out); tmap_prefetch(&p.tm_xe);
                mbar_wait(sb + SM_BARS + B_KVLD * 8, 0);
                l2_prefetch(p.ssm_k + (size_t)(4 * b) * SEQ, 4 * SEQ * 2);
                l2_prefetch(p.wd + (size_t)b * (FF * DM / NCTA), FF * DM / NCTA * 2);
                mbar_wait(sb + SM_BARS + (B_HD + 0) * 8, 0);
                if (convCTA) {
                    flag_wait(&g_cnt_kv[0], ep * 256);
                    asm volatile("fence.proxy.async.global;" ::: "memory");
                    PROF(53);
                    mbar_wait(sb + SM_BARS + B_XFREE * 8, 0);
                    PROF(54);
                    mbar_expect_tx(sb + SM_BARS + B_CONV * 8, 65536);
                    bulk_g2s(sb + SM_CVX, g_kvT + (size_t)(8 * cidx) * SEQ, 32768, sb + SM_BARS + B_CONV * 8);
                    bulk_g2s(sb + SM_CVH, p.ssm_k + (size_t)(8 * cidx) * SEQ, 32768, sb + SM_BARS + B_CONV * 8);
                } else {
                    flag_wait(&g_flag_h[(i * 2 + 0) * 8], ep * 16);
                }
            }
            __syncwarp();
            if (!convCTA) {
                asm volatile("fence.proxy.async.global;" ::: "memory");
                int st = 3; uint32_t eph = 1;
                const uint8_t* hsrc = (const uint8_t*)g_h + (size_t)i * 56 * 8192;
                #pragma unroll 1
                for (int u = 0; u < 28; u++) {
                    mbar_wait(sb + SM_BARS + (B_EMPTY + st) * 8, (eph >> st) & 1);
                    eph ^= 1u << st;
                    if (u == 16) {
                        mbar_wait(sb + SM_BARS + (B_HRDY + 1) * 8, 0);
                        asm volatile("fence.proxy.async.global;" ::: "memory");
                    }
                    if (elect_one()) bulk_g2s(sb + stage_off_rt(st) + 16384, hsrc + u * 16384, 16384, sb + SM_BARS + (B_FULL + st) * 8);
                    st = next_st2(st);
                }
            }
        }
    }
}

typedef CUresult (*EncodeFn)(CUtensorMap*, CUtensorMapDataType, cuuint32_t, void*, const cuuint64_t*, const cuuint64_t*,
                             const cuuint32_t*, const cuuint32_t*, CUtensorMapInterleave, CUtensorMapSwizzle,
                             CUtensorMapL2promotion, CUtensorMapFloatOOBfill);

void encode(EncodeFn fn, CUtensorMap* tm, const void* base, int rank, const cuuint64_t* dims, const cuuint64_t* strides,
            const cuuint32_t* box, CUtensorMapSwizzle swz) {
    cuuint32_t es[5] = {1, 1, 1, 1, 1};
    fn(tm, CU_TENSOR_MAP_DATA_TYPE_BFLOAT16, rank, (void*)base, dims, strides, box, es, CU_TENSOR_MAP_INTERLEAVE_NONE, swz,
       CU_TENSOR_MAP_L2_PROMOTION_L2_128B, CU_TENSOR_MAP_FLOAT_OOB_FILL_NONE);
}

}

extern "C" void kernel_launch(void* const* d_in, const int* in_sizes, int n_in, void* d_out, int out_size) {
    (void)in_sizes; (void)n_in; (void)out_size;
    static EncodeFn enc = nullptr;
    static void* yT_ptr = nullptr;
    if (!enc) {
        void* fn = nullptr; cudaDriverEntryPointQueryResult qr;
        cudaGetDriverEntryPoint("cuTensorMapEncodeTiled", &fn, cudaEnableDefault, &qr);
        enc = (EncodeFn)fn;
        cudaGetSymbolAddress(&yT_ptr, g_yT);
        cudaFuncSetAttribute(fused_kernel, cudaFuncAttributeMaxDynamicSharedMemorySize, SM_TOTAL);
    }
    Params p;
    p.q = (const __nv_bfloat16*)d_in[0]; p.k = (const __nv_bfloat16*)d_in[1]; p.v = (const __nv_bfloat16*)d_in[2];
    p.shift_k = (const __nv_bfloat16*)d_in[3]; p.ssm_k = (const __nv_bfloat16*)d_in[4]; p.ssm_D = (const __nv_bfloat16*)d_in[5];
    p.wg = (const __nv_bfloat16*)d_in[7]; p.wu = (const __nv_bfloat16*)d_in[8]; p.wd = (const __nv_bfloat16*)d_in[9];
    {
        cuuint64_t dims[2] = {DM, SEQ}; cuuint64_t str[1] = {DM * 2};
        cuuint64_t dims3[3] = {64, SEQ, DM / 64}; cuuint64_t str3[2] = {DM * 2, 128};
        cuuint32_t box[3] = {64, 64, 8}, boxe[3] = {64, 128, 2};
        encode(enc, &p.tm_x, p.q, 3, dims3, str3, box, CU_TENSOR_MAP_SWIZZLE_128B);
        encode(enc, &p.tm_xe, p.q, 3, dims3, str3, boxe, CU_TENSOR_MAP_SWIZZLE_128B);
        cuuint32_t box2[2] = {64, 64};
        encode(enc, &p.tm_out, d_out, 2, dims, str, box2, CU_TENSOR_MAP_SWIZZLE_128B);
    }
    {
        cuuint64_t dims[3] = {32, DM, FF / 32}; cuuint64_t str[2] = {FF * 2, 64};
        cuuint32_t boxA[3] = {32, 64, 4}, boxB[3] = {32, 64, 2};
        encode(enc, &p.tm_gA, p.wg, 3, dims, str, boxA, CU_TENSOR_MAP_SWIZZLE_64B);
        encode(enc, &p.tm_gB, p.wg, 3, dims, str, boxB, CU_TENSOR_MAP_SWIZZLE_64B);
        encode(enc, &p.tm_uA, p.wu, 3, dims, str, boxA, CU_TENSOR_MAP_SWIZZLE_64B);
        encode(enc, &p.tm_uB, p.wu, 3, dims, str, boxB, CU_TENSOR_MAP_SWIZZLE_64B);
    }
    {
        cuuint64_t dims[3] = {64, FF, DM / 64}; cuuint64_t str[2] = {DM * 2, 128};
        cuuint32_t box[3] = {64, 32, 2};
        encode(enc, &p.tm_w2, p.wd, 3, dims, str, box, CU_TENSOR_MAP_SWIZZLE_128B);
    }
    {
        cuuint64_t dims[2] = {SEQ, DM}; cuuint64_t str[1] = {SEQ * 2};
        cuuint32_t box[2] = {64, 128};
        encode(enc, &p.tm_yT, yT_ptr, 2, dims, str, box, CU_TENSOR_MAP_SWIZZLE_128B);
    }
    fused_kernel<<<NCTA, NTHREADS, SM_TOTAL>>>(p);
}
```

```cpp
#include <cuda_runtime.h>
#include <cuda_bf16.h>
#include <cuda.h>
#include <stdint.h>

namespace {

constexpr int SEQ = 2048, DM = 512, FF = 1792;
constexpr int NCTA = 128;
constexpr int NTHREADS = 384;
constexpr int STAGE_BYTES = 32768;
#define KV_STAGGER 300
#define KV_GAP 150

constexpr uint32_t SM_X = 0;
constexpr uint32_t SM_RING = 131072;
constexpr uint32_t SM_MISC = SM_RING + 3 * STAGE_BYTES;
constexpr uint32_t SM_BARS = SM_MISC;
constexpr uint32_t SM_EPOCH = SM_MISC + 248;
constexpr uint32_t SM_STATS = SM_MISC + 256;
constexpr uint32_t SM_TOTAL = SM_STATS + 1024;
static_assert(SM_TOTAL <= 232448, "smem");
constexpr uint32_t SM_CVX = 0;
constexpr uint32_t SM_CVH = 65536;
constexpr uint32_t SM_YT = 32768;
constexpr uint32_t SM_XE = 98304;

constexpr int B_FULL = 0, B_EMPTY = 5, B_XFULL = 10, B_CONV = 14, B_YT = 15, B_XR = 16, B_G1DONE = 17, B_HD = 18, B_HRDY = 22,
              B_XFREE = 24, B_YST = 25, B_KVLD = 26, B_LN = 27, B_COUNT = 28;
static_assert(B_COUNT * 8 <= 248, "barrier space");

__device__ __align__(128) uint32_t g_h[16 * 56 * 2048];
__device__ __align__(128) __nv_bfloat16 g_kvT[DM * SEQ];
__device__ __align__(128) __nv_bfloat16 g_yT[DM * SEQ];
__device__ unsigned g_launch[NCTA];
__device__ unsigned g_cnt_kv[32];
__device__ unsigned g_cnt_y[4 * 32];
__device__ unsigned g_flag_h[16 * 2 * 8];

#define PROF(idx)
#define PROF2(a, idx)
#define PROFW(idx, w)

struct Params {
    CUtensorMap tm_x, tm_gA, tm_gB, tm_uA, tm_uB, tm_w2, tm_yT, tm_out, tm_xe;
    const __nv_bfloat16 *q, *k, *v, *shift_k, *ssm_k, *ssm_D, *wg, *wu, *wd;
};

__device__ __forceinline__ void wgmma_rs_n32(float (&d)[16], uint32_t a0, uint32_t a1, uint32_t a2, uint32_t a3, uint64_t db, int sc) {
  asm volatile("{\n.reg .pred p;\nsetp.ne.b32 p, %21, 0;\n"
    "wgmma.mma_async.sync.aligned.m64n32k16.f32.bf16.bf16 {%0,%1,%2,%3,%4,%5,%6,%7,%8,%9,%10,%11,%12,%13,%14,%15}, {%16,%17,%18,%19}, %20, p, 1, 1, 0;\n}\n"
    : "+f"(d[0]),"+f"(d[1]),"+f"(d[2]),"+f"(d[3]),"+f"(d[4]),"+f"(d[5]),"+f"(d[6]),"+f"(d[7]),"+f"(d[8]),"+f"(d[9]),"+f"(d[10]),"+f"(d[11]),"+f"(d[12]),"+f"(d[13]),"+f"(d[14]),"+f"(d[15])
    : "r"(a0),"r"(a1),"r"(a2),"r"(a3),"l"(db),"r"(sc));
}
__device__ __forceinline__ void wgmma_rs_n128_tb(float (&d)[64], uint32_t a0, uint32_t a1, uint32_t a2, uint32_t a3, uint64_t db, int sc) {
  asm volatile("{\n.reg .pred p;\nsetp.ne.b32 p, %69, 0;\n"
    "wgmma.mma_async.sync.aligned.m64n128k16.f32.bf16.bf16 {%0,%1,%2,%3,%4,%5,%6,%7,%8,%9,%10,%11,%12,%13,%14,%15,%16,%17,%18,%19,%20,%21,%22,%23,%24,%25,%26,%27,%28,%29,%30,%31,%32,%33,%34,%35,%36,%37,%38,%39,%40,%41,%42,%43,%44,%45,%46,%47,%48,%49,%50,%51,%52,%53,%54,%55,%56,%57,%58,%59,%60,%61,%62,%63}, {%64,%65,%66,%67}, %68, p, 1, 1, 1;\n}\n"
    : "+f"(d[0]),"+f"(d[1]),"+f"(d[2]),"+f"(d[3]),"+f"(d[4]),"+f"(d[5]),"+f"(d[6]),"+f"(d[7]),"+f"(d[8]),"+f"(d[9]),"+f"(d[10]),"+f"(d[11]),"+f"(d[12]),"+f"(d[13]),"+f"(d[14]),"+f"(d[15]),"+f"(d[16]),"+f"(d[17]),"+f"(d[18]),"+f"(d[19]),"+f"(d[20]),"+f"(d[21]),"+f"(d[22]),"+f"(d[23]),"+f"(d[24]),"+f"(d[25]),"+f"(d[26]),"+f"(d[27]),"+f"(d[28]),"+f"(d[29]),"+f"(d[30]),"+f"(d[31]),"+f"(d[32]),"+f"(d[33]),"+f"(d[34]),"+f"(d[35]),"+f"(d[36]),"+f"(d[37]),"+f"(d[38]),"+f"(d[39]),"+f"(d[40]),"+f"(d[41]),"+f"(d[42]),"+f"(d[43]),"+f"(d[44]),"+f"(d[45]),"+f"(d[46]),"+f"(d[47]),"+f"(d[48]),"+f"(d[49]),"+f"(d[50]),"+f"(d[51]),"+f"(d[52]),"+f"(d[53]),"+f"(d[54]),"+f"(d[55]),"+f"(d[56]),"+f"(d[57]),"+f"(d[58]),"+f"(d[59]),"+f"(d[60]),"+f"(d[61]),"+f"(d[62]),"+f"(d[63])
    : "r"(a0),"r"(a1),"r"(a2),"r"(a3),"l"(db),"r"(sc));
}
__device__ __forceinline__ void wgmma_ss_n256_tb(float (&d)[128], uint64_t da, uint64_t db, int sc) {
  asm volatile("{\n.reg .pred p;\nsetp.ne.b32 p, %130, 0;\n"
    "wgmma.mma_async.sync.aligned.m64n256k16.f32.bf16.bf16 {%0,%1,%2,%3,%4,%5,%6,%7,%8,%9,%10,%11,%12,%13,%14,%15,%16,%17,%18,%19,%20,%21,%22,%23,%24,%25,%26,%27,%28,%29,%30,%31,%32,%33,%34,%35,%36,%37,%38,%39,%40,%41,%42,%43,%44,%45,%46,%47,%48,%49,%50,%51,%52,%53,%54,%55,%56,%57,%58,%59,%60,%61,%62,%63,%64,%65,%66,%67,%68,%69,%70,%71,%72,%73,%74,%75,%76,%77,%78,%79,%80,%81,%82,%83,%84,%85,%86,%87,%88,%89,%90,%91,%92,%93,%94,%95,%96,%97,%98,%99,%100,%101,%102,%103,%104,%105,%106,%107,%108,%109,%110,%111,%112,%113,%114,%115,%116,%117,%118,%119,%120,%121,%122,%123,%124,%125,%126,%127}, %128, %129, p, 1, 1, 0, 1;\n}\n"
    : "+f"(d[0]),"+f"(d[1]),"+f"(d[2]),"+f"(d[3]),"+f"(d[4]),"+f"(d[5]),"+f"(d[6]),"+f"(d[7]),"+f"(d[8]),"+f"(d[9]),"+f"(d[10]),"+f"(d[11]),"+f"(d[12]),"+f"(d[13]),"+f"(d[14]),"+f"(d[15]),"+f"(d[16]),"+f"(d[17]),"+f"(d[18]),"+f"(d[19]),"+f"(d[20]),"+f"(d[21]),"+f"(d[22]),"+f"(d[23]),"+f"(d[24]),"+f"(d[25]),"+f"(d[26]),"+f"(d[27]),"+f"(d[28]),"+f"(d[29]),"+f"(d[30]),"+f"(d[31]),"+f"(d[32]),"+f"(d[33]),"+f"(d[34]),"+f"(d[35]),"+f"(d[36]),"+f"(d[37]),"+f"(d[38]),"+f"(d[39]),"+f"(d[40]),"+f"(d[41]),"+f"(d[42]),"+f"(d[43]),"+f"(d[44]),"+f"(d[45]),"+f"(d[46]),"+f"(d[47]),"+f"(d[48]),"+f"(d[49]),"+f"(d[50]),"+f"(d[51]),"+f"(d[52]),"+f"(d[53]),"+f"(d[54]),"+f"(d[55]),"+f"(d[56]),"+f"(d[57]),"+f"(d[58]),"+f"(d[59]),"+f"(d[60]),"+f"(d[61]),"+f"(d[62]),"+f"(d[63]),"+f"(d[64]),"+f"(d[65]),"+f"(d[66]),"+f"(d[67]),"+f"(d[68]),"+f"(d[69]),"+f"(d[70]),"+f"(d[71]),"+f"(d[72]),"+f"(d[73]),"+f"(d[74]),"+f"(d[75]),"+f"(d[76]),"+f"(d[77]),"+f"(d[78]),"+f"(d[79]),"+f"(d[80]),"+f"(d[81]),"+f"(d[82]),"+f"(d[83]),"+f"(d[84]),"+f"(d[85]),"+f"(d[86]),"+f"(d[87]),"+f"(d[88]),"+f"(d[89]),"+f"(d[90]),"+f"(d[91]),"+f"(d[92]),"+f"(d[93]),"+f"(d[94]),"+f"(d[95]),"+f"(d[96]),"+f"(d[97]),"+f"(d[98]),"+f"(d[99]),"+f"(d[100]),"+f"(d[101]),"+f"(d[102]),"+f"(d[103]),"+f"(d[104]),"+f"(d[105]),"+f"(d[106]),"+f"(d[107]),"+f"(d[108]),"+f"(d[109]),"+f"(d[110]),"+f"(d[111]),"+f"(d[112]),"+f"(d[113]),"+f"(d[114]),"+f"(d[115]),"+f"(d[116]),"+f"(d[117]),"+f"(d[118]),"+f"(d[119]),"+f"(d[120]),"+f"(d[121]),"+f"(d[122]),"+f"(d[123]),"+f"(d[124]),"+f"(d[125]),"+f"(d[126]),"+f"(d[127])
    : "l"(da),"l"(db),"r"(sc));
}
__device__ __forceinline__ void wgmma_ss_n192_tb(float (&d)[96], uint64_t da, uint64_t db, int sc) {
  asm volatile("{\n.reg .pred p;\nsetp.ne.b32 p, %98, 0;\n"
    "wgmma.mma_async.sync.aligned.m64n192k16.f32.bf16.bf16 {%0,%1,%2,%3,%4,%5,%6,%7,%8,%9,%10,%11,%12,%13,%14,%15,%16,%17,%18,%19,%20,%21,%22,%23,%24,%25,%26,%27,%28,%29,%30,%31,%32,%33,%34,%35,%36,%37,%38,%39,%40,%41,%42,%43,%44,%45,%46,%47,%48,%49,%50,%51,%52,%53,%54,%55,%56,%57,%58,%59,%60,%61,%62,%63,%64,%65,%66,%67,%68,%69,%70,%71,%72,%73,%74,%75,%76,%77,%78,%79,%80,%81,%82,%83,%84,%85,%86,%87,%88,%89,%90,%91,%92,%93,%94,%95}, %96, %97, p, 1, 1, 0, 1;\n}\n"
    : "+f"(d[0]),"+f"(d[1]),"+f"(d[2]),"+f"(d[3]),"+f"(d[4]),"+f"(d[5]),"+f"(d[6]),"+f"(d[7]),"+f"(d[8]),"+f"(d[9]),"+f"(d[10]),"+f"(d[11]),"+f"(d[12]),"+f"(d[13]),"+f"(d[14]),"+f"(d[15]),"+f"(d[16]),"+f"(d[17]),"+f"(d[18]),"+f"(d[19]),"+f"(d[20]),"+f"(d[21]),"+f"(d[22]),"+f"(d[23]),"+f"(d[24]),"+f"(d[25]),"+f"(d[26]),"+f"(d[27]),"+f"(d[28]),"+f"(d[29]),"+f"(d[30]),"+f"(d[31]),"+f"(d[32]),"+f"(d[33]),"+f"(d[34]),"+f"(d[35]),"+f"(d[36]),"+f"(d[37]),"+f"(d[38]),"+f"(d[39]),"+f"(d[40]),"+f"(d[41]),"+f"(d[42]),"+f"(d[43]),"+f"(d[44]),"+f"(d[45]),"+f"(d[46]),"+f"(d[47]),"+f"(d[48]),"+f"(d[49]),"+f"(d[50]),"+f"(d[51]),"+f"(d[52]),"+f"(d[53]),"+f"(d[54]),"+f"(d[55]),"+f"(d[56]),"+f"(d[57]),"+f"(d[58]),"+f"(d[59]),"+f"(d[60]),"+f"(d[61]),"+f"(d[62]),"+f"(d[63]),"+f"(d[64]),"+f"(d[65]),"+f"(d[66]),"+f"(d[67]),"+f"(d[68]),"+f"(d[69]),"+f"(d[70]),"+f"(d[71]),"+f"(d[72]),"+f"(d[73]),"+f"(d[74]),"+f"(d[75]),"+f"(d[76]),"+f"(d[77]),"+f"(d[78]),"+f"(d[79]),"+f"(d[80]),"+f"(d[81]),"+f"(d[82]),"+f"(d[83]),"+f"(d[84]),"+f"(d[85]),"+f"(d[86]),"+f"(d[87]),"+f"(d[88]),"+f"(d[89]),"+f"(d[90]),"+f"(d[91]),"+f"(d[92]),"+f"(d[93]),"+f"(d[94]),"+f"(d[95])
    : "l"(da),"l"(db),"r"(sc));
}

__device__ __forceinline__ uint32_t smem_u32(const void* p) { return (uint32_t)__cvta_generic_to_shared(p); }
__device__ __forceinline__ void mbar_init(uint32_t bar, uint32_t cnt) { asm volatile("mbarrier.init.shared::cta.b64 [%0], %1;" :: "r"(bar), "r"(cnt)); }
__device__ __forceinline__ void mbar_expect_tx(uint32_t bar, uint32_t bytes) { asm volatile("mbarrier.arrive.expect_tx.shared::cta.b64 _, [%0], %1;" :: "r"(bar), "r"(bytes) : "memory"); }
__device__ __forceinline__ void mbar_arrive(uint32_t bar) { asm volatile("mbarrier.arrive.shared::cta.b64 _, [%0];" :: "r"(bar) : "memory"); }
__device__ __forceinline__ void mbar_arrive_cluster(uint32_t cbar, uint32_t cnt) { asm volatile("mbarrier.arrive.shared::cluster.b64 _, [%0], %1;" :: "r"(cbar), "r"(cnt) : "memory"); }
__device__ __forceinline__ uint32_t mapa(uint32_t a, uint32_t rank) { uint32_t r; asm volatile("mapa.shared::cluster.u32 %0, %1, %2;" : "=r"(r) : "r"(a), "r"(rank)); return r; }
__device__ __forceinline__ void mbar_wait(uint32_t bar, uint32_t parity) {
    uint32_t ok; uint32_t n = 0;
    do {
        asm volatile("{\n.reg .pred p;\nmbarrier.try_wait.parity.shared::cta.b64 p, [%1], %2;\nselp.u32 %0, 1, 0, p;\n}" : "=r"(ok) : "r"(bar), "r"(parity) : "memory");
    } while (!ok && ++n < (1u << 17));
}
__device__ __forceinline__ void pace_wait(uint32_t a, uint32_t target) {
    uint32_t v, n = 0;
    do {
        asm volatile("ld.volatile.shared.u32 %0, [%1];" : "=r"(v) : "r"(a) : "memory");
        if (v < target) __nanosleep(150);
    } while (v < target && ++n < (1u << 14));
}
__device__ __forceinline__ void flag_wait(const unsigned* p, unsigned target) {
    unsigned v; uint32_t n = 0;
    while (true) {
        asm volatile("ld.acquire.gpu.global.u32 %0, [%1];" : "=r"(v) : "l"(p) : "memory");
        if ((int)(v - target) >= 0 || ++n >= (1u << 17)) break;
        __nanosleep(40);
    }
}
__device__ __forceinline__ void flag_add(unsigned* p) {
    asm volatile("fence.acq_rel.gpu;\nred.relaxed.gpu.global.add.u32 [%0], 1;" :: "l"(p) : "memory");
}
__device__ __forceinline__ uint64_t make_desc(uint32_t addr, uint32_t lbo, uint32_t sbo, uint32_t swz) {
    return (uint64_t)((addr & 0x3FFFF) >> 4) | ((uint64_t)((lbo & 0x3FFFF) >> 4) << 16) | ((uint64_t)((sbo & 0x3FFFF) >> 4) << 32) | ((uint64_t)swz << 62);
}
__device__ __forceinline__ uint64_t desc_add(uint64_t d, uint32_t off16) {
    return (d & 0xFFFFFFFF00000000ull) | (uint64_t)((uint32_t)d + off16);
}
__device__ __forceinline__ void tma2d(uint32_t dst, const CUtensorMap* tm, int c0, int c1, uint32_t bar) {
    asm volatile("cp.async.bulk.tensor.2d.shared::cluster.global.mbarrier::complete_tx::bytes [%0], [%1, {%3, %4}], [%2];"
        :: "r"(dst), "l"((uint64_t)tm), "r"(bar), "r"(c0), "r"(c1) : "memory");
}
__device__ __forceinline__ void tma3d(uint32_t dst, const CUtensorMap* tm, int c0, int c1, int c2, uint32_t bar) {
    asm volatile("cp.async.bulk.tensor.3d.shared::cluster.global.mbarrier::complete_tx::bytes [%0], [%1, {%3, %4, %5}], [%2];"
        :: "r"(dst), "l"((uint64_t)tm), "r"(bar), "r"(c0), "r"(c1), "r"(c2) : "memory");
}
__device__ __forceinline__ void tma3d_mc(uint32_t dst, const CUtensorMap* tm, int c0, int c1, int c2, uint32_t bar) {
    asm volatile("cp.async.bulk.tensor.3d.shared::cluster.global.mbarrier::complete_tx::bytes.multicast::cluster [%0], [%1, {%3, %4, %5}], [%2], %6;"
        :: "r"(dst), "l"((uint64_t)tm), "r"(bar), "r"(c0), "r"(c1), "r"(c2), "h"((uint16_t)3) : "memory");
}
__device__ __forceinline__ void bulk_g2s(uint32_t dst, const void* src, uint32_t bytes, uint32_t bar) {
    asm volatile("cp.async.bulk.shared::cluster.global.mbarrier::complete_tx::bytes [%0], [%1], %2, [%3];"
        :: "r"(dst), "l"(src), "r"(bytes), "r"(bar) : "memory");
}
__device__ __forceinline__ void bulk_s2g(void* dst, uint32_t src, uint32_t bytes) {
    asm volatile("cp.async.bulk.global.shared::cta.bulk_group [%0], [%1], %2;" :: "l"(dst), "r"(src), "r"(bytes) : "memory");
}
__device__ __forceinline__ void tma2d_store(const CUtensorMap* tm, int c0, int c1, uint32_t src) {
    asm volatile("cp.async.bulk.tensor.2d.global.shared::cta.bulk_group [%0, {%2, %3}], [%1];"
        :: "l"((uint64_t)tm), "r"(src), "r"(c0), "r"(c1) : "memory");
}
__device__ __forceinline__ void l2_prefetch(const void* p, uint32_t bytes) {
    asm volatile("cp.async.bulk.prefetch.L2.global [%0], %1;" :: "l"(p), "r"(bytes) : "memory");
}
__device__ __forceinline__ void tmap_prefetch(const CUtensorMap* tm) { asm volatile("prefetch.tensormap [%0];" :: "l"((uint64_t)tm) : "memory"); }
__device__ __forceinline__ uint32_t lds32(uint32_t a) { uint32_t v; asm volatile("ld.shared.u32 %0, [%1];" : "=r"(v) : "r"(a)); return v; }
__device__ __forceinline__ uint2 lds64(uint32_t a) { uint2 v; asm volatile("ld.shared.v2.u32 {%0,%1}, [%2];" : "=r"(v.x), "=r"(v.y) : "r"(a)); return v; }
__device__ __forceinline__ uint4 lds128(uint32_t a) { uint4 v; asm volatile("ld.shared.v4.u32 {%0,%1,%2,%3}, [%4];" : "=r"(v.x), "=r"(v.y), "=r"(v.z), "=r"(v.w) : "r"(a)); return v; }
__device__ __forceinline__ float2 lds64f(uint32_t a) { float2 v; asm volatile("ld.shared.v2.f32 {%0,%1}, [%2];" : "=f"(v.x), "=f"(v.y) : "r"(a)); return v; }
__device__ __forceinline__ void sts32(uint32_t a, uint32_t v) { asm volatile("st.shared.u32 [%0], %1;" :: "r"(a), "r"(v) : "memory"); }
__device__ __forceinline__ void sts128(uint32_t a, uint4 v) { asm volatile("st.shared.v4.u32 [%0], {%1,%2,%3,%4};" :: "r"(a), "r"(v.x), "r"(v.y), "r"(v.z), "r"(v.w) : "memory"); }
__device__ __forceinline__ uint4 ldg_cg128(const void* p) { uint4 v; asm volatile("ld.global.cg.v4.u32 {%0,%1,%2,%3}, [%4];" : "=r"(v.x), "=r"(v.y), "=r"(v.z), "=r"(v.w) : "l"(p)); return v; }
__device__ __forceinline__ uint4 ldg_nc128(const void* p) { uint4 v; asm volatile("ld.global.nc.L1::no_allocate.v4.u32 {%0,%1,%2,%3}, [%4];" : "=r"(v.x), "=r"(v.y), "=r"(v.z), "=r"(v.w) : "l"(p)); return v; }
__device__ __forceinline__ uint32_t ldg_nc32(const void* p) { uint32_t v; asm volatile("ld.global.nc.u32 %0, [%1];" : "=r"(v) : "l"(p)); return v; }
__device__ __forceinline__ uint2 ldg_nc64(const void* p) { uint2 v; asm volatile("ld.global.nc.L1::no_allocate.v2.u32 {%0,%1}, [%2];" : "=r"(v.x), "=r"(v.y) : "l"(p)); return v; }
#define WG_FENCE() asm volatile("wgmma.fence.sync.aligned;\n" ::: "memory")
#define WG_COMMIT() asm volatile("wgmma.commit_group.sync.aligned;\n" ::: "memory")
template<int N> __device__ __forceinline__ void wg_wait() { asm volatile("wgmma.wait_group.sync.aligned %0;\n" :: "n"(N) : "memory"); }
__device__ __forceinline__ bool elect_one() {
    uint32_t pr;
    asm volatile("{\n.reg .pred p;\nelect.sync _|p, 0xffffffff;\nselp.u32 %0, 1, 0, p;\n}" : "=r"(pr));
    return pr != 0;
}
__device__ __forceinline__ void named_bar(int id, int n) { asm volatile("bar.sync %0, %1;" :: "r"(id), "r"(n) : "memory"); }

__device__ __forceinline__ float bf_lo(uint32_t u) { return __uint_as_float(u << 16); }
__device__ __forceinline__ float bf_hi(uint32_t u) { return __uint_as_float(u & 0xFFFF0000u); }
__device__ __forceinline__ uint32_t pack_bf(float lo, float hi) { uint32_t r; asm("cvt.rn.bf16x2.f32 %0, %1, %2;" : "=r"(r) : "f"(hi), "f"(lo)); return r; }
__device__ __forceinline__ float bf_round(float x) { return __bfloat162float(__float2bfloat16_rn(x)); }
__device__ __forceinline__ uint32_t bmul2(uint32_t a, uint32_t b) { uint32_t r; asm("mul.rn.bf16x2 %0, %1, %2;" : "=r"(r) : "r"(a), "r"(b)); return r; }
__device__ __forceinline__ uint32_t badd2(uint32_t a, uint32_t b) { uint32_t r; asm("add.rn.bf16x2 %0, %1, %2;" : "=r"(r) : "r"(a), "r"(b)); return r; }
__device__ __forceinline__ uint32_t bsub2(uint32_t a, uint32_t b) { uint32_t r; asm("sub.rn.bf16x2 %0, %1, %2;" : "=r"(r) : "r"(a), "r"(b)); return r; }
__device__ __forceinline__ void mma16816(float (&d)[4], uint32_t a0, uint32_t a1, uint32_t a2, uint32_t a3, uint2 b) {
    asm volatile("mma.sync.aligned.m16n8k16.row.col.f32.bf16.bf16.f32 {%0,%1,%2,%3}, {%4,%5,%6,%7}, {%8,%9}, {%0,%1,%2,%3};\n"
        : "+f"(d[0]), "+f"(d[1]), "+f"(d[2]), "+f"(d[3]) : "r"(a0), "r"(a1), "r"(a2), "r"(a3), "r"(b.x), "r"(b.y));
}

template<int HS> __device__ __forceinline__ void xreduce(float (&v)[8], int lane) {
    const int up = lane & HS;
    #pragma unroll
    for (int e = 0; e < HS; e++) {
        float keep, send;
        asm("{\n.reg .pred p;\nsetp.ne.b32 p, %4, 0;\nselp.f32 %0, %3, %2, p;\nselp.f32 %1, %2, %3, p;\n}"
            : "=f"(keep), "=f"(send) : "f"(v[e]), "f"(v[e + HS]), "r"(up));
        v[e] = keep + __shfl_xor_sync(0xffffffffu, send, HS);
    }
}

__device__ __forceinline__ int blk_f0(int s) {
    if (s < 32) return 32 * (14 * (s >> 3) + 8 * ((s >> 2) & 1) + (s & 3));
    const int s2 = s - 32, c6 = (s2 * 11) >> 6, t = s2 - 6 * c6;
    return 32 * (14 * c6 + (t < 4 ? 4 + t : 8 + t));
}
__device__ __forceinline__ int next_st2(int s) { return (0x14023 >> (4 * s)) & 7; }
__device__ __forceinline__ uint32_t stage_off_rt(int s) { return s < 3 ? SM_RING + s * STAGE_BYTES : (uint32_t)(s - 3) * 65536; }

__device__ __forceinline__ void store_h(uint32_t* dst, const uint32_t (&hp)[32], int q) {
    #pragma unroll
    for (int kk = 0; kk < 2; kk++) {
        uint32_t* d2 = dst + q * 2048 + kk * 512;
        d2[0] = hp[8 * q + 4 * kk]; d2[64] = hp[8 * q + 4 * kk + 1]; d2[32] = hp[8 * q + 4 * kk + 2]; d2[96] = hp[8 * q + 4 * kk + 3];
    }
}
template<int NB, bool passA>
__device__ __forceinline__ void gemm1_pass(uint32_t sb, int wgi, int warp4, int lane, int& st, uint32_t& fph, uint32_t e_cl,
                                           uint32_t (&hp)[32], uint32_t* prev_dst, bool convCTA) {
    float acc[NB * 32];
    const uint64_t descA0 = make_desc(sb + SM_X + wgi * 65536, 16, 1024, 1);
    const uint64_t descB0 = make_desc(sb + SM_RING, 4096, 512, 2);
    int prev = 0;
    auto group = [&](int sl) {
        if (warp4 == 0 && wgi == 0) PROF2(2, sl + (passA ? 0 : 8));
        mbar_wait(sb + SM_BARS + (B_FULL + st) * 8, (fph >> st) & 1);
        fph ^= 1u << st;
        if (sl == 0 && warp4 == 0) PROF(2 + wgi * 8 + (passA ? 0 : 3));
        if (warp4 == 0 && wgi == 0) PROF2(1, sl + (passA ? 0 : 8));
        const uint64_t da = desc_add(descA0, sl * 512), db = desc_add(descB0, st * 2048);
        WG_FENCE();
        #pragma unroll
        for (int kk = 0; kk < 4; kk++) {
            int sc = (sl | kk) ? 1 : 0;
            if constexpr (NB == 4) wgmma_ss_n256_tb(acc, da + kk * 2, db + kk * 64, sc); else wgmma_ss_n128_tb(acc, da + kk * 2, db + kk * 64, sc);
        }
        WG_COMMIT();
        wg_wait<1>();
        if (warp4 == 0 && wgi == 0) PROF2(3, sl + (passA ? 0 : 8));
        if (lane < 2 && sl && (passA || !convCTA || sl < 6)) mbar_arrive_cluster(e_cl + prev * 8, 1);
        if (!passA && sl == 4) {
            if (convCTA) { if (lane == 0) mbar_arrive(sb + SM_BARS + B_XFREE * 8); }
            else if (lane < 4) mbar_arrive_cluster(e_cl + (3 + (lane >> 1)) * 8, 1);
        }
        prev = st;
        st = (st == 2) ? 0 : st + 1;
    };
    if constexpr (passA) {
        #pragma unroll 1
        for (int sl = 0; sl < 8; sl++) group(sl);
    } else {
        #pragma unroll
        for (int sl = 0; sl < 4; sl++) { group(sl); store_h(prev_dst, hp, sl); }
        __syncwarp();
        if (lane == 0) mbar_arrive(sb + SM_BARS + (B_HD + wgi * 2) * 8);
        #pragma unroll 1
        for (int sl = 4; sl < 8; sl++) group(sl);
    }
    wg_wait<0>();
    if (lane < 2 && (passA || !convCTA)) mbar_arrive_cluster(e_cl + prev * 8, 1);
    if (!passA && lane == 0) mbar_arrive(sb + SM_BARS + B_G1DONE * 8);
    if (warp4 == 0) PROF(3 + wgi * 8 + (passA ? 0 : 3));
    const int g = lane >> 2;
    const int r0 = wgi * 64 + warp4 * 16 + g;
    const float s0 = __uint_as_float(lds32(sb + SM_STATS + r0 * 8 + 4)), s1 = __uint_as_float(lds32(sb + SM_STATS + (r0 + 8) * 8 + 4));
    #pragma unroll
    for (int t = 0; t < NB * 4; t++) {
        const float* ag = &acc[4 * t];
        const float* au = &acc[NB * 16 + 4 * t];
        hp[2 * t] = bmul2(pack_bf(ag[0] * s0, ag[1] * s0), pack_bf(au[0] * s0, au[1] * s0));
        hp[2 * t + 1] = bmul2(pack_bf(ag[2] * s1, ag[3] * s1), pack_bf(au[2] * s1, au[3] * s1));
    }
    if (warp4 == 0) PROF(4 + wgi * 8 + (passA ? 0 : 3));
}

__global__ void __cluster_dims__(2, 1, 1) __launch_bounds__(NTHREADS, 1)
fused_kernel(const __grid_constant__ Params p) {
    extern __shared__ __align__(1024) uint8_t smem_raw[];
    const uint32_t sb = smem_u32(smem_raw);
    const int tid = threadIdx.x, warp = tid >> 5, lane = tid & 31;
    const int b = blockIdx.x;
    const int rank = b & 1;
    const int j = (b >> 1) & 7;
    const int i = ((b >> 4) << 1) | rank;
    const int cb = j >> 1;
    const bool convCTA = j & 1;
    const int cidx = 4 * i + cb;

    if (tid == 256) {
        mbar_init(sb + SM_BARS + B_XFULL * 8, 1);
        mbar_init(sb + SM_BARS + (B_XFULL + 1) * 8, 1);
        asm volatile("fence.proxy.async.shared::cta;" ::: "memory");
        mbar_expect_tx(sb + SM_BARS + B_XFULL * 8, 65536);
        tma3d(sb + SM_X, &p.tm_x, 0, 128 * i, 0, sb + SM_BARS + B_XFULL * 8);
        mbar_expect_tx(sb + SM_BARS + (B_XFULL + 1) * 8, 65536);
        tma3d(sb + SM_X + 65536, &p.tm_x, 0, 128 * i + 64, 0, sb + SM_BARS + (B_XFULL + 1) * 8);
    }
    if (tid == 288) {
        for (int s = 0; s < 5; s++) { mbar_init(sb + SM_BARS + (B_FULL + s) * 8, 1); mbar_init(sb + SM_BARS + (B_EMPTY + s) * 8, 16); }
        mbar_init(sb + SM_BARS + B_CONV * 8, 1);
        mbar_init(sb + SM_BARS + B_YT * 8, 1);
        mbar_init(sb + SM_BARS + B_XR * 8, 1);
        mbar_init(sb + SM_BARS + B_G1DONE * 8, 8);
        mbar_init(sb + SM_BARS + B_XFREE * 8, 8);
        mbar_init(sb + SM_BARS + B_YST * 8, 8);
        mbar_init(sb + SM_BARS + B_KVLD * 8, 2);
        mbar_init(sb + SM_BARS + B_LN * 8, 8);
        for (int s = 0; s < 4; s++) mbar_init(sb + SM_BARS + (B_HD + s) * 8, 4);
        for (int s = 0; s < 2; s++) mbar_init(sb + SM_BARS + (B_HRDY + s) * 8, 1);
        asm volatile("fence.mbarrier_init.release.cluster;" ::: "memory");
        asm volatile("fence.proxy.async.shared::cta;" ::: "memory");
    }
    __syncwarp();
    asm volatile("barrier.cluster.arrive.relaxed.aligned;\n" ::: "memory");
    asm volatile("barrier.cluster.wait.aligned;\n" ::: "memory");
    PROFW(1, 0);

    if (warp < 8) {
        asm volatile("setmaxnreg.inc.sync.aligned.u32 200;");
        const int wgi = warp >> 2, warp4 = warp & 3;
        const int g = lane >> 2, c = lane & 3;
        const uint32_t e_cl = mapa(sb + SM_BARS + B_EMPTY * 8, lane & 1);
        {
            const int lr16 = (lane & 7) + ((lane >> 3) & 1) * 8;
            const uint32_t xa = sb + SM_X + wgi * 65536 + (warp4 * 16 + lr16) * 128;
            uint32_t xf[32][4];
            float aS[4][4], aQ0[4][4], aQ1[4][4];
            #pragma unroll
            for (int e = 0; e < 4; e++) {
                #pragma unroll
                for (int f = 0; f < 4; f++) { aS[e][f] = 0.f; aQ0[e][f] = 0.f; aQ1[e][f] = 0.f; }
            }
            mbar_wait(sb + SM_BARS + (B_XFULL + wgi) * 8, 0);
            PROFW(16, 0); PROFW(18, 4);
            #pragma unroll
            for (int ks = 0; ks < 32; ks++) {
                const uint32_t a = xa + (ks >> 2) * 8192 + (((2 * (ks & 3) + (lane >> 4)) ^ (lane & 7)) << 4);
                asm volatile("ldmatrix.sync.aligned.m8n8.x4.shared.b16 {%0,%1,%2,%3}, [%4];"
                    : "=r"(xf[ks][0]), "=r"(xf[ks][1]), "=r"(xf[ks][2]), "=r"(xf[ks][3]) : "r"(a) : "memory");
            }
            PROFW(40, 4);
            #pragma unroll
            for (int ks = 0; ks < 32; ks++)
                mma16816(aS[ks & 3], xf[ks][0], xf[ks][1], xf[ks][2], xf[ks][3], make_uint2(0x3F803F80u, 0x3F803F80u));
            const float mean0 = ((aS[0][0] + aS[1][0]) + (aS[2][0] + aS[3][0])) * (1.0f / DM);
            const float mean1 = ((aS[0][2] + aS[1][2]) + (aS[2][2] + aS[3][2])) * (1.0f / DM);
            const uint32_t m0 = pack_bf(mean0, mean0), m1 = pack_bf(mean1, mean1);
            PROFW(41, 4);
            #pragma unroll
            for (int ks = 0; ks < 32; ks++) {
                const uint32_t a = xa + (ks >> 2) * 8192 + (((2 * (ks & 3) + (lane >> 4)) ^ (lane & 7)) << 4);
                asm volatile("stmatrix.sync.aligned.m8n8.x4.shared.b16 [%0], {%1,%2,%3,%4};"
                    :: "r"(a), "r"(bsub2(xf[ks][0], m0)), "r"(bsub2(xf[ks][1], m1)), "r"(bsub2(xf[ks][2], m0)), "r"(bsub2(xf[ks][3], m1)) : "memory");
            }
            PROFW(42, 4);
            asm volatile("fence.proxy.async.shared::cta;" ::: "memory");
            __syncwarp();
            if (lane == 0) mbar_arrive(sb + SM_BARS + B_LN * 8);
            #pragma unroll
            for (int ks = 0; ks < 32; ks++) {
                mma16816(aQ0[ks & 3], xf[ks][0], xf[ks][1], xf[ks][2], xf[ks][3], make_uint2(xf[ks][0], xf[ks][2]));
                mma16816(aQ1[ks & 3], xf[ks][0], xf[ks][1], xf[ks][2], xf[ks][3], make_uint2(xf[ks][1], xf[ks][3]));
            }
            if (c == (g >> 1)) {
                const float q0 = (g & 1) ? (aQ0[0][1] + aQ0[1][1]) + (aQ0[2][1] + aQ0[3][1]) : (aQ0[0][0] + aQ0[1][0]) + (aQ0[2][0] + aQ0[3][0]);
                const float q1 = (g & 1) ? (aQ1[0][3] + aQ1[1][3]) + (aQ1[2][3] + aQ1[3][3]) : (aQ1[0][2] + aQ1[1][2]) + (aQ1[2][2] + aQ1[3][2]);
                const float sd0 = bf_round(sqrtf(bf_round(bf_round(fmaxf(q0 * (1.0f / DM) - mean0 * mean0, 0.f)) + 1e-5f)));
                const float sd1 = bf_round(sqrtf(bf_round(bf_round(fmaxf(q1 * (1.0f / DM) - mean1 * mean1, 0.f)) + 1e-5f)));
                const uint32_t sa = sb + SM_STATS + (warp * 16 + g) * 8;
                sts32(sa, m0); sts32(sa + 4, __float_as_uint(1.0f / sd0));
                sts32(sa + 64, m1); sts32(sa + 68, __float_as_uint(1.0f / sd1));
            }
            mbar_wait(sb + SM_BARS + B_LN * 8, 0);
            PROFW(19, 4);
            PROFW(17, 0);
        }
        int st = 0; uint32_t fph = 0;
        uint32_t hp[32];
        uint32_t* const hdst = g_h + (size_t)(i * 56) * 2048 + wgi * 1024 + warp4 * 128 + lane;
        gemm1_pass<4, true>(sb, wgi, warp4, lane, st, fph, e_cl, hp, hdst, convCTA);

        if (convCTA) {
            gemm1_pass<2, false>(sb, wgi, warp4, lane, st, fph, e_cl, hp, hdst + 4 * j * 2048, true);
            store_h(hdst + (36 + 6 * cb) * 2048, hp, 0); store_h(hdst + (36 + 6 * cb) * 2048, hp, 1);
            __syncwarp();
            if (lane == 0) mbar_arrive(sb + SM_BARS + (B_HD + wgi * 2 + 1) * 8);
            const int gch = 8 * cidx + warp;
            const uint32_t xb = sb + SM_CVX + warp * 4096;
            const uint32_t hb = sb + SM_CVH + warp * 4096;
            const uint32_t dw = ((const unsigned short*)p.ssm_D)[gch];
            const uint32_t d2 = dw | (dw << 16);
            mbar_wait(sb + SM_BARS + B_CONV * 8, 0);
            PROFW(32, 4);
            float acc[16][4];
            #pragma unroll
            for (int jj = 0; jj < 16; jj++) { acc[jj][0] = 0.f; acc[jj][1] = 0.f; acc[jj][2] = 0.f; acc[jj][3] = 0.f; }
            uint2 bh[8], bl0[8], bl1[8];
            uint32_t xl = xb + g * 32 + c * 8;
            uint32_t hl = hb + (g + 2 * c - 8) * 4;
            #pragma unroll
            for (int d = 0; d < 8; d++) { bl0[d] = lds64(xl + d * 256); bh[d] = lds64(xl + (8 + d) * 256); }
            uint32_t w[6];
            w[0] = 0; w[1] = 0; w[2] = 0;
            if (g + 2 * c >= 8) w[0] = lds32(hl);
            if (g + 2 * c >= 7) w[1] = lds32(hl + 4);
            if (g + 2 * c >= 6) w[2] = lds32(hl + 8);
            w[3] = lds32(hl + 2048); w[4] = lds32(hl + 2052); w[5] = lds32(hl + 2056);
            auto conv_m0 = [&](int m0, uint2 (&bl)[8], uint2 (&bn)[8]) {
                xl -= 32;
                #pragma unroll
                for (int k = 0; k < 8; k++) {
                    const uint32_t a0 = w[1], a1 = __byte_perm(w[0], w[1], 0x5432), a2 = w[2], a3 = __byte_perm(w[1], w[2], 0x5432);
                    const uint32_t c0 = w[4], c1 = __byte_perm(w[3], w[4], 0x5432), c2 = w[5], c3 = __byte_perm(w[4], w[5], 0x5432);
                    const uint32_t nx = (k < 7) ? hl + (k + 1) * 256 : hl + 32;
                    w[0] = lds32(nx); w[1] = lds32(nx + 4); w[2] = lds32(nx + 8);
                    w[3] = lds32(nx + 2048); w[4] = lds32(nx + 2052); w[5] = lds32(nx + 2056);
                    if (k > 0) bn[k] = lds64(xl + k * 256);
                    else { bn[0] = make_uint2(0, 0); if (g > m0) bn[0] = lds64(xl); }
                    #pragma unroll
                    for (int jj = k; jj < 16; jj++) mma16816(acc[jj], a0, a1, a2, a3, (jj - k < 8) ? bl[(jj - k) & 7] : bh[(jj - k) & 7]);
                    bh[7 - k] = lds64(xl + (15 - k) * 256);
                    #pragma unroll
                    for (int jj = k + 8; jj < 16; jj++) mma16816(acc[jj], c0, c1, c2, c3, bl[jj - k - 8]);
                }
                hl += 32;
            };
            #pragma unroll 1
            for (int m0 = 0; m0 < 8; m0 += 2) {
                conv_m0(m0, bl0, bl1);
                conv_m0(m0 + 1, bl1, bl0);
                PROFW(34 + (m0 >> 1), 4);
            }
            PROFW(33, 4);
            const uint32_t kvl = xb + c * 64 + (7 - g) * 4;
            uint32_t* ydst = (uint32_t*)(g_yT + (size_t)gch * SEQ + 32 * c + 2 * g);
            uint32_t kk0[16], kk1[16];
            #pragma unroll
            for (int jj = 0; jj < 16; jj++) { kk0[jj] = lds32(kvl + jj * 256); kk1[jj] = lds32(kvl + jj * 256 + 32); }
            #pragma unroll
            for (int jj = 0; jj < 16; jj++) {
                ydst[jj * 64] = badd2(pack_bf(acc[jj][2], acc[jj][0]), bmul2(__byte_perm(kk0[jj], kk0[jj], 0x1032), d2));
                ydst[jj * 64 + 8] = badd2(pack_bf(acc[jj][3], acc[jj][1]), bmul2(__byte_perm(kk1[jj], kk1[jj], 0x1032), d2));
            }
            __syncwarp();
            PROFW(44, 4);
            if (lane == 0) flag_add(&g_cnt_y[(cidx >> 4) * 32]);
            PROFW(46, 4);
        } else {
            gemm1_pass<4, false>(sb, wgi, warp4, lane, st, fph, e_cl, hp, hdst + 4 * j * 2048, false);
            float acc[64];
            const uint64_t descB0 = make_desc(sb, 4096, 1024, 1);
            const uint64_t descA0 = make_desc(sb + 16384 + wgi * 4096, 128, 256, 0);
            int sg = 3, p0 = 0; uint32_t ph = 6;
            PROFW(20, 0);
            auto g2 = [&](int u) {
                if (warp == 0 && !(u & 1)) PROF2(2, 16 + (u >> 1));
                mbar_wait(sb + SM_BARS + (B_FULL + sg) * 8, (ph >> sg) & 1);
                ph ^= 1u << sg;
                if (warp == 0 && !(u & 1)) PROF2(1, 16 + (u >> 1));
                const uint32_t o0 = stage_off_rt(sg) >> 4;
                const uint64_t da0 = desc_add(descA0, o0), db0 = desc_add(descB0, o0);
                WG_FENCE();
                #pragma unroll
                for (int kk = 0; kk < 4; kk++) wgmma_ss_n128_tb(acc, da0 + ((kk >> 1) * 512 + (kk & 1) * 128), db0 + ((kk >> 1) * 512 + (kk & 1) * 128), (u | kk) ? 1 : 0);
                WG_COMMIT();
                wg_wait<1>();
                if (warp == 0 && !(u & 1)) PROF2(3, 16 + (u >> 1));
                if (lane < 2 && u > 0 && u + 4 < 28) mbar_arrive_cluster(e_cl + p0 * 8, 1);
                p0 = sg;
                sg = next_st2(sg);
            };
            #pragma unroll
            for (int u = 0; u < 4; u++) { g2(u); store_h(hdst + (32 + 6 * cb) * 2048, hp, u); }
            __syncwarp();
            if (lane == 0) mbar_arrive(sb + SM_BARS + (B_HD + wgi * 2 + 1) * 8);
            #pragma unroll 1
            for (int u = 4; u < 28; u++) g2(u);
            wg_wait<0>();
            PROFW(27, 0);
            mbar_wait(sb + SM_BARS + B_XR * 8, 0);
            const int r0 = wgi * 64 + warp4 * 16 + g;
            const float2 st0 = lds64f(sb + SM_STATS + r0 * 8), st1 = lds64f(sb + SM_STATS + (r0 + 8) * 8);
            const uint32_t m0 = __float_as_uint(st0.x), m1 = __float_as_uint(st1.x);
            const uint32_t xrow0 = sb + SM_XE + r0 * 128 + c * 4;
            const int mi = lane >> 3, lr = lane & 7;
            const uint32_t yaddr = sb + SM_YT + wgi * 16384 + ((mi >> 1) * 8 + lr) * 128 + (((2 * warp4 + (mi & 1)) ^ lr) << 4);
            uint32_t y[8][4], xv[16][2], nv[16][2], bv[16][2];
            #pragma unroll
            for (int t = 0; t < 16; t++) {
                const uint32_t off = (t >> 3) * 16384 + (((t & 7) ^ g) << 4);
                xv[t][0] = lds32(xrow0 + off); xv[t][1] = lds32(xrow0 + 1024 + off);
            }
            #pragma unroll
            for (int t = 0; t < 16; t++) {
                const uint32_t d0 = bsub2(xv[t][0], m0), d1 = bsub2(xv[t][1], m1);
                nv[t][0] = pack_bf(bf_lo(d0) * st0.y, bf_hi(d0) * st0.y); nv[t][1] = pack_bf(bf_lo(d1) * st1.y, bf_hi(d1) * st1.y);
                bv[t][0] = pack_bf(acc[4 * t], acc[4 * t + 1]); bv[t][1] = pack_bf(acc[4 * t + 2], acc[4 * t + 3]);
            }
            mbar_wait(sb + SM_BARS + B_YT * 8, 0);
            PROFW(28, 0);
            #pragma unroll
            for (int t2 = 0; t2 < 8; t2++)
                asm volatile("ldmatrix.sync.aligned.m8n8.x4.trans.shared.b16 {%0,%1,%2,%3}, [%4];"
                    : "=r"(y[t2][0]), "=r"(y[t2][1]), "=r"(y[t2][2]), "=r"(y[t2][3]) : "r"(yaddr + t2 * 2048) : "memory");
            #pragma unroll
            for (int t = 0; t < 16; t++) {
                const uint32_t off = (t >> 3) * 16384 + (((t & 7) ^ g) << 4);
                sts32(xrow0 + off, badd2(badd2(xv[t][0], bmul2(nv[t][0], y[t >> 1][2 * (t & 1)])), bv[t][0]));
                sts32(xrow0 + 1024 + off, badd2(badd2(xv[t][1], bmul2(nv[t][1], y[t >> 1][2 * (t & 1) + 1])), bv[t][1]));
            }
            asm volatile("fence.proxy.async.shared::cta;" ::: "memory");
            named_bar(1 + wgi, 128);
            if ((tid & 127) == 0) {
                tma2d_store(&p.tm_out, 128 * cb, 128 * i + 64 * wgi, sb + SM_XE + wgi * 8192);
                tma2d_store(&p.tm_out, 128 * cb + 64, 128 * i + 64 * wgi, sb + SM_XE + 16384 + wgi * 8192);
                asm volatile("cp.async.bulk.commit_group;" ::: "memory");
                asm volatile("cp.async.bulk.wait_group.read 0;" ::: "memory");
                PROFW(29, 0);
            }
        }
    } else {
        asm volatile("setmaxnreg.dec.sync.aligned.u32 104;");
        if (warp == 8) {
            int st = 0; uint32_t eph = 7;
            #pragma unroll 1
            for (int it = 0; it < 16; it++) {
                const int pass = it >> 3, sl = it & 7;
                const bool narrow = pass && convCTA;
                const int nb = narrow ? 2 : 4;
                const CUtensorMap* tm = narrow ? (rank ? &p.tm_uB : &p.tm_gB) : (rank ? &p.tm_uA : &p.tm_gA);
                mbar_wait(sb + SM_BARS + (B_EMPTY + st) * 8, (eph >> st) & 1);
                eph ^= 1u << st;
                if (it == 1) mbar_wait(sb + SM_BARS + B_XFULL * 8, 0);
                PROF2(0, it);
                if (elect_one()) {
                    mbar_expect_tx(sb + SM_BARS + (B_FULL + st) * 8, nb * 8192);
                    tma3d_mc(sb + SM_RING + st * STAGE_BYTES + rank * nb * 4096, tm, 0, sl * 64, 14 * cb + 8 * (j & 1) + 4 * pass, sb + SM_BARS + (B_FULL + st) * 8);
                }
                st = (st == 2) ? 0 : st + 1;
            }
            if (!convCTA) {
                st = 3;
                const int f0_lane = blk_f0(2 * lane + rank);
                #pragma unroll 1
                for (int u = 0; u < 28; u++) {
                    const uint32_t bar = sb + SM_BARS + (B_FULL + st) * 8;
                    const int f0 = __shfl_sync(0xffffffffu, f0_lane, u);
                    mbar_wait(sb + SM_BARS + (B_EMPTY + st) * 8, (eph >> st) & 1);
                    eph ^= 1u << st;
                    if ((u & 1) == 0) PROF2(0, 16 + (u >> 1));
                    if (elect_one()) {
                        mbar_expect_tx(bar, 32768);
                        tma3d_mc(sb + stage_off_rt(st) + rank * 8192, &p.tm_w2, 0, f0, 2 * cb, bar);
                    }
                    st = next_st2(st);
                }
                PROF(48);
            }
        } else if (warp < 11) {
            mbar_wait(sb + SM_BARS + (B_XFULL + 1) * 8, 0);
            {
                const int q = lane & 3;
                const int t0 = 32 * (b >> 1) + 8 * q;
                const int ch0 = 256 * (b & 1) + 16 * (warp - 9) + 2 * (lane >> 2);
                const uint32_t* kp = (const uint32_t*)(p.k + (size_t)t0 * DM + ch0);
                const uint32_t* vp = (const uint32_t*)(p.v + (size_t)t0 * DM + ch0);
                __nv_bfloat16* dst0 = g_kvT + (size_t)ch0 * SEQ + (t0 ^ 8);
                #pragma unroll 1
                for (int rnd = 0; rnd < 2; rnd++) {
                    uint32_t kr[4][11], vr[4][8]; uint4 skw[4];
                    #pragma unroll
                    for (int u = 0; u < 4; u++) {
                        const int co = (rnd * 4 + u) * 16;
                        skw[u] = ldg_nc128(p.shift_k + 4 * (ch0 + 2 * co));
                        #pragma unroll
                        for (int r = 0; r < 11; r++) kr[u][r] = (r >= 3 || t0 > 0) ? ldg_nc32(kp + co + (r - 3) * (DM / 2)) : 0u;
                        #pragma unroll
                        for (int r = 0; r < 8; r++) vr[u][r] = ldg_nc32(vp + co + r * (DM / 2));
                    }
                    #pragma unroll
                    for (int u = 0; u < 4; u++) {
                        const uint32_t s0 = __byte_perm(skw[u].x, skw[u].z, 0x5410), s1 = __byte_perm(skw[u].x, skw[u].z, 0x7632);
                        const uint32_t s2 = __byte_perm(skw[u].y, skw[u].w, 0x5410), s3 = __byte_perm(skw[u].y, skw[u].w, 0x7632);
                        #pragma unroll
                        for (int r = 0; r < 8; r++) {
                            uint32_t a = bmul2(kr[u][r], s3);
                            a = badd2(a, bmul2(kr[u][r + 1], s2));
                            a = badd2(a, bmul2(kr[u][r + 2], s1));
                            a = badd2(a, bmul2(kr[u][r + 3], s0));
                            vr[u][r] = bmul2(a, vr[u][r]);
                        }
                        __nv_bfloat16* dst = dst0 + (size_t)((rnd * 4 + u) * 32) * SEQ;
                        *(uint4*)dst = make_uint4(__byte_perm(vr[u][7], vr[u][6], 0x5410), __byte_perm(vr[u][5], vr[u][4], 0x5410),
                                                  __byte_perm(vr[u][3], vr[u][2], 0x5410), __byte_perm(vr[u][1], vr[u][0], 0x5410));
                        *(uint4*)(dst + SEQ) = make_uint4(__byte_perm(vr[u][7], vr[u][6], 0x7632), __byte_perm(vr[u][5], vr[u][4], 0x7632),
                                                          __byte_perm(vr[u][3], vr[u][2], 0x7632), __byte_perm(vr[u][1], vr[u][0], 0x7632));
                    }
                    PROFW(57 + 2 * rnd, 9);
                }
                if (lane == 0) mbar_arrive(sb + SM_BARS + B_KVLD * 8);
            }
            asm volatile("fence.proxy.async.global;" ::: "memory");
            __syncwarp();
            if (lane == 0) {
                flag_add(&g_cnt_kv[0]);
                PROFW(50, 9);
                const int wgi = warp - 9;
                mbar_wait(sb + SM_BARS + (B_HD + wgi * 2) * 8, 0);
                flag_add(&g_flag_h[(i * 2 + 0) * 8]);
                mbar_wait(sb + SM_BARS + (B_HD + wgi * 2 + 1) * 8, 0);
                flag_add(&g_flag_h[(i * 2 + 1) * 8]);
                if (wgi == 1 && !convCTA) {
                    const unsigned ep = lds32(sb + SM_EPOCH);
                    mbar_wait(sb + SM_BARS + B_G1DONE * 8, 0);
                    mbar_expect_tx(sb + SM_BARS + B_XR * 8, 32768);
                    tma3d(sb + SM_XE, &p.tm_xe, 0, 128 * i, 2 * cb, sb + SM_BARS + B_XR * 8);
                    flag_wait(&g_flag_h[(i * 2 + 1) * 8], ep * 16);
                    mbar_arrive(sb + SM_BARS + (B_HRDY + 1) * 8);
                    __nanosleep(3000);
                    flag_wait(&g_cnt_y[cb * 32], ep * 128);
                    PROF(49);
                    asm volatile("fence.proxy.async.global;" ::: "memory");
                    mbar_expect_tx(sb + SM_BARS + B_YT * 8, 32768);
                    tma2d(sb + SM_YT, &p.tm_yT, 128 * i, 128 * cb, sb + SM_BARS + B_YT * 8);
                    tma2d(sb + SM_YT + 16384, &p.tm_yT, 128 * i + 64, 128 * cb, sb + SM_BARS + B_YT * 8);
                }
            }
        } else {
            if (lane == 0) {
                l2_prefetch(p.wg + (size_t)b * (FF * DM / NCTA), FF * DM / NCTA * 2);
                l2_prefetch(p.wu + (size_t)b * (FF * DM / NCTA), FF * DM / NCTA * 2);
                const unsigned ep = g_launch[b] + 1;
                g_launch[b] = ep;
                sts32(sb + SM_EPOCH, ep);
                tmap_prefetch(rank ? &p.tm_uA : &p.tm_gA);
                tmap_prefetch(rank ? &p.tm_uB : &p.tm_gB);
                tmap_prefetch(&p.tm_w2); tmap_prefetch(&p.tm_yT); tmap_prefetch(&p.tm_out); tmap_prefetch(&p.tm_xe);
                mbar_wait(sb + SM_BARS + B_KVLD * 8, 0);
                l2_prefetch(p.ssm_k + (size_t)(4 * b) * SEQ, 4 * SEQ * 2);
                l2_prefetch(p.wd + (size_t)b * (FF * DM / NCTA), FF * DM / NCTA * 2);
                mbar_wait(sb + SM_BARS + (B_HD + 0) * 8, 0);
                if (convCTA) {
                    flag_wait(&g_cnt_kv[0], ep * 256);
                    asm volatile("fence.proxy.async.global;" ::: "memory");
                    PROF(53);
                    mbar_wait(sb + SM_BARS + B_XFREE * 8, 0);
                    PROF(54);
                    mbar_expect_tx(sb + SM_BARS + B_CONV * 8, 65536);
                    bulk_g2s(sb + SM_CVX, g_kvT + (size_t)(8 * cidx) * SEQ, 32768, sb + SM_BARS + B_CONV * 8);
                    bulk_g2s(sb + SM_CVH, p.ssm_k + (size_t)(8 * cidx) * SEQ, 32768, sb + SM_BARS + B_CONV * 8);
                } else {
                    flag_wait(&g_flag_h[(i * 2 + 0) * 8], ep * 16);
                }
            }
            __syncwarp();
            if (!convCTA) {
                asm volatile("fence.proxy.async.global;" ::: "memory");
                int st = 3; uint32_t eph = 1;
                const uint8_t* hsrc = (const uint8_t*)g_h + (size_t)i * 56 * 8192;
                #pragma unroll 1
                for (int u = 0; u < 28; u++) {
                    mbar_wait(sb + SM_BARS + (B_EMPTY + st) * 8, (eph >> st) & 1);
                    eph ^= 1u << st;
                    if (u == 16) {
                        mbar_wait(sb + SM_BARS + (B_HRDY + 1) * 8, 0);
                        asm volatile("fence.proxy.async.global;" ::: "memory");
                    }
                    if (elect_one()) bulk_g2s(sb + stage_off_rt(st) + 16384, hsrc + u * 16384, 16384, sb + SM_BARS + (B_FULL + st) * 8);
                    st = next_st2(st);
                }
            }
        }
    }
}

typedef CUresult (*EncodeFn)(CUtensorMap*, CUtensorMapDataType, cuuint32_t, void*, const cuuint64_t*, const cuuint64_t*,
                             const cuuint32_t*, const cuuint32_t*, CUtensorMapInterleave, CUtensorMapSwizzle,
                             CUtensorMapL2promotion, CUtensorMapFloatOOBfill);

void encode(EncodeFn fn, CUtensorMap* tm, const void* base, int rank, const cuuint64_t* dims, const cuuint64_t* strides,
            const cuuint32_t* box, CUtensorMapSwizzle swz) {
    cuuint32_t es[5] = {1, 1, 1, 1, 1};
    fn(tm, CU_TENSOR_MAP_DATA_TYPE_BFLOAT16, rank, (void*)base, dims, strides, box, es, CU_TENSOR_MAP_INTERLEAVE_NONE, swz,
       CU_TENSOR_MAP_L2_PROMOTION_L2_128B, CU_TENSOR_MAP_FLOAT_OOB_FILL_NONE);
}

}

extern "C" void kernel_launch(void* const* d_in, const int* in_sizes, int n_in, void* d_out, int out_size) {
    (void)in_sizes; (void)n_in; (void)out_size;
    static EncodeFn enc = nullptr;
    static void* yT_ptr = nullptr;
    if (!enc) {
        void* fn = nullptr; cudaDriverEntryPointQueryResult qr;
        cudaGetDriverEntryPoint("cuTensorMapEncodeTiled", &fn, cudaEnableDefault, &qr);
        enc = (EncodeFn)fn;
        cudaGetSymbolAddress(&yT_ptr, g_yT);
        cudaFuncSetAttribute(fused_kernel, cudaFuncAttributeMaxDynamicSharedMemorySize, SM_TOTAL);
    }
    Params p;
    p.q = (const __nv_bfloat16*)d_in[0]; p.k = (const __nv_bfloat16*)d_in[1]; p.v = (const __nv_bfloat16*)d_in[2];
    p.shift_k = (const __nv_bfloat16*)d_in[3]; p.ssm_k = (const __nv_bfloat16*)d_in[4]; p.ssm_D = (const __nv_bfloat16*)d_in[5];
    p.wg = (const __nv_bfloat16*)d_in[7]; p.wu = (const __nv_bfloat16*)d_in[8]; p.wd = (const __nv_bfloat16*)d_in[9];
    {
        cuuint64_t dims[2] = {DM, SEQ}; cuuint64_t str[1] = {DM * 2};
        cuuint64_t dims3[3] = {64, SEQ, DM / 64}; cuuint64_t str3[2] = {DM * 2, 128};
        cuuint32_t box[3] = {64, 64, 8}, boxe[3] = {64, 128, 2};
        encode(enc, &p.tm_x, p.q, 3, dims3, str3, box, CU_TENSOR_MAP_SWIZZLE_128B);
        encode(enc, &p.tm_xe, p.q, 3, dims3, str3, boxe, CU_TENSOR_MAP_SWIZZLE_128B);
        cuuint32_t box2[2] = {64, 64};
        encode(enc, &p.tm_out, d_out, 2, dims, str, box2, CU_TENSOR_MAP_SWIZZLE_128B);
    }
    {
        cuuint64_t dims[3] = {32, DM, FF / 32}; cuuint64_t str[2] = {FF * 2, 64};
        cuuint32_t boxA[3] = {32, 64, 4}, boxB[3] = {32, 64, 2};
        encode(enc, &p.tm_gA, p.wg, 3, dims, str, boxA, CU_TENSOR_MAP_SWIZZLE_64B);
        encode(enc, &p.tm_gB, p.wg, 3, dims, str, boxB, CU_TENSOR_MAP_SWIZZLE_64B);
        encode(enc, &p.tm_uA, p.wu, 3, dims, str, boxA, CU_TENSOR_MAP_SWIZZLE_64B);
        encode(enc, &p.tm_uB, p.wu, 3, dims, str, boxB, CU_TENSOR_MAP_SWIZZLE_64B);
    }
    {
        cuuint64_t dims[3] = {64, FF, DM / 64}; cuuint64_t str[2] = {DM * 2, 128};
        cuuint32_t box[3] = {64, 32, 2};
        encode(enc, &p.tm_w2, p.wd, 3, dims, str, box, CU_TENSOR_MAP_SWIZZLE_128B);
    }
    {
        cuuint64_t dims[2] = {SEQ, DM}; cuuint64_t str[1] = {SEQ * 2};
        cuuint32_t box[2] = {64, 128};
        encode(enc, &p.tm_yT, yT_ptr, 2, dims, str, box, CU_TENSOR_MAP_SWIZZLE_128B);
    }
    fused_kernel<<<NCTA, NTHREADS, SM_TOTAL>>>(p);
}
```

```cpp
#include <cuda_runtime.h>
#include <cuda_bf16.h>
#include <cuda.h>
#include <stdint.h>

namespace {

constexpr int SEQ = 2048, DM = 512, FF = 1792;
constexpr int NCTA = 128;
constexpr int NTHREADS = 384;
constexpr int STAGE_BYTES = 32768;
#define KV_STAGGER 300
#define KV_GAP 150

constexpr uint32_t SM_X = 0;
constexpr uint32_t SM_RING = 131072;
constexpr uint32_t SM_MISC = SM_RING + 3 * STAGE_BYTES;
constexpr uint32_t SM_BARS = SM_MISC;
constexpr uint32_t SM_EPOCH = SM_MISC + 248;
constexpr uint32_t SM_STATS = SM_MISC + 256;
constexpr uint32_t SM_TOTAL = SM_STATS + 1024;
static_assert(SM_TOTAL <= 232448, "smem");
constexpr uint32_t SM_CVX = 0;
constexpr uint32_t SM_CVH = 65536;
constexpr uint32_t SM_YT = 32768;
constexpr uint32_t SM_XE = 98304;

constexpr int B_FULL = 0, B_EMPTY = 5, B_XFULL = 10, B_CONV = 14, B_YT = 15, B_XR = 16, B_G1DONE = 17, B_HD = 18, B_HRDY = 22,
              B_XFREE = 24, B_YST = 25, B_KVLD = 26, B_LN = 27, B_COUNT = 28;
static_assert(B_COUNT * 8 <= 248, "barrier space");

__device__ __align__(128) uint32_t g_h[16 * 56 * 2048];
__device__ __align__(128) __nv_bfloat16 g_kvT[DM * SEQ];
__device__ __align__(128) __nv_bfloat16 g_yT[DM * SEQ];
__device__ unsigned g_launch[NCTA];
__device__ unsigned g_cnt_kv[32];
__device__ unsigned g_cnt_y[4 * 32];
__device__ unsigned g_flag_h[16 * 2 * 8];

#define PROF(idx)
#define PROF2(a, idx)
#define PROFW(idx, w)

struct Params {
    CUtensorMap tm_x, tm_gA, tm_gB, tm_uA, tm_uB, tm_w2, tm_yT, tm_out, tm_xe;
    const __nv_bfloat16 *q, *k, *v, *shift_k, *ssm_k, *ssm_D, *wg, *wu, *wd;
};

__device__ __forceinline__ void wgmma_rs_n32(float (&d)[16], uint32_t a0, uint32_t a1, uint32_t a2, uint32_t a3, uint64_t db, int sc) {
  asm volatile("{\n.reg .pred p;\nsetp.ne.b32 p, %21, 0;\n"
    "wgmma.mma_async.sync.aligned.m64n32k16.f32.bf16.bf16 {%0,%1,%2,%3,%4,%5,%6,%7,%8,%9,%10,%11,%12,%13,%14,%15}, {%16,%17,%18,%19}, %20, p, 1, 1, 0;\n}\n"
    : "+f"(d[0]),"+f"(d[1]),"+f"(d[2]),"+f"(d[3]),"+f"(d[4]),"+f"(d[5]),"+f"(d[6]),"+f"(d[7]),"+f"(d[8]),"+f"(d[9]),"+f"(d[10]),"+f"(d[11]),"+f"(d[12]),"+f"(d[13]),"+f"(d[14]),"+f"(d[15])
    : "r"(a0),"r"(a1),"r"(a2),"r"(a3),"l"(db),"r"(sc));
}
__device__ __forceinline__ void wgmma_rs_n128_tb(float (&d)[64], uint32_t a0, uint32_t a1, uint32_t a2, uint32_t a3, uint64_t db, int sc) {
  asm volatile("{\n.reg .pred p;\nsetp.ne.b32 p, %69, 0;\n"
    "wgmma.mma_async.sync.aligned.m64n128k16.f32.bf16.bf16 {%0,%1,%2,%3,%4,%5,%6,%7,%8,%9,%10,%11,%12,%13,%14,%15,%16,%17,%18,%19,%20,%21,%22,%23,%24,%25,%26,%27,%28,%29,%30,%31,%32,%33,%34,%35,%36,%37,%38,%39,%40,%41,%42,%43,%44,%45,%46,%47,%48,%49,%50,%51,%52,%53,%54,%55,%56,%57,%58,%59,%60,%61,%62,%63}, {%64,%65,%66,%67}, %68, p, 1, 1, 1;\n}\n"
    : "+f"(d[0]),"+f"(d[1]),"+f"(d[2]),"+f"(d[3]),"+f"(d[4]),"+f"(d[5]),"+f"(d[6]),"+f"(d[7]),"+f"(d[8]),"+f"(d[9]),"+f"(d[10]),"+f"(d[11]),"+f"(d[12]),"+f"(d[13]),"+f"(d[14]),"+f"(d[15]),"+f"(d[16]),"+f"(d[17]),"+f"(d[18]),"+f"(d[19]),"+f"(d[20]),"+f"(d[21]),"+f"(d[22]),"+f"(d[23]),"+f"(d[24]),"+f"(d[25]),"+f"(d[26]),"+f"(d[27]),"+f"(d[28]),"+f"(d[29]),"+f"(d[30]),"+f"(d[31]),"+f"(d[32]),"+f"(d[33]),"+f"(d[34]),"+f"(d[35]),"+f"(d[36]),"+f"(d[37]),"+f"(d[38]),"+f"(d[39]),"+f"(d[40]),"+f"(d[41]),"+f"(d[42]),"+f"(d[43]),"+f"(d[44]),"+f"(d[45]),"+f"(d[46]),"+f"(d[47]),"+f"(d[48]),"+f"(d[49]),"+f"(d[50]),"+f"(d[51]),"+f"(d[52]),"+f"(d[53]),"+f"(d[54]),"+f"(d[55]),"+f"(d[56]),"+f"(d[57]),"+f"(d[58]),"+f"(d[59]),"+f"(d[60]),"+f"(d[61]),"+f"(d[62]),"+f"(d[63])
    : "r"(a0),"r"(a1),"r"(a2),"r"(a3),"l"(db),"r"(sc));
}
__device__ __forceinline__ void wgmma_ss_n256_tb(float (&d)[128], uint64_t da, uint64_t db, int sc) {
  asm volatile("{\n.reg .pred p;\nsetp.ne.b32 p, %130, 0;\n"
    "wgmma.mma_async.sync.aligned.m64n256k16.f32.bf16.bf16 {%0,%1,%2,%3,%4,%5,%6,%7,%8,%9,%10,%11,%12,%13,%14,%15,%16,%17,%18,%19,%20,%21,%22,%23,%24,%25,%26,%27,%28,%29,%30,%31,%32,%33,%34,%35,%36,%37,%38,%39,%40,%41,%42,%43,%44,%45,%46,%47,%48,%49,%50,%51,%52,%53,%54,%55,%56,%57,%58,%59,%60,%61,%62,%63,%64,%65,%66,%67,%68,%69,%70,%71,%72,%73,%74,%75,%76,%77,%78,%79,%80,%81,%82,%83,%84,%85,%86,%87,%88,%89,%90,%91,%92,%93,%94,%95,%96,%97,%98,%99,%100,%101,%102,%103,%104,%105,%106,%107,%108,%109,%110,%111,%112,%113,%114,%115,%116,%117,%118,%119,%120,%121,%122,%123,%124,%125,%126,%127}, %128, %129, p, 1, 1, 0, 1;\n}\n"
    : "+f"(d[0]),"+f"(d[1]),"+f"(d[2]),"+f"(d[3]),"+f"(d[4]),"+f"(d[5]),"+f"(d[6]),"+f"(d[7]),"+f"(d[8]),"+f"(d[9]),"+f"(d[10]),"+f"(d[11]),"+f"(d[12]),"+f"(d[13]),"+f"(d[14]),"+f"(d[15]),"+f"(d[16]),"+f"(d[17]),"+f"(d[18]),"+f"(d[19]),"+f"(d[20]),"+f"(d[21]),"+f"(d[22]),"+f"(d[23]),"+f"(d[24]),"+f"(d[25]),"+f"(d[26]),"+f"(d[27]),"+f"(d[28]),"+f"(d[29]),"+f"(d[30]),"+f"(d[31]),"+f"(d[32]),"+f"(d[33]),"+f"(d[34]),"+f"(d[35]),"+f"(d[36]),"+f"(d[37]),"+f"(d[38]),"+f"(d[39]),"+f"(d[40]),"+f"(d[41]),"+f"(d[42]),"+f"(d[43]),"+f"(d[44]),"+f"(d[45]),"+f"(d[46]),"+f"(d[47]),"+f"(d[48]),"+f"(d[49]),"+f"(d[50]),"+f"(d[51]),"+f"(d[52]),"+f"(d[53]),"+f"(d[54]),"+f"(d[55]),"+f"(d[56]),"+f"(d[57]),"+f"(d[58]),"+f"(d[59]),"+f"(d[60]),"+f"(d[61]),"+f"(d[62]),"+f"(d[63]),"+f"(d[64]),"+f"(d[65]),"+f"(d[66]),"+f"(d[67]),"+f"(d[68]),"+f"(d[69]),"+f"(d[70]),"+f"(d[71]),"+f"(d[72]),"+f"(d[73]),"+f"(d[74]),"+f"(d[75]),"+f"(d[76]),"+f"(d[77]),"+f"(d[78]),"+f"(d[79]),"+f"(d[80]),"+f"(d[81]),"+f"(d[82]),"+f"(d[83]),"+f"(d[84]),"+f"(d[85]),"+f"(d[86]),"+f"(d[87]),"+f"(d[88]),"+f"(d[89]),"+f"(d[90]),"+f"(d[91]),"+f"(d[92]),"+f"(d[93]),"+f"(d[94]),"+f"(d[95]),"+f"(d[96]),"+f"(d[97]),"+f"(d[98]),"+f"(d[99]),"+f"(d[100]),"+f"(d[101]),"+f"(d[102]),"+f"(d[103]),"+f"(d[104]),"+f"(d[105]),"+f"(d[106]),"+f"(d[107]),"+f"(d[108]),"+f"(d[109]),"+f"(d[110]),"+f"(d[111]),"+f"(d[112]),"+f"(d[113]),"+f"(d[114]),"+f"(d[115]),"+f"(d[116]),"+f"(d[117]),"+f"(d[118]),"+f"(d[119]),"+f"(d[120]),"+f"(d[121]),"+f"(d[122]),"+f"(d[123]),"+f"(d[124]),"+f"(d[125]),"+f"(d[126]),"+f"(d[127])
    : "l"(da),"l"(db),"r"(sc));
}
__device__ __forceinline__ void wgmma_ss_n192_tb(float (&d)[96], uint64_t da, uint64_t db, int sc) {
  asm volatile("{\n.reg .pred p;\nsetp.ne.b32 p, %98, 0;\n"
    "wgmma.mma_async.sync.aligned.m64n192k16.f32.bf16.bf16 {%0,%1,%2,%3,%4,%5,%6,%7,%8,%9,%10,%11,%12,%13,%14,%15,%16,%17,%18,%19,%20,%21,%22,%23,%24,%25,%26,%27,%28,%29,%30,%31,%32,%33,%34,%35,%36,%37,%38,%39,%40,%41,%42,%43,%44,%45,%46,%47,%48,%49,%50,%51,%52,%53,%54,%55,%56,%57,%58,%59,%60,%61,%62,%63,%64,%65,%66,%67,%68,%69,%70,%71,%72,%73,%74,%75,%76,%77,%78,%79,%80,%81,%82,%83,%84,%85,%86,%87,%88,%89,%90,%91,%92,%93,%94,%95}, %96, %97, p, 1, 1, 0, 1;\n}\n"
    : "+f"(d[0]),"+f"(d[1]),"+f"(d[2]),"+f"(d[3]),"+f"(d[4]),"+f"(d[5]),"+f"(d[6]),"+f"(d[7]),"+f"(d[8]),"+f"(d[9]),"+f"(d[10]),"+f"(d[11]),"+f"(d[12]),"+f"(d[13]),"+f"(d[14]),"+f"(d[15]),"+f"(d[16]),"+f"(d[17]),"+f"(d[18]),"+f"(d[19]),"+f"(d[20]),"+f"(d[21]),"+f"(d[22]),"+f"(d[23]),"+f"(d[24]),"+f"(d[25]),"+f"(d[26]),"+f"(d[27]),"+f"(d[28]),"+f"(d[29]),"+f"(d[30]),"+f"(d[31]),"+f"(d[32]),"+f"(d[33]),"+f"(d[34]),"+f"(d[35]),"+f"(d[36]),"+f"(d[37]),"+f"(d[38]),"+f"(d[39]),"+f"(d[40]),"+f"(d[41]),"+f"(d[42]),"+f"(d[43]),"+f"(d[44]),"+f"(d[45]),"+f"(d[46]),"+f"(d[47]),"+f"(d[48]),"+f"(d[49]),"+f"(d[50]),"+f"(d[51]),"+f"(d[52]),"+f"(d[53]),"+f"(d[54]),"+f"(d[55]),"+f"(d[56]),"+f"(d[57]),"+f"(d[58]),"+f"(d[59]),"+f"(d[60]),"+f"(d[61]),"+f"(d[62]),"+f"(d[63]),"+f"(d[64]),"+f"(d[65]),"+f"(d[66]),"+f"(d[67]),"+f"(d[68]),"+f"(d[69]),"+f"(d[70]),"+f"(d[71]),"+f"(d[72]),"+f"(d[73]),"+f"(d[74]),"+f"(d[75]),"+f"(d[76]),"+f"(d[77]),"+f"(d[78]),"+f"(d[79]),"+f"(d[80]),"+f"(d[81]),"+f"(d[82]),"+f"(d[83]),"+f"(d[84]),"+f"(d[85]),"+f"(d[86]),"+f"(d[87]),"+f"(d[88]),"+f"(d[89]),"+f"(d[90]),"+f"(d[91]),"+f"(d[92]),"+f"(d[93]),"+f"(d[94]),"+f"(d[95])
    : "l"(da),"l"(db),"r"(sc));
}

__device__ __forceinline__ uint32_t smem_u32(const void* p) { return (uint32_t)__cvta_generic_to_shared(p); }
__device__ __forceinline__ void mbar_init(uint32_t bar, uint32_t cnt) { asm volatile("mbarrier.init.shared::cta.b64 [%0], %1;" :: "r"(bar), "r"(cnt)); }
__device__ __forceinline__ void mbar_expect_tx(uint32_t bar, uint32_t bytes) { asm volatile("mbarrier.arrive.expect_tx.shared::cta.b64 _, [%0], %1;" :: "r"(bar), "r"(bytes) : "memory"); }
__device__ __forceinline__ void mbar_arrive(uint32_t bar) { asm volatile("mbarrier.arrive.shared::cta.b64 _, [%0];" :: "r"(bar) : "memory"); }
__device__ __forceinline__ void mbar_arrive_cluster(uint32_t cbar, uint32_t cnt) { asm volatile("mbarrier.arrive.shared::cluster.b64 _, [%0], %1;" :: "r"(cbar), "r"(cnt) : "memory"); }
__device__ __forceinline__ uint32_t mapa(uint32_t a, uint32_t rank) { uint32_t r; asm volatile("mapa.shared::cluster.u32 %0, %1, %2;" : "=r"(r) : "r"(a), "r"(rank)); return r; }
__device__ __forceinline__ void mbar_wait(uint32_t bar, uint32_t parity) {
    uint32_t ok; uint32_t n = 0;
    do {
        asm volatile("{\n.reg .pred p;\nmbarrier.try_wait.parity.shared::cta.b64 p, [%1], %2;\nselp.u32 %0, 1, 0, p;\n}" : "=r"(ok) : "r"(bar), "r"(parity) : "memory");
    } while (!ok && ++n < (1u << 17));
}
__device__ __forceinline__ void pace_wait(uint32_t a, uint32_t target) {
    uint32_t v, n = 0;
    do {
        asm volatile("ld.volatile.shared.u32 %0, [%1];" : "=r"(v) : "r"(a) : "memory");
        if (v < target) __nanosleep(150);
    } while (v < target && ++n < (1u << 14));
}
__device__ __forceinline__ void flag_wait(const unsigned* p, unsigned target) {
    unsigned v; uint32_t n = 0;
    while (true) {
        asm volatile("ld.acquire.gpu.global.u32 %0, [%1];" : "=r"(v) : "l"(p) : "memory");
        if ((int)(v - target) >= 0 || ++n >= (1u << 17)) break;
        __nanosleep(40);
    }
}
__device__ __forceinline__ void flag_add(unsigned* p) {
    asm volatile("fence.acq_rel.gpu;\nred.relaxed.gpu.global.add.u32 [%0], 1;" :: "l"(p) : "memory");
}
__device__ __forceinline__ uint64_t make_desc(uint32_t addr, uint32_t lbo, uint32_t sbo, uint32_t swz) {
    return (uint64_t)((addr & 0x3FFFF) >> 4) | ((uint64_t)((lbo & 0x3FFFF) >> 4) << 16) | ((uint64_t)((sbo & 0x3FFFF) >> 4) << 32) | ((uint64_t)swz << 62);
}
__device__ __forceinline__ uint64_t desc_add(uint64_t d, uint32_t off16) {
    return (d & 0xFFFFFFFF00000000ull) | (uint64_t)((uint32_t)d + off16);
}
__device__ __forceinline__ void tma2d(uint32_t dst, const CUtensorMap* tm, int c0, int c1, uint32_t bar) {
    asm volatile("cp.async.bulk.tensor.2d.shared::cluster.global.mbarrier::complete_tx::bytes [%0], [%1, {%3, %4}], [%2];"
        :: "r"(dst), "l"((uint64_t)tm), "r"(bar), "r"(c0), "r"(c1) : "memory");
}
__device__ __forceinline__ void tma3d(uint32_t dst, const CUtensorMap* tm, int c0, int c1, int c2, uint32_t bar) {
    asm volatile("cp.async.bulk.tensor.3d.shared::cluster.global.mbarrier::complete_tx::bytes [%0], [%1, {%3, %4, %5}], [%2];"
        :: "r"(dst), "l"((uint64_t)tm), "r"(bar), "r"(c0), "r"(c1), "r"(c2) : "memory");
}
__device__ __forceinline__ void tma3d_mc(uint32_t dst, const CUtensorMap* tm, int c0, int c1, int c2, uint32_t bar) {
    asm volatile("cp.async.bulk.tensor.3d.shared::cluster.global.mbarrier::complete_tx::bytes.multicast::cluster [%0], [%1, {%3, %4, %5}], [%2], %6;"
        :: "r"(dst), "l"((uint64_t)tm), "r"(bar), "r"(c0), "r"(c1), "r"(c2), "h"((uint16_t)3) : "memory");
}
__device__ __forceinline__ void bulk_g2s(uint32_t dst, const void* src, uint32_t bytes, uint32_t bar) {
    asm volatile("cp.async.bulk.shared::cluster.global.mbarrier::complete_tx::bytes [%0], [%1], %2, [%3];"
        :: "r"(dst), "l"(src), "r"(bytes), "r"(bar) : "memory");
}
__device__ __forceinline__ void bulk_s2g(void* dst, uint32_t src, uint32_t bytes) {
    asm volatile("cp.async.bulk.global.shared::cta.bulk_group [%0], [%1], %2;" :: "l"(dst), "r"(src), "r"(bytes) : "memory");
}
__device__ __forceinline__ void tma2d_store(const CUtensorMap* tm, int c0, int c1, uint32_t src) {
    asm volatile("cp.async.bulk.tensor.2d.global.shared::cta.bulk_group [%0, {%2, %3}], [%1];"
        :: "l"((uint64_t)tm), "r"(src), "r"(c0), "r"(c1) : "memory");
}
__device__ __forceinline__ void l2_prefetch(const void* p, uint32_t bytes) {
    asm volatile("cp.async.bulk.prefetch.L2.global [%0], %1;" :: "l"(p), "r"(bytes) : "memory");
}
__device__ __forceinline__ void tmap_prefetch(const CUtensorMap* tm) { asm volatile("prefetch.tensormap [%0];" :: "l"((uint64_t)tm) : "memory"); }
__device__ __forceinline__ uint32_t lds32(uint32_t a) { uint32_t v; asm volatile("ld.shared.u32 %0, [%1];" : "=r"(v) : "r"(a)); return v; }
__device__ __forceinline__ uint2 lds64(uint32_t a) { uint2 v; asm volatile("ld.shared.v2.u32 {%0,%1}, [%2];" : "=r"(v.x), "=r"(v.y) : "r"(a)); return v; }
__device__ __forceinline__ uint4 lds128(uint32_t a) { uint4 v; asm volatile("ld.shared.v4.u32 {%0,%1,%2,%3}, [%4];" : "=r"(v.x), "=r"(v.y), "=r"(v.z), "=r"(v.w) : "r"(a)); return v; }
__device__ __forceinline__ float2 lds64f(uint32_t a) { float2 v; asm volatile("ld.shared.v2.f32 {%0,%1}, [%2];" : "=f"(v.x), "=f"(v.y) : "r"(a)); return v; }
__device__ __forceinline__ void sts32(uint32_t a, uint32_t v) { asm volatile("st.shared.u32 [%0], %1;" :: "r"(a), "r"(v) : "memory"); }
__device__ __forceinline__ void sts128(uint32_t a, uint4 v) { asm volatile("st.shared.v4.u32 [%0], {%1,%2,%3,%4};" :: "r"(a), "r"(v.x), "r"(v.y), "r"(v.z), "r"(v.w) : "memory"); }
__device__ __forceinline__ uint4 ldg_cg128(const void* p) { uint4 v; asm volatile("ld.global.cg.v4.u32 {%0,%1,%2,%3}, [%4];" : "=r"(v.x), "=r"(v.y), "=r"(v.z), "=r"(v.w) : "l"(p)); return v; }
__device__ __forceinline__ uint4 ldg_nc128(const void* p) { uint4 v; asm volatile("ld.global.nc.L1::no_allocate.v4.u32 {%0,%1,%2,%3}, [%4];" : "=r"(v.x), "=r"(v.y), "=r"(v.z), "=r"(v.w) : "l"(p)); return v; }
__device__ __forceinline__ uint32_t ldg_nc32(const void* p) { uint32_t v; asm volatile("ld.global.nc.u32 %0, [%1];" : "=r"(v) : "l"(p)); return v; }
__device__ __forceinline__ uint2 ldg_nc64(const void* p) { uint2 v; asm volatile("ld.global.nc.L1::no_allocate.v2.u32 {%0,%1}, [%2];" : "=r"(v.x), "=r"(v.y) : "l"(p)); return v; }
#define WG_FENCE() asm volatile("wgmma.fence.sync.aligned;\n" ::: "memory")
#define WG_COMMIT() asm volatile("wgmma.commit_group.sync.aligned;\n" ::: "memory")
template<int N> __device__ __forceinline__ void wg_wait() { asm volatile("wgmma.wait_group.sync.aligned %0;\n" :: "n"(N) : "memory"); }
__device__ __forceinline__ bool elect_one() {
    uint32_t pr;
    asm volatile("{\n.reg .pred p;\nelect.sync _|p, 0xffffffff;\nselp.u32 %0, 1, 0, p;\n}" : "=r"(pr));
    return pr != 0;
}
__device__ __forceinline__ void named_bar(int id, int n) { asm volatile("bar.sync %0, %1;" :: "r"(id), "r"(n) : "memory"); }

__device__ __forceinline__ float bf_lo(uint32_t u) { return __uint_as_float(u << 16); }
__device__ __forceinline__ float bf_hi(uint32_t u) { return __uint_as_float(u & 0xFFFF0000u); }
__device__ __forceinline__ uint32_t pack_bf(float lo, float hi) { uint32_t r; asm("cvt.rn.bf16x2.f32 %0, %1, %2;" : "=r"(r) : "f"(hi), "f"(lo)); return r; }
__device__ __forceinline__ float bf_round(float x) { return __bfloat162float(__float2bfloat16_rn(x)); }
__device__ __forceinline__ uint32_t bmul2(uint32_t a, uint32_t b) { uint32_t r; asm("mul.rn.bf16x2 %0, %1, %2;" : "=r"(r) : "r"(a), "r"(b)); return r; }
__device__ __forceinline__ uint32_t badd2(uint32_t a, uint32_t b) { uint32_t r; asm("add.rn.bf16x2 %0, %1, %2;" : "=r"(r) : "r"(a), "r"(b)); return r; }
__device__ __forceinline__ uint32_t bsub2(uint32_t a, uint32_t b) { uint32_t r; asm("sub.rn.bf16x2 %0, %1, %2;" : "=r"(r) : "r"(a), "r"(b)); return r; }
__device__ __forceinline__ void mma16816(float (&d)[4], uint32_t a0, uint32_t a1, uint32_t a2, uint32_t a3, uint2 b) {
    asm volatile("mma.sync.aligned.m16n8k16.row.col.f32.bf16.bf16.f32 {%0,%1,%2,%3}, {%4,%5,%6,%7}, {%8,%9}, {%0,%1,%2,%3};\n"
        : "+f"(d[0]), "+f"(d[1]), "+f"(d[2]), "+f"(d[3]) : "r"(a0), "r"(a1), "r"(a2), "r"(a3), "r"(b.x), "r"(b.y));
}

template<int HS> __device__ __forceinline__ void xreduce(float (&v)[8], int lane) {
    const int up = lane & HS;
    #pragma unroll
    for (int e = 0; e < HS; e++) {
        float keep, send;
        asm("{\n.reg .pred p;\nsetp.ne.b32 p, %4, 0;\nselp.f32 %0, %3, %2, p;\nselp.f32 %1, %2, %3, p;\n}"
            : "=f"(keep), "=f"(send) : "f"(v[e]), "f"(v[e + HS]), "r"(up));
        v[e] = keep + __shfl_xor_sync(0xffffffffu, send, HS);
    }
}

__device__ __forceinline__ int blk_f0(int s) {
    if (s < 32) return 32 * (14 * (s >> 3) + 8 * ((s >> 2) & 1) + (s & 3));
    const int s2 = s - 32, c6 = (s2 * 11) >> 6, t = s2 - 6 * c6;
    return 32 * (14 * c6 + (t < 4 ? 4 + t : 8 + t));
}
__device__ __forceinline__ int next_st2(int s) { return (0x14023 >> (4 * s)) & 7; }
__device__ __forceinline__ uint32_t stage_off_rt(int s) { return s < 3 ? SM_RING + s * STAGE_BYTES : (uint32_t)(s - 3) * 65536; }

__device__ __forceinline__ void store_h(uint32_t* dst, const uint32_t (&hp)[32], int q) {
    #pragma unroll
    for (int kk = 0; kk < 2; kk++) {
        uint32_t* d2 = dst + q * 2048 + kk * 512;
        d2[0] = hp[8 * q + 4 * kk]; d2[64] = hp[8 * q + 4 * kk + 1]; d2[32] = hp[8 * q + 4 * kk + 2]; d2[96] = hp[8 * q + 4 * kk + 3];
    }
}
template<int NB, bool passA>
__device__ __forceinline__ void gemm1_pass(uint32_t sb, int wgi, int warp4, int lane, int& st, uint32_t& fph, uint32_t e_cl,
                                           uint32_t (&hp)[32], uint32_t* prev_dst, bool convCTA) {
    constexpr bool narrow = (NB == 2);
    float acc[NB * 32];
    const uint64_t descA0 = make_desc(sb + SM_X + wgi * 65536, 16, 1024, 1);
    const uint64_t descB0 = make_desc(sb + SM_RING, narrow ? 8192 : 4096, 512, 2);
    int prev = 0;
    auto group = [&](int sl) {
        if (warp4 == 0 && wgi == 0) PROF2(2, sl + (passA ? 0 : 8));
        mbar_wait(sb + SM_BARS + (B_FULL + st) * 8, (fph >> st) & 1);
        fph ^= 1u << st;
        if (sl == 0 && warp4 == 0) PROF(2 + wgi * 8 + (passA ? 0 : 3));
        if (warp4 == 0 && wgi == 0) PROF2(1, sl + (passA ? 0 : 8));
        const uint64_t da = desc_add(descA0, sl * (narrow ? 1024 : 512)), db = desc_add(descB0, st * 2048);
        WG_FENCE();
        #pragma unroll
        for (int kk = 0; kk < (narrow ? 8 : 4); kk++) {
            int sc = (sl | kk) ? 1 : 0;
            if constexpr (!narrow) wgmma_ss_n256_tb(acc, da + kk * 2, db + kk * 64, sc);
            else wgmma_ss_n128_tb(acc, da + ((kk >> 2) * 512 + (kk & 3) * 2), db + kk * 64, sc);
        }
        WG_COMMIT();
        wg_wait<1>();
        if (warp4 == 0 && wgi == 0) PROF2(3, sl + (passA ? 0 : 8));
        if (lane < 2 && sl && (!narrow || sl == 1)) mbar_arrive_cluster(e_cl + prev * 8, 1);
        if (narrow && sl == 2 && lane == 0) mbar_arrive(sb + SM_BARS + B_XFREE * 8);
        if (!passA && !narrow && sl == 4 && lane < 4) mbar_arrive_cluster(e_cl + (3 + (lane >> 1)) * 8, 1);
        prev = st;
        st = (st == 2) ? 0 : st + 1;
    };
    if constexpr (passA) {
        #pragma unroll 1
        for (int sl = 0; sl < 8; sl++) group(sl);
    } else {
        #pragma unroll
        for (int sl = 0; sl < 4; sl++) { group(sl); store_h(prev_dst, hp, sl); }
        __syncwarp();
        if (lane == 0) mbar_arrive(sb + SM_BARS + (B_HD + wgi * 2) * 8);
        if constexpr (!narrow) {
            #pragma unroll 1
            for (int sl = 4; sl < 8; sl++) group(sl);
        }
    }
    wg_wait<0>();
    if (lane < 2 && (passA || !convCTA)) mbar_arrive_cluster(e_cl + prev * 8, 1);
    if (!passA && lane == 0) mbar_arrive(sb + SM_BARS + B_G1DONE * 8);
    if (warp4 == 0) PROF(3 + wgi * 8 + (passA ? 0 : 3));
    const int g = lane >> 2;
    const int r0 = wgi * 64 + warp4 * 16 + g;
    const float s0 = __uint_as_float(lds32(sb + SM_STATS + r0 * 8 + 4)), s1 = __uint_as_float(lds32(sb + SM_STATS + (r0 + 8) * 8 + 4));
    #pragma unroll
    for (int t = 0; t < NB * 4; t++) {
        const float* ag = &acc[4 * t];
        const float* au = &acc[NB * 16 + 4 * t];
        hp[2 * t] = bmul2(pack_bf(ag[0] * s0, ag[1] * s0), pack_bf(au[0] * s0, au[1] * s0));
        hp[2 * t + 1] = bmul2(pack_bf(ag[2] * s1, ag[3] * s1), pack_bf(au[2] * s1, au[3] * s1));
    }
    if (warp4 == 0) PROF(4 + wgi * 8 + (passA ? 0 : 3));
}

__global__ void __cluster_dims__(2, 1, 1) __launch_bounds__(NTHREADS, 1)
fused_kernel(const __grid_constant__ Params p) {
    extern __shared__ __align__(1024) uint8_t smem_raw[];
    const uint32_t sb = smem_u32(smem_raw);
    const int tid = threadIdx.x, warp = tid >> 5, lane = tid & 31;
    const int b = blockIdx.x;
    const int rank = b & 1;
    const int j = (b >> 1) & 7;
    const int i = ((b >> 4) << 1) | rank;
    const int cb = j >> 1;
    const bool convCTA = j & 1;
    const int cidx = 4 * i + cb;

    if (tid == 256) {
        mbar_init(sb + SM_BARS + B_XFULL * 8, 1);
        mbar_init(sb + SM_BARS + (B_XFULL + 1) * 8, 1);
        asm volatile("fence.proxy.async.shared::cta;" ::: "memory");
        mbar_expect_tx(sb + SM_BARS + B_XFULL * 8, 65536);
        tma3d(sb + SM_X, &p.tm_x, 0, 128 * i, 0, sb + SM_BARS + B_XFULL * 8);
        mbar_expect_tx(sb + SM_BARS + (B_XFULL + 1) * 8, 65536);
        tma3d(sb + SM_X + 65536, &p.tm_x, 0, 128 * i + 64, 0, sb + SM_BARS + (B_XFULL + 1) * 8);
    }
    if (tid == 288) {
        for (int s = 0; s < 5; s++) { mbar_init(sb + SM_BARS + (B_FULL + s) * 8, 1); mbar_init(sb + SM_BARS + (B_EMPTY + s) * 8, 16); }
        mbar_init(sb + SM_BARS + B_CONV * 8, 1);
        mbar_init(sb + SM_BARS + B_YT * 8, 1);
        mbar_init(sb + SM_BARS + B_XR * 8, 1);
        mbar_init(sb + SM_BARS + B_G1DONE * 8, 8);
        mbar_init(sb + SM_BARS + B_XFREE * 8, 8);
        mbar_init(sb + SM_BARS + B_YST * 8, 8);
        mbar_init(sb + SM_BARS + B_KVLD * 8, 2);
        mbar_init(sb + SM_BARS + B_LN * 8, 8);
        for (int s = 0; s < 4; s++) mbar_init(sb + SM_BARS + (B_HD + s) * 8, 4);
        for (int s = 0; s < 2; s++) mbar_init(sb + SM_BARS + (B_HRDY + s) * 8, 1);
        asm volatile("fence.mbarrier_init.release.cluster;" ::: "memory");
        asm volatile("fence.proxy.async.shared::cta;" ::: "memory");
    }
    __syncwarp();
    asm volatile("barrier.cluster.arrive.relaxed.aligned;\n" ::: "memory");
    asm volatile("barrier.cluster.wait.aligned;\n" ::: "memory");
    PROFW(1, 0);

    if (warp < 8) {
        asm volatile("setmaxnreg.inc.sync.aligned.u32 200;");
        const int wgi = warp >> 2, warp4 = warp & 3;
        const int g = lane >> 2, c = lane & 3;
        const uint32_t e_cl = mapa(sb + SM_BARS + B_EMPTY * 8, lane & 1);
        {
            const int lr16 = (lane & 7) + ((lane >> 3) & 1) * 8;
            const uint32_t xa = sb + SM_X + wgi * 65536 + (warp4 * 16 + lr16) * 128;
            uint32_t xf[32][4];
            float aS[4][4], aQ0[4][4], aQ1[4][4];
            #pragma unroll
            for (int e = 0; e < 4; e++) {
                #pragma unroll
                for (int f = 0; f < 4; f++) { aS[e][f] = 0.f; aQ0[e][f] = 0.f; aQ1[e][f] = 0.f; }
            }
            mbar_wait(sb + SM_BARS + (B_XFULL + wgi) * 8, 0);
            PROFW(16, 0); PROFW(18, 4);
            #pragma unroll
            for (int ks = 0; ks < 32; ks++) {
                const uint32_t a = xa + (ks >> 2) * 8192 + (((2 * (ks & 3) + (lane >> 4)) ^ (lane & 7)) << 4);
                asm volatile("ldmatrix.sync.aligned.m8n8.x4.shared.b16 {%0,%1,%2,%3}, [%4];"
                    : "=r"(xf[ks][0]), "=r"(xf[ks][1]), "=r"(xf[ks][2]), "=r"(xf[ks][3]) : "r"(a) : "memory");
            }
            PROFW(40, 4);
            #pragma unroll
            for (int ks = 0; ks < 32; ks++)
                mma16816(aS[ks & 3], xf[ks][0], xf[ks][1], xf[ks][2], xf[ks][3], make_uint2(0x3F803F80u, 0x3F803F80u));
            const float mean0 = ((aS[0][0] + aS[1][0]) + (aS[2][0] + aS[3][0])) * (1.0f / DM);
            const float mean1 = ((aS[0][2] + aS[1][2]) + (aS[2][2] + aS[3][2])) * (1.0f / DM);
            const uint32_t m0 = pack_bf(mean0, mean0), m1 = pack_bf(mean1, mean1);
            PROFW(41, 4);
            #pragma unroll
            for (int ks = 0; ks < 32; ks++) {
                const uint32_t a = xa + (ks >> 2) * 8192 + (((2 * (ks & 3) + (lane >> 4)) ^ (lane & 7)) << 4);
                asm volatile("stmatrix.sync.aligned.m8n8.x4.shared.b16 [%0], {%1,%2,%3,%4};"
                    :: "r"(a), "r"(bsub2(xf[ks][0], m0)), "r"(bsub2(xf[ks][1], m1)), "r"(bsub2(xf[ks][2], m0)), "r"(bsub2(xf[ks][3], m1)) : "memory");
            }
            PROFW(42, 4);
            asm volatile("fence.proxy.async.shared::cta;" ::: "memory");
            __syncwarp();
            if (lane == 0) mbar_arrive(sb + SM_BARS + B_LN * 8);
            #pragma unroll
            for (int ks = 0; ks < 32; ks++) {
                mma16816(aQ0[ks & 3], xf[ks][0], xf[ks][1], xf[ks][2], xf[ks][3], make_uint2(xf[ks][0], xf[ks][2]));
                mma16816(aQ1[ks & 3], xf[ks][0], xf[ks][1], xf[ks][2], xf[ks][3], make_uint2(xf[ks][1], xf[ks][3]));
            }
            if (c == (g >> 1)) {
                const float q0 = (g & 1) ? (aQ0[0][1] + aQ0[1][1]) + (aQ0[2][1] + aQ0[3][1]) : (aQ0[0][0] + aQ0[1][0]) + (aQ0[2][0] + aQ0[3][0]);
                const float q1 = (g & 1) ? (aQ1[0][3] + aQ1[1][3]) + (aQ1[2][3] + aQ1[3][3]) : (aQ1[0][2] + aQ1[1][2]) + (aQ1[2][2] + aQ1[3][2]);
                const float sd0 = bf_round(sqrtf(bf_round(bf_round(fmaxf(q0 * (1.0f / DM) - mean0 * mean0, 0.f)) + 1e-5f)));
                const float sd1 = bf_round(sqrtf(bf_round(bf_round(fmaxf(q1 * (1.0f / DM) - mean1 * mean1, 0.f)) + 1e-5f)));
                const uint32_t sa = sb + SM_STATS + (warp * 16 + g) * 8;
                sts32(sa, m0); sts32(sa + 4, __float_as_uint(1.0f / sd0));
                sts32(sa + 64, m1); sts32(sa + 68, __float_as_uint(1.0f / sd1));
            }
            mbar_wait(sb + SM_BARS + B_LN * 8, 0);
            PROFW(19, 4);
            PROFW(17, 0);
        }
        int st = 0; uint32_t fph = 0;
        uint32_t hp[32];
        uint32_t* const hdst = g_h + (size_t)(i * 56) * 2048 + wgi * 1024 + warp4 * 128 + lane;
        gemm1_pass<4, true>(sb, wgi, warp4, lane, st, fph, e_cl, hp, hdst, convCTA);

        if (convCTA) {
            gemm1_pass<2, false>(sb, wgi, warp4, lane, st, fph, e_cl, hp, hdst + 4 * j * 2048, true);
            store_h(hdst + (36 + 6 * cb) * 2048, hp, 0); store_h(hdst + (36 + 6 * cb) * 2048, hp, 1);
            __syncwarp();
            if (lane == 0) mbar_arrive(sb + SM_BARS + (B_HD + wgi * 2 + 1) * 8);
            const int gch = 8 * cidx + warp;
            const uint32_t xb = sb + SM_CVX + warp * 4096;
            const uint32_t hb = sb + SM_CVH + warp * 4096;
            const uint32_t dw = ((const unsigned short*)p.ssm_D)[gch];
            const uint32_t d2 = dw | (dw << 16);
            mbar_wait(sb + SM_BARS + B_CONV * 8, 0);
            PROFW(32, 4);
            float acc[16][4];
            #pragma unroll
            for (int jj = 0; jj < 16; jj++) { acc[jj][0] = 0.f; acc[jj][1] = 0.f; acc[jj][2] = 0.f; acc[jj][3] = 0.f; }
            uint2 bh[8], bl0[8], bl1[8];
            uint32_t xl = xb + g * 32 + c * 8;
            uint32_t hl = hb + (g + 2 * c - 8) * 4;
            #pragma unroll
            for (int d = 0; d < 8; d++) { bl0[d] = lds64(xl + d * 256); bh[d] = lds64(xl + (8 + d) * 256); }
            uint32_t w[6];
            w[0] = 0; w[1] = 0; w[2] = 0;
            if (g + 2 * c >= 8) w[0] = lds32(hl);
            if (g + 2 * c >= 7) w[1] = lds32(hl + 4);
            if (g + 2 * c >= 6) w[2] = lds32(hl + 8);
            w[3] = lds32(hl + 2048); w[4] = lds32(hl + 2052); w[5] = lds32(hl + 2056);
            auto conv_m0 = [&](int m0, uint2 (&bl)[8], uint2 (&bn)[8]) {
                xl -= 32;
                #pragma unroll
                for (int k = 0; k < 8; k++) {
                    const uint32_t a0 = w[1], a1 = __byte_perm(w[0], w[1], 0x5432), a2 = w[2], a3 = __byte_perm(w[1], w[2], 0x5432);
                    const uint32_t c0 = w[4], c1 = __byte_perm(w[3], w[4], 0x5432), c2 = w[5], c3 = __byte_perm(w[4], w[5], 0x5432);
                    const uint32_t nx = (k < 7) ? hl + (k + 1) * 256 : hl + 32;
                    w[0] = lds32(nx); w[1] = lds32(nx + 4); w[2] = lds32(nx + 8);
                    w[3] = lds32(nx + 2048); w[4] = lds32(nx + 2052); w[5] = lds32(nx + 2056);
                    if (k > 0) bn[k] = lds64(xl + k * 256);
                    else { bn[0] = make_uint2(0, 0); if (g > m0) bn[0] = lds64(xl); }
                    #pragma unroll
                    for (int jj = k; jj < 16; jj++) mma16816(acc[jj], a0, a1, a2, a3, (jj - k < 8) ? bl[(jj - k) & 7] : bh[(jj - k) & 7]);
                    bh[7 - k] = lds64(xl + (15 - k) * 256);
                    #pragma unroll
                    for (int jj = k + 8; jj < 16; jj++) mma16816(acc[jj], c0, c1, c2, c3, bl[jj - k - 8]);
                }
                hl += 32;
            };
            #pragma unroll 1
            for (int m0 = 0; m0 < 8; m0 += 2) {
                conv_m0(m0, bl0, bl1);
                conv_m0(m0 + 1, bl1, bl0);
                PROFW(34 + (m0 >> 1), 4);
            }
            PROFW(33, 4);
            const uint32_t kvl = xb + c * 64 + (7 - g) * 4;
            uint32_t* ydst = (uint32_t*)(g_yT + (size_t)gch * SEQ + 32 * c + 2 * g);
            uint32_t kk0[16], kk1[16];
            #pragma unroll
            for (int jj = 0; jj < 16; jj++) { kk0[jj] = lds32(kvl + jj * 256); kk1[jj] = lds32(kvl + jj * 256 + 32); }
            #pragma unroll
            for (int jj = 0; jj < 16; jj++) {
                ydst[jj * 64] = badd2(pack_bf(acc[jj][2], acc[jj][0]), bmul2(__byte_perm(kk0[jj], kk0[jj], 0x1032), d2));
                ydst[jj * 64 + 8] = badd2(pack_bf(acc[jj][3], acc[jj][1]), bmul2(__byte_perm(kk1[jj], kk1[jj], 0x1032), d2));
            }
            __syncwarp();
            PROFW(44, 4);
            if (lane == 0) flag_add(&g_cnt_y[(cidx >> 4) * 32]);
            PROFW(46, 4);
        } else {
            gemm1_pass<4, false>(sb, wgi, warp4, lane, st, fph, e_cl, hp, hdst + 4 * j * 2048, false);
            float acc[64];
            const uint64_t descB0 = make_desc(sb, 4096, 1024, 1);
            const uint64_t descA0 = make_desc(sb + 16384 + wgi * 4096, 128, 256, 0);
            int sg = 3, p0 = 0; uint32_t ph = 6;
            PROFW(20, 0);
            auto g2 = [&](int u) {
                if (warp == 0 && !(u & 1)) PROF2(2, 16 + (u >> 1));
                mbar_wait(sb + SM_BARS + (B_FULL + sg) * 8, (ph >> sg) & 1);
                ph ^= 1u << sg;
                if (warp == 0 && !(u & 1)) PROF2(1, 16 + (u >> 1));
                const uint32_t o0 = stage_off_rt(sg) >> 4;
                const uint64_t da0 = desc_add(descA0, o0), db0 = desc_add(descB0, o0);
                WG_FENCE();
                #pragma unroll
                for (int kk = 0; kk < 4; kk++) wgmma_ss_n128_tb(acc, da0 + ((kk >> 1) * 512 + (kk & 1) * 128), db0 + ((kk >> 1) * 512 + (kk & 1) * 128), (u | kk) ? 1 : 0);
                WG_COMMIT();
                wg_wait<1>();
                if (warp == 0 && !(u & 1)) PROF2(3, 16 + (u >> 1));
                if (lane < 2 && u > 0 && u + 4 < 28) mbar_arrive_cluster(e_cl + p0 * 8, 1);
                p0 = sg;
                sg = next_st2(sg);
            };
            #pragma unroll
            for (int u = 0; u < 4; u++) { g2(u); store_h(hdst + (32 + 6 * cb) * 2048, hp, u); }
            __syncwarp();
            if (lane == 0) mbar_arrive(sb + SM_BARS + (B_HD + wgi * 2 + 1) * 8);
            #pragma unroll 1
            for (int u = 4; u < 28; u++) g2(u);
            wg_wait<0>();
            PROFW(27, 0);
            mbar_wait(sb + SM_BARS + B_XR * 8, 0);
            const int r0 = wgi * 64 + warp4 * 16 + g;
            const float2 st0 = lds64f(sb + SM_STATS + r0 * 8), st1 = lds64f(sb + SM_STATS + (r0 + 8) * 8);
            const uint32_t m0 = __float_as_uint(st0.x), m1 = __float_as_uint(st1.x);
            const uint32_t xrow0 = sb + SM_XE + r0 * 128 + c * 4;
            const int mi = lane >> 3, lr = lane & 7;
            const uint32_t yaddr = sb + SM_YT + wgi * 16384 + ((mi >> 1) * 8 + lr) * 128 + (((2 * warp4 + (mi & 1)) ^ lr) << 4);
            uint32_t y[8][4], xv[16][2], nv[16][2], bv[16][2];
            #pragma unroll
            for (int t = 0; t < 16; t++) {
                const uint32_t off = (t >> 3) * 16384 + (((t & 7) ^ g) << 4);
                xv[t][0] = lds32(xrow0 + off); xv[t][1] = lds32(xrow0 + 1024 + off);
            }
            #pragma unroll
            for (int t = 0; t < 16; t++) {
                const uint32_t d0 = bsub2(xv[t][0], m0), d1 = bsub2(xv[t][1], m1);
                nv[t][0] = pack_bf(bf_lo(d0) * st0.y, bf_hi(d0) * st0.y); nv[t][1] = pack_bf(bf_lo(d1) * st1.y, bf_hi(d1) * st1.y);
                bv[t][0] = pack_bf(acc[4 * t], acc[4 * t + 1]); bv[t][1] = pack_bf(acc[4 * t + 2], acc[4 * t + 3]);
            }
            mbar_wait(sb + SM_BARS + B_YT * 8, 0);
            PROFW(28, 0);
            #pragma unroll
            for (int t2 = 0; t2 < 8; t2++)
                asm volatile("ldmatrix.sync.aligned.m8n8.x4.trans.shared.b16 {%0,%1,%2,%3}, [%4];"
                    : "=r"(y[t2][0]), "=r"(y[t2][1]), "=r"(y[t2][2]), "=r"(y[t2][3]) : "r"(yaddr + t2 * 2048) : "memory");
            #pragma unroll
            for (int hf = 0; hf < 2; hf++) {
                #pragma unroll
                for (int t = 8 * hf; t < 8 * hf + 8; t++) {
                    const uint32_t off = (t >> 3) * 16384 + (((t & 7) ^ g) << 4);
                    sts32(xrow0 + off, badd2(badd2(xv[t][0], bmul2(nv[t][0], y[t >> 1][2 * (t & 1)])), bv[t][0]));
                    sts32(xrow0 + 1024 + off, badd2(badd2(xv[t][1], bmul2(nv[t][1], y[t >> 1][2 * (t & 1) + 1])), bv[t][1]));
                }
                asm volatile("fence.proxy.async.shared::cta;" ::: "memory");
                __syncwarp();
                if (lane == 0) tma2d_store(&p.tm_out, 128 * cb + 64 * hf, 128 * i + 16 * warp, sb + SM_XE + hf * 16384 + warp * 2048);
            }
            if (lane == 0) {
                asm volatile("cp.async.bulk.commit_group;" ::: "memory");
                asm volatile("cp.async.bulk.wait_group.read 0;" ::: "memory");
                PROFW(29, 0);
            }
        }
    } else {
        asm volatile("setmaxnreg.dec.sync.aligned.u32 104;");
        if (warp == 8) {
            int st = 0; uint32_t eph = 7;
            const int nit = convCTA ? 12 : 16;
            #pragma unroll 1
            for (int it = 0; it < nit; it++) {
                const int pass = it >> 3, sl = it & 7;
                const bool narrow = pass && convCTA;
                const CUtensorMap* tm = narrow ? (rank ? &p.tm_uB : &p.tm_gB) : (rank ? &p.tm_uA : &p.tm_gA);
                mbar_wait(sb + SM_BARS + (B_EMPTY + st) * 8, (eph >> st) & 1);
                eph ^= 1u << st;
                if (it == 1) mbar_wait(sb + SM_BARS + B_XFULL * 8, 0);
                PROF2(0, it);
                if (elect_one()) {
                    mbar_expect_tx(sb + SM_BARS + (B_FULL + st) * 8, 32768);
                    tma3d_mc(sb + SM_RING + st * STAGE_BYTES + rank * 16384, tm, 0, sl * (narrow ? 128 : 64), 14 * cb + 8 * (j & 1) + 4 * pass, sb + SM_BARS + (B_FULL + st) * 8);
                }
                st = (st == 2) ? 0 : st + 1;
            }
            if (!convCTA) {
                st = 3;
                const int f0_lane = blk_f0(2 * lane + rank);
                #pragma unroll 1
                for (int u = 0; u < 28; u++) {
                    const uint32_t bar = sb + SM_BARS + (B_FULL + st) * 8;
                    const int f0 = __shfl_sync(0xffffffffu, f0_lane, u);
                    mbar_wait(sb + SM_BARS + (B_EMPTY + st) * 8, (eph >> st) & 1);
                    eph ^= 1u << st;
                    if ((u & 1) == 0) PROF2(0, 16 + (u >> 1));
                    if (elect_one()) {
                        mbar_expect_tx(bar, 32768);
                        tma3d_mc(sb + stage_off_rt(st) + rank * 8192, &p.tm_w2, 0, f0, 2 * cb, bar);
                    }
                    st = next_st2(st);
                }
                PROF(48);
            }
        } else if (warp < 11) {
            mbar_wait(sb + SM_BARS + (B_XFULL + 1) * 8, 0);
            {
                const int q = lane & 3;
                const int t0 = 32 * (b >> 1) + 8 * q;
                const int ch0 = 256 * (b & 1) + 16 * (warp - 9) + 2 * (lane >> 2);
                const uint32_t* kp = (const uint32_t*)(p.k + (size_t)t0 * DM + ch0);
                const uint32_t* vp = (const uint32_t*)(p.v + (size_t)t0 * DM + ch0);
                __nv_bfloat16* dst0 = g_kvT + (size_t)ch0 * SEQ + (t0 ^ 8);
                #pragma unroll 1
                for (int rnd = 0; rnd < 2; rnd++) {
                    uint32_t kr[4][11], vr[4][8]; uint4 skw[4];
                    #pragma unroll
                    for (int u = 0; u < 4; u++) {
                        const int co = (rnd * 4 + u) * 16;
                        skw[u] = ldg_nc128(p.shift_k + 4 * (ch0 + 2 * co));
                        #pragma unroll
                        for (int r = 0; r < 11; r++) kr[u][r] = (r >= 3 || t0 > 0) ? ldg_nc32(kp + co + (r - 3) * (DM / 2)) : 0u;
                        #pragma unroll
                        for (int r = 0; r < 8; r++) vr[u][r] = ldg_nc32(vp + co + r * (DM / 2));
                    }
                    #pragma unroll
                    for (int u = 0; u < 4; u++) {
                        const uint32_t s0 = __byte_perm(skw[u].x, skw[u].z, 0x5410), s1 = __byte_perm(skw[u].x, skw[u].z, 0x7632);
                        const uint32_t s2 = __byte_perm(skw[u].y, skw[u].w, 0x5410), s3 = __byte_perm(skw[u].y, skw[u].w, 0x7632);
                        #pragma unroll
                        for (int r = 0; r < 8; r++) {
                            uint32_t a = bmul2(kr[u][r], s3);
                            a = badd2(a, bmul2(kr[u][r + 1], s2));
                            a = badd2(a, bmul2(kr[u][r + 2], s1));
                            a = badd2(a, bmul2(kr[u][r + 3], s0));
                            vr[u][r] = bmul2(a, vr[u][r]);
                        }
                        __nv_bfloat16* dst = dst0 + (size_t)((rnd * 4 + u) * 32) * SEQ;
                        *(uint4*)dst = make_uint4(__byte_perm(vr[u][7], vr[u][6], 0x5410), __byte_perm(vr[u][5], vr[u][4], 0x5410),
                                                  __byte_perm(vr[u][3], vr[u][2], 0x5410), __byte_perm(vr[u][1], vr[u][0], 0x5410));
                        *(uint4*)(dst + SEQ) = make_uint4(__byte_perm(vr[u][7], vr[u][6], 0x7632), __byte_perm(vr[u][5], vr[u][4], 0x7632),
                                                          __byte_perm(vr[u][3], vr[u][2], 0x7632), __byte_perm(vr[u][1], vr[u][0], 0x7632));
                    }
                    PROFW(57 + 2 * rnd, 9);
                }
                if (lane == 0) mbar_arrive(sb + SM_BARS + B_KVLD * 8);
            }
            asm volatile("fence.proxy.async.global;" ::: "memory");
            __syncwarp();
            if (lane == 0) {
                flag_add(&g_cnt_kv[0]);
                PROFW(50, 9);
                const int wgi = warp - 9;
                mbar_wait(sb + SM_BARS + (B_HD + wgi * 2) * 8, 0);
                flag_add(&g_flag_h[(i * 2 + 0) * 8]);
                mbar_wait(sb + SM_BARS + (B_HD + wgi * 2 + 1) * 8, 0);
                flag_add(&g_flag_h[(i * 2 + 1) * 8]);
                if (wgi == 1 && !convCTA) {
                    const unsigned ep = lds32(sb + SM_EPOCH);
                    mbar_wait(sb + SM_BARS + B_G1DONE * 8, 0);
                    mbar_expect_tx(sb + SM_BARS + B_XR * 8, 32768);
                    tma3d(sb + SM_XE, &p.tm_xe, 0, 128 * i, 2 * cb, sb + SM_BARS + B_XR * 8);
                    flag_wait(&g_flag_h[(i * 2 + 1) * 8], ep * 16);
                    mbar_arrive(sb + SM_BARS + (B_HRDY + 1) * 8);
                    __nanosleep(3000);
                    flag_wait(&g_cnt_y[cb * 32], ep * 128);
                    PROF(49);
                    asm volatile("fence.proxy.async.global;" ::: "memory");
                    mbar_expect_tx(sb + SM_BARS + B_YT * 8, 32768);
                    tma2d(sb + SM_YT, &p.tm_yT, 128 * i, 128 * cb, sb + SM_BARS + B_YT * 8);
                    tma2d(sb + SM_YT + 16384, &p.tm_yT, 128 * i + 64, 128 * cb, sb + SM_BARS + B_YT * 8);
                }
            }
        } else {
            if (lane == 0) {
                l2_prefetch(p.wg + (size_t)b * (FF * DM / NCTA), FF * DM / NCTA * 2);
                l2_prefetch(p.wu + (size_t)b * (FF * DM / NCTA), FF * DM / NCTA * 2);
                const unsigned ep = g_launch[b] + 1;
                g_launch[b] = ep;
                sts32(sb + SM_EPOCH, ep);
                tmap_prefetch(rank ? &p.tm_uA : &p.tm_gA);
                tmap_prefetch(rank ? &p.tm_uB : &p.tm_gB);
                tmap_prefetch(&p.tm_w2); tmap_prefetch(&p.tm_yT); tmap_prefetch(&p.tm_out); tmap_prefetch(&p.tm_xe);
                mbar_wait(sb + SM_BARS + B_KVLD * 8, 0);
                l2_prefetch(p.ssm_k + (size_t)(4 * b) * SEQ, 4 * SEQ * 2);
                l2_prefetch(p.wd + (size_t)b * (FF * DM / NCTA), FF * DM / NCTA * 2);
                mbar_wait(sb + SM_BARS + (B_HD + 0) * 8, 0);
                if (convCTA) {
                    flag_wait(&g_cnt_kv[0], ep * 256);
                    asm volatile("fence.proxy.async.global;" ::: "memory");
                    PROF(53);
                    mbar_wait(sb + SM_BARS + B_XFREE * 8, 0);
                    PROF(54);
                    mbar_expect_tx(sb + SM_BARS + B_CONV * 8, 65536);
                    bulk_g2s(sb + SM_CVX, g_kvT + (size_t)(8 * cidx) * SEQ, 32768, sb + SM_BARS + B_CONV * 8);
                    bulk_g2s(sb + SM_CVH, p.ssm_k + (size_t)(8 * cidx) * SEQ, 32768, sb + SM_BARS + B_CONV * 8);
                } else {
                    flag_wait(&g_flag_h[(i * 2 + 0) * 8], ep * 16);
                }
            }
            __syncwarp();
            if (!convCTA) {
                asm volatile("fence.proxy.async.global;" ::: "memory");
                int st = 3; uint32_t eph = 1;
                const uint8_t* hsrc = (const uint8_t*)g_h + (size_t)i * 56 * 8192;
                #pragma unroll 1
                for (int u = 0; u < 28; u++) {
                    mbar_wait(sb + SM_BARS + (B_EMPTY + st) * 8, (eph >> st) & 1);
                    eph ^= 1u << st;
                    if (u == 16) {
                        mbar_wait(sb + SM_BARS + (B_HRDY + 1) * 8, 0);
                        asm volatile("fence.proxy.async.global;" ::: "memory");
                    }
                    if (elect_one()) bulk_g2s(sb + stage_off_rt(st) + 16384, hsrc + u * 16384, 16384, sb + SM_BARS + (B_FULL + st) * 8);
                    st = next_st2(st);
                }
            }
        }
    }
}

typedef CUresult (*EncodeFn)(CUtensorMap*, CUtensorMapDataType, cuuint32_t, void*, const cuuint64_t*, const cuuint64_t*,
                             const cuuint32_t*, const cuuint32_t*, CUtensorMapInterleave, CUtensorMapSwizzle,
                             CUtensorMapL2promotion, CUtensorMapFloatOOBfill);

void encode(EncodeFn fn, CUtensorMap* tm, const void* base, int rank, const cuuint64_t* dims, const cuuint64_t* strides,
            const cuuint32_t* box, CUtensorMapSwizzle swz) {
    cuuint32_t es[5] = {1, 1, 1, 1, 1};
    fn(tm, CU_TENSOR_MAP_DATA_TYPE_BFLOAT16, rank, (void*)base, dims, strides, box, es, CU_TENSOR_MAP_INTERLEAVE_NONE, swz,
       CU_TENSOR_MAP_L2_PROMOTION_L2_128B, CU_TENSOR_MAP_FLOAT_OOB_FILL_NONE);
}

}

extern "C" void kernel_launch(void* const* d_in, const int* in_sizes, int n_in, void* d_out, int out_size) {
    (void)in_sizes; (void)n_in; (void)out_size;
    static EncodeFn enc = nullptr;
    static void* yT_ptr = nullptr;
    if (!enc) {
        void* fn = nullptr; cudaDriverEntryPointQueryResult qr;
        cudaGetDriverEntryPoint("cuTensorMapEncodeTiled", &fn, cudaEnableDefault, &qr);
        enc = (EncodeFn)fn;
        cudaGetSymbolAddress(&yT_ptr, g_yT);
        cudaFuncSetAttribute(fused_kernel, cudaFuncAttributeMaxDynamicSharedMemorySize, SM_TOTAL);
    }
    Params p;
    p.q = (const __nv_bfloat16*)d_in[0]; p.k = (const __nv_bfloat16*)d_in[1]; p.v = (const __nv_bfloat16*)d_in[2];
    p.shift_k = (const __nv_bfloat16*)d_in[3]; p.ssm_k = (const __nv_bfloat16*)d_in[4]; p.ssm_D = (const __nv_bfloat16*)d_in[5];
    p.wg = (const __nv_bfloat16*)d_in[7]; p.wu = (const __nv_bfloat16*)d_in[8]; p.wd = (const __nv_bfloat16*)d_in[9];
    {
        cuuint64_t dims[2] = {DM, SEQ}; cuuint64_t str[1] = {DM * 2};
        cuuint64_t dims3[3] = {64, SEQ, DM / 64}; cuuint64_t str3[2] = {DM * 2, 128};
        cuuint32_t box[3] = {64, 64, 8}, boxe[3] = {64, 128, 2};
        encode(enc, &p.tm_x, p.q, 3, dims3, str3, box, CU_TENSOR_MAP_SWIZZLE_128B);
        encode(enc, &p.tm_xe, p.q, 3, dims3, str3, boxe, CU_TENSOR_MAP_SWIZZLE_128B);
        cuuint32_t box2[2] = {64, 16};
        encode(enc, &p.tm_out, d_out, 2, dims, str, box2, CU_TENSOR_MAP_SWIZZLE_128B);
    }
    {
        cuuint64_t dims[3] = {32, DM, FF / 32}; cuuint64_t str[2] = {FF * 2, 64};
        cuuint32_t boxA[3] = {32, 64, 4}, boxB[3] = {32, 128, 2};
        encode(enc, &p.tm_gA, p.wg, 3, dims, str, boxA, CU_TENSOR_MAP_SWIZZLE_64B);
        encode(enc, &p.tm_gB, p.wg, 3, dims, str, boxB, CU_TENSOR_MAP_SWIZZLE_64B);
        encode(enc, &p.tm_uA, p.wu, 3, dims, str, boxA, CU_TENSOR_MAP_SWIZZLE_64B);
        encode(enc, &p.tm_uB, p.wu, 3, dims, str, boxB, CU_TENSOR_MAP_SWIZZLE_64B);
    }
    {
        cuuint64_t dims[3] = {64, FF, DM / 64}; cuuint64_t str[2] = {DM * 2, 128};
        cuuint32_t box[3] = {64, 32, 2};
        encode(enc, &p.tm_w2, p.wd, 3, dims, str, box, CU_TENSOR_MAP_SWIZZLE_128B);
    }
    {
        cuuint64_t dims[2] = {SEQ, DM}; cuuint64_t str[1] = {SEQ * 2};
        cuuint32_t box[2] = {64, 128};
        encode(enc, &p.tm_yT, yT_ptr, 2, dims, str, box, CU_TENSOR_MAP_SWIZZLE_128B);
    }
    fused_kernel<<<NCTA, NTHREADS, SM_TOTAL>>>(p);
}
```

```cpp
#include <cuda_runtime.h>
#include <cuda_bf16.h>
#include <cuda.h>
#include <stdint.h>

namespace {

constexpr int SEQ = 2048, DM = 512, FF = 1792;
constexpr int NCTA = 128;
constexpr int NTHREADS = 384;
constexpr int STAGE_BYTES = 32768;
#define KV_STAGGER 300
#define KV_GAP 150

constexpr uint32_t SM_X = 0;
constexpr uint32_t SM_RING = 131072;
constexpr uint32_t SM_MISC = SM_RING + 3 * STAGE_BYTES;
constexpr uint32_t SM_BARS = SM_MISC;
constexpr uint32_t SM_EPOCH = SM_MISC + 248;
constexpr uint32_t SM_STATS = SM_MISC + 256;
constexpr uint32_t SM_TOTAL = SM_STATS + 1024;
static_assert(SM_TOTAL <= 232448, "smem");
constexpr uint32_t SM_CVX = 0;
constexpr uint32_t SM_CVH = 65536;
constexpr uint32_t SM_YT = 32768;
constexpr uint32_t SM_XE = 98304;

constexpr int B_FULL = 0, B_EMPTY = 5, B_XFULL = 10, B_CONV = 14, B_YT = 15, B_XR = 16, B_G1DONE = 17, B_HD = 18, B_HRDY = 22,
              B_XFREE = 24, B_YST = 25, B_KVLD = 26, B_LN = 27, B_COUNT = 28;
static_assert(B_COUNT * 8 <= 248, "barrier space");

__device__ __align__(128) uint32_t g_h[16 * 56 * 2048];
__device__ __align__(128) __nv_bfloat16 g_kvT[DM * SEQ];
__device__ __align__(128) __nv_bfloat16 g_yT[DM * SEQ];
__device__ unsigned g_launch[NCTA];
__device__ unsigned g_cnt_kv[32];
__device__ unsigned g_cnt_y[4 * 32];
__device__ unsigned g_flag_h[16 * 2 * 8];

#define PROF(idx)
#define PROF2(a, idx)
#define PROFW(idx, w)

struct Params {
    CUtensorMap tm_x, tm_gA, tm_gB, tm_uA, tm_uB, tm_w2, tm_yT, tm_out, tm_xe;
    const __nv_bfloat16 *q, *k, *v, *shift_k, *ssm_k, *ssm_D, *wg, *wu, *wd;
};

__device__ __forceinline__ void wgmma_rs_n32(float (&d)[16], uint32_t a0, uint32_t a1, uint32_t a2, uint32_t a3, uint64_t db, int sc) {
  asm volatile("{\n.reg .pred p;\nsetp.ne.b32 p, %21, 0;\n"
    "wgmma.mma_async.sync.aligned.m64n32k16.f32.bf16.bf16 {%0,%1,%2,%3,%4,%5,%6,%7,%8,%9,%10,%11,%12,%13,%14,%15}, {%16,%17,%18,%19}, %20, p, 1, 1, 0;\n}\n"
    : "+f"(d[0]),"+f"(d[1]),"+f"(d[2]),"+f"(d[3]),"+f"(d[4]),"+f"(d[5]),"+f"(d[6]),"+f"(d[7]),"+f"(d[8]),"+f"(d[9]),"+f"(d[10]),"+f"(d[11]),"+f"(d[12]),"+f"(d[13]),"+f"(d[14]),"+f"(d[15])
    : "r"(a0),"r"(a1),"r"(a2),"r"(a3),"l"(db),"r"(sc));
}
__device__ __forceinline__ void wgmma_rs_n128_tb(float (&d)[64], uint32_t a0, uint32_t a1, uint32_t a2, uint32_t a3, uint64_t db, int sc) {
  asm volatile("{\n.reg .pred p;\nsetp.ne.b32 p, %69, 0;\n"
    "wgmma.mma_async.sync.aligned.m64n128k16.f32.bf16.bf16 {%0,%1,%2,%3,%4,%5,%6,%7,%8,%9,%10,%11,%12,%13,%14,%15,%16,%17,%18,%19,%20,%21,%22,%23,%24,%25,%26,%27,%28,%29,%30,%31,%32,%33,%34,%35,%36,%37,%38,%39,%40,%41,%42,%43,%44,%45,%46,%47,%48,%49,%50,%51,%52,%53,%54,%55,%56,%57,%58,%59,%60,%61,%62,%63}, {%64,%65,%66,%67}, %68, p, 1, 1, 1;\n}\n"
    : "+f"(d[0]),"+f"(d[1]),"+f"(d[2]),"+f"(d[3]),"+f"(d[4]),"+f"(d[5]),"+f"(d[6]),"+f"(d[7]),"+f"(d[8]),"+f"(d[9]),"+f"(d[10]),"+f"(d[11]),"+f"(d[12]),"+f"(d[13]),"+f"(d[14]),"+f"(d[15]),"+f"(d[16]),"+f"(d[17]),"+f"(d[18]),"+f"(d[19]),"+f"(d[20]),"+f"(d[21]),"+f"(d[22]),"+f"(d[23]),"+f"(d[24]),"+f"(d[25]),"+f"(d[26]),"+f"(d[27]),"+f"(d[28]),"+f"(d[29]),"+f"(d[30]),"+f"(d[31]),"+f"(d[32]),"+f"(d[33]),"+f"(d[34]),"+f"(d[35]),"+f"(d[36]),"+f"(d[37]),"+f"(d[38]),"+f"(d[39]),"+f"(d[40]),"+f"(d[41]),"+f"(d[42]),"+f"(d[43]),"+f"(d[44]),"+f"(d[45]),"+f"(d[46]),"+f"(d[47]),"+f"(d[48]),"+f"(d[49]),"+f"(d[50]),"+f"(d[51]),"+f"(d[52]),"+f"(d[53]),"+f"(d[54]),"+f"(d[55]),"+f"(d[56]),"+f"(d[57]),"+f"(d[58]),"+f"(d[59]),"+f"(d[60]),"+f"(d[61]),"+f"(d[62]),"+f"(d[63])
    : "r"(a0),"r"(a1),"r"(a2),"r"(a3),"l"(db),"r"(sc));
}
__device__ __forceinline__ void wgmma_ss_n256_tb(float (&d)[128], uint64_t da, uint64_t db, int sc) {
  asm volatile("{\n.reg .pred p;\nsetp.ne.b32 p, %130, 0;\n"
    "wgmma.mma_async.sync.aligned.m64n256k16.f32.bf16.bf16 {%0,%1,%2,%3,%4,%5,%6,%7,%8,%9,%10,%11,%12,%13,%14,%15,%16,%17,%18,%19,%20,%21,%22,%23,%24,%25,%26,%27,%28,%29,%30,%31,%32,%33,%34,%35,%36,%37,%38,%39,%40,%41,%42,%43,%44,%45,%46,%47,%48,%49,%50,%51,%52,%53,%54,%55,%56,%57,%58,%59,%60,%61,%62,%63,%64,%65,%66,%67,%68,%69,%70,%71,%72,%73,%74,%75,%76,%77,%78,%79,%80,%81,%82,%83,%84,%85,%86,%87,%88,%89,%90,%91,%92,%93,%94,%95,%96,%97,%98,%99,%100,%101,%102,%103,%104,%105,%106,%107,%108,%109,%110,%111,%112,%113,%114,%115,%116,%117,%118,%119,%120,%121,%122,%123,%124,%125,%126,%127}, %128, %129, p, 1, 1, 0, 1;\n}\n"
    : "+f"(d[0]),"+f"(d[1]),"+f"(d[2]),"+f"(d[3]),"+f"(d[4]),"+f"(d[5]),"+f"(d[6]),"+f"(d[7]),"+f"(d[8]),"+f"(d[9]),"+f"(d[10]),"+f"(d[11]),"+f"(d[12]),"+f"(d[13]),"+f"(d[14]),"+f"(d[15]),"+f"(d[16]),"+f"(d[17]),"+f"(d[18]),"+f"(d[19]),"+f"(d[20]),"+f"(d[21]),"+f"(d[22]),"+f"(d[23]),"+f"(d[24]),"+f"(d[25]),"+f"(d[26]),"+f"(d[27]),"+f"(d[28]),"+f"(d[29]),"+f"(d[30]),"+f"(d[31]),"+f"(d[32]),"+f"(d[33]),"+f"(d[34]),"+f"(d[35]),"+f"(d[36]),"+f"(d[37]),"+f"(d[38]),"+f"(d[39]),"+f"(d[40]),"+f"(d[41]),"+f"(d[42]),"+f"(d[43]),"+f"(d[44]),"+f"(d[45]),"+f"(d[46]),"+f"(d[47]),"+f"(d[48]),"+f"(d[49]),"+f"(d[50]),"+f"(d[51]),"+f"(d[52]),"+f"(d[53]),"+f"(d[54]),"+f"(d[55]),"+f"(d[56]),"+f"(d[57]),"+f"(d[58]),"+f"(d[59]),"+f"(d[60]),"+f"(d[61]),"+f"(d[62]),"+f"(d[63]),"+f"(d[64]),"+f"(d[65]),"+f"(d[66]),"+f"(d[67]),"+f"(d[68]),"+f"(d[69]),"+f"(d[70]),"+f"(d[71]),"+f"(d[72]),"+f"(d[73]),"+f"(d[74]),"+f"(d[75]),"+f"(d[76]),"+f"(d[77]),"+f"(d[78]),"+f"(d[79]),"+f"(d[80]),"+f"(d[81]),"+f"(d[82]),"+f"(d[83]),"+f"(d[84]),"+f"(d[85]),"+f"(d[86]),"+f"(d[87]),"+f"(d[88]),"+f"(d[89]),"+f"(d[90]),"+f"(d[91]),"+f"(d[92]),"+f"(d[93]),"+f"(d[94]),"+f"(d[95]),"+f"(d[96]),"+f"(d[97]),"+f"(d[98]),"+f"(d[99]),"+f"(d[100]),"+f"(d[101]),"+f"(d[102]),"+f"(d[103]),"+f"(d[104]),"+f"(d[105]),"+f"(d[106]),"+f"(d[107]),"+f"(d[108]),"+f"(d[109]),"+f"(d[110]),"+f"(d[111]),"+f"(d[112]),"+f"(d[113]),"+f"(d[114]),"+f"(d[115]),"+f"(d[116]),"+f"(d[117]),"+f"(d[118]),"+f"(d[119]),"+f"(d[120]),"+f"(d[121]),"+f"(d[122]),"+f"(d[123]),"+f"(d[124]),"+f"(d[125]),"+f"(d[126]),"+f"(d[127])
    : "l"(da),"l"(db),"r"(sc));
}
__device__ __forceinline__ void wgmma_ss_n192_tb(float (&d)[96], uint64_t da, uint64_t db, int sc) {
  asm volatile("{\n.reg .pred p;\nsetp.ne.b32 p, %98, 0;\n"
    "wgmma.mma_async.sync.aligned.m64n192k16.f32.bf16.bf16 {%0,%1,%2,%3,%4,%5,%6,%7,%8,%9,%10,%11,%12,%13,%14,%15,%16,%17,%18,%19,%20,%21,%22,%23,%24,%25,%26,%27,%28,%29,%30,%31,%32,%33,%34,%35,%36,%37,%38,%39,%40,%41,%42,%43,%44,%45,%46,%47,%48,%49,%50,%51,%52,%53,%54,%55,%56,%57,%58,%59,%60,%61,%62,%63,%64,%65,%66,%67,%68,%69,%70,%71,%72,%73,%74,%75,%76,%77,%78,%79,%80,%81,%82,%83,%84,%85,%86,%87,%88,%89,%90,%91,%92,%93,%94,%95}, %96, %97, p, 1, 1, 0, 1;\n}\n"
    : "+f"(d[0]),"+f"(d[1]),"+f"(d[2]),"+f"(d[3]),"+f"(d[4]),"+f"(d[5]),"+f"(d[6]),"+f"(d[7]),"+f"(d[8]),"+f"(d[9]),"+f"(d[10]),"+f"(d[11]),"+f"(d[12]),"+f"(d[13]),"+f"(d[14]),"+f"(d[15]),"+f"(d[16]),"+f"(d[17]),"+f"(d[18]),"+f"(d[19]),"+f"(d[20]),"+f"(d[21]),"+f"(d[22]),"+f"(d[23]),"+f"(d[24]),"+f"(d[25]),"+f"(d[26]),"+f"(d[27]),"+f"(d[28]),"+f"(d[29]),"+f"(d[30]),"+f"(d[31]),"+f"(d[32]),"+f"(d[33]),"+f"(d[34]),"+f"(d[35]),"+f"(d[36]),"+f"(d[37]),"+f"(d[38]),"+f"(d[39]),"+f"(d[40]),"+f"(d[41]),"+f"(d[42]),"+f"(d[43]),"+f"(d[44]),"+f"(d[45]),"+f"(d[46]),"+f"(d[47]),"+f"(d[48]),"+f"(d[49]),"+f"(d[50]),"+f"(d[51]),"+f"(d[52]),"+f"(d[53]),"+f"(d[54]),"+f"(d[55]),"+f"(d[56]),"+f"(d[57]),"+f"(d[58]),"+f"(d[59]),"+f"(d[60]),"+f"(d[61]),"+f"(d[62]),"+f"(d[63]),"+f"(d[64]),"+f"(d[65]),"+f"(d[66]),"+f"(d[67]),"+f"(d[68]),"+f"(d[69]),"+f"(d[70]),"+f"(d[71]),"+f"(d[72]),"+f"(d[73]),"+f"(d[74]),"+f"(d[75]),"+f"(d[76]),"+f"(d[77]),"+f"(d[78]),"+f"(d[79]),"+f"(d[80]),"+f"(d[81]),"+f"(d[82]),"+f"(d[83]),"+f"(d[84]),"+f"(d[85]),"+f"(d[86]),"+f"(d[87]),"+f"(d[88]),"+f"(d[89]),"+f"(d[90]),"+f"(d[91]),"+f"(d[92]),"+f"(d[93]),"+f"(d[94]),"+f"(d[95])
    : "l"(da),"l"(db),"r"(sc));
}

__device__ __forceinline__ uint32_t smem_u32(const void* p) { return (uint32_t)__cvta_generic_to_shared(p); }
__device__ __forceinline__ void mbar_init(uint32_t bar, uint32_t cnt) { asm volatile("mbarrier.init.shared::cta.b64 [%0], %1;" :: "r"(bar), "r"(cnt)); }
__device__ __forceinline__ void mbar_expect_tx(uint32_t bar, uint32_t bytes) { asm volatile("mbarrier.arrive.expect_tx.shared::cta.b64 _, [%0], %1;" :: "r"(bar), "r"(bytes) : "memory"); }
__device__ __forceinline__ void mbar_arrive(uint32_t bar) { asm volatile("mbarrier.arrive.shared::cta.b64 _, [%0];" :: "r"(bar) : "memory"); }
__device__ __forceinline__ void mbar_arrive_cluster(uint32_t cbar, uint32_t cnt) { asm volatile("mbarrier.arrive.shared::cluster.b64 _, [%0], %1;" :: "r"(cbar), "r"(cnt) : "memory"); }
__device__ __forceinline__ uint32_t mapa(uint32_t a, uint32_t rank) { uint32_t r; asm volatile("mapa.shared::cluster.u32 %0, %1, %2;" : "=r"(r) : "r"(a), "r"(rank)); return r; }
__device__ __forceinline__ void mbar_wait(uint32_t bar, uint32_t parity) {
    uint32_t ok; uint32_t n = 0;
    do {
        asm volatile("{\n.reg .pred p;\nmbarrier.try_wait.parity.shared::cta.b64 p, [%1], %2;\nselp.u32 %0, 1, 0, p;\n}" : "=r"(ok) : "r"(bar), "r"(parity) : "memory");
    } while (!ok && ++n < (1u << 17));
}
__device__ __forceinline__ void pace_wait(uint32_t a, uint32_t target) {
    uint32_t v, n = 0;
    do {
        asm volatile("ld.volatile.shared.u32 %0, [%1];" : "=r"(v) : "r"(a) : "memory");
        if (v < target) __nanosleep(150);
    } while (v < target && ++n < (1u << 14));
}
__device__ __forceinline__ void flag_wait(const unsigned* p, unsigned target) {
    unsigned v; uint32_t n = 0;
    while (true) {
        asm volatile("ld.acquire.gpu.global.u32 %0, [%1];" : "=r"(v) : "l"(p) : "memory");
        if ((int)(v - target) >= 0 || ++n >= (1u << 17)) break;
        __nanosleep(40);
    }
}
__device__ __forceinline__ void flag_add(unsigned* p) {
    asm volatile("fence.acq_rel.gpu;\nred.relaxed.gpu.global.add.u32 [%0], 1;" :: "l"(p) : "memory");
}
__device__ __forceinline__ uint64_t make_desc(uint32_t addr, uint32_t lbo, uint32_t sbo, uint32_t swz) {
    return (uint64_t)((addr & 0x3FFFF) >> 4) | ((uint64_t)((lbo & 0x3FFFF) >> 4) << 16) | ((uint64_t)((sbo & 0x3FFFF) >> 4) << 32) | ((uint64_t)swz << 62);
}
__device__ __forceinline__ uint64_t desc_add(uint64_t d, uint32_t off16) {
    return (d & 0xFFFFFFFF00000000ull) | (uint64_t)((uint32_t)d + off16);
}
__device__ __forceinline__ void tma2d(uint32_t dst, const CUtensorMap* tm, int c0, int c1, uint32_t bar) {
    asm volatile("cp.async.bulk.tensor.2d.shared::cluster.global.mbarrier::complete_tx::bytes [%0], [%1, {%3, %4}], [%2];"
        :: "r"(dst), "l"((uint64_t)tm), "r"(bar), "r"(c0), "r"(c1) : "memory");
}
__device__ __forceinline__ void tma3d(uint32_t dst, const CUtensorMap* tm, int c0, int c1, int c2, uint32_t bar) {
    asm volatile("cp.async.bulk.tensor.3d.shared::cluster.global.mbarrier::complete_tx::bytes [%0], [%1, {%3, %4, %5}], [%2];"
        :: "r"(dst), "l"((uint64_t)tm), "r"(bar), "r"(c0), "r"(c1), "r"(c2) : "memory");
}
__device__ __forceinline__ void tma3d_mc(uint32_t dst, const CUtensorMap* tm, int c0, int c1, int c2, uint32_t bar) {
    asm volatile("cp.async.bulk.tensor.3d.shared::cluster.global.mbarrier::complete_tx::bytes.multicast::cluster [%0], [%1, {%3, %4, %5}], [%2], %6;"
        :: "r"(dst), "l"((uint64_t)tm), "r"(bar), "r"(c0), "r"(c1), "r"(c2), "h"((uint16_t)3) : "memory");
}
__device__ __forceinline__ void bulk_g2s(uint32_t dst, const void* src, uint32_t bytes, uint32_t bar) {
    asm volatile("cp.async.bulk.shared::cluster.global.mbarrier::complete_tx::bytes [%0], [%1], %2, [%3];"
        :: "r"(dst), "l"(src), "r"(bytes), "r"(bar) : "memory");
}
__device__ __forceinline__ void bulk_s2g(void* dst, uint32_t src, uint32_t bytes) {
    asm volatile("cp.async.bulk.global.shared::cta.bulk_group [%0], [%1], %2;" :: "l"(dst), "r"(src), "r"(bytes) : "memory");
}
__device__ __forceinline__ void tma2d_store(const CUtensorMap* tm, int c0, int c1, uint32_t src) {
    asm volatile("cp.async.bulk.tensor.2d.global.shared::cta.bulk_group [%0, {%2, %3}], [%1];"
        :: "l"((uint64_t)tm), "r"(src), "r"(c0), "r"(c1) : "memory");
}
__device__ __forceinline__ void l2_prefetch(const void* p, uint32_t bytes) {
    asm volatile("cp.async.bulk.prefetch.L2.global [%0], %1;" :: "l"(p), "r"(bytes) : "memory");
}
__device__ __forceinline__ void tmap_prefetch(const CUtensorMap* tm) { asm volatile("prefetch.tensormap [%0];" :: "l"((uint64_t)tm) : "memory"); }
__device__ __forceinline__ uint32_t lds32(uint32_t a) { uint32_t v; asm volatile("ld.shared.u32 %0, [%1];" : "=r"(v) : "r"(a)); return v; }
__device__ __forceinline__ uint2 lds64(uint32_t a) { uint2 v; asm volatile("ld.shared.v2.u32 {%0,%1}, [%2];" : "=r"(v.x), "=r"(v.y) : "r"(a)); return v; }
__device__ __forceinline__ uint4 lds128(uint32_t a) { uint4 v; asm volatile("ld.shared.v4.u32 {%0,%1,%2,%3}, [%4];" : "=r"(v.x), "=r"(v.y), "=r"(v.z), "=r"(v.w) : "r"(a)); return v; }
__device__ __forceinline__ float2 lds64f(uint32_t a) { float2 v; asm volatile("ld.shared.v2.f32 {%0,%1}, [%2];" : "=f"(v.x), "=f"(v.y) : "r"(a)); return v; }
__device__ __forceinline__ void sts32(uint32_t a, uint32_t v) { asm volatile("st.shared.u32 [%0], %1;" :: "r"(a), "r"(v) : "memory"); }
__device__ __forceinline__ void sts128(uint32_t a, uint4 v) { asm volatile("st.shared.v4.u32 [%0], {%1,%2,%3,%4};" :: "r"(a), "r"(v.x), "r"(v.y), "r"(v.z), "r"(v.w) : "memory"); }
__device__ __forceinline__ uint4 ldg_cg128(const void* p) { uint4 v; asm volatile("ld.global.cg.v4.u32 {%0,%1,%2,%3}, [%4];" : "=r"(v.x), "=r"(v.y), "=r"(v.z), "=r"(v.w) : "l"(p)); return v; }
__device__ __forceinline__ uint4 ldg_nc128(const void* p) { uint4 v; asm volatile("ld.global.nc.L1::no_allocate.v4.u32 {%0,%1,%2,%3}, [%4];" : "=r"(v.x), "=r"(v.y), "=r"(v.z), "=r"(v.w) : "l"(p)); return v; }
__device__ __forceinline__ uint32_t ldg_nc32(const void* p) { uint32_t v; asm volatile("ld.global.nc.u32 %0, [%1];" : "=r"(v) : "l"(p)); return v; }
__device__ __forceinline__ uint2 ldg_nc64(const void* p) { uint2 v; asm volatile("ld.global.nc.L1::no_allocate.v2.u32 {%0,%1}, [%2];" : "=r"(v.x), "=r"(v.y) : "l"(p)); return v; }
#define WG_FENCE() asm volatile("wgmma.fence.sync.aligned;\n" ::: "memory")
#define WG_COMMIT() asm volatile("wgmma.commit_group.sync.aligned;\n" ::: "memory")
template<int N> __device__ __forceinline__ void wg_wait() { asm volatile("wgmma.wait_group.sync.aligned %0;\n" :: "n"(N) : "memory"); }
__device__ __forceinline__ bool elect_one() {
    uint32_t pr;
    asm volatile("{\n.reg .pred p;\nelect.sync _|p, 0xffffffff;\nselp.u32 %0, 1, 0, p;\n}" : "=r"(pr));
    return pr != 0;
}
__device__ __forceinline__ void named_bar(int id, int n) { asm volatile("bar.sync %0, %1;" :: "r"(id), "r"(n) : "memory"); }

__device__ __forceinline__ float bf_lo(uint32_t u) { return __uint_as_float(u << 16); }
__device__ __forceinline__ float bf_hi(uint32_t u) { return __uint_as_float(u & 0xFFFF0000u); }
__device__ __forceinline__ uint32_t pack_bf(float lo, float hi) { uint32_t r; asm("cvt.rn.bf16x2.f32 %0, %1, %2;" : "=r"(r) : "f"(hi), "f"(lo)); return r; }
__device__ __forceinline__ float bf_round(float x) { return __bfloat162float(__float2bfloat16_rn(x)); }
__device__ __forceinline__ uint32_t bmul2(uint32_t a, uint32_t b) { uint32_t r; asm("mul.rn.bf16x2 %0, %1, %2;" : "=r"(r) : "r"(a), "r"(b)); return r; }
__device__ __forceinline__ uint32_t badd2(uint32_t a, uint32_t b) { uint32_t r; asm("add.rn.bf16x2 %0, %1, %2;" : "=r"(r) : "r"(a), "r"(b)); return r; }
__device__ __forceinline__ uint32_t bsub2(uint32_t a, uint32_t b) { uint32_t r; asm("sub.rn.bf16x2 %0, %1, %2;" : "=r"(r) : "r"(a), "r"(b)); return r; }
__device__ __forceinline__ void mma16816(float (&d)[4], uint32_t a0, uint32_t a1, uint32_t a2, uint32_t a3, uint2 b) {
    asm volatile("mma.sync.aligned.m16n8k16.row.col.f32.bf16.bf16.f32 {%0,%1,%2,%3}, {%4,%5,%6,%7}, {%8,%9}, {%0,%1,%2,%3};\n"
        : "+f"(d[0]), "+f"(d[1]), "+f"(d[2]), "+f"(d[3]) : "r"(a0), "r"(a1), "r"(a2), "r"(a3), "r"(b.x), "r"(b.y));
}

template<int HS> __device__ __forceinline__ void xreduce(float (&v)[8], int lane) {
    const int up = lane & HS;
    #pragma unroll
    for (int e = 0; e < HS; e++) {
        float keep, send;
        asm("{\n.reg .pred p;\nsetp.ne.b32 p, %4, 0;\nselp.f32 %0, %3, %2, p;\nselp.f32 %1, %2, %3, p;\n}"
            : "=f"(keep), "=f"(send) : "f"(v[e]), "f"(v[e + HS]), "r"(up));
        v[e] = keep + __shfl_xor_sync(0xffffffffu, send, HS);
    }
}

__device__ __forceinline__ int blk_f0(int s) {
    if (s < 32) return 32 * (14 * (s >> 3) + 8 * ((s >> 2) & 1) + (s & 3));
    const int s2 = s - 32, c6 = (s2 * 11) >> 6, t = s2 - 6 * c6;
    return 32 * (14 * c6 + (t < 4 ? 4 + t : 8 + t));
}
__device__ __forceinline__ int next_st2(int s) { return (0x14023 >> (4 * s)) & 7; }
__device__ __forceinline__ uint32_t stage_off_rt(int s) { return s < 3 ? SM_RING + s * STAGE_BYTES : (uint32_t)(s - 3) * 65536; }

__device__ __forceinline__ void store_h(uint32_t* dst, const uint32_t (&hp)[32], int q) {
    #pragma unroll
    for (int kk = 0; kk < 2; kk++) {
        uint32_t* d2 = dst + q * 2048 + kk * 512;
        d2[0] = hp[8 * q + 4 * kk]; d2[64] = hp[8 * q + 4 * kk + 1]; d2[32] = hp[8 * q + 4 * kk + 2]; d2[96] = hp[8 * q + 4 * kk + 3];
    }
}
template<int NB, bool passA>
__device__ __forceinline__ void gemm1_pass(uint32_t sb, int wgi, int warp4, int lane, int& st, uint32_t& fph, uint32_t e_cl,
                                           uint32_t (&hp)[32], uint32_t* prev_dst, bool convCTA) {
    constexpr bool narrow = (NB == 2);
    float acc[NB * 32];
    const uint64_t descA0 = make_desc(sb + SM_X + wgi * 65536, 16, 1024, 1);
    const uint64_t descB0 = make_desc(sb + SM_RING, narrow ? 8192 : 4096, 512, 2);
    int prev = 0;
    auto group = [&](int sl) {
        if (warp4 == 0 && wgi == 0) PROF2(2, sl + (passA ? 0 : 8));
        mbar_wait(sb + SM_BARS + (B_FULL + st) * 8, (fph >> st) & 1);
        fph ^= 1u << st;
        if (sl == 0 && warp4 == 0) PROF(2 + wgi * 8 + (passA ? 0 : 3));
        if (warp4 == 0 && wgi == 0) PROF2(1, sl + (passA ? 0 : 8));
        const uint64_t da = desc_add(descA0, sl * (narrow ? 1024 : 512)), db = desc_add(descB0, st * 2048);
        WG_FENCE();
        #pragma unroll
        for (int kk = 0; kk < (narrow ? 8 : 4); kk++) {
            int sc = (sl | kk) ? 1 : 0;
            if constexpr (!narrow) wgmma_ss_n256_tb(acc, da + kk * 2, db + kk * 64, sc);
            else wgmma_ss_n128_tb(acc, da + ((kk >> 2) * 512 + (kk & 3) * 2), db + kk * 64, sc);
        }
        WG_COMMIT();
        wg_wait<1>();
        if (warp4 == 0 && wgi == 0) PROF2(3, sl + (passA ? 0 : 8));
        if (lane < 2 && sl && (!narrow || sl == 1)) mbar_arrive_cluster(e_cl + prev * 8, 1);
        if (narrow && sl == 2 && lane == 0) mbar_arrive(sb + SM_BARS + B_XFREE * 8);
        if (!passA && !narrow && sl == 4 && lane < 4) mbar_arrive_cluster(e_cl + (3 + (lane >> 1)) * 8, 1);
        prev = st;
        st = (st == 2) ? 0 : st + 1;
    };
    if constexpr (passA) {
        #pragma unroll 1
        for (int sl = 0; sl < 8; sl++) group(sl);
    } else {
        #pragma unroll
        for (int sl = 0; sl < 4; sl++) { group(sl); store_h(prev_dst, hp, sl); }
        __syncwarp();
        if (lane == 0) mbar_arrive(sb + SM_BARS + (B_HD + wgi * 2) * 8);
        if constexpr (!narrow) {
            #pragma unroll 1
            for (int sl = 4; sl < 8; sl++) group(sl);
        }
    }
    wg_wait<0>();
    if (lane < 2 && (passA || !convCTA)) mbar_arrive_cluster(e_cl + prev * 8, 1);
    if (!passA && lane == 0) mbar_arrive(sb + SM_BARS + B_G1DONE * 8);
    if (warp4 == 0) PROF(3 + wgi * 8 + (passA ? 0 : 3));
    const int g = lane >> 2;
    const int r0 = wgi * 64 + warp4 * 16 + g;
    const float s0 = __uint_as_float(lds32(sb + SM_STATS + r0 * 8 + 4)), s1 = __uint_as_float(lds32(sb + SM_STATS + (r0 + 8) * 8 + 4));
    #pragma unroll
    for (int t = 0; t < NB * 4; t++) {
        const float* ag = &acc[4 * t];
        const float* au = &acc[NB * 16 + 4 * t];
        hp[2 * t] = bmul2(pack_bf(ag[0] * s0, ag[1] * s0), pack_bf(au[0] * s0, au[1] * s0));
        hp[2 * t + 1] = bmul2(pack_bf(ag[2] * s1, ag[3] * s1), pack_bf(au[2] * s1, au[3] * s1));
    }
    if (warp4 == 0) PROF(4 + wgi * 8 + (passA ? 0 : 3));
}

__global__ void __cluster_dims__(2, 1, 1) __launch_bounds__(NTHREADS, 1)
fused_kernel(const __grid_constant__ Params p) {
    extern __shared__ __align__(1024) uint8_t smem_raw[];
    const uint32_t sb = smem_u32(smem_raw);
    const int tid = threadIdx.x, warp = tid >> 5, lane = tid & 31;
    const int b = blockIdx.x;
    const int rank = b & 1;
    const int j = (b >> 1) & 7;
    const int i = ((b >> 4) << 1) | rank;
    const int cb = j >> 1;
    const bool convCTA = j & 1;
    const int cidx = 4 * i + cb;

    if (tid == 256) {
        mbar_init(sb + SM_BARS + B_XFULL * 8, 1);
        mbar_init(sb + SM_BARS + (B_XFULL + 1) * 8, 1);
        asm volatile("fence.proxy.async.shared::cta;" ::: "memory");
        mbar_expect_tx(sb + SM_BARS + B_XFULL * 8, 65536);
        tma3d(sb + SM_X, &p.tm_x, 0, 128 * i, 0, sb + SM_BARS + B_XFULL * 8);
        mbar_expect_tx(sb + SM_BARS + (B_XFULL + 1) * 8, 65536);
        tma3d(sb + SM_X + 65536, &p.tm_x, 0, 128 * i + 64, 0, sb + SM_BARS + (B_XFULL + 1) * 8);
    }
    if (tid == 288) {
        for (int s = 0; s < 5; s++) { mbar_init(sb + SM_BARS + (B_FULL + s) * 8, 1); mbar_init(sb + SM_BARS + (B_EMPTY + s) * 8, 16); }
        mbar_init(sb + SM_BARS + B_CONV * 8, 1);
        mbar_init(sb + SM_BARS + B_YT * 8, 1);
        mbar_init(sb + SM_BARS + B_XR * 8, 1);
        mbar_init(sb + SM_BARS + B_G1DONE * 8, 8);
        mbar_init(sb + SM_BARS + B_XFREE * 8, 8);
        mbar_init(sb + SM_BARS + B_YST * 8, 8);
        mbar_init(sb + SM_BARS + B_KVLD * 8, 2);
        mbar_init(sb + SM_BARS + B_LN * 8, 8);
        for (int s = 0; s < 4; s++) mbar_init(sb + SM_BARS + (B_HD + s) * 8, 4);
        for (int s = 0; s < 2; s++) mbar_init(sb + SM_BARS + (B_HRDY + s) * 8, 1);
        asm volatile("fence.mbarrier_init.release.cluster;" ::: "memory");
        asm volatile("fence.proxy.async.shared::cta;" ::: "memory");
    }
    __syncwarp();
    asm volatile("barrier.cluster.arrive.relaxed.aligned;\n" ::: "memory");
    asm volatile("barrier.cluster.wait.aligned;\n" ::: "memory");
    PROFW(1, 0);

    if (warp < 8) {
        asm volatile("setmaxnreg.inc.sync.aligned.u32 200;");
        const int wgi = warp >> 2, warp4 = warp & 3;
        const int g = lane >> 2, c = lane & 3;
        const uint32_t e_cl = mapa(sb + SM_BARS + B_EMPTY * 8, lane & 1);
        {
            const int lr16 = (lane & 7) + ((lane >> 3) & 1) * 8;
            const uint32_t xa = sb + SM_X + wgi * 65536 + (warp4 * 16 + lr16) * 128;
            uint32_t xf[32][4];
            float aS[4][4], aQ0[4][4], aQ1[4][4];
            #pragma unroll
            for (int e = 0; e < 4; e++) {
                #pragma unroll
                for (int f = 0; f < 4; f++) { aS[e][f] = 0.f; aQ0[e][f] = 0.f; aQ1[e][f] = 0.f; }
            }
            mbar_wait(sb + SM_BARS + (B_XFULL + wgi) * 8, 0);
            PROFW(16, 0); PROFW(18, 4);
            #pragma unroll
            for (int ks = 0; ks < 32; ks++) {
                const uint32_t a = xa + (ks >> 2) * 8192 + (((2 * (ks & 3) + (lane >> 4)) ^ (lane & 7)) << 4);
                asm volatile("ldmatrix.sync.aligned.m8n8.x4.shared.b16 {%0,%1,%2,%3}, [%4];"
                    : "=r"(xf[ks][0]), "=r"(xf[ks][1]), "=r"(xf[ks][2]), "=r"(xf[ks][3]) : "r"(a) : "memory");
            }
            PROFW(40, 4);
            #pragma unroll
            for (int ks = 0; ks < 32; ks++)
                mma16816(aS[ks & 3], xf[ks][0], xf[ks][1], xf[ks][2], xf[ks][3], make_uint2(0x3F803F80u, 0x3F803F80u));
            const float mean0 = ((aS[0][0] + aS[1][0]) + (aS[2][0] + aS[3][0])) * (1.0f / DM);
            const float mean1 = ((aS[0][2] + aS[1][2]) + (aS[2][2] + aS[3][2])) * (1.0f / DM);
            const uint32_t m0 = pack_bf(mean0, mean0), m1 = pack_bf(mean1, mean1);
            PROFW(41, 4);
            #pragma unroll
            for (int ks = 0; ks < 32; ks++) {
                const uint32_t a = xa + (ks >> 2) * 8192 + (((2 * (ks & 3) + (lane >> 4)) ^ (lane & 7)) << 4);
                asm volatile("stmatrix.sync.aligned.m8n8.x4.shared.b16 [%0], {%1,%2,%3,%4};"
                    :: "r"(a), "r"(bsub2(xf[ks][0], m0)), "r"(bsub2(xf[ks][1], m1)), "r"(bsub2(xf[ks][2], m0)), "r"(bsub2(xf[ks][3], m1)) : "memory");
            }
            PROFW(42, 4);
            asm volatile("fence.proxy.async.shared::cta;" ::: "memory");
            __syncwarp();
            if (lane == 0) mbar_arrive(sb + SM_BARS + B_LN * 8);
            #pragma unroll
            for (int ks = 0; ks < 32; ks++) {
                mma16816(aQ0[ks & 3], xf[ks][0], xf[ks][1], xf[ks][2], xf[ks][3], make_uint2(xf[ks][0], xf[ks][2]));
                mma16816(aQ1[ks & 3], xf[ks][0], xf[ks][1], xf[ks][2], xf[ks][3], make_uint2(xf[ks][1], xf[ks][3]));
            }
            if (c == (g >> 1)) {
                const float q0 = (g & 1) ? (aQ0[0][1] + aQ0[1][1]) + (aQ0[2][1] + aQ0[3][1]) : (aQ0[0][0] + aQ0[1][0]) + (aQ0[2][0] + aQ0[3][0]);
                const float q1 = (g & 1) ? (aQ1[0][3] + aQ1[1][3]) + (aQ1[2][3] + aQ1[3][3]) : (aQ1[0][2] + aQ1[1][2]) + (aQ1[2][2] + aQ1[3][2]);
                const float sd0 = bf_round(sqrtf(bf_round(bf_round(fmaxf(q0 * (1.0f / DM) - mean0 * mean0, 0.f)) + 1e-5f)));
                const float sd1 = bf_round(sqrtf(bf_round(bf_round(fmaxf(q1 * (1.0f / DM) - mean1 * mean1, 0.f)) + 1e-5f)));
                const uint32_t sa = sb + SM_STATS + (warp * 16 + g) * 8;
                sts32(sa, m0); sts32(sa + 4, __float_as_uint(1.0f / sd0));
                sts32(sa + 64, m1); sts32(sa + 68, __float_as_uint(1.0f / sd1));
            }
            mbar_wait(sb + SM_BARS + B_LN * 8, 0);
            PROFW(19, 4);
            PROFW(17, 0);
        }
        int st = 0; uint32_t fph = 0;
        uint32_t hp[32];
        uint32_t* const hdst = g_h + (size_t)(i * 56) * 2048 + wgi * 1024 + warp4 * 128 + lane;
        gemm1_pass<4, true>(sb, wgi, warp4, lane, st, fph, e_cl, hp, hdst, convCTA);

        if (convCTA) {
            gemm1_pass<2, false>(sb, wgi, warp4, lane, st, fph, e_cl, hp, hdst + 4 * j * 2048, true);
            store_h(hdst + (36 + 6 * cb) * 2048, hp, 0); store_h(hdst + (36 + 6 * cb) * 2048, hp, 1);
            __syncwarp();
            if (lane == 0) mbar_arrive(sb + SM_BARS + (B_HD + wgi * 2 + 1) * 8);
            const int gch = 8 * cidx + warp;
            const uint32_t xb = sb + SM_CVX + warp * 4096;
            const uint32_t hb = sb + SM_CVH + warp * 4096;
            const uint32_t dw = ((const unsigned short*)p.ssm_D)[gch];
            const uint32_t d2 = dw | (dw << 16);
            mbar_wait(sb + SM_BARS + B_CONV * 8, 0);
            PROFW(32, 4);
            float acc[16][4];
            #pragma unroll
            for (int jj = 0; jj < 16; jj++) { acc[jj][0] = 0.f; acc[jj][1] = 0.f; acc[jj][2] = 0.f; acc[jj][3] = 0.f; }
            uint2 bh[8], bl0[8], bl1[8];
            uint32_t xl = xb + g * 32 + c * 8;
            uint32_t hl = hb + (g + 2 * c - 8) * 4;
            #pragma unroll
            for (int d = 0; d < 8; d++) { bl0[d] = lds64(xl + d * 256); bh[d] = lds64(xl + (8 + d) * 256); }
            uint32_t w[6];
            w[0] = 0; w[1] = 0; w[2] = 0;
            if (g + 2 * c >= 8) w[0] = lds32(hl);
            if (g + 2 * c >= 7) w[1] = lds32(hl + 4);
            if (g + 2 * c >= 6) w[2] = lds32(hl + 8);
            w[3] = lds32(hl + 2048); w[4] = lds32(hl + 2052); w[5] = lds32(hl + 2056);
            auto conv_m0 = [&](int m0, uint2 (&bl)[8], uint2 (&bn)[8]) {
                xl -= 32;
                #pragma unroll
                for (int k = 0; k < 8; k++) {
                    const uint32_t a0 = w[1], a1 = __byte_perm(w[0], w[1], 0x5432), a2 = w[2], a3 = __byte_perm(w[1], w[2], 0x5432);
                    const uint32_t c0 = w[4], c1 = __byte_perm(w[3], w[4], 0x5432), c2 = w[5], c3 = __byte_perm(w[4], w[5], 0x5432);
                    const uint32_t nx = (k < 7) ? hl + (k + 1) * 256 : hl + 32;
                    w[0] = lds32(nx); w[1] = lds32(nx + 4); w[2] = lds32(nx + 8);
                    w[3] = lds32(nx + 2048); w[4] = lds32(nx + 2052); w[5] = lds32(nx + 2056);
                    if (k > 0) bn[k] = lds64(xl + k * 256);
                    else { bn[0] = make_uint2(0, 0); if (g > m0) bn[0] = lds64(xl); }
                    #pragma unroll
                    for (int jj = k; jj < 16; jj++) mma16816(acc[jj], a0, a1, a2, a3, (jj - k < 8) ? bl[(jj - k) & 7] : bh[(jj - k) & 7]);
                    bh[7 - k] = lds64(xl + (15 - k) * 256);
                    #pragma unroll
                    for (int jj = k + 8; jj < 16; jj++) mma16816(acc[jj], c0, c1, c2, c3, bl[jj - k - 8]);
                }
                hl += 32;
            };
            #pragma unroll 1
            for (int m0 = 0; m0 < 8; m0 += 2) {
                conv_m0(m0, bl0, bl1);
                conv_m0(m0 + 1, bl1, bl0);
                PROFW(34 + (m0 >> 1), 4);
            }
            PROFW(33, 4);
            const uint32_t kvl = xb + c * 64 + (7 - g) * 4;
            uint32_t* ydst = (uint32_t*)(g_yT + (size_t)gch * SEQ + 32 * c + 2 * g);
            uint32_t kk0[16], kk1[16];
            #pragma unroll
            for (int jj = 0; jj < 16; jj++) { kk0[jj] = lds32(kvl + jj * 256); kk1[jj] = lds32(kvl + jj * 256 + 32); }
            #pragma unroll
            for (int jj = 0; jj < 16; jj++) {
                ydst[jj * 64] = badd2(pack_bf(acc[jj][2], acc[jj][0]), bmul2(__byte_perm(kk0[jj], kk0[jj], 0x1032), d2));
                ydst[jj * 64 + 8] = badd2(pack_bf(acc[jj][3], acc[jj][1]), bmul2(__byte_perm(kk1[jj], kk1[jj], 0x1032), d2));
            }
            __syncwarp();
            PROFW(44, 4);
            if (lane == 0) flag_add(&g_cnt_y[(cidx >> 4) * 32]);
            PROFW(46, 4);
        } else {
            gemm1_pass<4, false>(sb, wgi, warp4, lane, st, fph, e_cl, hp, hdst + 4 * j * 2048, false);
            float acc[64];
            const uint64_t descB0 = make_desc(sb, 4096, 1024, 1);
            const uint64_t descA0 = make_desc(sb + 16384 + wgi * 4096, 128, 256, 0);
            int sg = 3, p0 = 0; uint32_t ph = 6;
            PROFW(20, 0);
            auto g2 = [&](int u) {
                if (warp == 0 && !(u & 1)) PROF2(2, 16 + (u >> 1));
                mbar_wait(sb + SM_BARS + (B_FULL + sg) * 8, (ph >> sg) & 1);
                ph ^= 1u << sg;
                if (warp == 0 && !(u & 1)) PROF2(1, 16 + (u >> 1));
                const uint32_t o0 = stage_off_rt(sg) >> 4;
                const uint64_t da0 = desc_add(descA0, o0), db0 = desc_add(descB0, o0);
                WG_FENCE();
                #pragma unroll
                for (int kk = 0; kk < 4; kk++) wgmma_ss_n128_tb(acc, da0 + ((kk >> 1) * 512 + (kk & 1) * 128), db0 + ((kk >> 1) * 512 + (kk & 1) * 128), (u | kk) ? 1 : 0);
                WG_COMMIT();
                wg_wait<1>();
                if (warp == 0 && !(u & 1)) PROF2(3, 16 + (u >> 1));
                if (lane < 2 && u > 0 && u + 4 < 28) mbar_arrive_cluster(e_cl + p0 * 8, 1);
                p0 = sg;
                sg = next_st2(sg);
            };
            #pragma unroll
            for (int u = 0; u < 4; u++) { g2(u); store_h(hdst + (32 + 6 * cb) * 2048, hp, u); }
            __syncwarp();
            if (lane == 0) mbar_arrive(sb + SM_BARS + (B_HD + wgi * 2 + 1) * 8);
            #pragma unroll 1
            for (int u = 4; u < 8; u++) g2(u);
            mbar_wait(sb + SM_BARS + B_XR * 8, 0);
            const int r0 = wgi * 64 + warp4 * 16 + g;
            const float2 st0 = lds64f(sb + SM_STATS + r0 * 8), st1 = lds64f(sb + SM_STATS + (r0 + 8) * 8);
            const uint32_t m0 = __float_as_uint(st0.x), m1 = __float_as_uint(st1.x);
            const uint32_t xrow0 = sb + SM_XE + r0 * 128 + c * 4;
            const int mi = lane >> 3, lr = lane & 7;
            const uint32_t yaddr = sb + SM_YT + wgi * 16384 + ((mi >> 1) * 8 + lr) * 128 + (((2 * warp4 + (mi & 1)) ^ lr) << 4);
            uint32_t y[8][4], xv[16][2], nv[16][2], bv[16][2];
            #pragma unroll
            for (int t = 0; t < 16; t++) {
                const uint32_t off = (t >> 3) * 16384 + (((t & 7) ^ g) << 4);
                xv[t][0] = lds32(xrow0 + off); xv[t][1] = lds32(xrow0 + 1024 + off);
            }
            #pragma unroll
            for (int t = 0; t < 16; t++) {
                const uint32_t d0 = bsub2(xv[t][0], m0), d1 = bsub2(xv[t][1], m1);
                nv[t][0] = pack_bf(bf_lo(d0) * st0.y, bf_hi(d0) * st0.y); nv[t][1] = pack_bf(bf_lo(d1) * st1.y, bf_hi(d1) * st1.y);
            }
            #pragma unroll 1
            for (int u = 8; u < 28; u++) g2(u);
            wg_wait<0>();
            PROFW(27, 0);
            #pragma unroll
            for (int t = 0; t < 16; t++) { bv[t][0] = pack_bf(acc[4 * t], acc[4 * t + 1]); bv[t][1] = pack_bf(acc[4 * t + 2], acc[4 * t + 3]); }
            mbar_wait(sb + SM_BARS + B_YT * 8, 0);
            PROFW(28, 0);
            #pragma unroll
            for (int t2 = 0; t2 < 8; t2++)
                asm volatile("ldmatrix.sync.aligned.m8n8.x4.trans.shared.b16 {%0,%1,%2,%3}, [%4];"
                    : "=r"(y[t2][0]), "=r"(y[t2][1]), "=r"(y[t2][2]), "=r"(y[t2][3]) : "r"(yaddr + t2 * 2048) : "memory");
            #pragma unroll
            for (int hf = 0; hf < 2; hf++) {
                #pragma unroll
                for (int t = 8 * hf; t < 8 * hf + 8; t++) {
                    const uint32_t off = (t >> 3) * 16384 + (((t & 7) ^ g) << 4);
                    sts32(xrow0 + off, badd2(badd2(xv[t][0], bmul2(nv[t][0], y[t >> 1][2 * (t & 1)])), bv[t][0]));
                    sts32(xrow0 + 1024 + off, badd2(badd2(xv[t][1], bmul2(nv[t][1], y[t >> 1][2 * (t & 1) + 1])), bv[t][1]));
                }
                asm volatile("fence.proxy.async.shared::cta;" ::: "memory");
                __syncwarp();
                if (lane == 0) tma2d_store(&p.tm_out, 128 * cb + 64 * hf, 128 * i + 16 * warp, sb + SM_XE + hf * 16384 + warp * 2048);
            }
            if (lane == 0) {
                asm volatile("cp.async.bulk.commit_group;" ::: "memory");
                asm volatile("cp.async.bulk.wait_group.read 0;" ::: "memory");
                PROFW(29, 0);
            }
        }
    } else {
        asm volatile("setmaxnreg.dec.sync.aligned.u32 104;");
        if (warp == 8) {
            int st = 0; uint32_t eph = 7;
            const int nit = convCTA ? 12 : 16;
            #pragma unroll 1
            for (int it = 0; it < nit; it++) {
                const int pass = it >> 3, sl = it & 7;
                const bool narrow = pass && convCTA;
                const CUtensorMap* tm = narrow ? (rank ? &p.tm_uB : &p.tm_gB) : (rank ? &p.tm_uA : &p.tm_gA);
                mbar_wait(sb + SM_BARS + (B_EMPTY + st) * 8, (eph >> st) & 1);
                eph ^= 1u << st;
                if (it == 1) mbar_wait(sb + SM_BARS + B_XFULL * 8, 0);
                PROF2(0, it);
                if (elect_one()) {
                    mbar_expect_tx(sb + SM_BARS + (B_FULL + st) * 8, 32768);
                    tma3d_mc(sb + SM_RING + st * STAGE_BYTES + rank * 16384, tm, 0, sl * (narrow ? 128 : 64), 14 * cb + 8 * (j & 1) + 4 * pass, sb + SM_BARS + (B_FULL + st) * 8);
                }
                st = (st == 2) ? 0 : st + 1;
            }
            if (!convCTA) {
                st = 3;
                const int f0_lane = blk_f0(2 * lane + rank);
                #pragma unroll 1
                for (int u = 0; u < 28; u++) {
                    const uint32_t bar = sb + SM_BARS + (B_FULL + st) * 8;
                    const int f0 = __shfl_sync(0xffffffffu, f0_lane, u);
                    mbar_wait(sb + SM_BARS + (B_EMPTY + st) * 8, (eph >> st) & 1);
                    eph ^= 1u << st;
                    if ((u & 1) == 0) PROF2(0, 16 + (u >> 1));
                    if (elect_one()) {
                        mbar_expect_tx(bar, 32768);
                        tma3d_mc(sb + stage_off_rt(st) + rank * 8192, &p.tm_w2, 0, f0, 2 * cb, bar);
                    }
                    st = next_st2(st);
                }
                PROF(48);
            }
        } else if (warp < 11) {
            mbar_wait(sb + SM_BARS + (B_XFULL + 1) * 8, 0);
            {
                const int q = lane & 3;
                const int t0 = 32 * (b >> 1) + 8 * q;
                const int ch0 = 256 * (b & 1) + 16 * (warp - 9) + 2 * (lane >> 2);
                const uint32_t* kp = (const uint32_t*)(p.k + (size_t)t0 * DM + ch0);
                const uint32_t* vp = (const uint32_t*)(p.v + (size_t)t0 * DM + ch0);
                __nv_bfloat16* dst0 = g_kvT + (size_t)ch0 * SEQ + (t0 ^ 8);
                #pragma unroll 1
                for (int rnd = 0; rnd < 2; rnd++) {
                    uint32_t kr[4][11], vr[4][8]; uint4 skw[4];
                    #pragma unroll
                    for (int u = 0; u < 4; u++) {
                        const int co = (rnd * 4 + u) * 16;
                        skw[u] = ldg_nc128(p.shift_k + 4 * (ch0 + 2 * co));
                        #pragma unroll
                        for (int r = 0; r < 11; r++) kr[u][r] = (r >= 3 || t0 > 0) ? ldg_nc32(kp + co + (r - 3) * (DM / 2)) : 0u;
                        #pragma unroll
                        for (int r = 0; r < 8; r++) vr[u][r] = ldg_nc32(vp + co + r * (DM / 2));
                    }
                    #pragma unroll
                    for (int u = 0; u < 4; u++) {
                        const uint32_t s0 = __byte_perm(skw[u].x, skw[u].z, 0x5410), s1 = __byte_perm(skw[u].x, skw[u].z, 0x7632);
                        const uint32_t s2 = __byte_perm(skw[u].y, skw[u].w, 0x5410), s3 = __byte_perm(skw[u].y, skw[u].w, 0x7632);
                        #pragma unroll
                        for (int r = 0; r < 8; r++) {
                            uint32_t a = bmul2(kr[u][r], s3);
                            a = badd2(a, bmul2(kr[u][r + 1], s2));
                            a = badd2(a, bmul2(kr[u][r + 2], s1));
                            a = badd2(a, bmul2(kr[u][r + 3], s0));
                            vr[u][r] = bmul2(a, vr[u][r]);
                        }
                        __nv_bfloat16* dst = dst0 + (size_t)((rnd * 4 + u) * 32) * SEQ;
                        *(uint4*)dst = make_uint4(__byte_perm(vr[u][7], vr[u][6], 0x5410), __byte_perm(vr[u][5], vr[u][4], 0x5410),
                                                  __byte_perm(vr[u][3], vr[u][2], 0x5410), __byte_perm(vr[u][1], vr[u][0], 0x5410));
                        *(uint4*)(dst + SEQ) = make_uint4(__byte_perm(vr[u][7], vr[u][6], 0x7632), __byte_perm(vr[u][5], vr[u][4], 0x7632),
                                                          __byte_perm(vr[u][3], vr[u][2], 0x7632), __byte_perm(vr[u][1], vr[u][0], 0x7632));
                    }
                    PROFW(57 + 2 * rnd, 9);
                }
                if (lane == 0) mbar_arrive(sb + SM_BARS + B_KVLD * 8);
            }
            asm volatile("fence.proxy.async.global;" ::: "memory");
            __syncwarp();
            if (lane == 0) {
                flag_add(&g_cnt_kv[0]);
                PROFW(50, 9);
                const int wgi = warp - 9;
                mbar_wait(sb + SM_BARS + (B_HD + wgi * 2) * 8, 0);
                flag_add(&g_flag_h[(i * 2 + 0) * 8]);
                mbar_wait(sb + SM_BARS + (B_HD + wgi * 2 + 1) * 8, 0);
                flag_add(&g_flag_h[(i * 2 + 1) * 8]);
                if (wgi == 1 && !convCTA) {
                    const unsigned ep = lds32(sb + SM_EPOCH);
                    mbar_wait(sb + SM_BARS + B_G1DONE * 8, 0);
                    mbar_expect_tx(sb + SM_BARS + B_XR * 8, 32768);
                    tma3d(sb + SM_XE, &p.tm_xe, 0, 128 * i, 2 * cb, sb + SM_BARS + B_XR * 8);
                    flag_wait(&g_flag_h[(i * 2 + 1) * 8], ep * 16);
                    mbar_arrive(sb + SM_BARS + (B_HRDY + 1) * 8);
                    __nanosleep(3000);
                    flag_wait(&g_cnt_y[cb * 32], ep * 128);
                    PROF(49);
                    asm volatile("fence.proxy.async.global;" ::: "memory");
                    mbar_expect_tx(sb + SM_BARS + B_YT * 8, 32768);
                    tma2d(sb + SM_YT, &p.tm_yT, 128 * i, 128 * cb, sb + SM_BARS + B_YT * 8);
                    tma2d(sb + SM_YT + 16384, &p.tm_yT, 128 * i + 64, 128 * cb, sb + SM_BARS + B_YT * 8);
                }
            }
        } else {
            if (lane == 0) {
                l2_prefetch(p.wg + (size_t)b * (FF * DM / NCTA), FF * DM / NCTA * 2);
                l2_prefetch(p.wu + (size_t)b * (FF * DM / NCTA), FF * DM / NCTA * 2);
                const unsigned ep = g_launch[b] + 1;
                g_launch[b] = ep;
                sts32(sb + SM_EPOCH, ep);
                tmap_prefetch(rank ? &p.tm_uA : &p.tm_gA);
                tmap_prefetch(rank ? &p.tm_uB : &p.tm_gB);
                tmap_prefetch(&p.tm_w2); tmap_prefetch(&p.tm_yT); tmap_prefetch(&p.tm_out); tmap_prefetch(&p.tm_xe);
                mbar_wait(sb + SM_BARS + B_KVLD * 8, 0);
                l2_prefetch(p.ssm_k + (size_t)(4 * b) * SEQ, 4 * SEQ * 2);
                l2_prefetch(p.wd + (size_t)b * (FF * DM / NCTA), FF * DM / NCTA * 2);
                if (convCTA) {
                    __nanosleep(1000);
                    flag_wait(&g_cnt_kv[0], ep * 256);
                    asm volatile("fence.proxy.async.global;" ::: "memory");
                    PROF(53);
                    mbar_wait(sb + SM_BARS + B_XFREE * 8, 0);
                    PROF(54);
                    mbar_expect_tx(sb + SM_BARS + B_CONV * 8, 65536);
                    bulk_g2s(sb + SM_CVX, g_kvT + (size_t)(8 * cidx) * SEQ, 32768, sb + SM_BARS + B_CONV * 8);
                    bulk_g2s(sb + SM_CVH, p.ssm_k + (size_t)(8 * cidx) * SEQ, 32768, sb + SM_BARS + B_CONV * 8);
                } else {
                    mbar_wait(sb + SM_BARS + (B_HD + 0) * 8, 0);
                    flag_wait(&g_flag_h[(i * 2 + 0) * 8], ep * 16);
                }
            }
            __syncwarp();
            if (!convCTA) {
                asm volatile("fence.proxy.async.global;" ::: "memory");
                int st = 3; uint32_t eph = 1;
                const uint8_t* hsrc = (const uint8_t*)g_h + (size_t)i * 56 * 8192;
                #pragma unroll 1
                for (int u = 0; u < 28; u++) {
                    mbar_wait(sb + SM_BARS + (B_EMPTY + st) * 8, (eph >> st) & 1);
                    eph ^= 1u << st;
                    if (u == 16) {
                        mbar_wait(sb + SM_BARS + (B_HRDY + 1) * 8, 0);
                        asm volatile("fence.proxy.async.global;" ::: "memory");
                    }
                    if (elect_one()) bulk_g2s(sb + stage_off_rt(st) + 16384, hsrc + u * 16384, 16384, sb + SM_BARS + (B_FULL + st) * 8);
                    st = next_st2(st);
                }
            }
        }
    }
}

typedef CUresult (*EncodeFn)(CUtensorMap*, CUtensorMapDataType, cuuint32_t, void*, const cuuint64_t*, const cuuint64_t*,
                             const cuuint32_t*, const cuuint32_t*, CUtensorMapInterleave, CUtensorMapSwizzle,
                             CUtensorMapL2promotion, CUtensorMapFloatOOBfill);

void encode(EncodeFn fn, CUtensorMap* tm, const void* base, int rank, const cuuint64_t* dims, const cuuint64_t* strides,
            const cuuint32_t* box, CUtensorMapSwizzle swz) {
    cuuint32_t es[5] = {1, 1, 1, 1, 1};
    fn(tm, CU_TENSOR_MAP_DATA_TYPE_BFLOAT16, rank, (void*)base, dims, strides, box, es, CU_TENSOR_MAP_INTERLEAVE_NONE, swz,
       CU_TENSOR_MAP_L2_PROMOTION_L2_128B, CU_TENSOR_MAP_FLOAT_OOB_FILL_NONE);
}

}

extern "C" void kernel_launch(void* const* d_in, const int* in_sizes, int n_in, void* d_out, int out_size) {
    (void)in_sizes; (void)n_in; (void)out_size;
    static EncodeFn enc = nullptr;
    static void* yT_ptr = nullptr;
    if (!enc) {
        void* fn = nullptr; cudaDriverEntryPointQueryResult qr;
        cudaGetDriverEntryPoint("cuTensorMapEncodeTiled", &fn, cudaEnableDefault, &qr);
        enc = (EncodeFn)fn;
        cudaGetSymbolAddress(&yT_ptr, g_yT);
        cudaFuncSetAttribute(fused_kernel, cudaFuncAttributeMaxDynamicSharedMemorySize, SM_TOTAL);
    }
    Params p;
    p.q = (const __nv_bfloat16*)d_in[0]; p.k = (const __nv_bfloat16*)d_in[1]; p.v = (const __nv_bfloat16*)d_in[2];
    p.shift_k = (const __nv_bfloat16*)d_in[3]; p.ssm_k = (const __nv_bfloat16*)d_in[4]; p.ssm_D = (const __nv_bfloat16*)d_in[5];
    p.wg = (const __nv_bfloat16*)d_in[7]; p.wu = (const __nv_bfloat16*)d_in[8]; p.wd = (const __nv_bfloat16*)d_in[9];
    {
        cuuint64_t dims[2] = {DM, SEQ}; cuuint64_t str[1] = {DM * 2};
        cuuint64_t dims3[3] = {64, SEQ, DM / 64}; cuuint64_t str3[2] = {DM * 2, 128};
        cuuint32_t box[3] = {64, 64, 8}, boxe[3] = {64, 128, 2};
        encode(enc, &p.tm_x, p.q, 3, dims3, str3, box, CU_TENSOR_MAP_SWIZZLE_128B);
        encode(enc, &p.tm_xe, p.q, 3, dims3, str3, boxe, CU_TENSOR_MAP_SWIZZLE_128B);
        cuuint32_t box2[2] = {64, 16};
        encode(enc, &p.tm_out, d_out, 2, dims, str, box2, CU_TENSOR_MAP_SWIZZLE_128B);
    }
    {
        cuuint64_t dims[3] = {32, DM, FF / 32}; cuuint64_t str[2] = {FF * 2, 64};
        cuuint32_t boxA[3] = {32, 64, 4}, boxB[3] = {32, 128, 2};
        encode(enc, &p.tm_gA, p.wg, 3, dims, str, boxA, CU_TENSOR_MAP_SWIZZLE_64B);
        encode(enc, &p.tm_gB, p.wg, 3, dims, str, boxB, CU_TENSOR_MAP_SWIZZLE_64B);
        encode(enc, &p.tm_uA, p.wu, 3, dims, str, boxA, CU_TENSOR_MAP_SWIZZLE_64B);
        encode(enc, &p.tm_uB, p.wu, 3, dims, str, boxB, CU_TENSOR_MAP_SWIZZLE_64B);
    }
    {
        cuuint64_t dims[3] = {64, FF, DM / 64}; cuuint64_t str[2] = {DM * 2, 128};
        cuuint32_t box[3] = {64, 32, 2};
        encode(enc, &p.tm_w2, p.wd, 3, dims, str, box, CU_TENSOR_MAP_SWIZZLE_128B);
    }
    {
        cuuint64_t dims[2] = {SEQ, DM}; cuuint64_t str[1] = {SEQ * 2};
        cuuint32_t box[2] = {64, 128};
        encode(enc, &p.tm_yT, yT_ptr, 2, dims, str, box, CU_TENSOR_MAP_SWIZZLE_128B);
    }
    fused_kernel<<<NCTA, NTHREADS, SM_TOTAL>>>(p);
}
```

```cpp
#include <cuda_runtime.h>
#include <cuda_bf16.h>
#include <cuda.h>
#include <stdint.h>

namespace {

constexpr int SEQ = 2048, DM = 512, FF = 1792;
constexpr int NCTA = 128;
constexpr int NTHREADS = 384;
constexpr int STAGE_BYTES = 32768;
#define KV_STAGGER 300
#define KV_GAP 150

constexpr uint32_t SM_X = 0;
constexpr uint32_t SM_RING = 131072;
constexpr uint32_t SM_MISC = SM_RING + 3 * STAGE_BYTES;
constexpr uint32_t SM_BARS = SM_MISC;
constexpr uint32_t SM_EPOCH = SM_MISC + 312;
constexpr uint32_t SM_CS = SM_MISC + 320;
constexpr uint32_t SM_TOTAL = SM_CS + 2048;
static_assert(SM_TOTAL <= 232448, "smem");
constexpr uint32_t SM_CVX = 0;
constexpr uint32_t SM_CVH = 32768;
constexpr uint32_t SM_YT = 65536;
constexpr uint32_t SM_XE = 98304;

constexpr int B_FULL = 0, B_EMPTY = 5, B_XFULL = 10, B_CONV = 18, B_YT = 19, B_XR = 20, B_G1DONE = 21, B_HD = 22, B_HRDY = 26,
              B_XFREE = 27, B_CSD = 28, B_CS = 30, B_COUNT = 32;
static_assert(B_COUNT * 8 <= 312, "barrier space");

__device__ __align__(128) uint32_t g_h[16 * 56 * 2048];
__device__ __align__(128) __nv_bfloat16 g_kvT[DM * SEQ];
__device__ __align__(128) __nv_bfloat16 g_yT[DM * SEQ];
__device__ __align__(16) float g_csp[2 * 8 * 16 * 256];
__device__ unsigned g_flag_cs[2 * 8 * 8];
__device__ unsigned g_launch[NCTA];
__device__ unsigned g_cnt_kv[32];
__device__ unsigned g_cnt_y[4 * 32];
__device__ unsigned g_flag_h[16 * 2 * 8];

#define PROF(idx)
#define PROF2(a, idx)
#define PROFW(idx, w)

struct Params {
    CUtensorMap tm_x, tm_gA, tm_gB, tm_uA, tm_uB, tm_w2, tm_yT, tm_out, tm_xe;
    const __nv_bfloat16 *q, *k, *v, *shift_k, *ssm_k, *ssm_D, *wg, *wu, *wd;
};

__device__ __forceinline__ void wgmma_rs_n32(float (&d)[16], uint32_t a0, uint32_t a1, uint32_t a2, uint32_t a3, uint64_t db, int sc) {
  asm volatile("{\n.reg .pred p;\nsetp.ne.b32 p, %21, 0;\n"
    "wgmma.mma_async.sync.aligned.m64n32k16.f32.bf16.bf16 {%0,%1,%2,%3,%4,%5,%6,%7,%8,%9,%10,%11,%12,%13,%14,%15}, {%16,%17,%18,%19}, %20, p, 1, 1, 0;\n}\n"
    : "+f"(d[0]),"+f"(d[1]),"+f"(d[2]),"+f"(d[3]),"+f"(d[4]),"+f"(d[5]),"+f"(d[6]),"+f"(d[7]),"+f"(d[8]),"+f"(d[9]),"+f"(d[10]),"+f"(d[11]),"+f"(d[12]),"+f"(d[13]),"+f"(d[14]),"+f"(d[15])
    : "r"(a0),"r"(a1),"r"(a2),"r"(a3),"l"(db),"r"(sc));
}
__device__ __forceinline__ void wgmma_rs_n128_tb(float (&d)[64], uint32_t a0, uint32_t a1, uint32_t a2, uint32_t a3, uint64_t db, int sc) {
  asm volatile("{\n.reg .pred p;\nsetp.ne.b32 p, %69, 0;\n"
    "wgmma.mma_async.sync.aligned.m64n128k16.f32.bf16.bf16 {%0,%1,%2,%3,%4,%5,%6,%7,%8,%9,%10,%11,%12,%13,%14,%15,%16,%17,%18,%19,%20,%21,%22,%23,%24,%25,%26,%27,%28,%29,%30,%31,%32,%33,%34,%35,%36,%37,%38,%39,%40,%41,%42,%43,%44,%45,%46,%47,%48,%49,%50,%51,%52,%53,%54,%55,%56,%57,%58,%59,%60,%61,%62,%63}, {%64,%65,%66,%67}, %68, p, 1, 1, 1;\n}\n"
    : "+f"(d[0]),"+f"(d[1]),"+f"(d[2]),"+f"(d[3]),"+f"(d[4]),"+f"(d[5]),"+f"(d[6]),"+f"(d[7]),"+f"(d[8]),"+f"(d[9]),"+f"(d[10]),"+f"(d[11]),"+f"(d[12]),"+f"(d[13]),"+f"(d[14]),"+f"(d[15]),"+f"(d[16]),"+f"(d[17]),"+f"(d[18]),"+f"(d[19]),"+f"(d[20]),"+f"(d[21]),"+f"(d[22]),"+f"(d[23]),"+f"(d[24]),"+f"(d[25]),"+f"(d[26]),"+f"(d[27]),"+f"(d[28]),"+f"(d[29]),"+f"(d[30]),"+f"(d[31]),"+f"(d[32]),"+f"(d[33]),"+f"(d[34]),"+f"(d[35]),"+f"(d[36]),"+f"(d[37]),"+f"(d[38]),"+f"(d[39]),"+f"(d[40]),"+f"(d[41]),"+f"(d[42]),"+f"(d[43]),"+f"(d[44]),"+f"(d[45]),"+f"(d[46]),"+f"(d[47]),"+f"(d[48]),"+f"(d[49]),"+f"(d[50]),"+f"(d[51]),"+f"(d[52]),"+f"(d[53]),"+f"(d[54]),"+f"(d[55]),"+f"(d[56]),"+f"(d[57]),"+f"(d[58]),"+f"(d[59]),"+f"(d[60]),"+f"(d[61]),"+f"(d[62]),"+f"(d[63])
    : "r"(a0),"r"(a1),"r"(a2),"r"(a3),"l"(db),"r"(sc));
}
__device__ __forceinline__ void wgmma_ss_n256_tb(float (&d)[128], uint64_t da, uint64_t db, int sc) {
  asm volatile("{\n.reg .pred p;\nsetp.ne.b32 p, %130, 0;\n"
    "wgmma.mma_async.sync.aligned.m64n256k16.f32.bf16.bf16 {%0,%1,%2,%3,%4,%5,%6,%7,%8,%9,%10,%11,%12,%13,%14,%15,%16,%17,%18,%19,%20,%21,%22,%23,%24,%25,%26,%27,%28,%29,%30,%31,%32,%33,%34,%35,%36,%37,%38,%39,%40,%41,%42,%43,%44,%45,%46,%47,%48,%49,%50,%51,%52,%53,%54,%55,%56,%57,%58,%59,%60,%61,%62,%63,%64,%65,%66,%67,%68,%69,%70,%71,%72,%73,%74,%75,%76,%77,%78,%79,%80,%81,%82,%83,%84,%85,%86,%87,%88,%89,%90,%91,%92,%93,%94,%95,%96,%97,%98,%99,%100,%101,%102,%103,%104,%105,%106,%107,%108,%109,%110,%111,%112,%113,%114,%115,%116,%117,%118,%119,%120,%121,%122,%123,%124,%125,%126,%127}, %128, %129, p, 1, 1, 0, 1;\n}\n"
    : "+f"(d[0]),"+f"(d[1]),"+f"(d[2]),"+f"(d[3]),"+f"(d[4]),"+f"(d[5]),"+f"(d[6]),"+f"(d[7]),"+f"(d[8]),"+f"(d[9]),"+f"(d[10]),"+f"(d[11]),"+f"(d[12]),"+f"(d[13]),"+f"(d[14]),"+f"(d[15]),"+f"(d[16]),"+f"(d[17]),"+f"(d[18]),"+f"(d[19]),"+f"(d[20]),"+f"(d[21]),"+f"(d[22]),"+f"(d[23]),"+f"(d[24]),"+f"(d[25]),"+f"(d[26]),"+f"(d[27]),"+f"(d[28]),"+f"(d[29]),"+f"(d[30]),"+f"(d[31]),"+f"(d[32]),"+f"(d[33]),"+f"(d[34]),"+f"(d[35]),"+f"(d[36]),"+f"(d[37]),"+f"(d[38]),"+f"(d[39]),"+f"(d[40]),"+f"(d[41]),"+f"(d[42]),"+f"(d[43]),"+f"(d[44]),"+f"(d[45]),"+f"(d[46]),"+f"(d[47]),"+f"(d[48]),"+f"(d[49]),"+f"(d[50]),"+f"(d[51]),"+f"(d[52]),"+f"(d[53]),"+f"(d[54]),"+f"(d[55]),"+f"(d[56]),"+f"(d[57]),"+f"(d[58]),"+f"(d[59]),"+f"(d[60]),"+f"(d[61]),"+f"(d[62]),"+f"(d[63]),"+f"(d[64]),"+f"(d[65]),"+f"(d[66]),"+f"(d[67]),"+f"(d[68]),"+f"(d[69]),"+f"(d[70]),"+f"(d[71]),"+f"(d[72]),"+f"(d[73]),"+f"(d[74]),"+f"(d[75]),"+f"(d[76]),"+f"(d[77]),"+f"(d[78]),"+f"(d[79]),"+f"(d[80]),"+f"(d[81]),"+f"(d[82]),"+f"(d[83]),"+f"(d[84]),"+f"(d[85]),"+f"(d[86]),"+f"(d[87]),"+f"(d[88]),"+f"(d[89]),"+f"(d[90]),"+f"(d[91]),"+f"(d[92]),"+f"(d[93]),"+f"(d[94]),"+f"(d[95]),"+f"(d[96]),"+f"(d[97]),"+f"(d[98]),"+f"(d[99]),"+f"(d[100]),"+f"(d[101]),"+f"(d[102]),"+f"(d[103]),"+f"(d[104]),"+f"(d[105]),"+f"(d[106]),"+f"(d[107]),"+f"(d[108]),"+f"(d[109]),"+f"(d[110]),"+f"(d[111]),"+f"(d[112]),"+f"(d[113]),"+f"(d[114]),"+f"(d[115]),"+f"(d[116]),"+f"(d[117]),"+f"(d[118]),"+f"(d[119]),"+f"(d[120]),"+f"(d[121]),"+f"(d[122]),"+f"(d[123]),"+f"(d[124]),"+f"(d[125]),"+f"(d[126]),"+f"(d[127])
    : "l"(da),"l"(db),"r"(sc));
}
__device__ __forceinline__ void wgmma_ss_n192_tb(float (&d)[96], uint64_t da, uint64_t db, int sc) {
  asm volatile("{\n.reg .pred p;\nsetp.ne.b32 p, %98, 0;\n"
    "wgmma.mma_async.sync.aligned.m64n192k16.f32.bf16.bf16 {%0,%1,%2,%3,%4,%5,%6,%7,%8,%9,%10,%11,%12,%13,%14,%15,%16,%17,%18,%19,%20,%21,%22,%23,%24,%25,%26,%27,%28,%29,%30,%31,%32,%33,%34,%35,%36,%37,%38,%39,%40,%41,%42,%43,%44,%45,%46,%47,%48,%49,%50,%51,%52,%53,%54,%55,%56,%57,%58,%59,%60,%61,%62,%63,%64,%65,%66,%67,%68,%69,%70,%71,%72,%73,%74,%75,%76,%77,%78,%79,%80,%81,%82,%83,%84,%85,%86,%87,%88,%89,%90,%91,%92,%93,%94,%95}, %96, %97, p, 1, 1, 0, 1;\n}\n"
    : "+f"(d[0]),"+f"(d[1]),"+f"(d[2]),"+f"(d[3]),"+f"(d[4]),"+f"(d[5]),"+f"(d[6]),"+f"(d[7]),"+f"(d[8]),"+f"(d[9]),"+f"(d[10]),"+f"(d[11]),"+f"(d[12]),"+f"(d[13]),"+f"(d[14]),"+f"(d[15]),"+f"(d[16]),"+f"(d[17]),"+f"(d[18]),"+f"(d[19]),"+f"(d[20]),"+f"(d[21]),"+f"(d[22]),"+f"(d[23]),"+f"(d[24]),"+f"(d[25]),"+f"(d[26]),"+f"(d[27]),"+f"(d[28]),"+f"(d[29]),"+f"(d[30]),"+f"(d[31]),"+f"(d[32]),"+f"(d[33]),"+f"(d[34]),"+f"(d[35]),"+f"(d[36]),"+f"(d[37]),"+f"(d[38]),"+f"(d[39]),"+f"(d[40]),"+f"(d[41]),"+f"(d[42]),"+f"(d[43]),"+f"(d[44]),"+f"(d[45]),"+f"(d[46]),"+f"(d[47]),"+f"(d[48]),"+f"(d[49]),"+f"(d[50]),"+f"(d[51]),"+f"(d[52]),"+f"(d[53]),"+f"(d[54]),"+f"(d[55]),"+f"(d[56]),"+f"(d[57]),"+f"(d[58]),"+f"(d[59]),"+f"(d[60]),"+f"(d[61]),"+f"(d[62]),"+f"(d[63]),"+f"(d[64]),"+f"(d[65]),"+f"(d[66]),"+f"(d[67]),"+f"(d[68]),"+f"(d[69]),"+f"(d[70]),"+f"(d[71]),"+f"(d[72]),"+f"(d[73]),"+f"(d[74]),"+f"(d[75]),"+f"(d[76]),"+f"(d[77]),"+f"(d[78]),"+f"(d[79]),"+f"(d[80]),"+f"(d[81]),"+f"(d[82]),"+f"(d[83]),"+f"(d[84]),"+f"(d[85]),"+f"(d[86]),"+f"(d[87]),"+f"(d[88]),"+f"(d[89]),"+f"(d[90]),"+f"(d[91]),"+f"(d[92]),"+f"(d[93]),"+f"(d[94]),"+f"(d[95])
    : "l"(da),"l"(db),"r"(sc));
}

__device__ __forceinline__ uint32_t smem_u32(const void* p) { return (uint32_t)__cvta_generic_to_shared(p); }
__device__ __forceinline__ void mbar_init(uint32_t bar, uint32_t cnt) { asm volatile("mbarrier.init.shared::cta.b64 [%0], %1;" :: "r"(bar), "r"(cnt)); }
__device__ __forceinline__ void mbar_expect_tx(uint32_t bar, uint32_t bytes) { asm volatile("mbarrier.arrive.expect_tx.shared::cta.b64 _, [%0], %1;" :: "r"(bar), "r"(bytes) : "memory"); }
__device__ __forceinline__ void mbar_arrive(uint32_t bar) { asm volatile("mbarrier.arrive.shared::cta.b64 _, [%0];" :: "r"(bar) : "memory"); }
__device__ __forceinline__ void mbar_arrive_cluster(uint32_t cbar, uint32_t cnt) { asm volatile("mbarrier.arrive.shared::cluster.b64 _, [%0], %1;" :: "r"(cbar), "r"(cnt) : "memory"); }
__device__ __forceinline__ uint32_t mapa(uint32_t a, uint32_t rank) { uint32_t r; asm volatile("mapa.shared::cluster.u32 %0, %1, %2;" : "=r"(r) : "r"(a), "r"(rank)); return r; }
__device__ __forceinline__ void mbar_wait(uint32_t bar, uint32_t parity) {
    uint32_t ok; uint32_t n = 0;
    do {
        asm volatile("{\n.reg .pred p;\nmbarrier.try_wait.parity.shared::cta.b64 p, [%1], %2;\nselp.u32 %0, 1, 0, p;\n}" : "=r"(ok) : "r"(bar), "r"(parity) : "memory");
    } while (!ok && ++n < (1u << 17));
}
__device__ __forceinline__ void pace_wait(uint32_t a, uint32_t target) {
    uint32_t v, n = 0;
    do {
        asm volatile("ld.volatile.shared.u32 %0, [%1];" : "=r"(v) : "r"(a) : "memory");
        if (v < target) __nanosleep(150);
    } while (v < target && ++n < (1u << 14));
}
__device__ __forceinline__ void flag_wait(const unsigned* p, unsigned target) {
    unsigned v; uint32_t n = 0;
    while (true) {
        asm volatile("ld.acquire.gpu.global.u32 %0, [%1];" : "=r"(v) : "l"(p) : "memory");
        if ((int)(v - target) >= 0 || ++n >= (1u << 17)) break;
        __nanosleep(40);
    }
}
__device__ __forceinline__ void flag_add(unsigned* p) {
    asm volatile("fence.acq_rel.gpu;\nred.relaxed.gpu.global.add.u32 [%0], 1;" :: "l"(p) : "memory");
}
__device__ __forceinline__ uint64_t make_desc(uint32_t addr, uint32_t lbo, uint32_t sbo, uint32_t swz) {
    return (uint64_t)((addr & 0x3FFFF) >> 4) | ((uint64_t)((lbo & 0x3FFFF) >> 4) << 16) | ((uint64_t)((sbo & 0x3FFFF) >> 4) << 32) | ((uint64_t)swz << 62);
}
__device__ __forceinline__ uint64_t desc_add(uint64_t d, uint32_t off16) {
    return (d & 0xFFFFFFFF00000000ull) | (uint64_t)((uint32_t)d + off16);
}
__device__ __forceinline__ void tma2d(uint32_t dst, const CUtensorMap* tm, int c0, int c1, uint32_t bar) {
    asm volatile("cp.async.bulk.tensor.2d.shared::cluster.global.mbarrier::complete_tx::bytes [%0], [%1, {%3, %4}], [%2];"
        :: "r"(dst), "l"((uint64_t)tm), "r"(bar), "r"(c0), "r"(c1) : "memory");
}
__device__ __forceinline__ void tma3d(uint32_t dst, const CUtensorMap* tm, int c0, int c1, int c2, uint32_t bar) {
    asm volatile("cp.async.bulk.tensor.3d.shared::cluster.global.mbarrier::complete_tx::bytes [%0], [%1, {%3, %4, %5}], [%2];"
        :: "r"(dst), "l"((uint64_t)tm), "r"(bar), "r"(c0), "r"(c1), "r"(c2) : "memory");
}
__device__ __forceinline__ void tma3d_mc(uint32_t dst, const CUtensorMap* tm, int c0, int c1, int c2, uint32_t bar) {
    asm volatile("cp.async.bulk.tensor.3d.shared::cluster.global.mbarrier::complete_tx::bytes.multicast::cluster [%0], [%1, {%3, %4, %5}], [%2], %6;"
        :: "r"(dst), "l"((uint64_t)tm), "r"(bar), "r"(c0), "r"(c1), "r"(c2), "h"((uint16_t)3) : "memory");
}
__device__ __forceinline__ void bulk_g2s(uint32_t dst, const void* src, uint32_t bytes, uint32_t bar) {
    asm volatile("cp.async.bulk.shared::cluster.global.mbarrier::complete_tx::bytes [%0], [%1], %2, [%3];"
        :: "r"(dst), "l"(src), "r"(bytes), "r"(bar) : "memory");
}
__device__ __forceinline__ void bulk_s2g(void* dst, uint32_t src, uint32_t bytes) {
    asm volatile("cp.async.bulk.global.shared::cta.bulk_group [%0], [%1], %2;" :: "l"(dst), "r"(src), "r"(bytes) : "memory");
}
__device__ __forceinline__ void tma2d_store(const CUtensorMap* tm, int c0, int c1, uint32_t src) {
    asm volatile("cp.async.bulk.tensor.2d.global.shared::cta.bulk_group [%0, {%2, %3}], [%1];"
        :: "l"((uint64_t)tm), "r"(src), "r"(c0), "r"(c1) : "memory");
}
__device__ __forceinline__ void l2_prefetch(const void* p, uint32_t bytes) {
    asm volatile("cp.async.bulk.prefetch.L2.global [%0], %1;" :: "l"(p), "r"(bytes) : "memory");
}
__device__ __forceinline__ void tmap_prefetch(const CUtensorMap* tm) { asm volatile("prefetch.tensormap [%0];" :: "l"((uint64_t)tm) : "memory"); }
__device__ __forceinline__ uint32_t lds32(uint32_t a) { uint32_t v; asm volatile("ld.shared.u32 %0, [%1];" : "=r"(v) : "r"(a)); return v; }
__device__ __forceinline__ uint2 lds64(uint32_t a) { uint2 v; asm volatile("ld.shared.v2.u32 {%0,%1}, [%2];" : "=r"(v.x), "=r"(v.y) : "r"(a)); return v; }
__device__ __forceinline__ uint4 lds128(uint32_t a) { uint4 v; asm volatile("ld.shared.v4.u32 {%0,%1,%2,%3}, [%4];" : "=r"(v.x), "=r"(v.y), "=r"(v.z), "=r"(v.w) : "r"(a)); return v; }
__device__ __forceinline__ float2 lds64f(uint32_t a) { float2 v; asm volatile("ld.shared.v2.f32 {%0,%1}, [%2];" : "=f"(v.x), "=f"(v.y) : "r"(a)); return v; }
__device__ __forceinline__ void sts32(uint32_t a, uint32_t v) { asm volatile("st.shared.u32 [%0], %1;" :: "r"(a), "r"(v) : "memory"); }
__device__ __forceinline__ void sts128(uint32_t a, uint4 v) { asm volatile("st.shared.v4.u32 [%0], {%1,%2,%3,%4};" :: "r"(a), "r"(v.x), "r"(v.y), "r"(v.z), "r"(v.w) : "memory"); }
__device__ __forceinline__ uint4 ldg_cg128(const void* p) { uint4 v; asm volatile("ld.global.cg.v4.u32 {%0,%1,%2,%3}, [%4];" : "=r"(v.x), "=r"(v.y), "=r"(v.z), "=r"(v.w) : "l"(p)); return v; }
__device__ __forceinline__ uint4 ldg_nc128(const void* p) { uint4 v; asm volatile("ld.global.nc.L1::no_allocate.v4.u32 {%0,%1,%2,%3}, [%4];" : "=r"(v.x), "=r"(v.y), "=r"(v.z), "=r"(v.w) : "l"(p)); return v; }
__device__ __forceinline__ uint32_t ldg_nc32(const void* p) { uint32_t v; asm volatile("ld.global.nc.u32 %0, [%1];" : "=r"(v) : "l"(p)); return v; }
__device__ __forceinline__ uint2 ldg_nc64(const void* p) { uint2 v; asm volatile("ld.global.nc.L1::no_allocate.v2.u32 {%0,%1}, [%2];" : "=r"(v.x), "=r"(v.y) : "l"(p)); return v; }
#define WG_FENCE() asm volatile("wgmma.fence.sync.aligned;\n" ::: "memory")
#define WG_COMMIT() asm volatile("wgmma.commit_group.sync.aligned;\n" ::: "memory")
template<int N> __device__ __forceinline__ void wg_wait() { asm volatile("wgmma.wait_group.sync.aligned %0;\n" :: "n"(N) : "memory"); }
__device__ __forceinline__ bool elect_one() {
    uint32_t pr;
    asm volatile("{\n.reg .pred p;\nelect.sync _|p, 0xffffffff;\nselp.u32 %0, 1, 0, p;\n}" : "=r"(pr));
    return pr != 0;
}
__device__ __forceinline__ void named_bar(int id, int n) { asm volatile("bar.sync %0, %1;" :: "r"(id), "r"(n) : "memory"); }

__device__ __forceinline__ float bf_lo(uint32_t u) { return __uint_as_float(u << 16); }
__device__ __forceinline__ float bf_hi(uint32_t u) { return __uint_as_float(u & 0xFFFF0000u); }
__device__ __forceinline__ uint32_t pack_bf(float lo, float hi) { uint32_t r; asm("cvt.rn.bf16x2.f32 %0, %1, %2;" : "=r"(r) : "f"(hi), "f"(lo)); return r; }
__device__ __forceinline__ float bf_round(float x) { return __bfloat162float(__float2bfloat16_rn(x)); }
__device__ __forceinline__ uint32_t bmul2(uint32_t a, uint32_t b) { uint32_t r; asm("mul.rn.bf16x2 %0, %1, %2;" : "=r"(r) : "r"(a), "r"(b)); return r; }
__device__ __forceinline__ uint32_t badd2(uint32_t a, uint32_t b) { uint32_t r; asm("add.rn.bf16x2 %0, %1, %2;" : "=r"(r) : "r"(a), "r"(b)); return r; }
__device__ __forceinline__ uint32_t bsub2(uint32_t a, uint32_t b) { uint32_t r; asm("sub.rn.bf16x2 %0, %1, %2;" : "=r"(r) : "r"(a), "r"(b)); return r; }
__device__ __forceinline__ void mma16816(float (&d)[4], uint32_t a0, uint32_t a1, uint32_t a2, uint32_t a3, uint2 b) {
    asm volatile("mma.sync.aligned.m16n8k16.row.col.f32.bf16.bf16.f32 {%0,%1,%2,%3}, {%4,%5,%6,%7}, {%8,%9}, {%0,%1,%2,%3};\n"
        : "+f"(d[0]), "+f"(d[1]), "+f"(d[2]), "+f"(d[3]) : "r"(a0), "r"(a1), "r"(a2), "r"(a3), "r"(b.x), "r"(b.y));
}

template<int HS> __device__ __forceinline__ void xreduce(float (&v)[8], int lane) {
    const int up = lane & HS;
    #pragma unroll
    for (int e = 0; e < HS; e++) {
        float keep, send;
        asm("{\n.reg .pred p;\nsetp.ne.b32 p, %4, 0;\nselp.f32 %0, %3, %2, p;\nselp.f32 %1, %2, %3, p;\n}"
            : "=f"(keep), "=f"(send) : "f"(v[e]), "f"(v[e + HS]), "r"(up));
        v[e] = keep + __shfl_xor_sync(0xffffffffu, send, HS);
    }
}

__device__ __forceinline__ int blk_f0(int s) {
    if (s < 32) return 32 * (14 * (s >> 3) + 8 * ((s >> 2) & 1) + (s & 3));
    const int s2 = s - 32, c6 = (s2 * 11) >> 6, t = s2 - 6 * c6;
    return 32 * (14 * c6 + (t < 4 ? 4 + t : 8 + t));
}
__device__ __forceinline__ int next_st2(int s) { return (0x14023 >> (4 * s)) & 7; }
__device__ __forceinline__ uint32_t stage_off_rt(int s) { return s < 3 ? SM_RING + s * STAGE_BYTES : (uint32_t)(s - 3) * 32768; }

__device__ __forceinline__ void store_h(uint32_t* dst, const uint32_t (&hp)[32], int q) {
    #pragma unroll
    for (int kk = 0; kk < 2; kk++) {
        uint32_t* d2 = dst + q * 2048 + kk * 512;
        d2[0] = hp[8 * q + 4 * kk]; d2[64] = hp[8 * q + 4 * kk + 1]; d2[32] = hp[8 * q + 4 * kk + 2]; d2[96] = hp[8 * q + 4 * kk + 3];
    }
}
struct RowStats { uint32_t m0, m1; float r0, r1; };
template<int NB, bool passA>
__device__ __forceinline__ void gemm1_pass(uint32_t sb, int wgi, int warp4, int lane, int& st, uint32_t& fph, uint32_t e_cl,
                                           uint32_t (&hp)[32], uint32_t* prev_dst, float* csp, int rank, RowStats& rs) {
    constexpr bool narrow = (NB == 2);
    float acc[NB * 32];
    const uint64_t descA0 = make_desc(sb + SM_X + wgi * 8192, 16, 1024, 1);
    const uint64_t descB0 = make_desc(sb + SM_RING, 4096, 512, 2);
    const uint32_t xa = sb + SM_X + (wgi * 64 + warp4 * 16 + (lane & 15)) * 128;
    float s0 = 0.f, q0 = 0.f, s1 = 0.f, q1 = 0.f;
    int prev = 0;
    {
        mbar_wait(sb + SM_BARS + (B_FULL + st) * 8, (fph >> st) & 1);
        const uint64_t db = desc_add(descB0, st * 2048 + wgi * (NB * 256) + rank * 128);
        WG_FENCE();
        wgmma_rs_half_tb(acc, 0x3F803F80u, 0x3F803F80u, 0x3F803F80u, 0x3F803F80u, db, 0);
        wgmma_rs_half_tb(acc, 0x3F803F80u, 0x3F803F80u, 0x3F803F80u, 0x3F803F80u, db + 64, 1);
        WG_COMMIT();
        wg_wait<0>();
        if (warp4 == 0) {
            if (lane < 4) {
                #pragma unroll
                for (int t = 0; t < NB * 4; t++) *(float2*)(csp + wgi * (NB * 32) + 8 * t + 2 * lane) = make_float2(acc[4 * t], acc[4 * t + 1]);
            }
            __syncwarp();
            if (lane == 0) mbar_arrive(sb + SM_BARS + (B_CSD + (passA ? 0 : 1)) * 8);
        }
    }
    auto group = [&](int sl) {
        if (warp4 == 0 && wgi == 0) PROF2(2, sl + (passA ? 0 : 8));
        if (passA) mbar_wait(sb + SM_BARS + (B_XFULL + sl) * 8, 0);
        mbar_wait(sb + SM_BARS + (B_FULL + st) * 8, (fph >> st) & 1);
        fph ^= 1u << st;
        if (sl == 0 && warp4 == 0) PROF(2 + wgi * 8 + (passA ? 0 : 3));
        if (warp4 == 0 && wgi == 0) PROF2(1, sl + (passA ? 0 : 8));
        const uint64_t da = desc_add(descA0, sl * (narrow ? 2048 : 1024)), db = desc_add(descB0, st * 2048);
        WG_FENCE();
        #pragma unroll
        for (int kk = 0; kk < (narrow ? 8 : 4); kk++) {
            int sc = (sl | kk) ? 1 : 0;
            if constexpr (!narrow) wgmma_ss_n256_tb(acc, da + kk * 2, db + kk * 64, sc);
            else wgmma_ss_n128_tb(acc, da + ((kk >> 2) * 1024 + (kk & 3) * 2), db + ((kk >> 2) * 1024 + (kk & 3) * 64), sc);
        }
        WG_COMMIT();
        if constexpr (passA) {
            uint32_t xf[4][4];
            #pragma unroll
            for (int e = 0; e < 4; e++)
                asm volatile("ldmatrix.sync.aligned.m8n8.x4.shared.b16 {%0,%1,%2,%3}, [%4];"
                    : "=r"(xf[e][0]), "=r"(xf[e][1]), "=r"(xf[e][2]), "=r"(xf[e][3])
                    : "r"(xa + sl * 16384 + (((2 * e + (lane >> 4)) ^ (lane & 7)) << 4)) : "memory");
            #pragma unroll
            for (int e = 0; e < 4; e++) {
                #pragma unroll
                for (int hh = 0; hh < 2; hh++) {
                    float lo = bf_lo(xf[e][2 * hh]), hi = bf_hi(xf[e][2 * hh]);
                    s0 += lo + hi; q0 = fmaf(lo, lo, q0); q0 = fmaf(hi, hi, q0);
                    lo = bf_lo(xf[e][2 * hh + 1]); hi = bf_hi(xf[e][2 * hh + 1]);
                    s1 += lo + hi; q1 = fmaf(lo, lo, q1); q1 = fmaf(hi, hi, q1);
                }
            }
        }
        wg_wait<1>();
        if (warp4 == 0 && wgi == 0) PROF2(3, sl + (passA ? 0 : 8));
        if (lane < 2 && sl && (!narrow || sl == 1)) mbar_arrive_cluster(e_cl + prev * 8, 1);
        if (narrow && sl == 2 && lane == 0) mbar_arrive(sb + SM_BARS + B_XFREE * 8);
        if (!passA && !narrow && sl == 4 && lane < 4) mbar_arrive_cluster(e_cl + (3 + (lane >> 1)) * 8, 1);
        prev = st;
        st = (st == 2) ? 0 : st + 1;
    };
    if constexpr (passA) {
        #pragma unroll 1
        for (int sl = 0; sl < 8; sl++) group(sl);
        #pragma unroll
        for (int o = 1; o < 4; o <<= 1) {
            s0 += __shfl_xor_sync(0xffffffffu, s0, o); q0 += __shfl_xor_sync(0xffffffffu, q0, o);
            s1 += __shfl_xor_sync(0xffffffffu, s1, o); q1 += __shfl_xor_sync(0xffffffffu, q1, o);
        }
        const float mean0 = s0 * (1.0f / DM), mean1 = s1 * (1.0f / DM);
        rs.m0 = pack_bf(mean0, mean0); rs.m1 = pack_bf(mean1, mean1);
        rs.r0 = 1.0f / bf_round(sqrtf(bf_round(bf_round(fmaxf(q0 * (1.0f / DM) - mean0 * mean0, 0.f)) + 1e-5f)));
        rs.r1 = 1.0f / bf_round(sqrtf(bf_round(bf_round(fmaxf(q1 * (1.0f / DM) - mean1 * mean1, 0.f)) + 1e-5f)));
    } else {
        #pragma unroll
        for (int sl = 0; sl < 4; sl++) { group(sl); store_h(prev_dst, hp, sl); }
        __syncwarp();
        if (lane == 0) mbar_arrive(sb + SM_BARS + (B_HD + wgi * 2) * 8);
        if constexpr (!narrow) {
            #pragma unroll 1
            for (int sl = 4; sl < 8; sl++) group(sl);
        }
    }
    mbar_wait(sb + SM_BARS + (B_CS + (passA ? 0 : 1)) * 8, 0);
    wg_wait<0>();
    if (lane < 2 && !narrow) mbar_arrive_cluster(e_cl + prev * 8, 1);
    if (!passA && lane == 0) mbar_arrive(sb + SM_BARS + B_G1DONE * 8);
    if (warp4 == 0) PROF(3 + wgi * 8 + (passA ? 0 : 3));
    const float m0 = bf_lo(rs.m0), m1 = bf_lo(rs.m1);
    const uint32_t csa = sb + SM_CS + (passA ? 0 : 1024) + (lane & 3) * 8;
    #pragma unroll
    for (int t = 0; t < NB * 4; t++) {
        const float* ag = &acc[4 * t];
        const float* au = &acc[NB * 16 + 4 * t];
        const float2 cg = lds64f(csa + t * 32), cu = lds64f(csa + NB * 128 + t * 32);
        hp[2 * t] = bmul2(pack_bf((ag[0] - m0 * cg.x) * rs.r0, (ag[1] - m0 * cg.y) * rs.r0), pack_bf((au[0] - m0 * cu.x) * rs.r0, (au[1] - m0 * cu.y) * rs.r0));
        hp[2 * t + 1] = bmul2(pack_bf((ag[2] - m1 * cg.x) * rs.r1, (ag[3] - m1 * cg.y) * rs.r1), pack_bf((au[2] - m1 * cu.x) * rs.r1, (au[3] - m1 * cu.y) * rs.r1));
    }
    if (warp4 == 0) PROF(4 + wgi * 8 + (passA ? 0 : 3));
}

__global__ void __cluster_dims__(2, 1, 1) __launch_bounds__(NTHREADS, 1)
fused_kernel(const __grid_constant__ Params p) {
    extern __shared__ __align__(1024) uint8_t smem_raw[];
    const uint32_t sb = smem_u32(smem_raw);
    const int tid = threadIdx.x, warp = tid >> 5, lane = tid & 31;
    const int b = blockIdx.x;
    const int rank = b & 1;
    const int j = (b >> 1) & 7;
    const int i = ((b >> 4) << 1) | rank;
    const int cb = j >> 1;
    const bool convCTA = j & 1;
    const int cidx = 4 * i + cb;

    const int rot = i >> 1;
    if (tid == 256) {
        for (int s = 0; s < 8; s++) mbar_init(sb + SM_BARS + (B_XFULL + s) * 8, 1);
        asm volatile("fence.proxy.async.shared::cta;" ::: "memory");
        for (int s = 0; s < 2; s++) {
            mbar_expect_tx(sb + SM_BARS + (B_XFULL + s) * 8, 16384);
            tma2d(sb + SM_X + s * 16384, &p.tm_x, 64 * ((s + rot) & 7), 128 * i, sb + SM_BARS + (B_XFULL + s) * 8);
        }
    }
    if (tid == 288) {
        tmap_prefetch(rank ? &p.tm_uA : &p.tm_gA);
        for (int s = 0; s < 5; s++) { mbar_init(sb + SM_BARS + (B_FULL + s) * 8, 1); mbar_init(sb + SM_BARS + (B_EMPTY + s) * 8, 16); }
        mbar_init(sb + SM_BARS + B_CONV * 8, 1);
        mbar_init(sb + SM_BARS + B_YT * 8, 1);
        mbar_init(sb + SM_BARS + B_XR * 8, 1);
        mbar_init(sb + SM_BARS + B_G1DONE * 8, 8);
        mbar_init(sb + SM_BARS + B_XFREE * 8, 8);
        for (int s = 0; s < 4; s++) mbar_init(sb + SM_BARS + (B_HD + s) * 8, 4);
        mbar_init(sb + SM_BARS + B_HRDY * 8, 1);
        for (int s = 0; s < 2; s++) { mbar_init(sb + SM_BARS + (B_CSD + s) * 8, 2); mbar_init(sb + SM_BARS + (B_CS + s) * 8, 1); }
        asm volatile("fence.mbarrier_init.release.cluster;" ::: "memory");
        asm volatile("fence.proxy.async.shared::cta;" ::: "memory");
    }
    __syncwarp();
    asm volatile("barrier.cluster.arrive.relaxed.aligned;\n" ::: "memory");
    asm volatile("barrier.cluster.wait.aligned;\n" ::: "memory");
    PROFW(1, 0);

    if (warp < 8) {
        asm volatile("setmaxnreg.inc.sync.aligned.u32 200;");
        const int wgi = warp >> 2, warp4 = warp & 3;
        const int g = lane >> 2, c = lane & 3;
        const uint32_t e_cl = mapa(sb + SM_BARS + B_EMPTY * 8, lane & 1);
        int st = 0; uint32_t fph = 0;
        uint32_t hp[32];
        uint32_t* const hdst = g_h + (size_t)(i * 56) * 2048 + wgi * 1024 + warp4 * 128 + lane;
        RowStats rs;
        float* const csp = g_csp + (j * 16 + i) * 256;
        gemm1_pass<4, true>(sb, wgi, warp4, lane, st, fph, e_cl, hp, hdst, csp, rank, rs);

        if (convCTA) {
            gemm1_pass<2, false>(sb, wgi, warp4, lane, st, fph, e_cl, hp, hdst + 4 * j * 2048, csp + 8 * 16 * 256, rank, rs);
            store_h(hdst + (36 + 6 * cb) * 2048, hp, 0); store_h(hdst + (36 + 6 * cb) * 2048, hp, 1);
            __syncwarp();
            if (lane == 0) mbar_arrive(sb + SM_BARS + (B_HD + wgi * 2 + 1) * 8);
            const int gch = 8 * cidx + warp;
            const uint32_t xb = sb + SM_CVX + warp * 4096;
            const uint32_t hb = sb + SM_CVH + warp * 4096;
            const uint32_t dw = ((const unsigned short*)p.ssm_D)[gch];
            const uint32_t d2 = dw | (dw << 16);
            mbar_wait(sb + SM_BARS + B_CONV * 8, 0);
            PROFW(32, 4);
            float acc[16][4];
            #pragma unroll
            for (int jj = 0; jj < 16; jj++) { acc[jj][0] = 0.f; acc[jj][1] = 0.f; acc[jj][2] = 0.f; acc[jj][3] = 0.f; }
            uint2 bh[8], bl0[8], bl1[8];
            uint32_t xl = xb + g * 32 + c * 8;
            uint32_t hl = hb + (g + 2 * c - 8) * 4;
            #pragma unroll
            for (int d = 0; d < 8; d++) { bl0[d] = lds64(xl + d * 256); bh[d] = lds64(xl + (8 + d) * 256); }
            uint32_t w[6];
            w[0] = 0; w[1] = 0; w[2] = 0;
            if (g + 2 * c >= 8) w[0] = lds32(hl);
            if (g + 2 * c >= 7) w[1] = lds32(hl + 4);
            if (g + 2 * c >= 6) w[2] = lds32(hl + 8);
            w[3] = lds32(hl + 2048); w[4] = lds32(hl + 2052); w[5] = lds32(hl + 2056);
            auto conv_m0 = [&](int m0, uint2 (&bl)[8], uint2 (&bn)[8]) {
                xl -= 32;
                #pragma unroll
                for (int k = 0; k < 8; k++) {
                    const uint32_t a0 = w[1], a1 = __byte_perm(w[0], w[1], 0x5432), a2 = w[2], a3 = __byte_perm(w[1], w[2], 0x5432);
                    const uint32_t c0 = w[4], c1 = __byte_perm(w[3], w[4], 0x5432), c2 = w[5], c3 = __byte_perm(w[4], w[5], 0x5432);
                    const uint32_t nx = (k < 7) ? hl + (k + 1) * 256 : hl + 32;
                    w[0] = lds32(nx); w[1] = lds32(nx + 4); w[2] = lds32(nx + 8);
                    w[3] = lds32(nx + 2048); w[4] = lds32(nx + 2052); w[5] = lds32(nx + 2056);
                    if (k > 0) bn[k] = lds64(xl + k * 256);
                    else { bn[0] = make_uint2(0, 0); if (g > m0) bn[0] = lds64(xl); }
                    #pragma unroll
                    for (int jj = k; jj < 16; jj++) mma16816(acc[jj], a0, a1, a2, a3, (jj - k < 8) ? bl[(jj - k) & 7] : bh[(jj - k) & 7]);
                    bh[7 - k] = lds64(xl + (15 - k) * 256);
                    #pragma unroll
                    for (int jj = k + 8; jj < 16; jj++) mma16816(acc[jj], c0, c1, c2, c3, bl[jj - k - 8]);
                }
                hl += 32;
            };
            #pragma unroll 1
            for (int m0 = 0; m0 < 8; m0 += 2) {
                conv_m0(m0, bl0, bl1);
                conv_m0(m0 + 1, bl1, bl0);
                PROFW(34 + (m0 >> 1), 4);
            }
            PROFW(33, 4);
            const uint32_t kvl = xb + c * 64 + (7 - g) * 4;
            uint32_t* ydst = (uint32_t*)(g_yT + (size_t)gch * SEQ + 32 * c + 2 * g);
            uint32_t kk0[16], kk1[16];
            #pragma unroll
            for (int jj = 0; jj < 16; jj++) { kk0[jj] = lds32(kvl + jj * 256); kk1[jj] = lds32(kvl + jj * 256 + 32); }
            #pragma unroll
            for (int jj = 0; jj < 16; jj++) {
                ydst[jj * 64] = badd2(pack_bf(acc[jj][2], acc[jj][0]), bmul2(__byte_perm(kk0[jj], kk0[jj], 0x1032), d2));
                ydst[jj * 64 + 8] = badd2(pack_bf(acc[jj][3], acc[jj][1]), bmul2(__byte_perm(kk1[jj], kk1[jj], 0x1032), d2));
            }
            __syncwarp();
            PROFW(44, 4);
            if (lane == 0) flag_add(&g_cnt_y[(cidx >> 4) * 32]);
            PROFW(46, 4);
        } else {
            gemm1_pass<4, false>(sb, wgi, warp4, lane, st, fph, e_cl, hp, hdst + 4 * j * 2048, csp + 8 * 16 * 256, rank, rs);
            float acc[64];
            const uint64_t descB0 = make_desc(sb, 4096, 1024, 1);
            const uint64_t descA0 = make_desc(sb + 16384 + wgi * 4096, 128, 256, 0);
            int sg = 3, p0 = 0; uint32_t ph = 6;
            PROFW(20, 0);
            auto g2 = [&](int u) {
                if (warp == 0 && !(u & 1)) PROF2(2, 16 + (u >> 1));
                mbar_wait(sb + SM_BARS + (B_FULL + sg) * 8, (ph >> sg) & 1);
                ph ^= 1u << sg;
                if (warp == 0 && !(u & 1)) PROF2(1, 16 + (u >> 1));
                const uint32_t o0 = stage_off_rt(sg) >> 4;
                const uint64_t da0 = desc_add(descA0, o0), db0 = desc_add(descB0, o0);
                WG_FENCE();
                #pragma unroll
                for (int kk = 0; kk < 4; kk++) wgmma_ss_n128_tb(acc, da0 + ((kk >> 1) * 512 + (kk & 1) * 128), db0 + ((kk >> 1) * 512 + (kk & 1) * 128), (u | kk) ? 1 : 0);
                WG_COMMIT();
                wg_wait<1>();
                if (warp == 0 && !(u & 1)) PROF2(3, 16 + (u >> 1));
                if (lane < 2 && u > 0 && u + 4 < 28) mbar_arrive_cluster(e_cl + p0 * 8, 1);
                p0 = sg;
                sg = next_st2(sg);
            };
            #pragma unroll
            for (int u = 0; u < 4; u++) { g2(u); store_h(hdst + (32 + 6 * cb) * 2048, hp, u); }
            __syncwarp();
            if (lane == 0) mbar_arrive(sb + SM_BARS + (B_HD + wgi * 2 + 1) * 8);
            #pragma unroll 1
            for (int u = 4; u < 28; u++) g2(u);
            wg_wait<0>();
            PROFW(27, 0);
            mbar_wait(sb + SM_BARS + B_XR * 8, 0);
            const int r0 = wgi * 64 + warp4 * 16 + g;
            const uint32_t xrow0 = sb + SM_XE + r0 * 128 + c * 4;
            const int mi = lane >> 3, lr = lane & 7;
            const uint32_t yaddr = sb + SM_YT + wgi * 16384 + ((mi >> 1) * 8 + lr) * 128 + (((2 * warp4 + (mi & 1)) ^ lr) << 4);
            uint32_t y[8][4], xv[16][2], nv[16][2], bv[16][2];
            #pragma unroll
            for (int t = 0; t < 16; t++) {
                const uint32_t off = (t >> 3) * 16384 + (((t & 7) ^ g) << 4);
                xv[t][0] = lds32(xrow0 + off); xv[t][1] = lds32(xrow0 + 1024 + off);
            }
            #pragma unroll
            for (int t = 0; t < 16; t++) {
                const uint32_t d0 = bsub2(xv[t][0], rs.m0), d1 = bsub2(xv[t][1], rs.m1);
                nv[t][0] = pack_bf(bf_lo(d0) * rs.r0, bf_hi(d0) * rs.r0); nv[t][1] = pack_bf(bf_lo(d1) * rs.r1, bf_hi(d1) * rs.r1);
            }
            #pragma unroll
            for (int t = 0; t < 16; t++) { bv[t][0] = pack_bf(acc[4 * t], acc[4 * t + 1]); bv[t][1] = pack_bf(acc[4 * t + 2], acc[4 * t + 3]); }
            mbar_wait(sb + SM_BARS + B_YT * 8, 0);
            PROFW(28, 0);
            #pragma unroll
            for (int t2 = 0; t2 < 8; t2++)
                asm volatile("ldmatrix.sync.aligned.m8n8.x4.trans.shared.b16 {%0,%1,%2,%3}, [%4];"
                    : "=r"(y[t2][0]), "=r"(y[t2][1]), "=r"(y[t2][2]), "=r"(y[t2][3]) : "r"(yaddr + t2 * 2048) : "memory");
            #pragma unroll
            for (int hf = 0; hf < 2; hf++) {
                #pragma unroll
                for (int t = 8 * hf; t < 8 * hf + 8; t++) {
                    const uint32_t off = (t >> 3) * 16384 + (((t & 7) ^ g) << 4);
                    sts32(xrow0 + off, badd2(badd2(xv[t][0], bmul2(nv[t][0], y[t >> 1][2 * (t & 1)])), bv[t][0]));
                    sts32(xrow0 + 1024 + off, badd2(badd2(xv[t][1], bmul2(nv[t][1], y[t >> 1][2 * (t & 1) + 1])), bv[t][1]));
                }
                asm volatile("fence.proxy.async.shared::cta;" ::: "memory");
                __syncwarp();
                if (lane == 0) tma2d_store(&p.tm_out, 128 * cb + 64 * hf, 128 * i + 16 * warp, sb + SM_XE + hf * 16384 + warp * 2048);
            }
            if (lane == 0) {
                asm volatile("cp.async.bulk.commit_group;" ::: "memory");
                asm volatile("cp.async.bulk.wait_group.read 0;" ::: "memory");
                PROFW(29, 0);
            }
        }
    } else {
        asm volatile("setmaxnreg.dec.sync.aligned.u32 104;");
        if (warp == 8) {
            int st = 0; uint32_t eph = 7;
            const int nit = convCTA ? 12 : 16;
            const int cblk = 14 * cb + 8 * (j & 1);
            #pragma unroll 1
            for (int it = 0; it < nit; it++) {
                const int pass = it >> 3, sl = it & 7;
                const uint32_t bar = sb + SM_BARS + (B_FULL + st) * 8, dst = sb + SM_RING + st * STAGE_BYTES;
                mbar_wait(sb + SM_BARS + (B_EMPTY + st) * 8, (eph >> st) & 1);
                eph ^= 1u << st;
                PROF2(0, it);
                if (elect_one()) {
                    mbar_expect_tx(bar, 32768);
                    if (pass && convCTA) {
                        const CUtensorMap* tm = rank ? &p.tm_uB : &p.tm_gB;
                        tma3d_mc(dst + rank * 8192, tm, 0, ((2 * sl + rot) & 7) * 64, cblk + 4, bar);
                        tma3d_mc(dst + 16384 + rank * 8192, tm, 0, ((2 * sl + 1 + rot) & 7) * 64, cblk + 4, bar);
                    } else {
                        tma3d_mc(dst + rank * 16384, rank ? &p.tm_uA : &p.tm_gA, 0, ((sl + rot) & 7) * 64, cblk + 4 * pass, bar);
                    }
                    if (it < 3) {
                        for (int s2 = 2 + 2 * it; s2 < 4 + 2 * it; s2++) {
                            mbar_expect_tx(sb + SM_BARS + (B_XFULL + s2) * 8, 16384);
                            tma2d(sb + SM_X + s2 * 16384, &p.tm_x, 64 * ((s2 + rot) & 7), 128 * i, sb + SM_BARS + (B_XFULL + s2) * 8);
                        }
                    }
                }
                st = (st == 2) ? 0 : st + 1;
            }
            if (!convCTA) {
                st = 3;
                const int f0_lane = blk_f0(2 * lane + rank);
                #pragma unroll 1
                for (int u = 0; u < 28; u++) {
                    const uint32_t bar = sb + SM_BARS + (B_FULL + st) * 8;
                    const int f0 = __shfl_sync(0xffffffffu, f0_lane, u);
                    mbar_wait(sb + SM_BARS + (B_EMPTY + st) * 8, (eph >> st) & 1);
                    eph ^= 1u << st;
                    if ((u & 1) == 0) PROF2(0, 16 + (u >> 1));
                    if (elect_one()) {
                        mbar_expect_tx(bar, 32768);
                        tma3d_mc(sb + stage_off_rt(st) + rank * 8192, &p.tm_w2, 0, f0, 2 * cb, bar);
                    }
                    st = next_st2(st);
                }
                PROF(48);
            }
        } else if (warp < 11) {
            mbar_wait(sb + SM_BARS + (B_XFULL + 7) * 8, 0);
            {
                const int q = lane & 3;
                const int t0 = 32 * (b >> 1) + 8 * q;
                const int ch0 = 256 * (b & 1) + 16 * (warp - 9) + 2 * (lane >> 2);
                const uint32_t* kp = (const uint32_t*)(p.k + (size_t)t0 * DM + ch0);
                const uint32_t* vp = (const uint32_t*)(p.v + (size_t)t0 * DM + ch0);
                __nv_bfloat16* dst0 = g_kvT + (size_t)ch0 * SEQ + (t0 ^ 8);
                #pragma unroll 1
                for (int rnd = 0; rnd < 2; rnd++) {
                    uint32_t kr[4][11], vr[4][8]; uint4 skw[4];
                    #pragma unroll
                    for (int u = 0; u < 4; u++) {
                        const int co = (rnd * 4 + u) * 16;
                        skw[u] = ldg_nc128(p.shift_k + 4 * (ch0 + 2 * co));
                        #pragma unroll
                        for (int r = 0; r < 11; r++) kr[u][r] = (r >= 3 || t0 > 0) ? ldg_nc32(kp + co + (r - 3) * (DM / 2)) : 0u;
                        #pragma unroll
                        for (int r = 0; r < 8; r++) vr[u][r] = ldg_nc32(vp + co + r * (DM / 2));
                    }
                    #pragma unroll
                    for (int u = 0; u < 4; u++) {
                        const uint32_t s0 = __byte_perm(skw[u].x, skw[u].z, 0x5410), s1 = __byte_perm(skw[u].x, skw[u].z, 0x7632);
                        const uint32_t s2 = __byte_perm(skw[u].y, skw[u].w, 0x5410), s3 = __byte_perm(skw[u].y, skw[u].w, 0x7632);
                        #pragma unroll
                        for (int r = 0; r < 8; r++) {
                            uint32_t a = bmul2(kr[u][r], s3);
                            a = badd2(a, bmul2(kr[u][r + 1], s2));
                            a = badd2(a, bmul2(kr[u][r + 2], s1));
                            a = badd2(a, bmul2(kr[u][r + 3], s0));
                            vr[u][r] = bmul2(a, vr[u][r]);
                        }
                        __nv_bfloat16* dst = dst0 + (size_t)((rnd * 4 + u) * 32) * SEQ;
                        *(uint4*)dst = make_uint4(__byte_perm(vr[u][7], vr[u][6], 0x5410), __byte_perm(vr[u][5], vr[u][4], 0x5410),
                                                  __byte_perm(vr[u][3], vr[u][2], 0x5410), __byte_perm(vr[u][1], vr[u][0], 0x5410));
                        *(uint4*)(dst + SEQ) = make_uint4(__byte_perm(vr[u][7], vr[u][6], 0x7632), __byte_perm(vr[u][5], vr[u][4], 0x7632),
                                                          __byte_perm(vr[u][3], vr[u][2], 0x7632), __byte_perm(vr[u][1], vr[u][0], 0x7632));
                    }
                    PROFW(57 + 2 * rnd, 9);
                }
                if (lane == 0) {
                    if (warp == 9) l2_prefetch(p.ssm_k + (size_t)(4 * b) * SEQ, 4 * SEQ * 2);
                    else l2_prefetch(p.wd + (size_t)b * (FF * DM / NCTA), FF * DM / NCTA * 2);
                }
            }
            asm volatile("fence.proxy.async.global;" ::: "memory");
            __syncwarp();
            if (lane == 0) {
                flag_add(&g_cnt_kv[0]);
                PROFW(50, 9);
                const int wgi = warp - 9;
                mbar_wait(sb + SM_BARS + (B_HD + wgi * 2) * 8, 0);
                flag_add(&g_flag_h[(i * 2 + 0) * 8]);
                mbar_wait(sb + SM_BARS + (B_HD + wgi * 2 + 1) * 8, 0);
                flag_add(&g_flag_h[(i * 2 + 1) * 8]);
                if (wgi == 1 && !convCTA) {
                    const unsigned ep = lds32(sb + SM_EPOCH);
                    mbar_wait(sb + SM_BARS + B_G1DONE * 8, 0);
                    mbar_expect_tx(sb + SM_BARS + B_XR * 8, 32768);
                    tma3d(sb + SM_XE, &p.tm_xe, 0, 128 * i, 2 * cb, sb + SM_BARS + B_XR * 8);
                    flag_wait(&g_flag_h[(i * 2 + 1) * 8], ep * 16);
                    mbar_arrive(sb + SM_BARS + B_HRDY * 8);
                    __nanosleep(3000);
                    flag_wait(&g_cnt_y[cb * 32], ep * 128);
                    PROF(49);
                    asm volatile("fence.proxy.async.global;" ::: "memory");
                    mbar_expect_tx(sb + SM_BARS + B_YT * 8, 32768);
                    tma2d(sb + SM_YT, &p.tm_yT, 128 * i, 128 * cb, sb + SM_BARS + B_YT * 8);
                    tma2d(sb + SM_YT + 16384, &p.tm_yT, 128 * i + 64, 128 * cb, sb + SM_BARS + B_YT * 8);
                }
            }
        } else {
            unsigned ep = 0;
            if (lane == 0) {
                l2_prefetch(p.wg + (size_t)b * (FF * DM / NCTA), FF * DM / NCTA * 2);
                l2_prefetch(p.wu + (size_t)b * (FF * DM / NCTA), FF * DM / NCTA * 2);
                ep = g_launch[b] + 1;
                g_launch[b] = ep;
                sts32(sb + SM_EPOCH, ep);
                tmap_prefetch(rank ? &p.tm_uB : &p.tm_gB);
                tmap_prefetch(&p.tm_w2); tmap_prefetch(&p.tm_yT); tmap_prefetch(&p.tm_out); tmap_prefetch(&p.tm_xe);
            }
            #pragma unroll 1
            for (int pass = 0; pass < 2; pass++) {
                if (lane == 0) {
                    mbar_wait(sb + SM_BARS + (B_CSD + pass) * 8, 0);
                    flag_add(&g_flag_cs[(pass * 8 + j) * 8]);
                    flag_wait(&g_flag_cs[(pass * 8 + j) * 8], ep * 16);
                }
                __syncwarp();
                const uint4* src = (const uint4*)(g_csp + (pass * 8 + j) * 16 * 256) + lane;
                #pragma unroll
                for (int hh = 0; hh < 2; hh++) {
                    uint4 v[16];
                    #pragma unroll
                    for (int q = 0; q < 16; q++) v[q] = ldg_cg128(src + q * 64 + hh * 32);
                    float t0 = 0.f, t1 = 0.f, t2 = 0.f, t3 = 0.f;
                    #pragma unroll
                    for (int q = 0; q < 16; q++) { t0 += __uint_as_float(v[q].x); t1 += __uint_as_float(v[q].y); t2 += __uint_as_float(v[q].z); t3 += __uint_as_float(v[q].w); }
                    sts128(sb + SM_CS + pass * 1024 + hh * 512 + lane * 16, make_uint4(__float_as_uint(t0), __float_as_uint(t1), __float_as_uint(t2), __float_as_uint(t3)));
                }
                __syncwarp();
                if (lane == 0) mbar_arrive(sb + SM_BARS + (B_CS + pass) * 8);
                PROF(51 + pass);
            }
            if (lane == 0) {
                if (convCTA) {
                    flag_wait(&g_cnt_kv[0], ep * 256);
                    asm volatile("fence.proxy.async.global;" ::: "memory");
                    PROF(53);
                    mbar_wait(sb + SM_BARS + B_XFREE * 8, 0);
                    PROF(54);
                    mbar_expect_tx(sb + SM_BARS + B_CONV * 8, 65536);
                    bulk_g2s(sb + SM_CVX, g_kvT + (size_t)(8 * cidx) * SEQ, 32768, sb + SM_BARS + B_CONV * 8);
                    bulk_g2s(sb + SM_CVH, p.ssm_k + (size_t)(8 * cidx) * SEQ, 32768, sb + SM_BARS + B_CONV * 8);
                } else {
                    mbar_wait(sb + SM_BARS + (B_HD + 0) * 8, 0);
                    flag_wait(&g_flag_h[(i * 2 + 0) * 8], ep * 16);
                }
            }
            __syncwarp();
            if (!convCTA) {
                asm volatile("fence.proxy.async.global;" ::: "memory");
                int st = 3; uint32_t eph = 1;
                const uint8_t* hsrc = (const uint8_t*)g_h + (size_t)i * 56 * 8192;
                #pragma unroll 1
                for (int u = 0; u < 28; u++) {
                    mbar_wait(sb + SM_BARS + (B_EMPTY + st) * 8, (eph >> st) & 1);
                    eph ^= 1u << st;
                    if (u == 16) {
                        mbar_wait(sb + SM_BARS + B_HRDY * 8, 0);
                        asm volatile("fence.proxy.async.global;" ::: "memory");
                    }
                    if (elect_one()) bulk_g2s(sb + stage_off_rt(st) + 16384, hsrc + u * 16384, 16384, sb + SM_BARS + (B_FULL + st) * 8);
                    st = next_st2(st);
                }
            }
        }
    }
}

typedef CUresult (*EncodeFn)(CUtensorMap*, CUtensorMapDataType, cuuint32_t, void*, const cuuint64_t*, const cuuint64_t*,
                             const cuuint32_t*, const cuuint32_t*, CUtensorMapInterleave, CUtensorMapSwizzle,
                             CUtensorMapL2promotion, CUtensorMapFloatOOBfill);

void encode(EncodeFn fn, CUtensorMap* tm, const void* base, int rank, const cuuint64_t* dims, const cuuint64_t* strides,
            const cuuint32_t* box, CUtensorMapSwizzle swz) {
    cuuint32_t es[5] = {1, 1, 1, 1, 1};
    fn(tm, CU_TENSOR_MAP_DATA_TYPE_BFLOAT16, rank, (void*)base, dims, strides, box, es, CU_TENSOR_MAP_INTERLEAVE_NONE, swz,
       CU_TENSOR_MAP_L2_PROMOTION_L2_128B, CU_TENSOR_MAP_FLOAT_OOB_FILL_NONE);
}

}

extern "C" void kernel_launch(void* const* d_in, const int* in_sizes, int n_in, void* d_out, int out_size) {
    (void)in_sizes; (void)n_in; (void)out_size;
    static EncodeFn enc = nullptr;
    static void* yT_ptr = nullptr;
    if (!enc) {
        void* fn = nullptr; cudaDriverEntryPointQueryResult qr;
        cudaGetDriverEntryPoint("cuTensorMapEncodeTiled", &fn, cudaEnableDefault, &qr);
        enc = (EncodeFn)fn;
        cudaGetSymbolAddress(&yT_ptr, g_yT);
        cudaFuncSetAttribute(fused_kernel, cudaFuncAttributeMaxDynamicSharedMemorySize, SM_TOTAL);
    }
    Params p;
    p.q = (const __nv_bfloat16*)d_in[0]; p.k = (const __nv_bfloat16*)d_in[1]; p.v = (const __nv_bfloat16*)d_in[2];
    p.shift_k = (const __nv_bfloat16*)d_in[3]; p.ssm_k = (const __nv_bfloat16*)d_in[4]; p.ssm_D = (const __nv_bfloat16*)d_in[5];
    p.wg = (const __nv_bfloat16*)d_in[7]; p.wu = (const __nv_bfloat16*)d_in[8]; p.wd = (const __nv_bfloat16*)d_in[9];
    {
        cuuint64_t dims[2] = {DM, SEQ}; cuuint64_t str[1] = {DM * 2};
        cuuint64_t dims3[3] = {64, SEQ, DM / 64}; cuuint64_t str3[2] = {DM * 2, 128};
        cuuint32_t box[2] = {64, 128}, boxe[3] = {64, 128, 2};
        encode(enc, &p.tm_x, p.q, 2, dims, str, box, CU_TENSOR_MAP_SWIZZLE_128B);
        encode(enc, &p.tm_xe, p.q, 3, dims3, str3, boxe, CU_TENSOR_MAP_SWIZZLE_128B);
        cuuint32_t box2[2] = {64, 16};
        encode(enc, &p.tm_out, d_out, 2, dims, str, box2, CU_TENSOR_MAP_SWIZZLE_128B);
    }
    {
        cuuint64_t dims[3] = {32, DM, FF / 32}; cuuint64_t str[2] = {FF * 2, 64};
        cuuint32_t boxA[3] = {32, 64, 4}, boxB[3] = {32, 64, 2};
        encode(enc, &p.tm_gA, p.wg, 3, dims, str, boxA, CU_TENSOR_MAP_SWIZZLE_64B);
        encode(enc, &p.tm_gB, p.wg, 3, dims, str, boxB, CU_TENSOR_MAP_SWIZZLE_64B);
        encode(enc, &p.tm_uA, p.wu, 3, dims, str, boxA, CU_TENSOR_MAP_SWIZZLE_64B);
        encode(enc, &p.tm_uB, p.wu, 3, dims, str, boxB, CU_TENSOR_MAP_SWIZZLE_64B);
    }
    {
        cuuint64_t dims[3] = {64, FF, DM / 64}; cuuint64_t str[2] = {DM * 2, 128};
        cuuint32_t box[3] = {64, 32, 2};
        encode(enc, &p.tm_w2, p.wd, 3, dims, str, box, CU_TENSOR_MAP_SWIZZLE_128B);
    }
    {
        cuuint64_t dims[2] = {SEQ, DM}; cuuint64_t str[1] = {SEQ * 2};
        cuuint32_t box[2] = {64, 128};
        encode(enc, &p.tm_yT, yT_ptr, 2, dims, str, box, CU_TENSOR_MAP_SWIZZLE_128B);
    }
    fused_kernel<<<NCTA, NTHREADS, SM_TOTAL>>>(p);
}
```

```cpp
#include <cuda_runtime.h>
#include <cuda_bf16.h>
#include <cuda.h>
#include <stdint.h>

namespace {

constexpr int SEQ = 2048, DM = 512, FF = 1792;
constexpr int NCTA = 128;
constexpr int NTHREADS = 384;
constexpr int STAGE_BYTES = 32768;

constexpr uint32_t SM_X = 0;
constexpr uint32_t SM_RING = 131072;
constexpr uint32_t SM_MISC = SM_RING + 3 * STAGE_BYTES;
constexpr uint32_t SM_BARS = SM_MISC;
constexpr uint32_t SM_EPOCH = SM_MISC + 248;
constexpr uint32_t SM_STATS = SM_MISC + 256;
constexpr uint32_t SM_TOTAL = SM_STATS + 1024;
static_assert(SM_TOTAL <= 232448, "smem");
constexpr uint32_t SM_CVX = 0;
constexpr uint32_t SM_CVH = 65536;
constexpr uint32_t SM_YT = 32768;
constexpr uint32_t SM_XE = 98304;

constexpr int B_FULL = 0, B_EMPTY = 5, B_XFULL = 10, B_CONV = 14, B_YT = 15, B_XR = 16, B_G1DONE = 17, B_HD = 18, B_HRDY = 22,
              B_XFREE = 24, B_EP = 25, B_KVLD = 26, B_LN = 27, B_COUNT = 28;
static_assert(B_COUNT * 8 <= 248, "barrier space");

__device__ __align__(128) uint32_t g_h[16 * 56 * 2048];
__device__ __align__(128) __nv_bfloat16 g_kvT[DM * SEQ];
__device__ __align__(128) __nv_bfloat16 g_yT[DM * SEQ];
__device__ unsigned g_launch[NCTA];
__device__ unsigned g_cnt_kv[32];
__device__ unsigned g_cnt_y[4 * 32];
__device__ unsigned g_flag_h[16 * 2 * 8];


struct Params {
    CUtensorMap tm_x, tm_gA, tm_gB, tm_uA, tm_uB, tm_w2, tm_yT, tm_out, tm_xe;
    const __nv_bfloat16 *q, *k, *v, *shift_k, *ssm_k, *ssm_D, *wg, *wu, *wd;
};

__device__ __forceinline__ void wgmma_rs_n32(float (&d)[16], uint32_t a0, uint32_t a1, uint32_t a2, uint32_t a3, uint64_t db, int sc) {
  asm volatile("{\n.reg .pred p;\nsetp.ne.b32 p, %21, 0;\n"
    "wgmma.mma_async.sync.aligned.m64n32k16.f32.bf16.bf16 {%0,%1,%2,%3,%4,%5,%6,%7,%8,%9,%10,%11,%12,%13,%14,%15}, {%16,%17,%18,%19}, %20, p, 1, 1, 0;\n}\n"
    : "+f"(d[0]),"+f"(d[1]),"+f"(d[2]),"+f"(d[3]),"+f"(d[4]),"+f"(d[5]),"+f"(d[6]),"+f"(d[7]),"+f"(d[8]),"+f"(d[9]),"+f"(d[10]),"+f"(d[11]),"+f"(d[12]),"+f"(d[13]),"+f"(d[14]),"+f"(d[15])
    : "r"(a0),"r"(a1),"r"(a2),"r"(a3),"l"(db),"r"(sc));
}
__device__ __forceinline__ void wgmma_rs_n128_tb(float (&d)[64], uint32_t a0, uint32_t a1, uint32_t a2, uint32_t a3, uint64_t db, int sc) {
  asm volatile("{\n.reg .pred p;\nsetp.ne.b32 p, %69, 0;\n"
    "wgmma.mma_async.sync.aligned.m64n128k16.f32.bf16.bf16 {%0,%1,%2,%3,%4,%5,%6,%7,%8,%9,%10,%11,%12,%13,%14,%15,%16,%17,%18,%19,%20,%21,%22,%23,%24,%25,%26,%27,%28,%29,%30,%31,%32,%33,%34,%35,%36,%37,%38,%39,%40,%41,%42,%43,%44,%45,%46,%47,%48,%49,%50,%51,%52,%53,%54,%55,%56,%57,%58,%59,%60,%61,%62,%63}, {%64,%65,%66,%67}, %68, p, 1, 1, 1;\n}\n"
    : "+f"(d[0]),"+f"(d[1]),"+f"(d[2]),"+f"(d[3]),"+f"(d[4]),"+f"(d[5]),"+f"(d[6]),"+f"(d[7]),"+f"(d[8]),"+f"(d[9]),"+f"(d[10]),"+f"(d[11]),"+f"(d[12]),"+f"(d[13]),"+f"(d[14]),"+f"(d[15]),"+f"(d[16]),"+f"(d[17]),"+f"(d[18]),"+f"(d[19]),"+f"(d[20]),"+f"(d[21]),"+f"(d[22]),"+f"(d[23]),"+f"(d[24]),"+f"(d[25]),"+f"(d[26]),"+f"(d[27]),"+f"(d[28]),"+f"(d[29]),"+f"(d[30]),"+f"(d[31]),"+f"(d[32]),"+f"(d[33]),"+f"(d[34]),"+f"(d[35]),"+f"(d[36]),"+f"(d[37]),"+f"(d[38]),"+f"(d[39]),"+f"(d[40]),"+f"(d[41]),"+f"(d[42]),"+f"(d[43]),"+f"(d[44]),"+f"(d[45]),"+f"(d[46]),"+f"(d[47]),"+f"(d[48]),"+f"(d[49]),"+f"(d[50]),"+f"(d[51]),"+f"(d[52]),"+f"(d[53]),"+f"(d[54]),"+f"(d[55]),"+f"(d[56]),"+f"(d[57]),"+f"(d[58]),"+f"(d[59]),"+f"(d[60]),"+f"(d[61]),"+f"(d[62]),"+f"(d[63])
    : "r"(a0),"r"(a1),"r"(a2),"r"(a3),"l"(db),"r"(sc));
}
__device__ __forceinline__ void wgmma_ss_n256_tb(float (&d)[128], uint64_t da, uint64_t db, int sc) {
  asm volatile("{\n.reg .pred p;\nsetp.ne.b32 p, %130, 0;\n"
    "wgmma.mma_async.sync.aligned.m64n256k16.f32.bf16.bf16 {%0,%1,%2,%3,%4,%5,%6,%7,%8,%9,%10,%11,%12,%13,%14,%15,%16,%17,%18,%19,%20,%21,%22,%23,%24,%25,%26,%27,%28,%29,%30,%31,%32,%33,%34,%35,%36,%37,%38,%39,%40,%41,%42,%43,%44,%45,%46,%47,%48,%49,%50,%51,%52,%53,%54,%55,%56,%57,%58,%59,%60,%61,%62,%63,%64,%65,%66,%67,%68,%69,%70,%71,%72,%73,%74,%75,%76,%77,%78,%79,%80,%81,%82,%83,%84,%85,%86,%87,%88,%89,%90,%91,%92,%93,%94,%95,%96,%97,%98,%99,%100,%101,%102,%103,%104,%105,%106,%107,%108,%109,%110,%111,%112,%113,%114,%115,%116,%117,%118,%119,%120,%121,%122,%123,%124,%125,%126,%127}, %128, %129, p, 1, 1, 0, 1;\n}\n"
    : "+f"(d[0]),"+f"(d[1]),"+f"(d[2]),"+f"(d[3]),"+f"(d[4]),"+f"(d[5]),"+f"(d[6]),"+f"(d[7]),"+f"(d[8]),"+f"(d[9]),"+f"(d[10]),"+f"(d[11]),"+f"(d[12]),"+f"(d[13]),"+f"(d[14]),"+f"(d[15]),"+f"(d[16]),"+f"(d[17]),"+f"(d[18]),"+f"(d[19]),"+f"(d[20]),"+f"(d[21]),"+f"(d[22]),"+f"(d[23]),"+f"(d[24]),"+f"(d[25]),"+f"(d[26]),"+f"(d[27]),"+f"(d[28]),"+f"(d[29]),"+f"(d[30]),"+f"(d[31]),"+f"(d[32]),"+f"(d[33]),"+f"(d[34]),"+f"(d[35]),"+f"(d[36]),"+f"(d[37]),"+f"(d[38]),"+f"(d[39]),"+f"(d[40]),"+f"(d[41]),"+f"(d[42]),"+f"(d[43]),"+f"(d[44]),"+f"(d[45]),"+f"(d[46]),"+f"(d[47]),"+f"(d[48]),"+f"(d[49]),"+f"(d[50]),"+f"(d[51]),"+f"(d[52]),"+f"(d[53]),"+f"(d[54]),"+f"(d[55]),"+f"(d[56]),"+f"(d[57]),"+f"(d[58]),"+f"(d[59]),"+f"(d[60]),"+f"(d[61]),"+f"(d[62]),"+f"(d[63]),"+f"(d[64]),"+f"(d[65]),"+f"(d[66]),"+f"(d[67]),"+f"(d[68]),"+f"(d[69]),"+f"(d[70]),"+f"(d[71]),"+f"(d[72]),"+f"(d[73]),"+f"(d[74]),"+f"(d[75]),"+f"(d[76]),"+f"(d[77]),"+f"(d[78]),"+f"(d[79]),"+f"(d[80]),"+f"(d[81]),"+f"(d[82]),"+f"(d[83]),"+f"(d[84]),"+f"(d[85]),"+f"(d[86]),"+f"(d[87]),"+f"(d[88]),"+f"(d[89]),"+f"(d[90]),"+f"(d[91]),"+f"(d[92]),"+f"(d[93]),"+f"(d[94]),"+f"(d[95]),"+f"(d[96]),"+f"(d[97]),"+f"(d[98]),"+f"(d[99]),"+f"(d[100]),"+f"(d[101]),"+f"(d[102]),"+f"(d[103]),"+f"(d[104]),"+f"(d[105]),"+f"(d[106]),"+f"(d[107]),"+f"(d[108]),"+f"(d[109]),"+f"(d[110]),"+f"(d[111]),"+f"(d[112]),"+f"(d[113]),"+f"(d[114]),"+f"(d[115]),"+f"(d[116]),"+f"(d[117]),"+f"(d[118]),"+f"(d[119]),"+f"(d[120]),"+f"(d[121]),"+f"(d[122]),"+f"(d[123]),"+f"(d[124]),"+f"(d[125]),"+f"(d[126]),"+f"(d[127])
    : "l"(da),"l"(db),"r"(sc));
}
__device__ __forceinline__ void wgmma_ss_n192_tb(float (&d)[96], uint64_t da, uint64_t db, int sc) {
  asm volatile("{\n.reg .pred p;\nsetp.ne.b32 p, %98, 0;\n"
    "wgmma.mma_async.sync.aligned.m64n192k16.f32.bf16.bf16 {%0,%1,%2,%3,%4,%5,%6,%7,%8,%9,%10,%11,%12,%13,%14,%15,%16,%17,%18,%19,%20,%21,%22,%23,%24,%25,%26,%27,%28,%29,%30,%31,%32,%33,%34,%35,%36,%37,%38,%39,%40,%41,%42,%43,%44,%45,%46,%47,%48,%49,%50,%51,%52,%53,%54,%55,%56,%57,%58,%59,%60,%61,%62,%63,%64,%65,%66,%67,%68,%69,%70,%71,%72,%73,%74,%75,%76,%77,%78,%79,%80,%81,%82,%83,%84,%85,%86,%87,%88,%89,%90,%91,%92,%93,%94,%95}, %96, %97, p, 1, 1, 0, 1;\n}\n"
    : "+f"(d[0]),"+f"(d[1]),"+f"(d[2]),"+f"(d[3]),"+f"(d[4]),"+f"(d[5]),"+f"(d[6]),"+f"(d[7]),"+f"(d[8]),"+f"(d[9]),"+f"(d[10]),"+f"(d[11]),"+f"(d[12]),"+f"(d[13]),"+f"(d[14]),"+f"(d[15]),"+f"(d[16]),"+f"(d[17]),"+f"(d[18]),"+f"(d[19]),"+f"(d[20]),"+f"(d[21]),"+f"(d[22]),"+f"(d[23]),"+f"(d[24]),"+f"(d[25]),"+f"(d[26]),"+f"(d[27]),"+f"(d[28]),"+f"(d[29]),"+f"(d[30]),"+f"(d[31]),"+f"(d[32]),"+f"(d[33]),"+f"(d[34]),"+f"(d[35]),"+f"(d[36]),"+f"(d[37]),"+f"(d[38]),"+f"(d[39]),"+f"(d[40]),"+f"(d[41]),"+f"(d[42]),"+f"(d[43]),"+f"(d[44]),"+f"(d[45]),"+f"(d[46]),"+f"(d[47]),"+f"(d[48]),"+f"(d[49]),"+f"(d[50]),"+f"(d[51]),"+f"(d[52]),"+f"(d[53]),"+f"(d[54]),"+f"(d[55]),"+f"(d[56]),"+f"(d[57]),"+f"(d[58]),"+f"(d[59]),"+f"(d[60]),"+f"(d[61]),"+f"(d[62]),"+f"(d[63]),"+f"(d[64]),"+f"(d[65]),"+f"(d[66]),"+f"(d[67]),"+f"(d[68]),"+f"(d[69]),"+f"(d[70]),"+f"(d[71]),"+f"(d[72]),"+f"(d[73]),"+f"(d[74]),"+f"(d[75]),"+f"(d[76]),"+f"(d[77]),"+f"(d[78]),"+f"(d[79]),"+f"(d[80]),"+f"(d[81]),"+f"(d[82]),"+f"(d[83]),"+f"(d[84]),"+f"(d[85]),"+f"(d[86]),"+f"(d[87]),"+f"(d[88]),"+f"(d[89]),"+f"(d[90]),"+f"(d[91]),"+f"(d[92]),"+f"(d[93]),"+f"(d[94]),"+f"(d[95])
    : "l"(da),"l"(db),"r"(sc));
}


__device__ __forceinline__ uint32_t smem_u32(const void* p) { return (uint32_t)__cvta_generic_to_shared(p); }
__device__ __forceinline__ void mbar_init(uint32_t bar, uint32_t cnt) { asm volatile("mbarrier.init.shared::cta.b64 [%0], %1;" :: "r"(bar), "r"(cnt)); }
__device__ __forceinline__ void mbar_expect_tx(uint32_t bar, uint32_t bytes) { asm volatile("mbarrier.arrive.expect_tx.shared::cta.b64 _, [%0], %1;" :: "r"(bar), "r"(bytes) : "memory"); }
__device__ __forceinline__ void mbar_arrive(uint32_t bar) { asm volatile("mbarrier.arrive.shared::cta.b64 _, [%0];" :: "r"(bar) : "memory"); }
__device__ __forceinline__ void mbar_arrive_cluster(uint32_t cbar, uint32_t cnt) { asm volatile("mbarrier.arrive.shared::cluster.b64 _, [%0], %1;" :: "r"(cbar), "r"(cnt) : "memory"); }
__device__ __forceinline__ uint32_t mapa(uint32_t a, uint32_t rank) { uint32_t r; asm volatile("mapa.shared::cluster.u32 %0, %1, %2;" : "=r"(r) : "r"(a), "r"(rank)); return r; }
__device__ __forceinline__ void mbar_wait(uint32_t bar, uint32_t parity) {
    uint32_t ok; uint32_t n = 0;
    do {
        asm volatile("{\n.reg .pred p;\nmbarrier.try_wait.parity.shared::cta.b64 p, [%1], %2;\nselp.u32 %0, 1, 0, p;\n}" : "=r"(ok) : "r"(bar), "r"(parity) : "memory");
    } while (!ok && ++n < (1u << 17));
}
__device__ __forceinline__ void flag_wait(const unsigned* p, unsigned target) {
    unsigned v; uint32_t n = 0;
    while (true) {
        asm volatile("ld.acquire.gpu.global.u32 %0, [%1];" : "=r"(v) : "l"(p) : "memory");
        if ((int)(v - target) >= 0 || ++n >= (1u << 17)) break;
        __nanosleep(40);
    }
}
__device__ __forceinline__ void flag_add(unsigned* p) {
    asm volatile("fence.acq_rel.gpu;\nred.relaxed.gpu.global.add.u32 [%0], 1;" :: "l"(p) : "memory");
}
__device__ __forceinline__ uint64_t make_desc(uint32_t addr, uint32_t lbo, uint32_t sbo, uint32_t swz) {
    return (uint64_t)((addr & 0x3FFFF) >> 4) | ((uint64_t)((lbo & 0x3FFFF) >> 4) << 16) | ((uint64_t)((sbo & 0x3FFFF) >> 4) << 32) | ((uint64_t)swz << 62);
}
__device__ __forceinline__ uint64_t desc_add(uint64_t d, uint32_t off16) {
    return (d & 0xFFFFFFFF00000000ull) | (uint64_t)((uint32_t)d + off16);
}
__device__ __forceinline__ void tma2d(uint32_t dst, const CUtensorMap* tm, int c0, int c1, uint32_t bar) {
    asm volatile("cp.async.bulk.tensor.2d.shared::cluster.global.mbarrier::complete_tx::bytes [%0], [%1, {%3, %4}], [%2];"
        :: "r"(dst), "l"((uint64_t)tm), "r"(bar), "r"(c0), "r"(c1) : "memory");
}
__device__ __forceinline__ void tma3d(uint32_t dst, const CUtensorMap* tm, int c0, int c1, int c2, uint32_t bar) {
    asm volatile("cp.async.bulk.tensor.3d.shared::cluster.global.mbarrier::complete_tx::bytes [%0], [%1, {%3, %4, %5}], [%2];"
        :: "r"(dst), "l"((uint64_t)tm), "r"(bar), "r"(c0), "r"(c1), "r"(c2) : "memory");
}
__device__ __forceinline__ void tma3d_mc(uint32_t dst, const CUtensorMap* tm, int c0, int c1, int c2, uint32_t bar) {
    asm volatile("cp.async.bulk.tensor.3d.shared::cluster.global.mbarrier::complete_tx::bytes.multicast::cluster [%0], [%1, {%3, %4, %5}], [%2], %6;"
        :: "r"(dst), "l"((uint64_t)tm), "r"(bar), "r"(c0), "r"(c1), "r"(c2), "h"((uint16_t)3) : "memory");
}
__device__ __forceinline__ void bulk_g2s(uint32_t dst, const void* src, uint32_t bytes, uint32_t bar) {
    asm volatile("cp.async.bulk.shared::cluster.global.mbarrier::complete_tx::bytes [%0], [%1], %2, [%3];"
        :: "r"(dst), "l"(src), "r"(bytes), "r"(bar) : "memory");
}
__device__ __forceinline__ void tma2d_store(const CUtensorMap* tm, int c0, int c1, uint32_t src) {
    asm volatile("cp.async.bulk.tensor.2d.global.shared::cta.bulk_group [%0, {%2, %3}], [%1];"
        :: "l"((uint64_t)tm), "r"(src), "r"(c0), "r"(c1) : "memory");
}
__device__ __forceinline__ void l2_prefetch(const void* p, uint32_t bytes) {
    asm volatile("cp.async.bulk.prefetch.L2.global [%0], %1;" :: "l"(p), "r"(bytes) : "memory");
}
__device__ __forceinline__ void tmap_prefetch(const CUtensorMap* tm) { asm volatile("prefetch.tensormap [%0];" :: "l"((uint64_t)tm) : "memory"); }
__device__ __forceinline__ uint32_t lds32(uint32_t a) { uint32_t v; asm volatile("ld.shared.u32 %0, [%1];" : "=r"(v) : "r"(a)); return v; }
__device__ __forceinline__ uint2 lds64(uint32_t a) { uint2 v; asm volatile("ld.shared.v2.u32 {%0,%1}, [%2];" : "=r"(v.x), "=r"(v.y) : "r"(a)); return v; }
__device__ __forceinline__ float2 lds64f(uint32_t a) { float2 v; asm volatile("ld.shared.v2.f32 {%0,%1}, [%2];" : "=f"(v.x), "=f"(v.y) : "r"(a)); return v; }
__device__ __forceinline__ uint4 lds128(uint32_t a) { uint4 v; asm volatile("ld.shared.v4.u32 {%0,%1,%2,%3}, [%4];" : "=r"(v.x), "=r"(v.y), "=r"(v.z), "=r"(v.w) : "r"(a)); return v; }
__device__ __forceinline__ void sts32(uint32_t a, uint32_t v) { asm volatile("st.shared.u32 [%0], %1;" :: "r"(a), "r"(v) : "memory"); }
__device__ __forceinline__ uint4 ldg_nc128(const void* p) { uint4 v; asm volatile("ld.global.nc.L1::no_allocate.v4.u32 {%0,%1,%2,%3}, [%4];" : "=r"(v.x), "=r"(v.y), "=r"(v.z), "=r"(v.w) : "l"(p)); return v; }
__device__ __forceinline__ uint32_t ldg_nc32(const void* p) { uint32_t v; asm volatile("ld.global.nc.u32 %0, [%1];" : "=r"(v) : "l"(p)); return v; }
#define WG_FENCE() asm volatile("wgmma.fence.sync.aligned;\n" ::: "memory")
#define WG_COMMIT() asm volatile("wgmma.commit_group.sync.aligned;\n" ::: "memory")
template<int N> __device__ __forceinline__ void wg_wait() { asm volatile("wgmma.wait_group.sync.aligned %0;\n" :: "n"(N) : "memory"); }
__device__ __forceinline__ bool elect_one() {
    uint32_t pr;
    asm volatile("{\n.reg .pred p;\nelect.sync _|p, 0xffffffff;\nselp.u32 %0, 1, 0, p;\n}" : "=r"(pr));
    return pr != 0;
}

__device__ __forceinline__ float bf_lo(uint32_t u) { return __uint_as_float(u << 16); }
__device__ __forceinline__ float bf_hi(uint32_t u) { return __uint_as_float(u & 0xFFFF0000u); }
__device__ __forceinline__ uint32_t pack_bf(float lo, float hi) { uint32_t r; asm("cvt.rn.bf16x2.f32 %0, %1, %2;" : "=r"(r) : "f"(hi), "f"(lo)); return r; }
__device__ __forceinline__ float bf_round(float x) { return __bfloat162float(__float2bfloat16_rn(x)); }
__device__ __forceinline__ uint32_t bmul2(uint32_t a, uint32_t b) { uint32_t r; asm("mul.rn.bf16x2 %0, %1, %2;" : "=r"(r) : "r"(a), "r"(b)); return r; }
__device__ __forceinline__ uint32_t badd2(uint32_t a, uint32_t b) { uint32_t r; asm("add.rn.bf16x2 %0, %1, %2;" : "=r"(r) : "r"(a), "r"(b)); return r; }
__device__ __forceinline__ uint32_t bsub2(uint32_t a, uint32_t b) { uint32_t r; asm("sub.rn.bf16x2 %0, %1, %2;" : "=r"(r) : "r"(a), "r"(b)); return r; }
__device__ __forceinline__ void mma16816(float (&d)[4], uint32_t a0, uint32_t a1, uint32_t a2, uint32_t a3, uint2 b) {
    asm volatile("mma.sync.aligned.m16n8k16.row.col.f32.bf16.bf16.f32 {%0,%1,%2,%3}, {%4,%5,%6,%7}, {%8,%9}, {%0,%1,%2,%3};\n"
        : "+f"(d[0]), "+f"(d[1]), "+f"(d[2]), "+f"(d[3]) : "r"(a0), "r"(a1), "r"(a2), "r"(a3), "r"(b.x), "r"(b.y));
}

__device__ __forceinline__ int blk_f0(int s) {
    if (s < 32) return 32 * (14 * (s >> 3) + 8 * ((s >> 2) & 1) + (s & 3));
    const int s2 = s - 32, c6 = (s2 * 11) >> 6, t = s2 - 6 * c6;
    return 32 * (14 * c6 + (t < 4 ? 4 + t : 8 + t));
}
__device__ __forceinline__ int next_st2(int s) { return (0x14023 >> (4 * s)) & 7; }
__device__ __forceinline__ uint32_t stage_off_rt(int s) { return s < 3 ? SM_RING + s * STAGE_BYTES : (uint32_t)(s - 3) * 65536; }

__device__ __forceinline__ void store_h(uint32_t* dst, const uint32_t (&hp)[32], int q) {
    *(uint4*)(dst + q * 2048) = make_uint4(hp[8 * q], hp[8 * q + 1], hp[8 * q + 2], hp[8 * q + 3]);
    *(uint4*)(dst + q * 2048 + 512) = make_uint4(hp[8 * q + 4], hp[8 * q + 5], hp[8 * q + 6], hp[8 * q + 7]);
}
template<int NB, bool passA>
__device__ __forceinline__ void gemm1_pass(uint32_t sb, int wgi, int warp4, int lane, int& st, uint32_t& fph, uint32_t e_cl,
                                           uint32_t (&hp)[32], uint32_t* prev_dst, bool convCTA) {
    constexpr bool narrow = (NB == 2);
    float acc[NB * 32];
    const uint64_t descA0 = make_desc(sb + SM_X + wgi * 65536, 16, 1024, 1);
    const uint64_t descB0 = make_desc(sb + SM_RING, narrow ? 8192 : 4096, 512, 2);
    int prev = 0;
    auto group = [&](int sl) {
        mbar_wait(sb + SM_BARS + (B_FULL + st) * 8, (fph >> st) & 1);
        fph ^= 1u << st;
        const uint64_t da = desc_add(descA0, sl * (narrow ? 1024 : 512)), db = desc_add(descB0, st * 2048);
        WG_FENCE();
        #pragma unroll
        for (int kk = 0; kk < (narrow ? 8 : 4); kk++) {
            int sc = (sl | kk) ? 1 : 0;
            if constexpr (!narrow) wgmma_ss_n256_tb(acc, da + kk * 2, db + kk * 64, sc);
            else wgmma_ss_n128_tb(acc, da + ((kk >> 2) * 512 + (kk & 3) * 2), db + kk * 64, sc);
        }
        WG_COMMIT();
        wg_wait<1>();
        if (lane < 2 && sl && (!narrow || sl == 1)) mbar_arrive_cluster(e_cl + prev * 8, 1);
        if (narrow && sl == 2 && lane == 0) mbar_arrive(sb + SM_BARS + B_XFREE * 8);
        if (!passA && !narrow && sl == 4 && lane < 4) mbar_arrive_cluster(e_cl + (3 + (lane >> 1)) * 8, 1);
        prev = st;
        st = (st == 2) ? 0 : st + 1;
    };
    if constexpr (passA) {
        #pragma unroll 1
        for (int sl = 0; sl < 8; sl++) group(sl);
    } else {
        #pragma unroll
        for (int sl = 0; sl < 4; sl++) { group(sl); store_h(prev_dst, hp, sl); }
        __syncwarp();
        if (lane == 0) mbar_arrive(sb + SM_BARS + (B_HD + wgi * 2) * 8);
        if constexpr (!narrow) {
            #pragma unroll 1
            for (int sl = 4; sl < 8; sl++) group(sl);
        }
    }
    wg_wait<0>();
    if (lane < 2 && (passA || !convCTA)) mbar_arrive_cluster(e_cl + prev * 8, 1);
    if (!passA && lane == 0) mbar_arrive(sb + SM_BARS + B_G1DONE * 8);
    const int g = lane >> 2;
    const int r0 = wgi * 64 + warp4 * 16 + g;
    const float s0 = __uint_as_float(lds32(sb + SM_STATS + r0 * 8 + 4)), s1 = __uint_as_float(lds32(sb + SM_STATS + (r0 + 8) * 8 + 4));
    #pragma unroll
    for (int t = 0; t < NB * 4; t++) {
        const float* ag = &acc[4 * t];
        const float* au = &acc[NB * 16 + 4 * t];
        hp[2 * t] = bmul2(pack_bf(ag[0] * s0, ag[1] * s0), pack_bf(au[0] * s0, au[1] * s0));
        hp[2 * t + 1] = bmul2(pack_bf(ag[2] * s1, ag[3] * s1), pack_bf(au[2] * s1, au[3] * s1));
    }
}

__global__ void __cluster_dims__(2, 1, 1) __launch_bounds__(NTHREADS, 1)
fused_kernel(const __grid_constant__ Params p) {
    extern __shared__ __align__(1024) uint8_t smem_raw[];
    const uint32_t sb = smem_u32(smem_raw);
    const int tid = threadIdx.x, warp = tid >> 5, lane = tid & 31;
    const int b = blockIdx.x;
    const int rank = b & 1;
    const int j = (b >> 1) & 7;
    const int i = ((b >> 4) << 1) | rank;
    const int cb = j >> 1;
    const bool convCTA = j & 1;
    const int cidx = 4 * i + cb;

    if (tid == 256) {
        mbar_init(sb + SM_BARS + B_XFULL * 8, 1);
        mbar_init(sb + SM_BARS + (B_XFULL + 1) * 8, 1);
        asm volatile("fence.proxy.async.shared::cta;" ::: "memory");
        mbar_expect_tx(sb + SM_BARS + B_XFULL * 8, 65536);
        tma3d(sb + SM_X, &p.tm_x, 0, 128 * i, 0, sb + SM_BARS + B_XFULL * 8);
        mbar_expect_tx(sb + SM_BARS + (B_XFULL + 1) * 8, 65536);
        tma3d(sb + SM_X + 65536, &p.tm_x, 0, 128 * i + 64, 0, sb + SM_BARS + (B_XFULL + 1) * 8);
    }
    if (tid == 288) {
        for (int s = 0; s < 5; s++) { mbar_init(sb + SM_BARS + (B_FULL + s) * 8, 1); mbar_init(sb + SM_BARS + (B_EMPTY + s) * 8, 16); }
        mbar_init(sb + SM_BARS + B_CONV * 8, 1);
        mbar_init(sb + SM_BARS + B_YT * 8, 1);
        mbar_init(sb + SM_BARS + B_XR * 8, 1);
        mbar_init(sb + SM_BARS + B_G1DONE * 8, 8);
        mbar_init(sb + SM_BARS + B_XFREE * 8, 8);
        mbar_init(sb + SM_BARS + B_KVLD * 8, 2);
        mbar_init(sb + SM_BARS + B_EP * 8, 1);
        mbar_init(sb + SM_BARS + B_LN * 8, 8);
        for (int s = 0; s < 4; s++) mbar_init(sb + SM_BARS + (B_HD + s) * 8, 4);
        for (int s = 0; s < 2; s++) mbar_init(sb + SM_BARS + (B_HRDY + s) * 8, 1);
        asm volatile("fence.mbarrier_init.release.cluster;" ::: "memory");
        asm volatile("fence.proxy.async.shared::cta;" ::: "memory");
    }
    __syncwarp();
    asm volatile("barrier.cluster.arrive.relaxed.aligned;\n" ::: "memory");
    asm volatile("barrier.cluster.wait.aligned;\n" ::: "memory");

    if (warp < 8) {
        asm volatile("setmaxnreg.inc.sync.aligned.u32 200;");
        const int wgi = warp >> 2, warp4 = warp & 3;
        const int g = lane >> 2, c = lane & 3;
        const uint32_t e_cl = mapa(sb + SM_BARS + B_EMPTY * 8, lane & 1);
        {
            const int lr16 = (lane & 7) + ((lane >> 3) & 1) * 8;
            const uint32_t xa = sb + SM_X + wgi * 65536 + (warp4 * 16 + lr16) * 128;
            uint32_t xf[32][4];
            float aS[4][4], aQ0[4][4], aQ1[4][4];
            #pragma unroll
            for (int e = 0; e < 4; e++) {
                #pragma unroll
                for (int f = 0; f < 4; f++) { aS[e][f] = 0.f; aQ0[e][f] = 0.f; aQ1[e][f] = 0.f; }
            }
            mbar_wait(sb + SM_BARS + (B_XFULL + wgi) * 8, 0);
            #pragma unroll
            for (int ks = 0; ks < 32; ks++) {
                const uint32_t a = xa + (ks >> 2) * 8192 + (((2 * (ks & 3) + (lane >> 4)) ^ (lane & 7)) << 4);
                asm volatile("ldmatrix.sync.aligned.m8n8.x4.shared.b16 {%0,%1,%2,%3}, [%4];"
                    : "=r"(xf[ks][0]), "=r"(xf[ks][1]), "=r"(xf[ks][2]), "=r"(xf[ks][3]) : "r"(a) : "memory");
            }
            #pragma unroll
            for (int ks = 0; ks < 32; ks++)
                mma16816(aS[ks & 3], xf[ks][0], xf[ks][1], xf[ks][2], xf[ks][3], make_uint2(0x3F803F80u, 0x3F803F80u));
            const float mean0 = ((aS[0][0] + aS[1][0]) + (aS[2][0] + aS[3][0])) * (1.0f / DM);
            const float mean1 = ((aS[0][2] + aS[1][2]) + (aS[2][2] + aS[3][2])) * (1.0f / DM);
            const uint32_t m0 = pack_bf(mean0, mean0), m1 = pack_bf(mean1, mean1);
            #pragma unroll
            for (int ks = 0; ks < 32; ks++) {
                const uint32_t a = xa + (ks >> 2) * 8192 + (((2 * (ks & 3) + (lane >> 4)) ^ (lane & 7)) << 4);
                asm volatile("stmatrix.sync.aligned.m8n8.x4.shared.b16 [%0], {%1,%2,%3,%4};"
                    :: "r"(a), "r"(bsub2(xf[ks][0], m0)), "r"(bsub2(xf[ks][1], m1)), "r"(bsub2(xf[ks][2], m0)), "r"(bsub2(xf[ks][3], m1)) : "memory");
            }
            asm volatile("fence.proxy.async.shared::cta;" ::: "memory");
            __syncwarp();
            if (lane == 0) mbar_arrive(sb + SM_BARS + B_LN * 8);
            #pragma unroll
            for (int ks = 0; ks < 32; ks++) {
                mma16816(aQ0[ks & 3], xf[ks][0], xf[ks][1], xf[ks][2], xf[ks][3], make_uint2(xf[ks][0], xf[ks][2]));
                mma16816(aQ1[ks & 3], xf[ks][0], xf[ks][1], xf[ks][2], xf[ks][3], make_uint2(xf[ks][1], xf[ks][3]));
            }
            if (c == (g >> 1)) {
                const float q0 = (g & 1) ? (aQ0[0][1] + aQ0[1][1]) + (aQ0[2][1] + aQ0[3][1]) : (aQ0[0][0] + aQ0[1][0]) + (aQ0[2][0] + aQ0[3][0]);
                const float q1 = (g & 1) ? (aQ1[0][3] + aQ1[1][3]) + (aQ1[2][3] + aQ1[3][3]) : (aQ1[0][2] + aQ1[1][2]) + (aQ1[2][2] + aQ1[3][2]);
                const float sd0 = bf_round(sqrtf(bf_round(bf_round(fmaxf(q0 * (1.0f / DM) - mean0 * mean0, 0.f)) + 1e-5f)));
                const float sd1 = bf_round(sqrtf(bf_round(bf_round(fmaxf(q1 * (1.0f / DM) - mean1 * mean1, 0.f)) + 1e-5f)));
                const uint32_t sa = sb + SM_STATS + (warp * 16 + g) * 8;
                sts32(sa, m0); sts32(sa + 4, __float_as_uint(1.0f / sd0));
                sts32(sa + 64, m1); sts32(sa + 68, __float_as_uint(1.0f / sd1));
            }
            mbar_wait(sb + SM_BARS + B_LN * 8, 0);
        }
        int st = 0; uint32_t fph = 0;
        uint32_t hp[32];
        uint32_t* const hdst = g_h + (size_t)(i * 56) * 2048 + wgi * 1024 + warp4 * 128 + lane * 4;
        gemm1_pass<4, true>(sb, wgi, warp4, lane, st, fph, e_cl, hp, hdst, convCTA);

        if (convCTA) {
            gemm1_pass<2, false>(sb, wgi, warp4, lane, st, fph, e_cl, hp, hdst + 4 * j * 2048, true);
            store_h(hdst + (36 + 6 * cb) * 2048, hp, 0); store_h(hdst + (36 + 6 * cb) * 2048, hp, 1);
            __syncwarp();
            if (lane == 0) mbar_arrive(sb + SM_BARS + (B_HD + wgi * 2 + 1) * 8);
            const int gch = 8 * cidx + warp;
            const uint32_t xb = sb + SM_CVX + warp * 4096;
            const uint32_t hb = sb + SM_CVH + warp * 4096;
            const uint32_t dw = ((const unsigned short*)p.ssm_D)[gch];
            const uint32_t d2 = dw | (dw << 16);
            mbar_wait(sb + SM_BARS + B_CONV * 8, 0);
            float acc[16][4];
            #pragma unroll
            for (int jj = 0; jj < 16; jj++) { acc[jj][0] = 0.f; acc[jj][1] = 0.f; acc[jj][2] = 0.f; acc[jj][3] = 0.f; }
            uint2 bh[8], bl0[8], bl1[8];
            uint32_t xl = xb + g * 32 + c * 8;
            uint32_t hl = hb + (g + 2 * c - 8) * 4;
            #pragma unroll
            for (int d = 0; d < 8; d++) { bl0[d] = lds64(xl + d * 256); bh[d] = lds64(xl + (8 + d) * 256); }
            uint32_t w[6];
            w[0] = 0; w[1] = 0; w[2] = 0;
            if (g + 2 * c >= 8) w[0] = lds32(hl);
            if (g + 2 * c >= 7) w[1] = lds32(hl + 4);
            if (g + 2 * c >= 6) w[2] = lds32(hl + 8);
            w[3] = lds32(hl + 2048); w[4] = lds32(hl + 2052); w[5] = lds32(hl + 2056);
            auto conv_m0 = [&](int m0, uint2 (&bl)[8], uint2 (&bn)[8]) {
                xl -= 32;
                #pragma unroll
                for (int k = 0; k < 8; k++) {
                    const uint32_t a0 = w[1], a1 = __byte_perm(w[0], w[1], 0x5432), a2 = w[2], a3 = __byte_perm(w[1], w[2], 0x5432);
                    const uint32_t c0 = w[4], c1 = __byte_perm(w[3], w[4], 0x5432), c2 = w[5], c3 = __byte_perm(w[4], w[5], 0x5432);
                    const uint32_t nx = (k < 7) ? hl + (k + 1) * 256 : hl + 32;
                    w[0] = lds32(nx); w[1] = lds32(nx + 4); w[2] = lds32(nx + 8);
                    w[3] = lds32(nx + 2048); w[4] = lds32(nx + 2052); w[5] = lds32(nx + 2056);
                    if (k > 0) bn[k] = lds64(xl + k * 256);
                    else { bn[0] = make_uint2(0, 0); if (g > m0) bn[0] = lds64(xl); }
                    #pragma unroll
                    for (int jj = k; jj < 16; jj++) mma16816(acc[jj], a0, a1, a2, a3, (jj - k < 8) ? bl[(jj - k) & 7] : bh[(jj - k) & 7]);
                    bh[7 - k] = lds64(xl + (15 - k) * 256);
                    #pragma unroll
                    for (int jj = k + 8; jj < 16; jj++) mma16816(acc[jj], c0, c1, c2, c3, bl[jj - k - 8]);
                }
                hl += 32;
            };
            #pragma unroll 1
            for (int m0 = 0; m0 < 8; m0 += 2) {
                conv_m0(m0, bl0, bl1);
                conv_m0(m0 + 1, bl1, bl0);
            }
            const uint32_t kvl = xb + c * 64 + (7 - g) * 4;
            uint32_t* ydst = (uint32_t*)(g_yT + (size_t)gch * SEQ + 32 * c + 2 * g);
            uint32_t kk0[16], kk1[16];
            #pragma unroll
            for (int jj = 0; jj < 16; jj++) { kk0[jj] = lds32(kvl + jj * 256); kk1[jj] = lds32(kvl + jj * 256 + 32); }
            #pragma unroll
            for (int jj = 0; jj < 16; jj++) {
                ydst[jj * 64] = badd2(pack_bf(acc[jj][2], acc[jj][0]), bmul2(__byte_perm(kk0[jj], kk0[jj], 0x1032), d2));
                ydst[jj * 64 + 8] = badd2(pack_bf(acc[jj][3], acc[jj][1]), bmul2(__byte_perm(kk1[jj], kk1[jj], 0x1032), d2));
            }
            __syncwarp();
            if (lane == 0) flag_add(&g_cnt_y[(cidx >> 4) * 32]);
        } else {
            gemm1_pass<4, false>(sb, wgi, warp4, lane, st, fph, e_cl, hp, hdst + 4 * j * 2048, false);
            float acc[64];
            const uint64_t descB0 = make_desc(sb, 4096, 1024, 1);
            const uint32_t ha = sb + 16384 + wgi * 4096 + warp4 * 512 + lane * 16;
            int sg = 3, p0 = 0; uint32_t ph = 6;
            uint4 af0[4], af1[4];
            auto load_a = [&](uint4 (&af)[4], int s) {
                mbar_wait(sb + SM_BARS + (B_FULL + s) * 8, (ph >> s) & 1);
                ph ^= 1u << s;
                const uint32_t a = ha + stage_off_rt(s);
                #pragma unroll
                for (int kk = 0; kk < 4; kk++) af[kk] = lds128(a + (kk >> 1) * 8192 + (kk & 1) * 2048);
            };
            auto g2 = [&](int u, uint4 (&cur)[4], uint4 (&nxt)[4], bool more) {
                const uint64_t db0 = desc_add(descB0, stage_off_rt(sg) >> 4);
                WG_FENCE();
                #pragma unroll
                for (int kk = 0; kk < 4; kk++) wgmma_rs_n128_tb(acc, cur[kk].x, cur[kk].y, cur[kk].z, cur[kk].w, db0 + ((kk >> 1) * 512 + (kk & 1) * 128), (u | kk) ? 1 : 0);
                WG_COMMIT();
                wg_wait<1>();
                if (lane < 2 && u > 0 && u + 4 < 28) mbar_arrive_cluster(e_cl + p0 * 8, 1);
                p0 = sg;
                sg = next_st2(sg);
                if (more) load_a(nxt, sg);
            };
            load_a(af0, sg);
            #pragma unroll
            for (int u = 0; u < 4; u += 2) {
                g2(u, af0, af1, true); store_h(hdst + (32 + 6 * cb) * 2048, hp, u);
                g2(u + 1, af1, af0, true); store_h(hdst + (32 + 6 * cb) * 2048, hp, u + 1);
            }
            __syncwarp();
            if (lane == 0) mbar_arrive(sb + SM_BARS + (B_HD + wgi * 2 + 1) * 8);
            #pragma unroll 1
            for (int u = 4; u < 26; u += 2) { g2(u, af0, af1, true); g2(u + 1, af1, af0, true); }
            g2(26, af0, af1, true);
            g2(27, af1, af0, false);
            wg_wait<0>();
            mbar_wait(sb + SM_BARS + B_XR * 8, 0);
            const int r0 = wgi * 64 + warp4 * 16 + g;
            const float2 st0 = lds64f(sb + SM_STATS + r0 * 8), st1 = lds64f(sb + SM_STATS + (r0 + 8) * 8);
            const uint32_t m0 = __float_as_uint(st0.x), m1 = __float_as_uint(st1.x);
            const uint32_t xrow0 = sb + SM_XE + r0 * 128 + c * 4;
            const int mi = lane >> 3, lr = lane & 7;
            const uint32_t yaddr = sb + SM_YT + wgi * 16384 + ((mi >> 1) * 8 + lr) * 128 + (((2 * warp4 + (mi & 1)) ^ lr) << 4);
            uint32_t y[8][4], xv[16][2], nv[16][2], bv[16][2];
            #pragma unroll
            for (int t = 0; t < 16; t++) {
                const uint32_t off = (t >> 3) * 16384 + (((t & 7) ^ g) << 4);
                xv[t][0] = lds32(xrow0 + off); xv[t][1] = lds32(xrow0 + 1024 + off);
            }
            #pragma unroll
            for (int t = 0; t < 16; t++) {
                const uint32_t d0 = bsub2(xv[t][0], m0), d1 = bsub2(xv[t][1], m1);
                nv[t][0] = pack_bf(bf_lo(d0) * st0.y, bf_hi(d0) * st0.y); nv[t][1] = pack_bf(bf_lo(d1) * st1.y, bf_hi(d1) * st1.y);
            }
            #pragma unroll
            for (int t = 0; t < 16; t++) { bv[t][0] = pack_bf(acc[4 * t], acc[4 * t + 1]); bv[t][1] = pack_bf(acc[4 * t + 2], acc[4 * t + 3]); }
            mbar_wait(sb + SM_BARS + B_YT * 8, 0);
            #pragma unroll
            for (int t2 = 0; t2 < 8; t2++)
                asm volatile("ldmatrix.sync.aligned.m8n8.x4.trans.shared.b16 {%0,%1,%2,%3}, [%4];"
                    : "=r"(y[t2][0]), "=r"(y[t2][1]), "=r"(y[t2][2]), "=r"(y[t2][3]) : "r"(yaddr + t2 * 2048) : "memory");
            #pragma unroll
            for (int hf = 0; hf < 2; hf++) {
                #pragma unroll
                for (int t = 8 * hf; t < 8 * hf + 8; t++) {
                    const uint32_t off = (t >> 3) * 16384 + (((t & 7) ^ g) << 4);
                    sts32(xrow0 + off, badd2(badd2(xv[t][0], bmul2(nv[t][0], y[t >> 1][2 * (t & 1)])), bv[t][0]));
                    sts32(xrow0 + 1024 + off, badd2(badd2(xv[t][1], bmul2(nv[t][1], y[t >> 1][2 * (t & 1) + 1])), bv[t][1]));
                }
                asm volatile("fence.proxy.async.shared::cta;" ::: "memory");
                __syncwarp();
                if (lane == 0) tma2d_store(&p.tm_out, 128 * cb + 64 * hf, 128 * i + 16 * warp, sb + SM_XE + hf * 16384 + warp * 2048);
            }
            if (lane == 0) {
                asm volatile("cp.async.bulk.commit_group;" ::: "memory");
                asm volatile("cp.async.bulk.wait_group.read 0;" ::: "memory");
            }
        }
    } else {
        asm volatile("setmaxnreg.dec.sync.aligned.u32 104;");
        if (warp == 8) {
            int st = 0; uint32_t eph = 7;
            const int nit = convCTA ? 12 : 16;
            #pragma unroll 1
            for (int it = 0; it < nit; it++) {
                const int pass = it >> 3, sl = it & 7;
                const bool narrow = pass && convCTA;
                const CUtensorMap* tm = narrow ? (rank ? &p.tm_uB : &p.tm_gB) : (rank ? &p.tm_uA : &p.tm_gA);
                mbar_wait(sb + SM_BARS + (B_EMPTY + st) * 8, (eph >> st) & 1);
                eph ^= 1u << st;
                if (it == 1) mbar_wait(sb + SM_BARS + B_XFULL * 8, 0);
                if (elect_one()) {
                    mbar_expect_tx(sb + SM_BARS + (B_FULL + st) * 8, 32768);
                    tma3d_mc(sb + SM_RING + st * STAGE_BYTES + rank * 16384, tm, 0, sl * (narrow ? 128 : 64), 14 * cb + 8 * (j & 1) + 4 * pass, sb + SM_BARS + (B_FULL + st) * 8);
                }
                st = (st == 2) ? 0 : st + 1;
            }
            if (!convCTA) {
                st = 3;
                const int f0_lane = blk_f0(2 * lane + rank);
                #pragma unroll 1
                for (int u = 0; u < 28; u++) {
                    const uint32_t bar = sb + SM_BARS + (B_FULL + st) * 8;
                    const int f0 = __shfl_sync(0xffffffffu, f0_lane, u);
                    mbar_wait(sb + SM_BARS + (B_EMPTY + st) * 8, (eph >> st) & 1);
                    eph ^= 1u << st;
                    if (elect_one()) {
                        mbar_expect_tx(bar, 32768);
                        tma3d_mc(sb + stage_off_rt(st) + rank * 8192, &p.tm_w2, 0, f0, 2 * cb, bar);
                    }
                    st = next_st2(st);
                }
            }
        } else if (warp < 11) {
            mbar_wait(sb + SM_BARS + (B_XFULL + 1) * 8, 0);
            {
                const int q = lane & 3;
                const int t0 = 32 * (b >> 1) + 8 * q;
                const int ch0 = 256 * (b & 1) + 16 * (warp - 9) + 2 * (lane >> 2);
                const uint32_t* kp = (const uint32_t*)(p.k + (size_t)t0 * DM + ch0);
                const uint32_t* vp = (const uint32_t*)(p.v + (size_t)t0 * DM + ch0);
                __nv_bfloat16* dst0 = g_kvT + (size_t)ch0 * SEQ + (t0 ^ 8);
                #pragma unroll 1
                for (int rnd = 0; rnd < 2; rnd++) {
                    uint32_t kr[4][11], vr[4][8]; uint4 skw[4];
                    #pragma unroll
                    for (int u = 0; u < 4; u++) {
                        const int co = (rnd * 4 + u) * 16;
                        skw[u] = ldg_nc128(p.shift_k + 4 * (ch0 + 2 * co));
                        #pragma unroll
                        for (int r = 0; r < 11; r++) kr[u][r] = (r >= 3 || t0 > 0) ? ldg_nc32(kp + co + (r - 3) * (DM / 2)) : 0u;
                        #pragma unroll
                        for (int r = 0; r < 8; r++) vr[u][r] = ldg_nc32(vp + co + r * (DM / 2));
                    }
                    #pragma unroll
                    for (int u = 0; u < 4; u++) {
                        const uint32_t s0 = __byte_perm(skw[u].x, skw[u].z, 0x5410), s1 = __byte_perm(skw[u].x, skw[u].z, 0x7632);
                        const uint32_t s2 = __byte_perm(skw[u].y, skw[u].w, 0x5410), s3 = __byte_perm(skw[u].y, skw[u].w, 0x7632);
                        #pragma unroll
                        for (int r = 0; r < 8; r++) {
                            uint32_t a = bmul2(kr[u][r], s3);
                            a = badd2(a, bmul2(kr[u][r + 1], s2));
                            a = badd2(a, bmul2(kr[u][r + 2], s1));
                            a = badd2(a, bmul2(kr[u][r + 3], s0));
                            vr[u][r] = bmul2(a, vr[u][r]);
                        }
                        __nv_bfloat16* dst = dst0 + (size_t)((rnd * 4 + u) * 32) * SEQ;
                        *(uint4*)dst = make_uint4(__byte_perm(vr[u][7], vr[u][6], 0x5410), __byte_perm(vr[u][5], vr[u][4], 0x5410),
                                                  __byte_perm(vr[u][3], vr[u][2], 0x5410), __byte_perm(vr[u][1], vr[u][0], 0x5410));
                        *(uint4*)(dst + SEQ) = make_uint4(__byte_perm(vr[u][7], vr[u][6], 0x7632), __byte_perm(vr[u][5], vr[u][4], 0x7632),
                                                          __byte_perm(vr[u][3], vr[u][2], 0x7632), __byte_perm(vr[u][1], vr[u][0], 0x7632));
                    }
                }
                if (lane == 0) mbar_arrive(sb + SM_BARS + B_KVLD * 8);
            }
            asm volatile("fence.proxy.async.global;" ::: "memory");
            __syncwarp();
            if (lane == 0) {
                flag_add(&g_cnt_kv[0]);
                const int wgi = warp - 9;
                mbar_wait(sb + SM_BARS + (B_HD + wgi * 2) * 8, 0);
                flag_add(&g_flag_h[(i * 2 + 0) * 8]);
                mbar_wait(sb + SM_BARS + (B_HD + wgi * 2 + 1) * 8, 0);
                flag_add(&g_flag_h[(i * 2 + 1) * 8]);
                if (wgi == 1 && !convCTA) {
                    mbar_wait(sb + SM_BARS + B_EP * 8, 0);
                    const unsigned ep = lds32(sb + SM_EPOCH);
                    mbar_wait(sb + SM_BARS + B_G1DONE * 8, 0);
                    mbar_expect_tx(sb + SM_BARS + B_XR * 8, 32768);
                    tma3d(sb + SM_XE, &p.tm_xe, 0, 128 * i, 2 * cb, sb + SM_BARS + B_XR * 8);
                    flag_wait(&g_flag_h[(i * 2 + 1) * 8], ep * 16);
                    mbar_arrive(sb + SM_BARS + (B_HRDY + 1) * 8);
                    __nanosleep(3000);
                    flag_wait(&g_cnt_y[cb * 32], ep * 128);
                    asm volatile("fence.proxy.async.global;" ::: "memory");
                    mbar_expect_tx(sb + SM_BARS + B_YT * 8, 32768);
                    tma2d(sb + SM_YT, &p.tm_yT, 128 * i, 128 * cb, sb + SM_BARS + B_YT * 8);
                    tma2d(sb + SM_YT + 16384, &p.tm_yT, 128 * i + 64, 128 * cb, sb + SM_BARS + B_YT * 8);
                }
            }
        } else {
            if (lane == 0) {
                l2_prefetch(p.wg + (size_t)b * (FF * DM / NCTA), FF * DM / NCTA * 2);
                l2_prefetch(p.wu + (size_t)b * (FF * DM / NCTA), FF * DM / NCTA * 2);
                const unsigned ep = g_launch[b] + 1;
                g_launch[b] = ep;
                sts32(sb + SM_EPOCH, ep);
                mbar_arrive(sb + SM_BARS + B_EP * 8);
                tmap_prefetch(rank ? &p.tm_uA : &p.tm_gA);
                tmap_prefetch(rank ? &p.tm_uB : &p.tm_gB);
                tmap_prefetch(&p.tm_w2); tmap_prefetch(&p.tm_yT); tmap_prefetch(&p.tm_out); tmap_prefetch(&p.tm_xe);
                mbar_wait(sb + SM_BARS + B_KVLD * 8, 0);
                l2_prefetch(p.ssm_k + (size_t)(4 * b) * SEQ, 4 * SEQ * 2);
                l2_prefetch(p.wd + (size_t)b * (FF * DM / NCTA), FF * DM / NCTA * 2);
                if (convCTA) {
                    __nanosleep(1000);
                    flag_wait(&g_cnt_kv[0], ep * 256);
                    asm volatile("fence.proxy.async.global;" ::: "memory");
                    mbar_wait(sb + SM_BARS + B_XFREE * 8, 0);
                    mbar_expect_tx(sb + SM_BARS + B_CONV * 8, 65536);
                    bulk_g2s(sb + SM_CVX, g_kvT + (size_t)(8 * cidx) * SEQ, 32768, sb + SM_BARS + B_CONV * 8);
                    bulk_g2s(sb + SM_CVH, p.ssm_k + (size_t)(8 * cidx) * SEQ, 32768, sb + SM_BARS + B_CONV * 8);
                } else {
                    mbar_wait(sb + SM_BARS + (B_HD + 0) * 8, 0);
                    flag_wait(&g_flag_h[(i * 2 + 0) * 8], ep * 16);
                }
            }
            __syncwarp();
            if (!convCTA) {
                asm volatile("fence.proxy.async.global;" ::: "memory");
                int st = 3; uint32_t eph = 1;
                const uint8_t* hsrc = (const uint8_t*)g_h + (size_t)i * 56 * 8192;
                #pragma unroll 1
                for (int u = 0; u < 28; u++) {
                    mbar_wait(sb + SM_BARS + (B_EMPTY + st) * 8, (eph >> st) & 1);
                    eph ^= 1u << st;
                    if (u == 16) {
                        mbar_wait(sb + SM_BARS + (B_HRDY + 1) * 8, 0);
                        asm volatile("fence.proxy.async.global;" ::: "memory");
                    }
                    if (elect_one()) bulk_g2s(sb + stage_off_rt(st) + 16384, hsrc + u * 16384, 16384, sb + SM_BARS + (B_FULL + st) * 8);
                    st = next_st2(st);
                }
            }
        }
    }
}

typedef CUresult (*EncodeFn)(CUtensorMap*, CUtensorMapDataType, cuuint32_t, void*, const cuuint64_t*, const cuuint64_t*,
                             const cuuint32_t*, const cuuint32_t*, CUtensorMapInterleave, CUtensorMapSwizzle,
                             CUtensorMapL2promotion, CUtensorMapFloatOOBfill);

void encode(EncodeFn fn, CUtensorMap* tm, const void* base, int rank, const cuuint64_t* dims, const cuuint64_t* strides,
            const cuuint32_t* box, CUtensorMapSwizzle swz) {
    cuuint32_t es[5] = {1, 1, 1, 1, 1};
    fn(tm, CU_TENSOR_MAP_DATA_TYPE_BFLOAT16, rank, (void*)base, dims, strides, box, es, CU_TENSOR_MAP_INTERLEAVE_NONE, swz,
       CU_TENSOR_MAP_L2_PROMOTION_L2_128B, CU_TENSOR_MAP_FLOAT_OOB_FILL_NONE);
}

}

extern "C" void kernel_launch(void* const* d_in, const int* in_sizes, int n_in, void* d_out, int out_size) {
    (void)in_sizes; (void)n_in; (void)out_size;
    static EncodeFn enc = nullptr;
    static void* yT_ptr = nullptr;
    if (!enc) {
        void* fn = nullptr; cudaDriverEntryPointQueryResult qr;
        cudaGetDriverEntryPoint("cuTensorMapEncodeTiled", &fn, cudaEnableDefault, &qr);
        enc = (EncodeFn)fn;
        cudaGetSymbolAddress(&yT_ptr, g_yT);
        cudaFuncSetAttribute(fused_kernel, cudaFuncAttributeMaxDynamicSharedMemorySize, SM_TOTAL);
    }
    Params p;
    p.q = (const __nv_bfloat16*)d_in[0]; p.k = (const __nv_bfloat16*)d_in[1]; p.v = (const __nv_bfloat16*)d_in[2];
    p.shift_k = (const __nv_bfloat16*)d_in[3]; p.ssm_k = (const __nv_bfloat16*)d_in[4]; p.ssm_D = (const __nv_bfloat16*)d_in[5];
    p.wg = (const __nv_bfloat16*)d_in[7]; p.wu = (const __nv_bfloat16*)d_in[8]; p.wd = (const __nv_bfloat16*)d_in[9];
    {
        cuuint64_t dims[2] = {DM, SEQ}; cuuint64_t str[1] = {DM * 2};
        cuuint64_t dims3[3] = {64, SEQ, DM / 64}; cuuint64_t str3[2] = {DM * 2, 128};
        cuuint32_t box[3] = {64, 64, 8}, boxe[3] = {64, 128, 2};
        encode(enc, &p.tm_x, p.q, 3, dims3, str3, box, CU_TENSOR_MAP_SWIZZLE_128B);
        encode(enc, &p.tm_xe, p.q, 3, dims3, str3, boxe, CU_TENSOR_MAP_SWIZZLE_128B);
        cuuint32_t box2[2] = {64, 16};
        encode(enc, &p.tm_out, d_out, 2, dims, str, box2, CU_TENSOR_MAP_SWIZZLE_128B);
    }
    {
        cuuint64_t dims[3] = {32, DM, FF / 32}; cuuint64_t str[2] = {FF * 2, 64};
        cuuint32_t boxA[3] = {32, 64, 4}, boxB[3] = {32, 128, 2};
        encode(enc, &p.tm_gA, p.wg, 3, dims, str, boxA, CU_TENSOR_MAP_SWIZZLE_64B);
        encode(enc, &p.tm_gB, p.wg, 3, dims, str, boxB, CU_TENSOR_MAP_SWIZZLE_64B);
        encode(enc, &p.tm_uA, p.wu, 3, dims, str, boxA, CU_TENSOR_MAP_SWIZZLE_64B);
        encode(enc, &p.tm_uB, p.wu, 3, dims, str, boxB, CU_TENSOR_MAP_SWIZZLE_64B);
    }
    {
        cuuint64_t dims[3] = {64, FF, DM / 64}; cuuint64_t str[2] = {DM * 2, 128};
        cuuint32_t box[3] = {64, 32, 2};
        encode(enc, &p.tm_w2, p.wd, 3, dims, str, box, CU_TENSOR_MAP_SWIZZLE_128B);
    }
    {
        cuuint64_t dims[2] = {SEQ, DM}; cuuint64_t str[1] = {SEQ * 2};
        cuuint32_t box[2] = {64, 128};
        encode(enc, &p.tm_yT, yT_ptr, 2, dims, str, box, CU_TENSOR_MAP_SWIZZLE_128B);
    }
    fused_kernel<<<NCTA, NTHREADS, SM_TOTAL>>>(p);
}
```

```cpp
#include <cuda_runtime.h>
#include <cuda_bf16.h>
#include <cuda.h>
#include <stdint.h>

namespace {

constexpr int SEQ = 2048, DM = 512, FF = 1792;
constexpr int NCTA = 128;
constexpr int NTHREADS = 384;
constexpr int STAGE_BYTES = 32768;

constexpr uint32_t SM_X = 0;
constexpr uint32_t SM_RING = 131072;
constexpr uint32_t SM_MISC = SM_RING + 3 * STAGE_BYTES;
constexpr uint32_t SM_BARS = SM_MISC;
constexpr uint32_t SM_EPOCH = SM_MISC + 248;
constexpr uint32_t SM_STATS = SM_MISC + 256;
constexpr uint32_t SM_TOTAL = SM_STATS + 1024;
static_assert(SM_TOTAL <= 232448, "smem");
constexpr uint32_t SM_CVX = 0;
constexpr uint32_t SM_CVH = 65536;
constexpr uint32_t SM_YT = 32768;
constexpr uint32_t SM_XE = 98304;

constexpr int B_FULL = 0, B_EMPTY = 5, B_XFULL = 10, B_CONV = 14, B_YT = 15, B_XR = 16, B_G1DONE = 17, B_HD = 18, B_HRDY = 22,
              B_XFREE = 24, B_EP = 25, B_KVLD = 26, B_LN = 27, B_COUNT = 28;
static_assert(B_COUNT * 8 <= 248, "barrier space");

__device__ __align__(128) uint32_t g_h[16 * 56 * 2048];
__device__ __align__(128) __nv_bfloat16 g_kvT[DM * SEQ];
__device__ __align__(128) __nv_bfloat16 g_yT[DM * SEQ];
__device__ unsigned g_launch[NCTA];
__device__ unsigned g_cnt_kv[32];
__device__ unsigned g_cnt_y[4 * 32];
__device__ unsigned g_flag_h[16 * 2 * 8];


struct Params {
    CUtensorMap tm_x, tm_gA, tm_gB, tm_uA, tm_uB, tm_w2, tm_yT, tm_out, tm_xe;
    const __nv_bfloat16 *q, *k, *v, *shift_k, *ssm_k, *ssm_D, *wg, *wu, *wd;
};

__device__ __forceinline__ void wgmma_rs_n32(float (&d)[16], uint32_t a0, uint32_t a1, uint32_t a2, uint32_t a3, uint64_t db, int sc) {
  asm volatile("{\n.reg .pred p;\nsetp.ne.b32 p, %21, 0;\n"
    "wgmma.mma_async.sync.aligned.m64n32k16.f32.bf16.bf16 {%0,%1,%2,%3,%4,%5,%6,%7,%8,%9,%10,%11,%12,%13,%14,%15}, {%16,%17,%18,%19}, %20, p, 1, 1, 0;\n}\n"
    : "+f"(d[0]),"+f"(d[1]),"+f"(d[2]),"+f"(d[3]),"+f"(d[4]),"+f"(d[5]),"+f"(d[6]),"+f"(d[7]),"+f"(d[8]),"+f"(d[9]),"+f"(d[10]),"+f"(d[11]),"+f"(d[12]),"+f"(d[13]),"+f"(d[14]),"+f"(d[15])
    : "r"(a0),"r"(a1),"r"(a2),"r"(a3),"l"(db),"r"(sc));
}
__device__ __forceinline__ void wgmma_rs_n128_tb(float (&d)[64], uint32_t a0, uint32_t a1, uint32_t a2, uint32_t a3, uint64_t db, int sc) {
  asm volatile("{\n.reg .pred p;\nsetp.ne.b32 p, %69, 0;\n"
    "wgmma.mma_async.sync.aligned.m64n128k16.f32.bf16.bf16 {%0,%1,%2,%3,%4,%5,%6,%7,%8,%9,%10,%11,%12,%13,%14,%15,%16,%17,%18,%19,%20,%21,%22,%23,%24,%25,%26,%27,%28,%29,%30,%31,%32,%33,%34,%35,%36,%37,%38,%39,%40,%41,%42,%43,%44,%45,%46,%47,%48,%49,%50,%51,%52,%53,%54,%55,%56,%57,%58,%59,%60,%61,%62,%63}, {%64,%65,%66,%67}, %68, p, 1, 1, 1;\n}\n"
    : "+f"(d[0]),"+f"(d[1]),"+f"(d[2]),"+f"(d[3]),"+f"(d[4]),"+f"(d[5]),"+f"(d[6]),"+f"(d[7]),"+f"(d[8]),"+f"(d[9]),"+f"(d[10]),"+f"(d[11]),"+f"(d[12]),"+f"(d[13]),"+f"(d[14]),"+f"(d[15]),"+f"(d[16]),"+f"(d[17]),"+f"(d[18]),"+f"(d[19]),"+f"(d[20]),"+f"(d[21]),"+f"(d[22]),"+f"(d[23]),"+f"(d[24]),"+f"(d[25]),"+f"(d[26]),"+f"(d[27]),"+f"(d[28]),"+f"(d[29]),"+f"(d[30]),"+f"(d[31]),"+f"(d[32]),"+f"(d[33]),"+f"(d[34]),"+f"(d[35]),"+f"(d[36]),"+f"(d[37]),"+f"(d[38]),"+f"(d[39]),"+f"(d[40]),"+f"(d[41]),"+f"(d[42]),"+f"(d[43]),"+f"(d[44]),"+f"(d[45]),"+f"(d[46]),"+f"(d[47]),"+f"(d[48]),"+f"(d[49]),"+f"(d[50]),"+f"(d[51]),"+f"(d[52]),"+f"(d[53]),"+f"(d[54]),"+f"(d[55]),"+f"(d[56]),"+f"(d[57]),"+f"(d[58]),"+f"(d[59]),"+f"(d[60]),"+f"(d[61]),"+f"(d[62]),"+f"(d[63])
    : "r"(a0),"r"(a1),"r"(a2),"r"(a3),"l"(db),"r"(sc));
}
__device__ __forceinline__ void wgmma_ss_n256_tb(float (&d)[128], uint64_t da, uint64_t db, int sc) {
  asm volatile("{\n.reg .pred p;\nsetp.ne.b32 p, %130, 0;\n"
    "wgmma.mma_async.sync.aligned.m64n256k16.f32.bf16.bf16 {%0,%1,%2,%3,%4,%5,%6,%7,%8,%9,%10,%11,%12,%13,%14,%15,%16,%17,%18,%19,%20,%21,%22,%23,%24,%25,%26,%27,%28,%29,%30,%31,%32,%33,%34,%35,%36,%37,%38,%39,%40,%41,%42,%43,%44,%45,%46,%47,%48,%49,%50,%51,%52,%53,%54,%55,%56,%57,%58,%59,%60,%61,%62,%63,%64,%65,%66,%67,%68,%69,%70,%71,%72,%73,%74,%75,%76,%77,%78,%79,%80,%81,%82,%83,%84,%85,%86,%87,%88,%89,%90,%91,%92,%93,%94,%95,%96,%97,%98,%99,%100,%101,%102,%103,%104,%105,%106,%107,%108,%109,%110,%111,%112,%113,%114,%115,%116,%117,%118,%119,%120,%121,%122,%123,%124,%125,%126,%127}, %128, %129, p, 1, 1, 0, 1;\n}\n"
    : "+f"(d[0]),"+f"(d[1]),"+f"(d[2]),"+f"(d[3]),"+f"(d[4]),"+f"(d[5]),"+f"(d[6]),"+f"(d[7]),"+f"(d[8]),"+f"(d[9]),"+f"(d[10]),"+f"(d[11]),"+f"(d[12]),"+f"(d[13]),"+f"(d[14]),"+f"(d[15]),"+f"(d[16]),"+f"(d[17]),"+f"(d[18]),"+f"(d[19]),"+f"(d[20]),"+f"(d[21]),"+f"(d[22]),"+f"(d[23]),"+f"(d[24]),"+f"(d[25]),"+f"(d[26]),"+f"(d[27]),"+f"(d[28]),"+f"(d[29]),"+f"(d[30]),"+f"(d[31]),"+f"(d[32]),"+f"(d[33]),"+f"(d[34]),"+f"(d[35]),"+f"(d[36]),"+f"(d[37]),"+f"(d[38]),"+f"(d[39]),"+f"(d[40]),"+f"(d[41]),"+f"(d[42]),"+f"(d[43]),"+f"(d[44]),"+f"(d[45]),"+f"(d[46]),"+f"(d[47]),"+f"(d[48]),"+f"(d[49]),"+f"(d[50]),"+f"(d[51]),"+f"(d[52]),"+f"(d[53]),"+f"(d[54]),"+f"(d[55]),"+f"(d[56]),"+f"(d[57]),"+f"(d[58]),"+f"(d[59]),"+f"(d[60]),"+f"(d[61]),"+f"(d[62]),"+f"(d[63]),"+f"(d[64]),"+f"(d[65]),"+f"(d[66]),"+f"(d[67]),"+f"(d[68]),"+f"(d[69]),"+f"(d[70]),"+f"(d[71]),"+f"(d[72]),"+f"(d[73]),"+f"(d[74]),"+f"(d[75]),"+f"(d[76]),"+f"(d[77]),"+f"(d[78]),"+f"(d[79]),"+f"(d[80]),"+f"(d[81]),"+f"(d[82]),"+f"(d[83]),"+f"(d[84]),"+f"(d[85]),"+f"(d[86]),"+f"(d[87]),"+f"(d[88]),"+f"(d[89]),"+f"(d[90]),"+f"(d[91]),"+f"(d[92]),"+f"(d[93]),"+f"(d[94]),"+f"(d[95]),"+f"(d[96]),"+f"(d[97]),"+f"(d[98]),"+f"(d[99]),"+f"(d[100]),"+f"(d[101]),"+f"(d[102]),"+f"(d[103]),"+f"(d[104]),"+f"(d[105]),"+f"(d[106]),"+f"(d[107]),"+f"(d[108]),"+f"(d[109]),"+f"(d[110]),"+f"(d[111]),"+f"(d[112]),"+f"(d[113]),"+f"(d[114]),"+f"(d[115]),"+f"(d[116]),"+f"(d[117]),"+f"(d[118]),"+f"(d[119]),"+f"(d[120]),"+f"(d[121]),"+f"(d[122]),"+f"(d[123]),"+f"(d[124]),"+f"(d[125]),"+f"(d[126]),"+f"(d[127])
    : "l"(da),"l"(db),"r"(sc));
}
__device__ __forceinline__ void wgmma_ss_n192_tb(float (&d)[96], uint64_t da, uint64_t db, int sc) {
  asm volatile("{\n.reg .pred p;\nsetp.ne.b32 p, %98, 0;\n"
    "wgmma.mma_async.sync.aligned.m64n192k16.f32.bf16.bf16 {%0,%1,%2,%3,%4,%5,%6,%7,%8,%9,%10,%11,%12,%13,%14,%15,%16,%17,%18,%19,%20,%21,%22,%23,%24,%25,%26,%27,%28,%29,%30,%31,%32,%33,%34,%35,%36,%37,%38,%39,%40,%41,%42,%43,%44,%45,%46,%47,%48,%49,%50,%51,%52,%53,%54,%55,%56,%57,%58,%59,%60,%61,%62,%63,%64,%65,%66,%67,%68,%69,%70,%71,%72,%73,%74,%75,%76,%77,%78,%79,%80,%81,%82,%83,%84,%85,%86,%87,%88,%89,%90,%91,%92,%93,%94,%95}, %96, %97, p, 1, 1, 0, 1;\n}\n"
    : "+f"(d[0]),"+f"(d[1]),"+f"(d[2]),"+f"(d[3]),"+f"(d[4]),"+f"(d[5]),"+f"(d[6]),"+f"(d[7]),"+f"(d[8]),"+f"(d[9]),"+f"(d[10]),"+f"(d[11]),"+f"(d[12]),"+f"(d[13]),"+f"(d[14]),"+f"(d[15]),"+f"(d[16]),"+f"(d[17]),"+f"(d[18]),"+f"(d[19]),"+f"(d[20]),"+f"(d[21]),"+f"(d[22]),"+f"(d[23]),"+f"(d[24]),"+f"(d[25]),"+f"(d[26]),"+f"(d[27]),"+f"(d[28]),"+f"(d[29]),"+f"(d[30]),"+f"(d[31]),"+f"(d[32]),"+f"(d[33]),"+f"(d[34]),"+f"(d[35]),"+f"(d[36]),"+f"(d[37]),"+f"(d[38]),"+f"(d[39]),"+f"(d[40]),"+f"(d[41]),"+f"(d[42]),"+f"(d[43]),"+f"(d[44]),"+f"(d[45]),"+f"(d[46]),"+f"(d[47]),"+f"(d[48]),"+f"(d[49]),"+f"(d[50]),"+f"(d[51]),"+f"(d[52]),"+f"(d[53]),"+f"(d[54]),"+f"(d[55]),"+f"(d[56]),"+f"(d[57]),"+f"(d[58]),"+f"(d[59]),"+f"(d[60]),"+f"(d[61]),"+f"(d[62]),"+f"(d[63]),"+f"(d[64]),"+f"(d[65]),"+f"(d[66]),"+f"(d[67]),"+f"(d[68]),"+f"(d[69]),"+f"(d[70]),"+f"(d[71]),"+f"(d[72]),"+f"(d[73]),"+f"(d[74]),"+f"(d[75]),"+f"(d[76]),"+f"(d[77]),"+f"(d[78]),"+f"(d[79]),"+f"(d[80]),"+f"(d[81]),"+f"(d[82]),"+f"(d[83]),"+f"(d[84]),"+f"(d[85]),"+f"(d[86]),"+f"(d[87]),"+f"(d[88]),"+f"(d[89]),"+f"(d[90]),"+f"(d[91]),"+f"(d[92]),"+f"(d[93]),"+f"(d[94]),"+f"(d[95])
    : "l"(da),"l"(db),"r"(sc));
}


__device__ __forceinline__ uint32_t smem_u32(const void* p) { return (uint32_t)__cvta_generic_to_shared(p); }
__device__ __forceinline__ void mbar_init(uint32_t bar, uint32_t cnt) { asm volatile("mbarrier.init.shared::cta.b64 [%0], %1;" :: "r"(bar), "r"(cnt)); }
__device__ __forceinline__ void mbar_expect_tx(uint32_t bar, uint32_t bytes) { asm volatile("mbarrier.arrive.expect_tx.shared::cta.b64 _, [%0], %1;" :: "r"(bar), "r"(bytes) : "memory"); }
__device__ __forceinline__ void mbar_arrive(uint32_t bar) { asm volatile("mbarrier.arrive.shared::cta.b64 _, [%0];" :: "r"(bar) : "memory"); }
__device__ __forceinline__ void mbar_arrive_cluster(uint32_t cbar, uint32_t cnt) { asm volatile("mbarrier.arrive.shared::cluster.b64 _, [%0], %1;" :: "r"(cbar), "r"(cnt) : "memory"); }
__device__ __forceinline__ uint32_t mapa(uint32_t a, uint32_t rank) { uint32_t r; asm volatile("mapa.shared::cluster.u32 %0, %1, %2;" : "=r"(r) : "r"(a), "r"(rank)); return r; }
__device__ __forceinline__ void mbar_wait(uint32_t bar, uint32_t parity) {
    uint32_t ok; uint32_t n = 0;
    do {
        asm volatile("{\n.reg .pred p;\nmbarrier.try_wait.parity.shared::cta.b64 p, [%1], %2;\nselp.u32 %0, 1, 0, p;\n}" : "=r"(ok) : "r"(bar), "r"(parity) : "memory");
    } while (!ok && ++n < (1u << 17));
}
__device__ __forceinline__ void flag_wait(const unsigned* p, unsigned target) {
    unsigned v; uint32_t n = 0;
    while (true) {
        asm volatile("ld.acquire.gpu.global.u32 %0, [%1];" : "=r"(v) : "l"(p) : "memory");
        if ((int)(v - target) >= 0 || ++n >= (1u << 17)) break;
        __nanosleep(40);
    }
}
__device__ __forceinline__ void flag_add(unsigned* p) {
    asm volatile("fence.acq_rel.gpu;\nred.relaxed.gpu.global.add.u32 [%0], 1;" :: "l"(p) : "memory");
}
__device__ __forceinline__ uint64_t make_desc(uint32_t addr, uint32_t lbo, uint32_t sbo, uint32_t swz) {
    return (uint64_t)((addr & 0x3FFFF) >> 4) | ((uint64_t)((lbo & 0x3FFFF) >> 4) << 16) | ((uint64_t)((sbo & 0x3FFFF) >> 4) << 32) | ((uint64_t)swz << 62);
}
__device__ __forceinline__ uint64_t desc_add(uint64_t d, uint32_t off16) {
    return (d & 0xFFFFFFFF00000000ull) | (uint64_t)((uint32_t)d + off16);
}
__device__ __forceinline__ void tma2d(uint32_t dst, const CUtensorMap* tm, int c0, int c1, uint32_t bar) {
    asm volatile("cp.async.bulk.tensor.2d.shared::cluster.global.mbarrier::complete_tx::bytes [%0], [%1, {%3, %4}], [%2];"
        :: "r"(dst), "l"((uint64_t)tm), "r"(bar), "r"(c0), "r"(c1) : "memory");
}
__device__ __forceinline__ void tma3d(uint32_t dst, const CUtensorMap* tm, int c0, int c1, int c2, uint32_t bar) {
    asm volatile("cp.async.bulk.tensor.3d.shared::cluster.global.mbarrier::complete_tx::bytes [%0], [%1, {%3, %4, %5}], [%2];"
        :: "r"(dst), "l"((uint64_t)tm), "r"(bar), "r"(c0), "r"(c1), "r"(c2) : "memory");
}
__device__ __forceinline__ void tma3d_mc(uint32_t dst, const CUtensorMap* tm, int c0, int c1, int c2, uint32_t bar) {
    asm volatile("cp.async.bulk.tensor.3d.shared::cluster.global.mbarrier::complete_tx::bytes.multicast::cluster [%0], [%1, {%3, %4, %5}], [%2], %6;"
        :: "r"(dst), "l"((uint64_t)tm), "r"(bar), "r"(c0), "r"(c1), "r"(c2), "h"((uint16_t)3) : "memory");
}
__device__ __forceinline__ void bulk_g2s(uint32_t dst, const void* src, uint32_t bytes, uint32_t bar) {
    asm volatile("cp.async.bulk.shared::cluster.global.mbarrier::complete_tx::bytes [%0], [%1], %2, [%3];"
        :: "r"(dst), "l"(src), "r"(bytes), "r"(bar) : "memory");
}
__device__ __forceinline__ void tma2d_store(const CUtensorMap* tm, int c0, int c1, uint32_t src) {
    asm volatile("cp.async.bulk.tensor.2d.global.shared::cta.bulk_group [%0, {%2, %3}], [%1];"
        :: "l"((uint64_t)tm), "r"(src), "r"(c0), "r"(c1) : "memory");
}
__device__ __forceinline__ void l2_prefetch(const void* p, uint32_t bytes) {
    asm volatile("cp.async.bulk.prefetch.L2.global [%0], %1;" :: "l"(p), "r"(bytes) : "memory");
}
__device__ __forceinline__ void tmap_prefetch(const CUtensorMap* tm) { asm volatile("prefetch.tensormap [%0];" :: "l"((uint64_t)tm) : "memory"); }
__device__ __forceinline__ uint32_t lds32(uint32_t a) { uint32_t v; asm volatile("ld.shared.u32 %0, [%1];" : "=r"(v) : "r"(a)); return v; }
__device__ __forceinline__ uint2 lds64(uint32_t a) { uint2 v; asm volatile("ld.shared.v2.u32 {%0,%1}, [%2];" : "=r"(v.x), "=r"(v.y) : "r"(a)); return v; }
__device__ __forceinline__ float2 lds64f(uint32_t a) { float2 v; asm volatile("ld.shared.v2.f32 {%0,%1}, [%2];" : "=f"(v.x), "=f"(v.y) : "r"(a)); return v; }
__device__ __forceinline__ uint4 lds128(uint32_t a) { uint4 v; asm volatile("ld.shared.v4.u32 {%0,%1,%2,%3}, [%4];" : "=r"(v.x), "=r"(v.y), "=r"(v.z), "=r"(v.w) : "r"(a)); return v; }
__device__ __forceinline__ void sts32(uint32_t a, uint32_t v) { asm volatile("st.shared.u32 [%0], %1;" :: "r"(a), "r"(v) : "memory"); }
__device__ __forceinline__ uint4 ldg_nc128(const void* p) { uint4 v; asm volatile("ld.global.nc.L1::no_allocate.v4.u32 {%0,%1,%2,%3}, [%4];" : "=r"(v.x), "=r"(v.y), "=r"(v.z), "=r"(v.w) : "l"(p)); return v; }
__device__ __forceinline__ uint32_t ldg_nc32(const void* p) { uint32_t v; asm volatile("ld.global.nc.u32 %0, [%1];" : "=r"(v) : "l"(p)); return v; }
#define WG_FENCE() asm volatile("wgmma.fence.sync.aligned;\n" ::: "memory")
#define WG_COMMIT() asm volatile("wgmma.commit_group.sync.aligned;\n" ::: "memory")
template<int N> __device__ __forceinline__ void wg_wait() { asm volatile("wgmma.wait_group.sync.aligned %0;\n" :: "n"(N) : "memory"); }
__device__ __forceinline__ bool elect_one() {
    uint32_t pr;
    asm volatile("{\n.reg .pred p;\nelect.sync _|p, 0xffffffff;\nselp.u32 %0, 1, 0, p;\n}" : "=r"(pr));
    return pr != 0;
}

__device__ __forceinline__ float bf_lo(uint32_t u) { return __uint_as_float(u << 16); }
__device__ __forceinline__ float bf_hi(uint32_t u) { return __uint_as_float(u & 0xFFFF0000u); }
__device__ __forceinline__ uint32_t pack_bf(float lo, float hi) { uint32_t r; asm("cvt.rn.bf16x2.f32 %0, %1, %2;" : "=r"(r) : "f"(hi), "f"(lo)); return r; }
__device__ __forceinline__ float bf_round(float x) { return __bfloat162float(__float2bfloat16_rn(x)); }
__device__ __forceinline__ uint32_t bmul2(uint32_t a, uint32_t b) { uint32_t r; asm("mul.rn.bf16x2 %0, %1, %2;" : "=r"(r) : "r"(a), "r"(b)); return r; }
__device__ __forceinline__ uint32_t badd2(uint32_t a, uint32_t b) { uint32_t r; asm("add.rn.bf16x2 %0, %1, %2;" : "=r"(r) : "r"(a), "r"(b)); return r; }
__device__ __forceinline__ uint32_t bsub2(uint32_t a, uint32_t b) { uint32_t r; asm("sub.rn.bf16x2 %0, %1, %2;" : "=r"(r) : "r"(a), "r"(b)); return r; }
__device__ __forceinline__ void mma16816(float (&d)[4], uint32_t a0, uint32_t a1, uint32_t a2, uint32_t a3, uint2 b) {
    asm volatile("mma.sync.aligned.m16n8k16.row.col.f32.bf16.bf16.f32 {%0,%1,%2,%3}, {%4,%5,%6,%7}, {%8,%9}, {%0,%1,%2,%3};\n"
        : "+f"(d[0]), "+f"(d[1]), "+f"(d[2]), "+f"(d[3]) : "r"(a0), "r"(a1), "r"(a2), "r"(a3), "r"(b.x), "r"(b.y));
}

__device__ __forceinline__ int blk_f0(int s) {
    if (s < 32) return 32 * (14 * (s >> 3) + 8 * ((s >> 2) & 1) + (s & 3));
    const int s2 = s - 32, c6 = (s2 * 11) >> 6, t = s2 - 6 * c6;
    return 32 * (14 * c6 + (t < 4 ? 4 + t : 8 + t));
}
__device__ __forceinline__ int g2_pair(int u, int cb) {
    if (u < 2) return 16 + 3 * cb + u;
    if (u < 18) return u - 2;
    return u - 2 + ((u - 18 >= 3 * cb) ? 2 : 0);
}
__device__ __forceinline__ int next_st2(int s) { return (0x14023 >> (4 * s)) & 7; }
__device__ __forceinline__ uint32_t stage_off_rt(int s) { return s < 3 ? SM_RING + s * STAGE_BYTES : (uint32_t)(s - 3) * 65536; }

__device__ __forceinline__ void store_h(uint32_t* dst, const uint32_t (&hp)[32], int q) {
    *(uint4*)(dst + q * 2048) = make_uint4(hp[8 * q], hp[8 * q + 1], hp[8 * q + 2], hp[8 * q + 3]);
    *(uint4*)(dst + q * 2048 + 512) = make_uint4(hp[8 * q + 4], hp[8 * q + 5], hp[8 * q + 6], hp[8 * q + 7]);
}
template<int NB, bool passA>
__device__ __forceinline__ void gemm1_pass(uint32_t sb, int wgi, int warp4, int lane, int& st, uint32_t& fph, uint32_t e_cl,
                                           uint32_t (&hp)[32], uint32_t* prev_dst, bool convCTA) {
    constexpr bool narrow = (NB == 2);
    float acc[NB * 32];
    const uint64_t descA0 = make_desc(sb + SM_X + wgi * 65536, 16, 1024, 1);
    const uint64_t descB0 = make_desc(sb + SM_RING, narrow ? 8192 : 4096, 512, 2);
    int prev = 0;
    auto group = [&](int sl) {
        mbar_wait(sb + SM_BARS + (B_FULL + st) * 8, (fph >> st) & 1);
        fph ^= 1u << st;
        const uint64_t da = desc_add(descA0, sl * (narrow ? 1024 : 512)), db = desc_add(descB0, st * 2048);
        WG_FENCE();
        #pragma unroll
        for (int kk = 0; kk < (narrow ? 8 : 4); kk++) {
            int sc = (sl | kk) ? 1 : 0;
            if constexpr (!narrow) wgmma_ss_n256_tb(acc, da + kk * 2, db + kk * 64, sc);
            else wgmma_ss_n128_tb(acc, da + ((kk >> 2) * 512 + (kk & 3) * 2), db + kk * 64, sc);
        }
        WG_COMMIT();
        wg_wait<1>();
        if (lane < 2 && sl && (!narrow || sl == 1)) mbar_arrive_cluster(e_cl + prev * 8, 1);
        if (narrow && sl == 2 && lane == 0) mbar_arrive(sb + SM_BARS + B_XFREE * 8);
        if (!passA && !narrow && sl == 4 && lane < 4) mbar_arrive_cluster(e_cl + (3 + (lane >> 1)) * 8, 1);
        prev = st;
        st = (st == 2) ? 0 : st + 1;
    };
    if constexpr (passA) {
        #pragma unroll 1
        for (int sl = 0; sl < 8; sl++) group(sl);
    } else {
        #pragma unroll
        for (int sl = 0; sl < 4; sl++) { group(sl); store_h(prev_dst, hp, sl); }
        __syncwarp();
        if (lane == 0) mbar_arrive(sb + SM_BARS + (B_HD + wgi * 2) * 8);
        if constexpr (!narrow) {
            #pragma unroll 1
            for (int sl = 4; sl < 8; sl++) group(sl);
        }
    }
    wg_wait<0>();
    if (lane < 2 && (passA || !convCTA)) mbar_arrive_cluster(e_cl + prev * 8, 1);
    if (!passA && lane == 0) mbar_arrive(sb + SM_BARS + B_G1DONE * 8);
    const int g = lane >> 2;
    const int r0 = wgi * 64 + warp4 * 16 + g;
    const float s0 = __uint_as_float(lds32(sb + SM_STATS + r0 * 8 + 4)), s1 = __uint_as_float(lds32(sb + SM_STATS + (r0 + 8) * 8 + 4));
    #pragma unroll
    for (int t = 0; t < NB * 4; t++) {
        const float* ag = &acc[4 * t];
        const float* au = &acc[NB * 16 + 4 * t];
        hp[2 * t] = bmul2(pack_bf(ag[0] * s0, ag[1] * s0), pack_bf(au[0] * s0, au[1] * s0));
        hp[2 * t + 1] = bmul2(pack_bf(ag[2] * s1, ag[3] * s1), pack_bf(au[2] * s1, au[3] * s1));
    }
}

__global__ void __cluster_dims__(2, 1, 1) __launch_bounds__(NTHREADS, 1)
fused_kernel(const __grid_constant__ Params p) {
    extern __shared__ __align__(1024) uint8_t smem_raw[];
    const uint32_t sb = smem_u32(smem_raw);
    const int tid = threadIdx.x, warp = tid >> 5, lane = tid & 31;
    const int b = blockIdx.x;
    const int rank = b & 1;
    const int j = (b >> 1) & 7;
    const int i = ((b >> 4) << 1) | rank;
    const int cb = j >> 1;
    const bool convCTA = j & 1;
    const int cidx = 4 * i + cb;

    if (tid == 256) {
        mbar_init(sb + SM_BARS + B_XFULL * 8, 1);
        mbar_init(sb + SM_BARS + (B_XFULL + 1) * 8, 1);
        asm volatile("fence.proxy.async.shared::cta;" ::: "memory");
        mbar_expect_tx(sb + SM_BARS + B_XFULL * 8, 65536);
        tma3d(sb + SM_X, &p.tm_x, 0, 128 * i, 0, sb + SM_BARS + B_XFULL * 8);
        mbar_expect_tx(sb + SM_BARS + (B_XFULL + 1) * 8, 65536);
        tma3d(sb + SM_X + 65536, &p.tm_x, 0, 128 * i + 64, 0, sb + SM_BARS + (B_XFULL + 1) * 8);
    }
    if (tid == 288) {
        for (int s = 0; s < 5; s++) { mbar_init(sb + SM_BARS + (B_FULL + s) * 8, 1); mbar_init(sb + SM_BARS + (B_EMPTY + s) * 8, 16); }
        mbar_init(sb + SM_BARS + B_CONV * 8, 1);
        mbar_init(sb + SM_BARS + B_YT * 8, 1);
        mbar_init(sb + SM_BARS + B_XR * 8, 1);
        mbar_init(sb + SM_BARS + B_G1DONE * 8, 8);
        mbar_init(sb + SM_BARS + B_XFREE * 8, 8);
        mbar_init(sb + SM_BARS + B_KVLD * 8, 2);
        mbar_init(sb + SM_BARS + B_EP * 8, 1);
        mbar_init(sb + SM_BARS + B_LN * 8, 8);
        for (int s = 0; s < 4; s++) mbar_init(sb + SM_BARS + (B_HD + s) * 8, 4);
        for (int s = 0; s < 2; s++) mbar_init(sb + SM_BARS + (B_HRDY + s) * 8, 1);
        asm volatile("fence.mbarrier_init.release.cluster;" ::: "memory");
        asm volatile("fence.proxy.async.shared::cta;" ::: "memory");
    }
    __syncwarp();
    asm volatile("barrier.cluster.arrive.relaxed.aligned;\n" ::: "memory");
    asm volatile("barrier.cluster.wait.aligned;\n" ::: "memory");

    if (warp < 8) {
        asm volatile("setmaxnreg.inc.sync.aligned.u32 200;");
        const int wgi = warp >> 2, warp4 = warp & 3;
        const int g = lane >> 2, c = lane & 3;
        const uint32_t e_cl = mapa(sb + SM_BARS + B_EMPTY * 8, lane & 1);
        {
            const int lr16 = (lane & 7) + ((lane >> 3) & 1) * 8;
            const uint32_t xa = sb + SM_X + wgi * 65536 + (warp4 * 16 + lr16) * 128;
            uint32_t xf[32][4];
            float aS[4][4], aQ0[4][4], aQ1[4][4];
            #pragma unroll
            for (int e = 0; e < 4; e++) {
                #pragma unroll
                for (int f = 0; f < 4; f++) { aS[e][f] = 0.f; aQ0[e][f] = 0.f; aQ1[e][f] = 0.f; }
            }
            mbar_wait(sb + SM_BARS + (B_XFULL + wgi) * 8, 0);
            #pragma unroll
            for (int ks = 0; ks < 32; ks++) {
                const uint32_t a = xa + (ks >> 2) * 8192 + (((2 * (ks & 3) + (lane >> 4)) ^ (lane & 7)) << 4);
                asm volatile("ldmatrix.sync.aligned.m8n8.x4.shared.b16 {%0,%1,%2,%3}, [%4];"
                    : "=r"(xf[ks][0]), "=r"(xf[ks][1]), "=r"(xf[ks][2]), "=r"(xf[ks][3]) : "r"(a) : "memory");
            }
            #pragma unroll
            for (int ks = 0; ks < 32; ks++)
                mma16816(aS[ks & 3], xf[ks][0], xf[ks][1], xf[ks][2], xf[ks][3], make_uint2(0x3F803F80u, 0x3F803F80u));
            const float mean0 = ((aS[0][0] + aS[1][0]) + (aS[2][0] + aS[3][0])) * (1.0f / DM);
            const float mean1 = ((aS[0][2] + aS[1][2]) + (aS[2][2] + aS[3][2])) * (1.0f / DM);
            const uint32_t m0 = pack_bf(mean0, mean0), m1 = pack_bf(mean1, mean1);
            #pragma unroll
            for (int ks = 0; ks < 32; ks++) {
                const uint32_t a = xa + (ks >> 2) * 8192 + (((2 * (ks & 3) + (lane >> 4)) ^ (lane & 7)) << 4);
                asm volatile("stmatrix.sync.aligned.m8n8.x4.shared.b16 [%0], {%1,%2,%3,%4};"
                    :: "r"(a), "r"(bsub2(xf[ks][0], m0)), "r"(bsub2(xf[ks][1], m1)), "r"(bsub2(xf[ks][2], m0)), "r"(bsub2(xf[ks][3], m1)) : "memory");
            }
            asm volatile("fence.proxy.async.shared::cta;" ::: "memory");
            __syncwarp();
            if (lane == 0) mbar_arrive(sb + SM_BARS + B_LN * 8);
            #pragma unroll
            for (int ks = 0; ks < 32; ks++) {
                mma16816(aQ0[ks & 3], xf[ks][0], xf[ks][1], xf[ks][2], xf[ks][3], make_uint2(xf[ks][0], xf[ks][2]));
                mma16816(aQ1[ks & 3], xf[ks][0], xf[ks][1], xf[ks][2], xf[ks][3], make_uint2(xf[ks][1], xf[ks][3]));
            }
            if (c == (g >> 1)) {
                const float q0 = (g & 1) ? (aQ0[0][1] + aQ0[1][1]) + (aQ0[2][1] + aQ0[3][1]) : (aQ0[0][0] + aQ0[1][0]) + (aQ0[2][0] + aQ0[3][0]);
                const float q1 = (g & 1) ? (aQ1[0][3] + aQ1[1][3]) + (aQ1[2][3] + aQ1[3][3]) : (aQ1[0][2] + aQ1[1][2]) + (aQ1[2][2] + aQ1[3][2]);
                const float sd0 = bf_round(sqrtf(bf_round(bf_round(fmaxf(q0 * (1.0f / DM) - mean0 * mean0, 0.f)) + 1e-5f)));
                const float sd1 = bf_round(sqrtf(bf_round(bf_round(fmaxf(q1 * (1.0f / DM) - mean1 * mean1, 0.f)) + 1e-5f)));
                const uint32_t sa = sb + SM_STATS + (warp * 16 + g) * 8;
                sts32(sa, m0); sts32(sa + 4, __float_as_uint(1.0f / sd0));
                sts32(sa + 64, m1); sts32(sa + 68, __float_as_uint(1.0f / sd1));
            }
            mbar_wait(sb + SM_BARS + B_LN * 8, 0);
        }
        int st = 0; uint32_t fph = 0;
        uint32_t hp[32];
        uint32_t* const hdst = g_h + (size_t)(i * 56) * 2048 + wgi * 1024 + warp4 * 128 + lane * 4;
        gemm1_pass<4, true>(sb, wgi, warp4, lane, st, fph, e_cl, hp, hdst, convCTA);

        if (convCTA) {
            gemm1_pass<2, false>(sb, wgi, warp4, lane, st, fph, e_cl, hp, hdst + 4 * j * 2048, true);
            store_h(hdst + (36 + 6 * cb) * 2048, hp, 0); store_h(hdst + (36 + 6 * cb) * 2048, hp, 1);
            __syncwarp();
            if (lane == 0) mbar_arrive(sb + SM_BARS + (B_HD + wgi * 2 + 1) * 8);
            const int gch = 8 * cidx + warp;
            const uint32_t xb = sb + SM_CVX + warp * 4096;
            const uint32_t hb = sb + SM_CVH + warp * 4096;
            const uint32_t dw = ((const unsigned short*)p.ssm_D)[gch];
            const uint32_t d2 = dw | (dw << 16);
            mbar_wait(sb + SM_BARS + B_CONV * 8, 0);
            float acc[16][4];
            #pragma unroll
            for (int jj = 0; jj < 16; jj++) { acc[jj][0] = 0.f; acc[jj][1] = 0.f; acc[jj][2] = 0.f; acc[jj][3] = 0.f; }
            uint2 bh[8], bl0[8], bl1[8];
            uint32_t xl = xb + g * 32 + c * 8;
            uint32_t hl = hb + (g + 2 * c - 8) * 4;
            #pragma unroll
            for (int d = 0; d < 8; d++) { bl0[d] = lds64(xl + d * 256); bh[d] = lds64(xl + (8 + d) * 256); }
            uint32_t w[6];
            w[0] = 0; w[1] = 0; w[2] = 0;
            if (g + 2 * c >= 8) w[0] = lds32(hl);
            if (g + 2 * c >= 7) w[1] = lds32(hl + 4);
            if (g + 2 * c >= 6) w[2] = lds32(hl + 8);
            w[3] = lds32(hl + 2048); w[4] = lds32(hl + 2052); w[5] = lds32(hl + 2056);
            auto conv_m0 = [&](int m0, uint2 (&bl)[8], uint2 (&bn)[8]) {
                xl -= 32;
                #pragma unroll
                for (int k = 0; k < 8; k++) {
                    const uint32_t a0 = w[1], a1 = __byte_perm(w[0], w[1], 0x5432), a2 = w[2], a3 = __byte_perm(w[1], w[2], 0x5432);
                    const uint32_t c0 = w[4], c1 = __byte_perm(w[3], w[4], 0x5432), c2 = w[5], c3 = __byte_perm(w[4], w[5], 0x5432);
                    const uint32_t nx = (k < 7) ? hl + (k + 1) * 256 : hl + 32;
                    w[0] = lds32(nx); w[1] = lds32(nx + 4); w[2] = lds32(nx + 8);
                    w[3] = lds32(nx + 2048); w[4] = lds32(nx + 2052); w[5] = lds32(nx + 2056);
                    if (k > 0) bn[k] = lds64(xl + k * 256);
                    else { bn[0] = make_uint2(0, 0); if (g > m0) bn[0] = lds64(xl); }
                    #pragma unroll
                    for (int jj = k; jj < 16; jj++) mma16816(acc[jj], a0, a1, a2, a3, (jj - k < 8) ? bl[(jj - k) & 7] : bh[(jj - k) & 7]);
                    bh[7 - k] = lds64(xl + (15 - k) * 256);
                    #pragma unroll
                    for (int jj = k + 8; jj < 16; jj++) mma16816(acc[jj], c0, c1, c2, c3, bl[jj - k - 8]);
                }
                hl += 32;
            };
            #pragma unroll 1
            for (int m0 = 0; m0 < 8; m0 += 2) {
                conv_m0(m0, bl0, bl1);
                conv_m0(m0 + 1, bl1, bl0);
            }
            const uint32_t kvl = xb + c * 64 + (7 - g) * 4;
            uint32_t* ydst = (uint32_t*)(g_yT + (size_t)gch * SEQ + 32 * c + 2 * g);
            uint32_t kk0[16], kk1[16];
            #pragma unroll
            for (int jj = 0; jj < 16; jj++) { kk0[jj] = lds32(kvl + jj * 256); kk1[jj] = lds32(kvl + jj * 256 + 32); }
            #pragma unroll
            for (int jj = 0; jj < 16; jj++) {
                ydst[jj * 64] = badd2(pack_bf(acc[jj][2], acc[jj][0]), bmul2(__byte_perm(kk0[jj], kk0[jj], 0x1032), d2));
                ydst[jj * 64 + 8] = badd2(pack_bf(acc[jj][3], acc[jj][1]), bmul2(__byte_perm(kk1[jj], kk1[jj], 0x1032), d2));
            }
            __syncwarp();
            if (lane == 0) flag_add(&g_cnt_y[(cidx >> 4) * 32]);
        } else {
            gemm1_pass<4, false>(sb, wgi, warp4, lane, st, fph, e_cl, hp, hdst + 4 * j * 2048, false);
            float acc[64];
            const uint64_t descB0 = make_desc(sb, 4096, 1024, 1);
            const uint32_t ha = sb + 16384 + wgi * 4096 + warp4 * 512 + lane * 16;
            int sg = 3, p0 = 0; uint32_t ph = 6;
            uint4 af0[4], af1[4];
            auto load_a = [&](uint4 (&af)[4], int s) {
                mbar_wait(sb + SM_BARS + (B_FULL + s) * 8, (ph >> s) & 1);
                ph ^= 1u << s;
                const uint32_t a = ha + stage_off_rt(s);
                #pragma unroll
                for (int kk = 0; kk < 4; kk++) af[kk] = lds128(a + (kk >> 1) * 8192 + (kk & 1) * 2048);
            };
            auto g2 = [&](int u, uint4 (&cur)[4], uint4 (&nxt)[4], bool more) {
                const uint64_t db0 = desc_add(descB0, stage_off_rt(sg) >> 4);
                WG_FENCE();
                #pragma unroll
                for (int kk = 0; kk < 4; kk++) wgmma_rs_n128_tb(acc, cur[kk].x, cur[kk].y, cur[kk].z, cur[kk].w, db0 + ((kk >> 1) * 512 + (kk & 1) * 128), (u | kk) ? 1 : 0);
                WG_COMMIT();
                wg_wait<1>();
                if (lane < 2 && u > 0 && u + 4 < 28) mbar_arrive_cluster(e_cl + p0 * 8, 1);
                p0 = sg;
                sg = next_st2(sg);
                if (more) load_a(nxt, sg);
            };
            #pragma unroll
            for (int kk = 0; kk < 4; kk++) {
                af0[kk] = make_uint4(hp[4 * kk], hp[4 * kk + 1], hp[4 * kk + 2], hp[4 * kk + 3]);
                af1[kk] = make_uint4(hp[16 + 4 * kk], hp[17 + 4 * kk], hp[18 + 4 * kk], hp[19 + 4 * kk]);
            }
            mbar_wait(sb + SM_BARS + (B_FULL + 3) * 8, 0);
            g2(0, af0, af1, false);
            store_h(hdst + (32 + 6 * cb) * 2048, hp, 0); store_h(hdst + (32 + 6 * cb) * 2048, hp, 1);
            mbar_wait(sb + SM_BARS + (B_FULL + 4) * 8, 0);
            ph ^= 0x18;
            g2(1, af1, af0, true);
            store_h(hdst + (32 + 6 * cb) * 2048, hp, 2); store_h(hdst + (32 + 6 * cb) * 2048, hp, 3);
            __syncwarp();
            if (lane == 0) mbar_arrive(sb + SM_BARS + (B_HD + wgi * 2 + 1) * 8);
            g2(2, af0, af1, true);
            g2(3, af1, af0, true);
            #pragma unroll 1
            for (int u = 4; u < 26; u += 2) { g2(u, af0, af1, true); g2(u + 1, af1, af0, true); }
            g2(26, af0, af1, true);
            g2(27, af1, af0, false);
            wg_wait<0>();
            mbar_wait(sb + SM_BARS + B_XR * 8, 0);
            const int r0 = wgi * 64 + warp4 * 16 + g;
            const float2 st0 = lds64f(sb + SM_STATS + r0 * 8), st1 = lds64f(sb + SM_STATS + (r0 + 8) * 8);
            const uint32_t m0 = __float_as_uint(st0.x), m1 = __float_as_uint(st1.x);
            const uint32_t xrow0 = sb + SM_XE + r0 * 128 + c * 4;
            const int mi = lane >> 3, lr = lane & 7;
            const uint32_t yaddr = sb + SM_YT + wgi * 16384 + ((mi >> 1) * 8 + lr) * 128 + (((2 * warp4 + (mi & 1)) ^ lr) << 4);
            uint32_t y[8][4], xv[16][2], nv[16][2], bv[16][2];
            #pragma unroll
            for (int t = 0; t < 16; t++) {
                const uint32_t off = (t >> 3) * 16384 + (((t & 7) ^ g) << 4);
                xv[t][0] = lds32(xrow0 + off); xv[t][1] = lds32(xrow0 + 1024 + off);
            }
            #pragma unroll
            for (int t = 0; t < 16; t++) {
                const uint32_t d0 = bsub2(xv[t][0], m0), d1 = bsub2(xv[t][1], m1);
                nv[t][0] = pack_bf(bf_lo(d0) * st0.y, bf_hi(d0) * st0.y); nv[t][1] = pack_bf(bf_lo(d1) * st1.y, bf_hi(d1) * st1.y);
            }
            #pragma unroll
            for (int t = 0; t < 16; t++) { bv[t][0] = pack_bf(acc[4 * t], acc[4 * t + 1]); bv[t][1] = pack_bf(acc[4 * t + 2], acc[4 * t + 3]); }
            mbar_wait(sb + SM_BARS + B_YT * 8, 0);
            #pragma unroll
            for (int t2 = 0; t2 < 8; t2++)
                asm volatile("ldmatrix.sync.aligned.m8n8.x4.trans.shared.b16 {%0,%1,%2,%3}, [%4];"
                    : "=r"(y[t2][0]), "=r"(y[t2][1]), "=r"(y[t2][2]), "=r"(y[t2][3]) : "r"(yaddr + t2 * 2048) : "memory");
            #pragma unroll
            for (int hf = 0; hf < 2; hf++) {
                #pragma unroll
                for (int t = 8 * hf; t < 8 * hf + 8; t++) {
                    const uint32_t off = (t >> 3) * 16384 + (((t & 7) ^ g) << 4);
                    sts32(xrow0 + off, badd2(badd2(xv[t][0], bmul2(nv[t][0], y[t >> 1][2 * (t & 1)])), bv[t][0]));
                    sts32(xrow0 + 1024 + off, badd2(badd2(xv[t][1], bmul2(nv[t][1], y[t >> 1][2 * (t & 1) + 1])), bv[t][1]));
                }
                asm volatile("fence.proxy.async.shared::cta;" ::: "memory");
                __syncwarp();
                if (lane == 0) tma2d_store(&p.tm_out, 128 * cb + 64 * hf, 128 * i + 16 * warp, sb + SM_XE + hf * 16384 + warp * 2048);
            }
            if (lane == 0) {
                asm volatile("cp.async.bulk.commit_group;" ::: "memory");
                asm volatile("cp.async.bulk.wait_group.read 0;" ::: "memory");
            }
        }
    } else {
        asm volatile("setmaxnreg.dec.sync.aligned.u32 104;");
        if (warp == 8) {
            int st = 0; uint32_t eph = 7;
            const int nit = convCTA ? 12 : 16;
            #pragma unroll 1
            for (int it = 0; it < nit; it++) {
                const int pass = it >> 3, sl = it & 7;
                const bool narrow = pass && convCTA;
                const CUtensorMap* tm = narrow ? (rank ? &p.tm_uB : &p.tm_gB) : (rank ? &p.tm_uA : &p.tm_gA);
                mbar_wait(sb + SM_BARS + (B_EMPTY + st) * 8, (eph >> st) & 1);
                eph ^= 1u << st;
                if (it == 1) mbar_wait(sb + SM_BARS + B_XFULL * 8, 0);
                if (elect_one()) {
                    mbar_expect_tx(sb + SM_BARS + (B_FULL + st) * 8, 32768);
                    tma3d_mc(sb + SM_RING + st * STAGE_BYTES + rank * 16384, tm, 0, sl * (narrow ? 128 : 64), 14 * cb + 8 * (j & 1) + 4 * pass, sb + SM_BARS + (B_FULL + st) * 8);
                }
                st = (st == 2) ? 0 : st + 1;
            }
            if (!convCTA) {
                st = 3;
                const int f0_lane = blk_f0(2 * g2_pair(lane, cb) + rank);
                #pragma unroll 1
                for (int u = 0; u < 28; u++) {
                    const uint32_t bar = sb + SM_BARS + (B_FULL + st) * 8;
                    const int f0 = __shfl_sync(0xffffffffu, f0_lane, u);
                    mbar_wait(sb + SM_BARS + (B_EMPTY + st) * 8, (eph >> st) & 1);
                    eph ^= 1u << st;
                    if (elect_one()) {
                        mbar_expect_tx(bar, u < 2 ? 16384 : 32768);
                        tma3d_mc(sb + stage_off_rt(st) + rank * 8192, &p.tm_w2, 0, f0, 2 * cb, bar);
                    }
                    st = next_st2(st);
                }
            }
        } else if (warp < 11) {
            mbar_wait(sb + SM_BARS + (B_XFULL + 1) * 8, 0);
            {
                const int q = lane & 3;
                const int t0 = 32 * (b >> 1) + 8 * q;
                const int ch0 = 256 * (b & 1) + 16 * (warp - 9) + 2 * (lane >> 2);
                const uint32_t* kp = (const uint32_t*)(p.k + (size_t)t0 * DM + ch0);
                const uint32_t* vp = (const uint32_t*)(p.v + (size_t)t0 * DM + ch0);
                __nv_bfloat16* dst0 = g_kvT + (size_t)ch0 * SEQ + (t0 ^ 8);
                #pragma unroll 1
                for (int rnd = 0; rnd < 2; rnd++) {
                    uint32_t kr[4][11], vr[4][8]; uint4 skw[4];
                    #pragma unroll
                    for (int u = 0; u < 4; u++) {
                        const int co = (rnd * 4 + u) * 16;
                        skw[u] = ldg_nc128(p.shift_k + 4 * (ch0 + 2 * co));
                        #pragma unroll
                        for (int r = 0; r < 11; r++) kr[u][r] = (r >= 3 || t0 > 0) ? ldg_nc32(kp + co + (r - 3) * (DM / 2)) : 0u;
                        #pragma unroll
                        for (int r = 0; r < 8; r++) vr[u][r] = ldg_nc32(vp + co + r * (DM / 2));
                    }
                    #pragma unroll
                    for (int u = 0; u < 4; u++) {
                        const uint32_t s0 = __byte_perm(skw[u].x, skw[u].z, 0x5410), s1 = __byte_perm(skw[u].x, skw[u].z, 0x7632);
                        const uint32_t s2 = __byte_perm(skw[u].y, skw[u].w, 0x5410), s3 = __byte_perm(skw[u].y, skw[u].w, 0x7632);
                        #pragma unroll
                        for (int r = 0; r < 8; r++) {
                            uint32_t a = bmul2(kr[u][r], s3);
                            a = badd2(a, bmul2(kr[u][r + 1], s2));
                            a = badd2(a, bmul2(kr[u][r + 2], s1));
                            a = badd2(a, bmul2(kr[u][r + 3], s0));
                            vr[u][r] = bmul2(a, vr[u][r]);
                        }
                        __nv_bfloat16* dst = dst0 + (size_t)((rnd * 4 + u) * 32) * SEQ;
                        *(uint4*)dst = make_uint4(__byte_perm(vr[u][7], vr[u][6], 0x5410), __byte_perm(vr[u][5], vr[u][4], 0x5410),
                                                  __byte_perm(vr[u][3], vr[u][2], 0x5410), __byte_perm(vr[u][1], vr[u][0], 0x5410));
                        *(uint4*)(dst + SEQ) = make_uint4(__byte_perm(vr[u][7], vr[u][6], 0x7632), __byte_perm(vr[u][5], vr[u][4], 0x7632),
                                                          __byte_perm(vr[u][3], vr[u][2], 0x7632), __byte_perm(vr[u][1], vr[u][0], 0x7632));
                    }
                }
                if (lane == 0) mbar_arrive(sb + SM_BARS + B_KVLD * 8);
            }
            asm volatile("fence.proxy.async.global;" ::: "memory");
            __syncwarp();
            if (lane == 0) {
                flag_add(&g_cnt_kv[0]);
                const int wgi = warp - 9;
                mbar_wait(sb + SM_BARS + (B_HD + wgi * 2) * 8, 0);
                flag_add(&g_flag_h[(i * 2 + 0) * 8]);
                mbar_wait(sb + SM_BARS + (B_HD + wgi * 2 + 1) * 8, 0);
                flag_add(&g_flag_h[(i * 2 + 1) * 8]);
                if (wgi == 1 && !convCTA) {
                    mbar_wait(sb + SM_BARS + B_EP * 8, 0);
                    const unsigned ep = lds32(sb + SM_EPOCH);
                    mbar_wait(sb + SM_BARS + B_G1DONE * 8, 0);
                    mbar_expect_tx(sb + SM_BARS + B_XR * 8, 32768);
                    tma3d(sb + SM_XE, &p.tm_xe, 0, 128 * i, 2 * cb, sb + SM_BARS + B_XR * 8);
                    flag_wait(&g_flag_h[(i * 2 + 1) * 8], ep * 16);
                    mbar_arrive(sb + SM_BARS + (B_HRDY + 1) * 8);
                    __nanosleep(3000);
                    flag_wait(&g_cnt_y[cb * 32], ep * 128);
                    asm volatile("fence.proxy.async.global;" ::: "memory");
                    mbar_expect_tx(sb + SM_BARS + B_YT * 8, 32768);
                    tma2d(sb + SM_YT, &p.tm_yT, 128 * i, 128 * cb, sb + SM_BARS + B_YT * 8);
                    tma2d(sb + SM_YT + 16384, &p.tm_yT, 128 * i + 64, 128 * cb, sb + SM_BARS + B_YT * 8);
                }
            }
        } else {
            if (lane == 0) {
                l2_prefetch(p.wg + (size_t)b * (FF * DM / NCTA), FF * DM / NCTA * 2);
                l2_prefetch(p.wu + (size_t)b * (FF * DM / NCTA), FF * DM / NCTA * 2);
                const unsigned ep = g_launch[b] + 1;
                g_launch[b] = ep;
                sts32(sb + SM_EPOCH, ep);
                mbar_arrive(sb + SM_BARS + B_EP * 8);
                tmap_prefetch(rank ? &p.tm_uA : &p.tm_gA);
                tmap_prefetch(rank ? &p.tm_uB : &p.tm_gB);
                tmap_prefetch(&p.tm_w2); tmap_prefetch(&p.tm_yT); tmap_prefetch(&p.tm_out); tmap_prefetch(&p.tm_xe);
                mbar_wait(sb + SM_BARS + B_KVLD * 8, 0);
                l2_prefetch(p.ssm_k + (size_t)(4 * b) * SEQ, 4 * SEQ * 2);
                l2_prefetch(p.wd + (size_t)b * (FF * DM / NCTA), FF * DM / NCTA * 2);
                if (convCTA) {
                    __nanosleep(1000);
                    flag_wait(&g_cnt_kv[0], ep * 256);
                    asm volatile("fence.proxy.async.global;" ::: "memory");
                    mbar_wait(sb + SM_BARS + B_XFREE * 8, 0);
                    mbar_expect_tx(sb + SM_BARS + B_CONV * 8, 65536);
                    bulk_g2s(sb + SM_CVX, g_kvT + (size_t)(8 * cidx) * SEQ, 32768, sb + SM_BARS + B_CONV * 8);
                    bulk_g2s(sb + SM_CVH, p.ssm_k + (size_t)(8 * cidx) * SEQ, 32768, sb + SM_BARS + B_CONV * 8);
                } else {
                    mbar_wait(sb + SM_BARS + (B_HD + 0) * 8, 0);
                    flag_wait(&g_flag_h[(i * 2 + 0) * 8], ep * 16);
                }
            }
            __syncwarp();
            if (!convCTA) {
                asm volatile("fence.proxy.async.global;" ::: "memory");
                int st = 1; uint32_t eph = 0x19;
                const uint8_t* hsrc = (const uint8_t*)g_h + (size_t)i * 56 * 8192;
                #pragma unroll 1
                for (int u = 2; u < 28; u++) {
                    mbar_wait(sb + SM_BARS + (B_EMPTY + st) * 8, (eph >> st) & 1);
                    eph ^= 1u << st;
                    if (u == 18) {
                        mbar_wait(sb + SM_BARS + (B_HRDY + 1) * 8, 0);
                        asm volatile("fence.proxy.async.global;" ::: "memory");
                    }
                    if (elect_one()) bulk_g2s(sb + stage_off_rt(st) + 16384, hsrc + g2_pair(u, cb) * 16384, 16384, sb + SM_BARS + (B_FULL + st) * 8);
                    st = next_st2(st);
                }
            }
        }
    }
}

typedef CUresult (*EncodeFn)(CUtensorMap*, CUtensorMapDataType, cuuint32_t, void*, const cuuint64_t*, const cuuint64_t*,
                             const cuuint32_t*, const cuuint32_t*, CUtensorMapInterleave, CUtensorMapSwizzle,
                             CUtensorMapL2promotion, CUtensorMapFloatOOBfill);

void encode(EncodeFn fn, CUtensorMap* tm, const void* base, int rank, const cuuint64_t* dims, const cuuint64_t* strides,
            const cuuint32_t* box, CUtensorMapSwizzle swz) {
    cuuint32_t es[5] = {1, 1, 1, 1, 1};
    fn(tm, CU_TENSOR_MAP_DATA_TYPE_BFLOAT16, rank, (void*)base, dims, strides, box, es, CU_TENSOR_MAP_INTERLEAVE_NONE, swz,
       CU_TENSOR_MAP_L2_PROMOTION_L2_128B, CU_TENSOR_MAP_FLOAT_OOB_FILL_NONE);
}

}

extern "C" void kernel_launch(void* const* d_in, const int* in_sizes, int n_in, void* d_out, int out_size) {
    (void)in_sizes; (void)n_in; (void)out_size;
    static EncodeFn enc = nullptr;
    static void* yT_ptr = nullptr;
    if (!enc) {
        void* fn = nullptr; cudaDriverEntryPointQueryResult qr;
        cudaGetDriverEntryPoint("cuTensorMapEncodeTiled", &fn, cudaEnableDefault, &qr);
        enc = (EncodeFn)fn;
        cudaGetSymbolAddress(&yT_ptr, g_yT);
        cudaFuncSetAttribute(fused_kernel, cudaFuncAttributeMaxDynamicSharedMemorySize, SM_TOTAL);
    }
    Params p;
    p.q = (const __nv_bfloat16*)d_in[0]; p.k = (const __nv_bfloat16*)d_in[1]; p.v = (const __nv_bfloat16*)d_in[2];
    p.shift_k = (const __nv_bfloat16*)d_in[3]; p.ssm_k = (const __nv_bfloat16*)d_in[4]; p.ssm_D = (const __nv_bfloat16*)d_in[5];
    p.wg = (const __nv_bfloat16*)d_in[7]; p.wu = (const __nv_bfloat16*)d_in[8]; p.wd = (const __nv_bfloat16*)d_in[9];
    {
        cuuint64_t dims[2] = {DM, SEQ}; cuuint64_t str[1] = {DM * 2};
        cuuint64_t dims3[3] = {64, SEQ, DM / 64}; cuuint64_t str3[2] = {DM * 2, 128};
        cuuint32_t box[3] = {64, 64, 8}, boxe[3] = {64, 128, 2};
        encode(enc, &p.tm_x, p.q, 3, dims3, str3, box, CU_TENSOR_MAP_SWIZZLE_128B);
        encode(enc, &p.tm_xe, p.q, 3, dims3, str3, boxe, CU_TENSOR_MAP_SWIZZLE_128B);
        cuuint32_t box2[2] = {64, 16};
        encode(enc, &p.tm_out, d_out, 2, dims, str, box2, CU_TENSOR_MAP_SWIZZLE_128B);
    }
    {
        cuuint64_t dims[3] = {32, DM, FF / 32}; cuuint64_t str[2] = {FF * 2, 64};
        cuuint32_t boxA[3] = {32, 64, 4}, boxB[3] = {32, 128, 2};
        encode(enc, &p.tm_gA, p.wg, 3, dims, str, boxA, CU_TENSOR_MAP_SWIZZLE_64B);
        encode(enc, &p.tm_gB, p.wg, 3, dims, str, boxB, CU_TENSOR_MAP_SWIZZLE_64B);
        encode(enc, &p.tm_uA, p.wu, 3, dims, str, boxA, CU_TENSOR_MAP_SWIZZLE_64B);
        encode(enc, &p.tm_uB, p.wu, 3, dims, str, boxB, CU_TENSOR_MAP_SWIZZLE_64B);
    }
    {
        cuuint64_t dims[3] = {64, FF, DM / 64}; cuuint64_t str[2] = {DM * 2, 128};
        cuuint32_t box[3] = {64, 32, 2};
        encode(enc, &p.tm_w2, p.wd, 3, dims, str, box, CU_TENSOR_MAP_SWIZZLE_128B);
    }
    {
        cuuint64_t dims[2] = {SEQ, DM}; cuuint64_t str[1] = {SEQ * 2};
        cuuint32_t box[2] = {64, 128};
        encode(enc, &p.tm_yT, yT_ptr, 2, dims, str, box, CU_TENSOR_MAP_SWIZZLE_128B);
    }
    fused_kernel<<<NCTA, NTHREADS, SM_TOTAL>>>(p);
}
```

```cpp
#include <cuda_runtime.h>
#include <cuda_bf16.h>
#include <cuda.h>
#include <stdint.h>

namespace {

constexpr int SEQ = 2048, DM = 512, FF = 1792;
constexpr int NCTA = 128;
constexpr int NTHREADS = 384;
constexpr int STAGE_BYTES = 32768;

constexpr uint32_t SM_X = 0;
constexpr uint32_t SM_RING = 131072;
constexpr uint32_t SM_MISC = SM_RING + 3 * STAGE_BYTES;
constexpr uint32_t SM_BARS = SM_MISC;
constexpr uint32_t SM_EPOCH = SM_MISC + 248;
constexpr uint32_t SM_STATS = SM_MISC + 256;
constexpr uint32_t SM_TOTAL = SM_STATS + 1024;
static_assert(SM_TOTAL <= 232448, "smem");
constexpr uint32_t SM_CVX = 0;
constexpr uint32_t SM_CVH = 65536;
constexpr uint32_t SM_YT = 32768;
constexpr uint32_t SM_XE = 98304;

constexpr int B_FULL = 0, B_EMPTY = 5, B_XFULL = 10, B_CONV = 14, B_YT = 15, B_XR = 16, B_G1DONE = 17, B_HD = 18, B_HRDY = 22,
              B_XFREE = 24, B_EP = 25, B_KVLD = 26, B_LN = 27, B_COUNT = 28;
static_assert(B_COUNT * 8 <= 248, "barrier space");

__device__ __align__(128) uint32_t g_h[16 * 56 * 2048];
__device__ __align__(128) __nv_bfloat16 g_kvT[DM * SEQ];
__device__ __align__(128) __nv_bfloat16 g_yT[DM * SEQ];
__device__ unsigned g_launch[NCTA];
__device__ unsigned g_cnt_kv[32];
__device__ unsigned g_cnt_y[4 * 32];
__device__ unsigned g_flag_h[16 * 2 * 8];


struct Params {
    CUtensorMap tm_x, tm_gA, tm_gB, tm_uA, tm_uB, tm_w2, tm_yT, tm_out, tm_xe;
    const __nv_bfloat16 *q, *k, *v, *shift_k, *ssm_k, *ssm_D, *wg, *wu, *wd;
};

__device__ __forceinline__ void wgmma_ss_n128_tb(float (&d)[64], uint64_t da, uint64_t db, int sc) {
  asm volatile("{\n.reg .pred p;\nsetp.ne.b32 p, %66, 0;\n"
    "wgmma.mma_async.sync.aligned.m64n128k16.f32.bf16.bf16 {%0,%1,%2,%3,%4,%5,%6,%7,%8,%9,%10,%11,%12,%13,%14,%15,%16,%17,%18,%19,%20,%21,%22,%23,%24,%25,%26,%27,%28,%29,%30,%31,%32,%33,%34,%35,%36,%37,%38,%39,%40,%41,%42,%43,%44,%45,%46,%47,%48,%49,%50,%51,%52,%53,%54,%55,%56,%57,%58,%59,%60,%61,%62,%63}, %64, %65, p, 1, 1, 0, 1;\n}\n"
    : "+f"(d[0]),"+f"(d[1]),"+f"(d[2]),"+f"(d[3]),"+f"(d[4]),"+f"(d[5]),"+f"(d[6]),"+f"(d[7]),"+f"(d[8]),"+f"(d[9]),"+f"(d[10]),"+f"(d[11]),"+f"(d[12]),"+f"(d[13]),"+f"(d[14]),"+f"(d[15]),"+f"(d[16]),"+f"(d[17]),"+f"(d[18]),"+f"(d[19]),"+f"(d[20]),"+f"(d[21]),"+f"(d[22]),"+f"(d[23]),"+f"(d[24]),"+f"(d[25]),"+f"(d[26]),"+f"(d[27]),"+f"(d[28]),"+f"(d[29]),"+f"(d[30]),"+f"(d[31]),"+f"(d[32]),"+f"(d[33]),"+f"(d[34]),"+f"(d[35]),"+f"(d[36]),"+f"(d[37]),"+f"(d[38]),"+f"(d[39]),"+f"(d[40]),"+f"(d[41]),"+f"(d[42]),"+f"(d[43]),"+f"(d[44]),"+f"(d[45]),"+f"(d[46]),"+f"(d[47]),"+f"(d[48]),"+f"(d[49]),"+f"(d[50]),"+f"(d[51]),"+f"(d[52]),"+f"(d[53]),"+f"(d[54]),"+f"(d[55]),"+f"(d[56]),"+f"(d[57]),"+f"(d[58]),"+f"(d[59]),"+f"(d[60]),"+f"(d[61]),"+f"(d[62]),"+f"(d[63])
    : "l"(da),"l"(db),"r"(sc));
}
__device__ __forceinline__ void wgmma_rs_n128_tb(float (&d)[64], uint32_t a0, uint32_t a1, uint32_t a2, uint32_t a3, uint64_t db, int sc) {
  asm volatile("{\n.reg .pred p;\nsetp.ne.b32 p, %69, 0;\n"
    "wgmma.mma_async.sync.aligned.m64n128k16.f32.bf16.bf16 {%0,%1,%2,%3,%4,%5,%6,%7,%8,%9,%10,%11,%12,%13,%14,%15,%16,%17,%18,%19,%20,%21,%22,%23,%24,%25,%26,%27,%28,%29,%30,%31,%32,%33,%34,%35,%36,%37,%38,%39,%40,%41,%42,%43,%44,%45,%46,%47,%48,%49,%50,%51,%52,%53,%54,%55,%56,%57,%58,%59,%60,%61,%62,%63}, {%64,%65,%66,%67}, %68, p, 1, 1, 1;\n}\n"
    : "+f"(d[0]),"+f"(d[1]),"+f"(d[2]),"+f"(d[3]),"+f"(d[4]),"+f"(d[5]),"+f"(d[6]),"+f"(d[7]),"+f"(d[8]),"+f"(d[9]),"+f"(d[10]),"+f"(d[11]),"+f"(d[12]),"+f"(d[13]),"+f"(d[14]),"+f"(d[15]),"+f"(d[16]),"+f"(d[17]),"+f"(d[18]),"+f"(d[19]),"+f"(d[20]),"+f"(d[21]),"+f"(d[22]),"+f"(d[23]),"+f"(d[24]),"+f"(d[25]),"+f"(d[26]),"+f"(d[27]),"+f"(d[28]),"+f"(d[29]),"+f"(d[30]),"+f"(d[31]),"+f"(d[32]),"+f"(d[33]),"+f"(d[34]),"+f"(d[35]),"+f"(d[36]),"+f"(d[37]),"+f"(d[38]),"+f"(d[39]),"+f"(d[40]),"+f"(d[41]),"+f"(d[42]),"+f"(d[43]),"+f"(d[44]),"+f"(d[45]),"+f"(d[46]),"+f"(d[47]),"+f"(d[48]),"+f"(d[49]),"+f"(d[50]),"+f"(d[51]),"+f"(d[52]),"+f"(d[53]),"+f"(d[54]),"+f"(d[55]),"+f"(d[56]),"+f"(d[57]),"+f"(d[58]),"+f"(d[59]),"+f"(d[60]),"+f"(d[61]),"+f"(d[62]),"+f"(d[63])
    : "r"(a0),"r"(a1),"r"(a2),"r"(a3),"l"(db),"r"(sc));
}
__device__ __forceinline__ void wgmma_ss_n256_tb(float (&d)[128], uint64_t da, uint64_t db, int sc) {
  asm volatile("{\n.reg .pred p;\nsetp.ne.b32 p, %130, 0;\n"
    "wgmma.mma_async.sync.aligned.m64n256k16.f32.bf16.bf16 {%0,%1,%2,%3,%4,%5,%6,%7,%8,%9,%10,%11,%12,%13,%14,%15,%16,%17,%18,%19,%20,%21,%22,%23,%24,%25,%26,%27,%28,%29,%30,%31,%32,%33,%34,%35,%36,%37,%38,%39,%40,%41,%42,%43,%44,%45,%46,%47,%48,%49,%50,%51,%52,%53,%54,%55,%56,%57,%58,%59,%60,%61,%62,%63,%64,%65,%66,%67,%68,%69,%70,%71,%72,%73,%74,%75,%76,%77,%78,%79,%80,%81,%82,%83,%84,%85,%86,%87,%88,%89,%90,%91,%92,%93,%94,%95,%96,%97,%98,%99,%100,%101,%102,%103,%104,%105,%106,%107,%108,%109,%110,%111,%112,%113,%114,%115,%116,%117,%118,%119,%120,%121,%122,%123,%124,%125,%126,%127}, %128, %129, p, 1, 1, 0, 1;\n}\n"
    : "+f"(d[0]),"+f"(d[1]),"+f"(d[2]),"+f"(d[3]),"+f"(d[4]),"+f"(d[5]),"+f"(d[6]),"+f"(d[7]),"+f"(d[8]),"+f"(d[9]),"+f"(d[10]),"+f"(d[11]),"+f"(d[12]),"+f"(d[13]),"+f"(d[14]),"+f"(d[15]),"+f"(d[16]),"+f"(d[17]),"+f"(d[18]),"+f"(d[19]),"+f"(d[20]),"+f"(d[21]),"+f"(d[22]),"+f"(d[23]),"+f"(d[24]),"+f"(d[25]),"+f"(d[26]),"+f"(d[27]),"+f"(d[28]),"+f"(d[29]),"+f"(d[30]),"+f"(d[31]),"+f"(d[32]),"+f"(d[33]),"+f"(d[34]),"+f"(d[35]),"+f"(d[36]),"+f"(d[37]),"+f"(d[38]),"+f"(d[39]),"+f"(d[40]),"+f"(d[41]),"+f"(d[42]),"+f"(d[43]),"+f"(d[44]),"+f"(d[45]),"+f"(d[46]),"+f"(d[47]),"+f"(d[48]),"+f"(d[49]),"+f"(d[50]),"+f"(d[51]),"+f"(d[52]),"+f"(d[53]),"+f"(d[54]),"+f"(d[55]),"+f"(d[56]),"+f"(d[57]),"+f"(d[58]),"+f"(d[59]),"+f"(d[60]),"+f"(d[61]),"+f"(d[62]),"+f"(d[63]),"+f"(d[64]),"+f"(d[65]),"+f"(d[66]),"+f"(d[67]),"+f"(d[68]),"+f"(d[69]),"+f"(d[70]),"+f"(d[71]),"+f"(d[72]),"+f"(d[73]),"+f"(d[74]),"+f"(d[75]),"+f"(d[76]),"+f"(d[77]),"+f"(d[78]),"+f"(d[79]),"+f"(d[80]),"+f"(d[81]),"+f"(d[82]),"+f"(d[83]),"+f"(d[84]),"+f"(d[85]),"+f"(d[86]),"+f"(d[87]),"+f"(d[88]),"+f"(d[89]),"+f"(d[90]),"+f"(d[91]),"+f"(d[92]),"+f"(d[93]),"+f"(d[94]),"+f"(d[95]),"+f"(d[96]),"+f"(d[97]),"+f"(d[98]),"+f"(d[99]),"+f"(d[100]),"+f"(d[101]),"+f"(d[102]),"+f"(d[103]),"+f"(d[104]),"+f"(d[105]),"+f"(d[106]),"+f"(d[107]),"+f"(d[108]),"+f"(d[109]),"+f"(d[110]),"+f"(d[111]),"+f"(d[112]),"+f"(d[113]),"+f"(d[114]),"+f"(d[115]),"+f"(d[116]),"+f"(d[117]),"+f"(d[118]),"+f"(d[119]),"+f"(d[120]),"+f"(d[121]),"+f"(d[122]),"+f"(d[123]),"+f"(d[124]),"+f"(d[125]),"+f"(d[126]),"+f"(d[127])
    : "l"(da),"l"(db),"r"(sc));
}


__device__ __forceinline__ uint32_t smem_u32(const void* p) { return (uint32_t)__cvta_generic_to_shared(p); }
__device__ __forceinline__ void mbar_init(uint32_t bar, uint32_t cnt) { asm volatile("mbarrier.init.shared::cta.b64 [%0], %1;" :: "r"(bar), "r"(cnt)); }
__device__ __forceinline__ void mbar_expect_tx(uint32_t bar, uint32_t bytes) { asm volatile("mbarrier.arrive.expect_tx.shared::cta.b64 _, [%0], %1;" :: "r"(bar), "r"(bytes) : "memory"); }
__device__ __forceinline__ void mbar_arrive(uint32_t bar) { asm volatile("mbarrier.arrive.shared::cta.b64 _, [%0];" :: "r"(bar) : "memory"); }
__device__ __forceinline__ void mbar_arrive_cluster(uint32_t cbar, uint32_t cnt) { asm volatile("mbarrier.arrive.shared::cluster.b64 _, [%0], %1;" :: "r"(cbar), "r"(cnt) : "memory"); }
__device__ __forceinline__ uint32_t mapa(uint32_t a, uint32_t rank) { uint32_t r; asm volatile("mapa.shared::cluster.u32 %0, %1, %2;" : "=r"(r) : "r"(a), "r"(rank)); return r; }
__device__ __forceinline__ void mbar_wait(uint32_t bar, uint32_t parity) {
    uint32_t ok; uint32_t n = 0;
    do {
        asm volatile("{\n.reg .pred p;\nmbarrier.try_wait.parity.shared::cta.b64 p, [%1], %2;\nselp.u32 %0, 1, 0, p;\n}" : "=r"(ok) : "r"(bar), "r"(parity) : "memory");
    } while (!ok && ++n < (1u << 17));
}
__device__ __forceinline__ void flag_wait(const unsigned* p, unsigned target) {
    unsigned v; uint32_t n = 0;
    while (true) {
        asm volatile("ld.acquire.gpu.global.u32 %0, [%1];" : "=r"(v) : "l"(p) : "memory");
        if ((int)(v - target) >= 0 || ++n >= (1u << 17)) break;
        __nanosleep(40);
    }
}
__device__ __forceinline__ void flag_add(unsigned* p) {
    asm volatile("fence.acq_rel.gpu;\nred.relaxed.gpu.global.add.u32 [%0], 1;" :: "l"(p) : "memory");
}
__device__ __forceinline__ uint64_t make_desc(uint32_t addr, uint32_t lbo, uint32_t sbo, uint32_t swz) {
    return (uint64_t)((addr & 0x3FFFF) >> 4) | ((uint64_t)((lbo & 0x3FFFF) >> 4) << 16) | ((uint64_t)((sbo & 0x3FFFF) >> 4) << 32) | ((uint64_t)swz << 62);
}
__device__ __forceinline__ uint64_t desc_add(uint64_t d, uint32_t off16) {
    return (d & 0xFFFFFFFF00000000ull) | (uint64_t)((uint32_t)d + off16);
}
__device__ __forceinline__ void tma2d(uint32_t dst, const CUtensorMap* tm, int c0, int c1, uint32_t bar) {
    asm volatile("cp.async.bulk.tensor.2d.shared::cluster.global.mbarrier::complete_tx::bytes [%0], [%1, {%3, %4}], [%2];"
        :: "r"(dst), "l"((uint64_t)tm), "r"(bar), "r"(c0), "r"(c1) : "memory");
}
__device__ __forceinline__ void tma3d(uint32_t dst, const CUtensorMap* tm, int c0, int c1, int c2, uint32_t bar) {
    asm volatile("cp.async.bulk.tensor.3d.shared::cluster.global.mbarrier::complete_tx::bytes [%0], [%1, {%3, %4, %5}], [%2];"
        :: "r"(dst), "l"((uint64_t)tm), "r"(bar), "r"(c0), "r"(c1), "r"(c2) : "memory");
}
__device__ __forceinline__ void tma3d_mc(uint32_t dst, const CUtensorMap* tm, int c0, int c1, int c2, uint32_t bar) {
    asm volatile("cp.async.bulk.tensor.3d.shared::cluster.global.mbarrier::complete_tx::bytes.multicast::cluster [%0], [%1, {%3, %4, %5}], [%2], %6;"
        :: "r"(dst), "l"((uint64_t)tm), "r"(bar), "r"(c0), "r"(c1), "r"(c2), "h"((uint16_t)3) : "memory");
}
__device__ __forceinline__ void bulk_g2s(uint32_t dst, const void* src, uint32_t bytes, uint32_t bar) {
    asm volatile("cp.async.bulk.shared::cluster.global.mbarrier::complete_tx::bytes [%0], [%1], %2, [%3];"
        :: "r"(dst), "l"(src), "r"(bytes), "r"(bar) : "memory");
}
__device__ __forceinline__ void tma2d_store(const CUtensorMap* tm, int c0, int c1, uint32_t src) {
    asm volatile("cp.async.bulk.tensor.2d.global.shared::cta.bulk_group [%0, {%2, %3}], [%1];"
        :: "l"((uint64_t)tm), "r"(src), "r"(c0), "r"(c1) : "memory");
}
__device__ __forceinline__ void l2_prefetch(const void* p, uint32_t bytes) {
    asm volatile("cp.async.bulk.prefetch.L2.global [%0], %1;" :: "l"(p), "r"(bytes) : "memory");
}
__device__ __forceinline__ void tmap_prefetch(const CUtensorMap* tm) { asm volatile("prefetch.tensormap [%0];" :: "l"((uint64_t)tm) : "memory"); }
__device__ __forceinline__ uint32_t lds32(uint32_t a) { uint32_t v; asm volatile("ld.shared.u32 %0, [%1];" : "=r"(v) : "r"(a)); return v; }
__device__ __forceinline__ uint2 lds64(uint32_t a) { uint2 v; asm volatile("ld.shared.v2.u32 {%0,%1}, [%2];" : "=r"(v.x), "=r"(v.y) : "r"(a)); return v; }
__device__ __forceinline__ float2 lds64f(uint32_t a) { float2 v; asm volatile("ld.shared.v2.f32 {%0,%1}, [%2];" : "=f"(v.x), "=f"(v.y) : "r"(a)); return v; }
__device__ __forceinline__ uint4 lds128(uint32_t a) { uint4 v; asm volatile("ld.shared.v4.u32 {%0,%1,%2,%3}, [%4];" : "=r"(v.x), "=r"(v.y), "=r"(v.z), "=r"(v.w) : "r"(a)); return v; }
__device__ __forceinline__ void sts32(uint32_t a, uint32_t v) { asm volatile("st.shared.u32 [%0], %1;" :: "r"(a), "r"(v) : "memory"); }
__device__ __forceinline__ uint4 ldg_nc128(const void* p) { uint4 v; asm volatile("ld.global.nc.L1::no_allocate.v4.u32 {%0,%1,%2,%3}, [%4];" : "=r"(v.x), "=r"(v.y), "=r"(v.z), "=r"(v.w) : "l"(p)); return v; }
__device__ __forceinline__ uint32_t ldg_nc32(const void* p) { uint32_t v; asm volatile("ld.global.nc.u32 %0, [%1];" : "=r"(v) : "l"(p)); return v; }
#define WG_FENCE() asm volatile("wgmma.fence.sync.aligned;\n" ::: "memory")
#define WG_COMMIT() asm volatile("wgmma.commit_group.sync.aligned;\n" ::: "memory")
template<int N> __device__ __forceinline__ void wg_wait() { asm volatile("wgmma.wait_group.sync.aligned %0;\n" :: "n"(N) : "memory"); }
__device__ __forceinline__ bool elect_one() {
    uint32_t pr;
    asm volatile("{\n.reg .pred p;\nelect.sync _|p, 0xffffffff;\nselp.u32 %0, 1, 0, p;\n}" : "=r"(pr));
    return pr != 0;
}

__device__ __forceinline__ float bf_lo(uint32_t u) { return __uint_as_float(u << 16); }
__device__ __forceinline__ float bf_hi(uint32_t u) { return __uint_as_float(u & 0xFFFF0000u); }
__device__ __forceinline__ uint32_t pack_bf(float lo, float hi) { uint32_t r; asm("cvt.rn.bf16x2.f32 %0, %1, %2;" : "=r"(r) : "f"(hi), "f"(lo)); return r; }
__device__ __forceinline__ float bf_round(float x) { return __bfloat162float(__float2bfloat16_rn(x)); }
__device__ __forceinline__ uint32_t bmul2(uint32_t a, uint32_t b) { uint32_t r; asm("mul.rn.bf16x2 %0, %1, %2;" : "=r"(r) : "r"(a), "r"(b)); return r; }
__device__ __forceinline__ uint32_t badd2(uint32_t a, uint32_t b) { uint32_t r; asm("add.rn.bf16x2 %0, %1, %2;" : "=r"(r) : "r"(a), "r"(b)); return r; }
__device__ __forceinline__ uint32_t bsub2(uint32_t a, uint32_t b) { uint32_t r; asm("sub.rn.bf16x2 %0, %1, %2;" : "=r"(r) : "r"(a), "r"(b)); return r; }
__device__ __forceinline__ void mma16816(float (&d)[4], uint32_t a0, uint32_t a1, uint32_t a2, uint32_t a3, uint2 b) {
    asm volatile("mma.sync.aligned.m16n8k16.row.col.f32.bf16.bf16.f32 {%0,%1,%2,%3}, {%4,%5,%6,%7}, {%8,%9}, {%0,%1,%2,%3};\n"
        : "+f"(d[0]), "+f"(d[1]), "+f"(d[2]), "+f"(d[3]) : "r"(a0), "r"(a1), "r"(a2), "r"(a3), "r"(b.x), "r"(b.y));
}

__device__ __forceinline__ int blk_f0(int s) {
    if (s < 32) return 32 * (14 * (s >> 3) + 8 * ((s >> 2) & 1) + (s & 3));
    const int s2 = s - 32, c6 = (s2 * 11) >> 6, t = s2 - 6 * c6;
    return 32 * (14 * c6 + (t < 4 ? 4 + t : 8 + t));
}
__device__ __forceinline__ int g2_pair(int u, int cb) {
    if (u < 2) return 16 + 3 * cb + u;
    if (u < 18) return u - 2;
    return u - 2 + ((u - 18 >= 3 * cb) ? 2 : 0);
}
__device__ __forceinline__ int next_st2(int s) { return (0x14023 >> (4 * s)) & 7; }
__device__ __forceinline__ uint32_t stage_off_rt(int s) { return s < 3 ? SM_RING + s * STAGE_BYTES : (uint32_t)(s - 3) * 65536; }

__device__ __forceinline__ void store_h(uint32_t* dst, const uint32_t (&hp)[32], int q) {
    *(uint4*)(dst + q * 2048) = make_uint4(hp[8 * q], hp[8 * q + 1], hp[8 * q + 2], hp[8 * q + 3]);
    *(uint4*)(dst + q * 2048 + 512) = make_uint4(hp[8 * q + 4], hp[8 * q + 5], hp[8 * q + 6], hp[8 * q + 7]);
}
template<int NB, bool passA>
__device__ __forceinline__ void gemm1_pass(uint32_t sb, int wgi, int warp4, int lane, int& st, uint32_t& fph, uint32_t e_cl,
                                           uint32_t (&hp)[32], uint32_t* prev_dst, bool convCTA) {
    constexpr bool narrow = (NB == 2);
    float acc[NB * 32];
    const uint64_t descA0 = make_desc(sb + SM_X + wgi * 65536, 16, 1024, 1);
    const uint64_t descB0 = make_desc(sb + SM_RING, narrow ? 8192 : 4096, 512, 2);
    int prev = 0;
    auto group = [&](int sl) {
        mbar_wait(sb + SM_BARS + (B_FULL + st) * 8, (fph >> st) & 1);
        fph ^= 1u << st;
        const uint64_t da = desc_add(descA0, sl * (narrow ? 1024 : 512)), db = desc_add(descB0, st * 2048);
        WG_FENCE();
        #pragma unroll
        for (int kk = 0; kk < (narrow ? 8 : 4); kk++) {
            int sc = (sl | kk) ? 1 : 0;
            if constexpr (!narrow) wgmma_ss_n256_tb(acc, da + kk * 2, db + kk * 64, sc);
            else wgmma_ss_n128_tb(acc, da + ((kk >> 2) * 512 + (kk & 3) * 2), db + kk * 64, sc);
        }
        WG_COMMIT();
        wg_wait<1>();
        if (lane < 2 && sl && (!narrow || sl == 1)) mbar_arrive_cluster(e_cl + prev * 8, 1);
        if (narrow && sl == 2 && lane == 0) mbar_arrive(sb + SM_BARS + B_XFREE * 8);
        if (!passA && !narrow && sl == 4 && lane < 4) mbar_arrive_cluster(e_cl + (3 + (lane >> 1)) * 8, 1);
        prev = st;
        st = (st == 2) ? 0 : st + 1;
    };
    if constexpr (passA) {
        #pragma unroll 1
        for (int sl = 0; sl < 8; sl++) group(sl);
    } else {
        #pragma unroll
        for (int sl = 0; sl < 4; sl++) { group(sl); store_h(prev_dst, hp, sl); }
        __syncwarp();
        if (lane == 0) mbar_arrive(sb + SM_BARS + (B_HD + wgi * 2) * 8);
        if constexpr (!narrow) {
            #pragma unroll 1
            for (int sl = 4; sl < 8; sl++) group(sl);
        }
    }
    wg_wait<0>();
    if (lane < 2 && (passA || !convCTA)) mbar_arrive_cluster(e_cl + prev * 8, 1);
    if (!passA && lane == 0) mbar_arrive(sb + SM_BARS + B_G1DONE * 8);
    const int g = lane >> 2;
    const int r0 = wgi * 64 + warp4 * 16 + g;
    const float s0 = __uint_as_float(lds32(sb + SM_STATS + r0 * 8 + 4)), s1 = __uint_as_float(lds32(sb + SM_STATS + (r0 + 8) * 8 + 4));
    #pragma unroll
    for (int t = 0; t < NB * 4; t++) {
        const float* ag = &acc[4 * t];
        const float* au = &acc[NB * 16 + 4 * t];
        hp[2 * t] = bmul2(pack_bf(ag[0] * s0, ag[1] * s0), pack_bf(au[0] * s0, au[1] * s0));
        hp[2 * t + 1] = bmul2(pack_bf(ag[2] * s1, ag[3] * s1), pack_bf(au[2] * s1, au[3] * s1));
    }
}

__global__ void __cluster_dims__(2, 1, 1) __launch_bounds__(NTHREADS, 1)
fused_kernel(const __grid_constant__ Params p) {
    extern __shared__ __align__(1024) uint8_t smem_raw[];
    const uint32_t sb = smem_u32(smem_raw);
    const int tid = threadIdx.x, warp = tid >> 5, lane = tid & 31;
    const int b = blockIdx.x;
    const int rank = b & 1;
    const int j = (b >> 1) & 7;
    const int i = ((b >> 4) << 1) | rank;
    const int cb = j >> 1;
    const bool convCTA = j & 1;
    const int cidx = 4 * i + cb;

    if (tid == 256) {
        mbar_init(sb + SM_BARS + B_XFULL * 8, 1);
        mbar_init(sb + SM_BARS + (B_XFULL + 1) * 8, 1);
        asm volatile("fence.proxy.async.shared::cta;" ::: "memory");
        mbar_expect_tx(sb + SM_BARS + B_XFULL * 8, 65536);
        tma3d(sb + SM_X, &p.tm_x, 0, 128 * i, 0, sb + SM_BARS + B_XFULL * 8);
        mbar_expect_tx(sb + SM_BARS + (B_XFULL + 1) * 8, 65536);
        tma3d(sb + SM_X + 65536, &p.tm_x, 0, 128 * i + 64, 0, sb + SM_BARS + (B_XFULL + 1) * 8);
        asm volatile("fence.mbarrier_init.release.cluster;" ::: "memory");
    }
    if (tid == 288) {
        for (int s = 0; s < 5; s++) { mbar_init(sb + SM_BARS + (B_FULL + s) * 8, 1); mbar_init(sb + SM_BARS + (B_EMPTY + s) * 8, 16); }
        mbar_init(sb + SM_BARS + B_CONV * 8, 1);
        mbar_init(sb + SM_BARS + B_YT * 8, 1);
        mbar_init(sb + SM_BARS + B_XR * 8, 1);
        mbar_init(sb + SM_BARS + B_G1DONE * 8, 8);
        mbar_init(sb + SM_BARS + B_XFREE * 8, 8);
        mbar_init(sb + SM_BARS + B_KVLD * 8, 2);
        mbar_init(sb + SM_BARS + B_EP * 8, 1);
        mbar_init(sb + SM_BARS + B_LN * 8, 8);
        for (int s = 0; s < 4; s++) mbar_init(sb + SM_BARS + (B_HD + s) * 8, 4);
        for (int s = 0; s < 2; s++) mbar_init(sb + SM_BARS + (B_HRDY + s) * 8, 1);
        asm volatile("fence.mbarrier_init.release.cluster;" ::: "memory");
        asm volatile("fence.proxy.async.shared::cta;" ::: "memory");
    }
    __syncwarp();
    asm volatile("barrier.cluster.arrive.relaxed.aligned;\n" ::: "memory");
    asm volatile("barrier.cluster.wait.aligned;\n" ::: "memory");

    if (warp < 8) {
        asm volatile("setmaxnreg.inc.sync.aligned.u32 200;");
        const int wgi = warp >> 2, warp4 = warp & 3;
        const int g = lane >> 2, c = lane & 3;
        const uint32_t e_cl = mapa(sb + SM_BARS + B_EMPTY * 8, lane & 1);
        {
            const int lr16 = (lane & 7) + ((lane >> 3) & 1) * 8;
            const uint32_t xa = sb + SM_X + wgi * 65536 + (warp4 * 16 + lr16) * 128;
            uint32_t xf[32][4];
            float aS[4][4], aQ0[4][4], aQ1[4][4];
            #pragma unroll
            for (int e = 0; e < 4; e++) {
                #pragma unroll
                for (int f = 0; f < 4; f++) { aS[e][f] = 0.f; aQ0[e][f] = 0.f; aQ1[e][f] = 0.f; }
            }
            mbar_wait(sb + SM_BARS + (B_XFULL + wgi) * 8, 0);
            #pragma unroll
            for (int ks = 0; ks < 32; ks++) {
                const uint32_t a = xa + (ks >> 2) * 8192 + (((2 * (ks & 3) + (lane >> 4)) ^ (lane & 7)) << 4);
                asm volatile("ldmatrix.sync.aligned.m8n8.x4.shared.b16 {%0,%1,%2,%3}, [%4];"
                    : "=r"(xf[ks][0]), "=r"(xf[ks][1]), "=r"(xf[ks][2]), "=r"(xf[ks][3]) : "r"(a) : "memory");
            }
            #pragma unroll
            for (int ks = 0; ks < 32; ks++)
                mma16816(aS[ks & 3], xf[ks][0], xf[ks][1], xf[ks][2], xf[ks][3], make_uint2(0x3F803F80u, 0x3F803F80u));
            const float mean0 = ((aS[0][0] + aS[1][0]) + (aS[2][0] + aS[3][0])) * (1.0f / DM);
            const float mean1 = ((aS[0][2] + aS[1][2]) + (aS[2][2] + aS[3][2])) * (1.0f / DM);
            const uint32_t m0 = pack_bf(mean0, mean0), m1 = pack_bf(mean1, mean1);
            #pragma unroll
            for (int ks = 0; ks < 32; ks++) {
                const uint32_t a = xa + (ks >> 2) * 8192 + (((2 * (ks & 3) + (lane >> 4)) ^ (lane & 7)) << 4);
                asm volatile("stmatrix.sync.aligned.m8n8.x4.shared.b16 [%0], {%1,%2,%3,%4};"
                    :: "r"(a), "r"(bsub2(xf[ks][0], m0)), "r"(bsub2(xf[ks][1], m1)), "r"(bsub2(xf[ks][2], m0)), "r"(bsub2(xf[ks][3], m1)) : "memory");
            }
            asm volatile("fence.proxy.async.shared::cta;" ::: "memory");
            __syncwarp();
            if (lane == 0) mbar_arrive(sb + SM_BARS + B_LN * 8);
            #pragma unroll
            for (int ks = 0; ks < 32; ks++) {
                mma16816(aQ0[ks & 3], xf[ks][0], xf[ks][1], xf[ks][2], xf[ks][3], make_uint2(xf[ks][0], xf[ks][2]));
                mma16816(aQ1[ks & 3], xf[ks][0], xf[ks][1], xf[ks][2], xf[ks][3], make_uint2(xf[ks][1], xf[ks][3]));
            }
            if (c == (g >> 1)) {
                const float q0 = (g & 1) ? (aQ0[0][1] + aQ0[1][1]) + (aQ0[2][1] + aQ0[3][1]) : (aQ0[0][0] + aQ0[1][0]) + (aQ0[2][0] + aQ0[3][0]);
                const float q1 = (g & 1) ? (aQ1[0][3] + aQ1[1][3]) + (aQ1[2][3] + aQ1[3][3]) : (aQ1[0][2] + aQ1[1][2]) + (aQ1[2][2] + aQ1[3][2]);
                const float sd0 = bf_round(sqrtf(bf_round(bf_round(fmaxf(q0 * (1.0f / DM) - mean0 * mean0, 0.f)) + 1e-5f)));
                const float sd1 = bf_round(sqrtf(bf_round(bf_round(fmaxf(q1 * (1.0f / DM) - mean1 * mean1, 0.f)) + 1e-5f)));
                const uint32_t sa = sb + SM_STATS + (warp * 16 + g) * 8;
                sts32(sa, m0); sts32(sa + 4, __float_as_uint(1.0f / sd0));
                sts32(sa + 64, m1); sts32(sa + 68, __float_as_uint(1.0f / sd1));
            }
            __syncwarp();
            mbar_wait(sb + SM_BARS + B_LN * 8, 0);
            if (wgi == 0) __nanosleep(250);
        }
        int st = 0; uint32_t fph = 0;
        uint32_t hp[32];
        uint32_t* const hdst = g_h + (size_t)(i * 56) * 2048 + wgi * 1024 + warp4 * 128 + lane * 4;
        gemm1_pass<4, true>(sb, wgi, warp4, lane, st, fph, e_cl, hp, hdst, convCTA);

        if (convCTA) {
            gemm1_pass<2, false>(sb, wgi, warp4, lane, st, fph, e_cl, hp, hdst + 4 * j * 2048, true);
            store_h(hdst + (36 + 6 * cb) * 2048, hp, 0); store_h(hdst + (36 + 6 * cb) * 2048, hp, 1);
            __syncwarp();
            if (lane == 0) mbar_arrive(sb + SM_BARS + (B_HD + wgi * 2 + 1) * 8);
            const int gch = 8 * cidx + warp;
            const uint32_t xb = sb + SM_CVX + warp * 4096;
            const uint32_t hb = sb + SM_CVH + warp * 4096;
            const uint32_t dw = ((const unsigned short*)p.ssm_D)[gch];
            const uint32_t d2 = dw | (dw << 16);
            mbar_wait(sb + SM_BARS + B_CONV * 8, 0);
            float acc[16][4];
            #pragma unroll
            for (int jj = 0; jj < 16; jj++) { acc[jj][0] = 0.f; acc[jj][1] = 0.f; acc[jj][2] = 0.f; acc[jj][3] = 0.f; }
            uint2 bh[8], bl0[8], bl1[8];
            uint32_t xl = xb + g * 32 + c * 8;
            uint32_t hl = hb + (g + 2 * c - 8) * 4;
            #pragma unroll
            for (int d = 0; d < 8; d++) { bl0[d] = lds64(xl + d * 256); bh[d] = lds64(xl + (8 + d) * 256); }
            uint32_t w[6];
            w[0] = 0; w[1] = 0; w[2] = 0;
            if (g + 2 * c >= 8) w[0] = lds32(hl);
            if (g + 2 * c >= 7) w[1] = lds32(hl + 4);
            if (g + 2 * c >= 6) w[2] = lds32(hl + 8);
            w[3] = lds32(hl + 2048); w[4] = lds32(hl + 2052); w[5] = lds32(hl + 2056);
            auto conv_m0 = [&](int m0, uint2 (&bl)[8], uint2 (&bn)[8]) {
                xl -= 32;
                #pragma unroll
                for (int k = 0; k < 8; k++) {
                    const uint32_t a0 = w[1], a1 = __byte_perm(w[0], w[1], 0x5432), a2 = w[2], a3 = __byte_perm(w[1], w[2], 0x5432);
                    const uint32_t c0 = w[4], c1 = __byte_perm(w[3], w[4], 0x5432), c2 = w[5], c3 = __byte_perm(w[4], w[5], 0x5432);
                    const uint32_t nx = (k < 7) ? hl + (k + 1) * 256 : hl + 32;
                    w[0] = lds32(nx); w[1] = lds32(nx + 4); w[2] = lds32(nx + 8);
                    w[3] = lds32(nx + 2048); w[4] = lds32(nx + 2052); w[5] = lds32(nx + 2056);
                    if (k > 0) bn[k] = lds64(xl + k * 256);
                    else { bn[0] = make_uint2(0, 0); if (g > m0) bn[0] = lds64(xl); }
                    #pragma unroll
                    for (int jj = k; jj < 16; jj++) mma16816(acc[jj], a0, a1, a2, a3, (jj - k < 8) ? bl[(jj - k) & 7] : bh[(jj - k) & 7]);
                    bh[7 - k] = lds64(xl + (15 - k) * 256);
                    #pragma unroll
                    for (int jj = k + 8; jj < 16; jj++) mma16816(acc[jj], c0, c1, c2, c3, bl[jj - k - 8]);
                }
                hl += 32;
            };
            #pragma unroll 1
            for (int m0 = 0; m0 < 8; m0 += 2) {
                conv_m0(m0, bl0, bl1);
                conv_m0(m0 + 1, bl1, bl0);
            }
            const uint32_t kvl = xb + c * 64 + (7 - g) * 4;
            uint32_t* ydst = (uint32_t*)(g_yT + (size_t)gch * SEQ + 32 * c + 2 * g);
            uint32_t kk0[16], kk1[16];
            #pragma unroll
            for (int jj = 0; jj < 16; jj++) { kk0[jj] = lds32(kvl + jj * 256); kk1[jj] = lds32(kvl + jj * 256 + 32); }
            #pragma unroll
            for (int jj = 0; jj < 16; jj++) {
                ydst[jj * 64] = badd2(pack_bf(acc[jj][2], acc[jj][0]), bmul2(__byte_perm(kk0[jj], kk0[jj], 0x1032), d2));
                ydst[jj * 64 + 8] = badd2(pack_bf(acc[jj][3], acc[jj][1]), bmul2(__byte_perm(kk1[jj], kk1[jj], 0x1032), d2));
            }
            __syncwarp();
            if (lane == 0) flag_add(&g_cnt_y[(cidx >> 4) * 32]);
        } else {
            gemm1_pass<4, false>(sb, wgi, warp4, lane, st, fph, e_cl, hp, hdst + 4 * j * 2048, false);
            float acc[64];
            const uint64_t descB0 = make_desc(sb, 4096, 1024, 1);
            const uint32_t ha = sb + 16384 + wgi * 4096 + warp4 * 512 + lane * 16;
            int sg = 3, p0 = 0; uint32_t ph = 6;
            uint4 af0[4], af1[4];
            auto load_a = [&](uint4 (&af)[4], int s) {
                mbar_wait(sb + SM_BARS + (B_FULL + s) * 8, (ph >> s) & 1);
                ph ^= 1u << s;
                const uint32_t a = ha + stage_off_rt(s);
                #pragma unroll
                for (int kk = 0; kk < 4; kk++) af[kk] = lds128(a + (kk >> 1) * 8192 + (kk & 1) * 2048);
            };
            auto g2 = [&](int u, uint4 (&cur)[4], uint4 (&nxt)[4], bool more) {
                const uint64_t db0 = desc_add(descB0, stage_off_rt(sg) >> 4);
                WG_FENCE();
                #pragma unroll
                for (int kk = 0; kk < 4; kk++) wgmma_rs_n128_tb(acc, cur[kk].x, cur[kk].y, cur[kk].z, cur[kk].w, db0 + ((kk >> 1) * 512 + (kk & 1) * 128), (u | kk) ? 1 : 0);
                WG_COMMIT();
                wg_wait<1>();
                if (lane < 2 && u > 0 && u + 4 < 28) mbar_arrive_cluster(e_cl + p0 * 8, 1);
                p0 = sg;
                sg = next_st2(sg);
                if (more) load_a(nxt, sg);
            };
            #pragma unroll
            for (int kk = 0; kk < 4; kk++) {
                af0[kk] = make_uint4(hp[4 * kk], hp[4 * kk + 1], hp[4 * kk + 2], hp[4 * kk + 3]);
                af1[kk] = make_uint4(hp[16 + 4 * kk], hp[17 + 4 * kk], hp[18 + 4 * kk], hp[19 + 4 * kk]);
            }
            mbar_wait(sb + SM_BARS + (B_FULL + 3) * 8, 0);
            g2(0, af0, af1, false);
            store_h(hdst + (32 + 6 * cb) * 2048, hp, 0); store_h(hdst + (32 + 6 * cb) * 2048, hp, 1);
            mbar_wait(sb + SM_BARS + (B_FULL + 4) * 8, 0);
            ph ^= 0x18;
            g2(1, af1, af0, true);
            store_h(hdst + (32 + 6 * cb) * 2048, hp, 2); store_h(hdst + (32 + 6 * cb) * 2048, hp, 3);
            __syncwarp();
            if (lane == 0) mbar_arrive(sb + SM_BARS + (B_HD + wgi * 2 + 1) * 8);
            g2(2, af0, af1, true);
            g2(3, af1, af0, true);
            #pragma unroll 1
            for (int u = 4; u < 26; u += 2) { g2(u, af0, af1, true); g2(u + 1, af1, af0, true); }
            g2(26, af0, af1, true);
            g2(27, af1, af0, false);
            wg_wait<0>();
            mbar_wait(sb + SM_BARS + B_XR * 8, 0);
            const int r0 = wgi * 64 + warp4 * 16 + g;
            const float2 st0 = lds64f(sb + SM_STATS + r0 * 8), st1 = lds64f(sb + SM_STATS + (r0 + 8) * 8);
            const uint32_t m0 = __float_as_uint(st0.x), m1 = __float_as_uint(st1.x);
            const uint32_t xrow0 = sb + SM_XE + r0 * 128 + c * 4;
            const int mi = lane >> 3, lr = lane & 7;
            const uint32_t yaddr = sb + SM_YT + wgi * 16384 + ((mi >> 1) * 8 + lr) * 128 + (((2 * warp4 + (mi & 1)) ^ lr) << 4);
            uint32_t y[8][4], xv[16][2], nv[16][2], bv[16][2];
            #pragma unroll
            for (int t = 0; t < 16; t++) {
                const uint32_t off = (t >> 3) * 16384 + (((t & 7) ^ g) << 4);
                xv[t][0] = lds32(xrow0 + off); xv[t][1] = lds32(xrow0 + 1024 + off);
            }
            #pragma unroll
            for (int t = 0; t < 16; t++) {
                const uint32_t d0 = bsub2(xv[t][0], m0), d1 = bsub2(xv[t][1], m1);
                nv[t][0] = pack_bf(bf_lo(d0) * st0.y, bf_hi(d0) * st0.y); nv[t][1] = pack_bf(bf_lo(d1) * st1.y, bf_hi(d1) * st1.y);
            }
            #pragma unroll
            for (int t = 0; t < 16; t++) { bv[t][0] = pack_bf(acc[4 * t], acc[4 * t + 1]); bv[t][1] = pack_bf(acc[4 * t + 2], acc[4 * t + 3]); }
            mbar_wait(sb + SM_BARS + B_YT * 8, 0);
            #pragma unroll
            for (int t2 = 0; t2 < 8; t2++)
                asm volatile("ldmatrix.sync.aligned.m8n8.x4.trans.shared.b16 {%0,%1,%2,%3}, [%4];"
                    : "=r"(y[t2][0]), "=r"(y[t2][1]), "=r"(y[t2][2]), "=r"(y[t2][3]) : "r"(yaddr + t2 * 2048) : "memory");
            #pragma unroll
            for (int hf = 0; hf < 2; hf++) {
                #pragma unroll
                for (int t = 8 * hf; t < 8 * hf + 8; t++) {
                    const uint32_t off = (t >> 3) * 16384 + (((t & 7) ^ g) << 4);
                    sts32(xrow0 + off, badd2(badd2(xv[t][0], bmul2(nv[t][0], y[t >> 1][2 * (t & 1)])), bv[t][0]));
                    sts32(xrow0 + 1024 + off, badd2(badd2(xv[t][1], bmul2(nv[t][1], y[t >> 1][2 * (t & 1) + 1])), bv[t][1]));
                }
                asm volatile("fence.proxy.async.shared::cta;" ::: "memory");
                __syncwarp();
                if (lane == 0) tma2d_store(&p.tm_out, 128 * cb + 64 * hf, 128 * i + 16 * warp, sb + SM_XE + hf * 16384 + warp * 2048);
            }
            if (lane == 0) {
                asm volatile("cp.async.bulk.commit_group;" ::: "memory");
                asm volatile("cp.async.bulk.wait_group.read 0;" ::: "memory");
            }
        }
    } else {
        asm volatile("setmaxnreg.dec.sync.aligned.u32 104;");
        if (warp == 8) {
            int st = 0; uint32_t eph = 7;
            const int nit = convCTA ? 12 : 16;
            #pragma unroll 1
            for (int it = 0; it < nit; it++) {
                const int pass = it >> 3, sl = it & 7;
                const bool narrow = pass && convCTA;
                const CUtensorMap* tm = narrow ? (rank ? &p.tm_uB : &p.tm_gB) : (rank ? &p.tm_uA : &p.tm_gA);
                mbar_wait(sb + SM_BARS + (B_EMPTY + st) * 8, (eph >> st) & 1);
                eph ^= 1u << st;
                if (it == 1) mbar_wait(sb + SM_BARS + B_XFULL * 8, 0);
                if (elect_one()) {
                    mbar_expect_tx(sb + SM_BARS + (B_FULL + st) * 8, 32768);
                    tma3d_mc(sb + SM_RING + st * STAGE_BYTES + rank * 16384, tm, 0, sl * (narrow ? 128 : 64), 14 * cb + 8 * (j & 1) + 4 * pass, sb + SM_BARS + (B_FULL + st) * 8);
                }
                st = (st == 2) ? 0 : st + 1;
            }
            if (!convCTA) {
                st = 3;
                const int f0_lane = blk_f0(2 * g2_pair(lane, cb) + rank);
                #pragma unroll 1
                for (int u = 0; u < 28; u++) {
                    const uint32_t bar = sb + SM_BARS + (B_FULL + st) * 8;
                    const int f0 = __shfl_sync(0xffffffffu, f0_lane, u);
                    mbar_wait(sb + SM_BARS + (B_EMPTY + st) * 8, (eph >> st) & 1);
                    eph ^= 1u << st;
                    if (elect_one()) {
                        mbar_expect_tx(bar, u < 2 ? 16384 : 32768);
                        tma3d_mc(sb + stage_off_rt(st) + rank * 8192, &p.tm_w2, 0, f0, 2 * cb, bar);
                    }
                    st = next_st2(st);
                }
            }
        } else if (warp < 11) {
            mbar_wait(sb + SM_BARS + (B_XFULL + 1) * 8, 0);
            {
                const int q = lane & 3;
                const int t0 = 32 * (b >> 1) + 8 * q;
                const int ch0 = 256 * (b & 1) + 16 * (warp - 9) + 2 * (lane >> 2);
                const uint32_t* kp = (const uint32_t*)(p.k + (size_t)t0 * DM + ch0);
                const uint32_t* vp = (const uint32_t*)(p.v + (size_t)t0 * DM + ch0);
                __nv_bfloat16* dst0 = g_kvT + (size_t)ch0 * SEQ + (t0 ^ 8);
                #pragma unroll 1
                for (int rnd = 0; rnd < 2; rnd++) {
                    uint32_t kr[4][11], vr[4][8]; uint4 skw[4];
                    #pragma unroll
                    for (int u = 0; u < 4; u++) {
                        const int co = (rnd * 4 + u) * 16;
                        skw[u] = ldg_nc128(p.shift_k + 4 * (ch0 + 2 * co));
                        #pragma unroll
                        for (int r = 0; r < 11; r++) kr[u][r] = (r >= 3 || t0 > 0) ? ldg_nc32(kp + co + (r - 3) * (DM / 2)) : 0u;
                        #pragma unroll
                        for (int r = 0; r < 8; r++) vr[u][r] = ldg_nc32(vp + co + r * (DM / 2));
                    }
                    #pragma unroll
                    for (int u = 0; u < 4; u++) {
                        const uint32_t s0 = __byte_perm(skw[u].x, skw[u].z, 0x5410), s1 = __byte_perm(skw[u].x, skw[u].z, 0x7632);
                        const uint32_t s2 = __byte_perm(skw[u].y, skw[u].w, 0x5410), s3 = __byte_perm(skw[u].y, skw[u].w, 0x7632);
                        #pragma unroll
                        for (int r = 0; r < 8; r++) {
                            uint32_t a = bmul2(kr[u][r], s3);
                            a = badd2(a, bmul2(kr[u][r + 1], s2));
                            a = badd2(a, bmul2(kr[u][r + 2], s1));
                            a = badd2(a, bmul2(kr[u][r + 3], s0));
                            vr[u][r] = bmul2(a, vr[u][r]);
                        }
                        __nv_bfloat16* dst = dst0 + (size_t)((rnd * 4 + u) * 32) * SEQ;
                        *(uint4*)dst = make_uint4(__byte_perm(vr[u][7], vr[u][6], 0x5410), __byte_perm(vr[u][5], vr[u][4], 0x5410),
                                                  __byte_perm(vr[u][3], vr[u][2], 0x5410), __byte_perm(vr[u][1], vr[u][0], 0x5410));
                        *(uint4*)(dst + SEQ) = make_uint4(__byte_perm(vr[u][7], vr[u][6], 0x7632), __byte_perm(vr[u][5], vr[u][4], 0x7632),
                                                          __byte_perm(vr[u][3], vr[u][2], 0x7632), __byte_perm(vr[u][1], vr[u][0], 0x7632));
                    }
                }
                if (lane == 0) mbar_arrive(sb + SM_BARS + B_KVLD * 8);
            }
            asm volatile("fence.proxy.async.global;" ::: "memory");
            __syncwarp();
            if (lane == 0) {
                flag_add(&g_cnt_kv[0]);
                const int wgi = warp - 9;
                mbar_wait(sb + SM_BARS + (B_HD + wgi * 2) * 8, 0);
                flag_add(&g_flag_h[(i * 2 + 0) * 8]);
                mbar_wait(sb + SM_BARS + (B_HD + wgi * 2 + 1) * 8, 0);
                flag_add(&g_flag_h[(i * 2 + 1) * 8]);
                if (wgi == 1 && !convCTA) {
                    mbar_wait(sb + SM_BARS + B_EP * 8, 0);
                    const unsigned ep = lds32(sb + SM_EPOCH);
                    mbar_wait(sb + SM_BARS + B_G1DONE * 8, 0);
                    mbar_expect_tx(sb + SM_BARS + B_XR * 8, 32768);
                    tma3d(sb + SM_XE, &p.tm_xe, 0, 128 * i, 2 * cb, sb + SM_BARS + B_XR * 8);
                    flag_wait(&g_flag_h[(i * 2 + 1) * 8], ep * 16);
                    mbar_arrive(sb + SM_BARS + (B_HRDY + 1) * 8);
                    __nanosleep(3000);
                    flag_wait(&g_cnt_y[cb * 32], ep * 128);
                    asm volatile("fence.proxy.async.global;" ::: "memory");
                    mbar_expect_tx(sb + SM_BARS + B_YT * 8, 32768);
                    tma2d(sb + SM_YT, &p.tm_yT, 128 * i, 128 * cb, sb + SM_BARS + B_YT * 8);
                    tma2d(sb + SM_YT + 16384, &p.tm_yT, 128 * i + 64, 128 * cb, sb + SM_BARS + B_YT * 8);
                }
            }
        } else {
            if (lane == 0) {
                l2_prefetch(p.wg + (size_t)b * (FF * DM / NCTA), FF * DM / NCTA * 2);
                l2_prefetch(p.wu + (size_t)b * (FF * DM / NCTA), FF * DM / NCTA * 2);
                const unsigned ep = g_launch[b] + 1;
                g_launch[b] = ep;
                sts32(sb + SM_EPOCH, ep);
                mbar_arrive(sb + SM_BARS + B_EP * 8);
                tmap_prefetch(rank ? &p.tm_uA : &p.tm_gA);
                tmap_prefetch(rank ? &p.tm_uB : &p.tm_gB);
                tmap_prefetch(&p.tm_w2); tmap_prefetch(&p.tm_yT); tmap_prefetch(&p.tm_out); tmap_prefetch(&p.tm_xe);
                mbar_wait(sb + SM_BARS + B_KVLD * 8, 0);
                l2_prefetch(p.ssm_k + (size_t)(4 * b) * SEQ, 4 * SEQ * 2);
                l2_prefetch(p.wd + (size_t)b * (FF * DM / NCTA), FF * DM / NCTA * 2);
                if (convCTA) {
                    __nanosleep(1000);
                    flag_wait(&g_cnt_kv[0], ep * 256);
                    asm volatile("fence.proxy.async.global;" ::: "memory");
                    mbar_wait(sb + SM_BARS + B_XFREE * 8, 0);
                    mbar_expect_tx(sb + SM_BARS + B_CONV * 8, 65536);
                    bulk_g2s(sb + SM_CVX, g_kvT + (size_t)(8 * cidx) * SEQ, 32768, sb + SM_BARS + B_CONV * 8);
                    bulk_g2s(sb + SM_CVH, p.ssm_k + (size_t)(8 * cidx) * SEQ, 32768, sb + SM_BARS + B_CONV * 8);
                } else {
                    mbar_wait(sb + SM_BARS + (B_HD + 0) * 8, 0);
                    flag_wait(&g_flag_h[(i * 2 + 0) * 8], ep * 16);
                }
            }
            __syncwarp();
            if (!convCTA) {
                asm volatile("fence.proxy.async.global;" ::: "memory");
                int st = 1; uint32_t eph = 0x19;
                const uint8_t* hsrc = (const uint8_t*)g_h + (size_t)i * 56 * 8192;
                #pragma unroll 1
                for (int u = 2; u < 28; u++) {
                    mbar_wait(sb + SM_BARS + (B_EMPTY + st) * 8, (eph >> st) & 1);
                    eph ^= 1u << st;
                    if (u == 18) {
                        mbar_wait(sb + SM_BARS + (B_HRDY + 1) * 8, 0);
                        asm volatile("fence.proxy.async.global;" ::: "memory");
                    }
                    if (elect_one()) bulk_g2s(sb + stage_off_rt(st) + 16384, hsrc + g2_pair(u, cb) * 16384, 16384, sb + SM_BARS + (B_FULL + st) * 8);
                    st = next_st2(st);
                }
            }
        }
    }
}

typedef CUresult (*EncodeFn)(CUtensorMap*, CUtensorMapDataType, cuuint32_t, void*, const cuuint64_t*, const cuuint64_t*,
                             const cuuint32_t*, const cuuint32_t*, CUtensorMapInterleave, CUtensorMapSwizzle,
                             CUtensorMapL2promotion, CUtensorMapFloatOOBfill);

void encode(EncodeFn fn, CUtensorMap* tm, const void* base, int rank, const cuuint64_t* dims, const cuuint64_t* strides,
            const cuuint32_t* box, CUtensorMapSwizzle swz) {
    cuuint32_t es[5] = {1, 1, 1, 1, 1};
    fn(tm, CU_TENSOR_MAP_DATA_TYPE_BFLOAT16, rank, (void*)base, dims, strides, box, es, CU_TENSOR_MAP_INTERLEAVE_NONE, swz,
       CU_TENSOR_MAP_L2_PROMOTION_L2_128B, CU_TENSOR_MAP_FLOAT_OOB_FILL_NONE);
}

}

extern "C" void kernel_launch(void* const* d_in, const int* in_sizes, int n_in, void* d_out, int out_size) {
    (void)in_sizes; (void)n_in; (void)out_size;
    static EncodeFn enc = nullptr;
    static void* yT_ptr = nullptr;
    if (!enc) {
        void* fn = nullptr; cudaDriverEntryPointQueryResult qr;
        cudaGetDriverEntryPoint("cuTensorMapEncodeTiled", &fn, cudaEnableDefault, &qr);
        enc = (EncodeFn)fn;
        cudaGetSymbolAddress(&yT_ptr, g_yT);
        cudaFuncSetAttribute(fused_kernel, cudaFuncAttributeMaxDynamicSharedMemorySize, SM_TOTAL);
    }
    Params p;
    p.q = (const __nv_bfloat16*)d_in[0]; p.k = (const __nv_bfloat16*)d_in[1]; p.v = (const __nv_bfloat16*)d_in[2];
    p.shift_k = (const __nv_bfloat16*)d_in[3]; p.ssm_k = (const __nv_bfloat16*)d_in[4]; p.ssm_D = (const __nv_bfloat16*)d_in[5];
    p.wg = (const __nv_bfloat16*)d_in[7]; p.wu = (const __nv_bfloat16*)d_in[8]; p.wd = (const __nv_bfloat16*)d_in[9];
    {
        cuuint64_t dims[2] = {DM, SEQ}; cuuint64_t str[1] = {DM * 2};
        cuuint64_t dims3[3] = {64, SEQ, DM / 64}; cuuint64_t str3[2] = {DM * 2, 128};
        cuuint32_t box[3] = {64, 64, 8}, boxe[3] = {64, 128, 2};
        encode(enc, &p.tm_x, p.q, 3, dims3, str3, box, CU_TENSOR_MAP_SWIZZLE_128B);
        encode(enc, &p.tm_xe, p.q, 3, dims3, str3, boxe, CU_TENSOR_MAP_SWIZZLE_128B);
        cuuint32_t box2[2] = {64, 16};
        encode(enc, &p.tm_out, d_out, 2, dims, str, box2, CU_TENSOR_MAP_SWIZZLE_128B);
    }
    {
        cuuint64_t dims[3] = {32, DM, FF / 32}; cuuint64_t str[2] = {FF * 2, 64};
        cuuint32_t boxA[3] = {32, 64, 4}, boxB[3] = {32, 128, 2};
        encode(enc, &p.tm_gA, p.wg, 3, dims, str, boxA, CU_TENSOR_MAP_SWIZZLE_64B);
        encode(enc, &p.tm_gB, p.wg, 3, dims, str, boxB, CU_TENSOR_MAP_SWIZZLE_64B);
        encode(enc, &p.tm_uA, p.wu, 3, dims, str, boxA, CU_TENSOR_MAP_SWIZZLE_64B);
        encode(enc, &p.tm_uB, p.wu, 3, dims, str, boxB, CU_TENSOR_MAP_SWIZZLE_64B);
    }
    {
        cuuint64_t dims[3] = {64, FF, DM / 64}; cuuint64_t str[2] = {DM * 2, 128};
        cuuint32_t box[3] = {64, 32, 2};
        encode(enc, &p.tm_w2, p.wd, 3, dims, str, box, CU_TENSOR_MAP_SWIZZLE_128B);
    }
    {
        cuuint64_t dims[2] = {SEQ, DM}; cuuint64_t str[1] = {SEQ * 2};
        cuuint32_t box[2] = {64, 128};
        encode(enc, &p.tm_yT, yT_ptr, 2, dims, str, box, CU_TENSOR_MAP_SWIZZLE_128B);
    }
    fused_kernel<<<NCTA, NTHREADS, SM_TOTAL>>>(p);
}
```
